```python
import torch

def _softmax(x, axis=-1):
    return torch.softmax(x, dim=axis)
def _gelu(x):
    return torch.nn.functional.gelu(x, approximate="tanh")
def _silu(x):
    return torch.nn.functional.silu(x)
def _sigmoid(x):
    return torch.sigmoid(x)
def _layernorm(x, axis=-1, eps=1e-5):
    m = x.mean(dim=axis, keepdim=True)
    v = x.var(dim=axis, keepdim=True, unbiased=False)
    return (x - m) / torch.sqrt(v + eps)
def _scatter_add(tgt, idx, src, axis=0):
    return tgt.clone().index_add_(axis, idx, src)
def _segment_sum(src, seg, n):
    out = torch.zeros((n,) + src.shape[1:], dtype=src.dtype)
    return out.index_add_(0, seg, src)
def _pad(x, pw):
    flat = tuple(v for pair in reversed(pw) for v in pair)
    return torch.nn.functional.pad(x, flat)

kernel_name = 'standalone__modern_conv_block_convnext_v2__vision'

def setup_inputs():

    _w = (lambda a: (lambda t: t.to(torch.bfloat16) if t.is_floating_point() else t)(torch.as_tensor(a)))
    H = W = 512
    C = 96
    K = 3
    return {
        "x": _w((lambda *s: torch.randn(*s, dtype=torch.bfloat16) * 0.05)(1, H, W, C)),
        "dw": _w((lambda *s: torch.randn(*s, dtype=torch.bfloat16) * 0.05)(K, K, C)),
        "w1": _w((lambda *s: torch.randn(*s, dtype=torch.bfloat16) * 0.05)(C, 4 * C)),
        "w2": _w((lambda *s: torch.randn(*s, dtype=torch.bfloat16) * 0.05)(4 * C, C)),
        "grn_gamma": _w((lambda *s: torch.randn(*s, dtype=torch.bfloat16) * 0.05)(4 * C)),
        "grn_beta": _w((lambda *s: torch.randn(*s, dtype=torch.bfloat16) * 0.05)(4 * C)),
    }

def reference(x, dw, w1, w2, grn_gamma, grn_beta):
    B, H, W, C = x.shape
    K = dw.shape[0]
    pad = K // 2
    xp = _pad(x, ((0,0),(pad,pad),(pad,pad),(0,0)))
    out = torch.zeros_like(x)
    for i in range(K):
        for j in range(K):
            out = out + xp[:, i:i+H, j:j+W, :] * dw[i, j][None, None, None, :]
    h = _layernorm(out, axis=-1)
    h = torch.einsum('bhwc,ce->bhwe', h, w1)
    h = _gelu(h)
    gx = torch.sqrt((h * h).sum(axis=(1, 2), keepdims=True) + 1e-6)
    nx = gx / (gx.mean(axis=-1, keepdims=True) + 1e-6)
    h = grn_gamma * (h * nx) + grn_beta + h
    h = torch.einsum('bhwe,ec->bhwc', h, w2)
    return x + h
```

```cpp
#include <cuda_runtime.h>
#include <cuda_bf16.h>
#include <cuda_fp16.h>
#include <cuda.h>
#include <stdint.h>

namespace cnx {

constexpr int IMG_H = 512, IMG_W = 512, CH = 96, EX = 384;
constexpr int TILE_W = 64;
constexpr int NTILES = (IMG_W / TILE_W) * IMG_H;
constexpr int NSLOT = 6;
constexpr int REGION_PX = 18;
constexpr int REGION_BYTES = REGION_PX * CH * 2;
constexpr int SLOT_BYTES = 4 * REGION_BYTES;
constexpr int A_LBO = 144, A_SBO = 12 * A_LBO;
constexpr int PREFETCH_ROWS = 3;
constexpr int NCONS = 3;
constexpr int CONS_THREADS = 128 * NCONS;
constexpr int NTHREADS = 128 + CONS_THREADS;
constexpr int MAX_ROWS = 52;
constexpr int TILE_BYTES = TILE_W * CH * 2, WARP_BYTES = TILE_BYTES / 4;
constexpr int S1_PASS = 1, S2_PASS = 1;
#define S2_FIRST 4
#define ORDER_P 3
#define ORDER_Q 1
static_assert(MAX_ROWS <= 128, "one table entry per producer thread");
static_assert(2 * A_SBO == REGION_BYTES && REGION_BYTES % 128 == 0, "region layout");

constexpr uint32_t SB = 1024;
constexpr int SM_W1 = 0;
constexpr int SM_W2 = SM_W1 + CH * EX * 2;
constexpr int SM_RING = SM_W2 + CH * EX * 2;
constexpr int SM_BIASH = SM_RING + NSLOT * SLOT_BYTES;
constexpr int SM_RED = SM_BIASH + 384;
constexpr int SM_ROWS = SM_RED + 256;
constexpr int SM_TILES = SM_ROWS + MAX_ROWS * 4;
constexpr int SM_ONES = SM_TILES + MAX_ROWS * 4;
constexpr int SM_BAR = SM_ONES + 128;
constexpr int BAR_X = SM_BAR;
constexpr int BAR_A = BAR_X + NSLOT * 4 * 8;
constexpr int BAR_E = BAR_A + NSLOT * 4 * 8;
constexpr int BAR_PIN = BAR_E + NSLOT * 4 * 8;
constexpr int BAR_W = BAR_PIN + 8;
constexpr int BAR_R = BAR_W + 6 * 8;
constexpr int SM_TOTAL = BAR_R + 16 * 8;
constexpr int SM_SQ = SM_W2;
static_assert(SM_ONES % 16 == 0 && SM_TOTAL <= 232448, "shared memory budget");

constexpr float KZ = 0.3292034911525734f;
constexpr uint32_t GELU_C2 = 0x40d940d9u;
constexpr float INV_2KZ = 0.5f / KZ;
constexpr unsigned SPIN_LIMIT = 1u << 19;

constexpr int REPLICAS = 4;
__device__ unsigned long long g_sums[2][REPLICAS][EX];
constexpr int MAX_CTAS = 256;
__device__ unsigned g_count;
constexpr int W2_GROUPS = EX / 8;
__device__ __align__(128) uint32_t g_w2h[EX * CH / 2];
__device__ float g_w2max[EX];
__device__ __align__(16) float g_bias[2][CH];
__device__ unsigned g_prep;

#define PROF(k)

__device__ __forceinline__ uint32_t smem_u32(const void* p) { return (uint32_t)__cvta_generic_to_shared(p); }
__device__ __forceinline__ void mbar_init(uint32_t bar, uint32_t cnt) {
    asm volatile("mbarrier.init.shared::cta.b64 [%0], %1;" ::"r"(bar), "r"(cnt) : "memory");
}
__device__ __forceinline__ void mbar_arrive(uint32_t bar) {
    asm volatile("mbarrier.arrive.shared::cta.b64 _, [%0];" ::"r"(bar) : "memory");
}
__device__ __forceinline__ void mbar_expect_tx(uint32_t bar, uint32_t bytes) {
    asm volatile("mbarrier.arrive.expect_tx.shared::cta.b64 _, [%0], %1;" ::"r"(bar), "r"(bytes) : "memory");
}
__device__ __forceinline__ bool mbar_try(uint32_t bar, uint32_t par) {
    uint32_t ok;
    asm volatile("{\n.reg .pred p;\nmbarrier.try_wait.parity.shared::cta.b64 p, [%1], %2;\nselp.u32 %0, 1, 0, p;\n}\n"
                 : "=r"(ok) : "r"(bar), "r"(par) : "memory");
    return ok != 0;
}
__device__ __forceinline__ void mbar_wait(uint32_t bar, uint32_t par) {
    unsigned n = 0;
    while (!mbar_try(bar, par)) {
        if (++n > SPIN_LIMIT) __trap();
    }
}
__device__ __forceinline__ bool mbar_test(uint32_t bar, uint32_t par) {
    uint32_t ok;
    asm volatile("{\n.reg .pred p;\nmbarrier.test_wait.parity.shared::cta.b64 p, [%1], %2;\nselp.u32 %0, 1, 0, p;\n}\n"
                 : "=r"(ok) : "r"(bar), "r"(par) : "memory");
    return ok != 0;
}
__device__ __forceinline__ bool elect_one() {
    uint32_t ok;
    asm volatile("{\n.reg .pred p;\nelect.sync _|p, 0xffffffff;\nselp.u32 %0, 1, 0, p;\n}\n" : "=r"(ok));
    return ok != 0;
}
__device__ __forceinline__ uint32_t opaque(uint32_t v) { return __shfl_sync(~0u, v, threadIdx.x & 31); }
__device__ __forceinline__ void named_bar(int id, int n) { asm volatile("bar.sync %0, %1;" ::"r"(id), "r"(n) : "memory"); }
__device__ __forceinline__ void named_arrive(int id, int n) { asm volatile("bar.arrive %0, %1;" ::"r"(id), "r"(n) : "memory"); }
__device__ __forceinline__ void fence_async() { asm volatile("fence.proxy.async.shared::cta;" ::: "memory"); }
__device__ __forceinline__ uint64_t evict_first() {
    uint64_t p;
    asm("createpolicy.fractional.L2::evict_first.b64 %0, 1.0;" : "=l"(p));
    return p;
}
__device__ __forceinline__ void tma_row(uint32_t dst, const CUtensorMap* tm, uint32_t bar, int x, int y) {
    asm volatile("cp.async.bulk.tensor.3d.shared::cluster.global.mbarrier::complete_tx::bytes.L2::cache_hint [%0], [%1, {%3, %4, %5}], [%2], %6;"
                 ::"r"(dst), "l"(tm), "r"(bar), "r"(0), "r"(x), "r"(y), "l"(evict_first()) : "memory");
}
__device__ __forceinline__ void bulk_load_stream(uint32_t dst, const void* src, uint32_t bytes, uint32_t bar) {
    asm volatile("cp.async.bulk.shared::cluster.global.mbarrier::complete_tx::bytes.L2::cache_hint [%0], [%1], %2, [%3], %4;"
                 ::"r"(dst), "l"(src), "r"(bytes), "r"(bar), "l"(evict_first()) : "memory");
}
__device__ __forceinline__ void prefetch_l2(const void* src, uint32_t bytes) {
    asm volatile("cp.async.bulk.prefetch.L2.global [%0], %1;" ::"l"(src), "r"(bytes) : "memory");
}
__device__ __forceinline__ void tma_2d(uint32_t dst, const CUtensorMap* tm, uint32_t bar, int x, int y) {
    asm volatile("cp.async.bulk.tensor.2d.shared::cluster.global.mbarrier::complete_tx::bytes [%0], [%1, {%3, %4}], [%2];"
                 ::"r"(dst), "l"(tm), "r"(bar), "r"(x), "r"(y) : "memory");
}
__device__ __forceinline__ void bulk_load(uint32_t dst, const void* src, uint32_t bytes, uint32_t bar) {
    asm volatile("cp.async.bulk.shared::cluster.global.mbarrier::complete_tx::bytes [%0], [%1], %2, [%3];"
                 ::"r"(dst), "l"(src), "r"(bytes), "r"(bar) : "memory");
}
__device__ __forceinline__ void wg_fence() { asm volatile("wgmma.fence.sync.aligned;" ::: "memory"); }
__device__ __forceinline__ void wg_commit() { asm volatile("wgmma.commit_group.sync.aligned;" ::: "memory"); }
template <int N> __device__ __forceinline__ void wg_wait() { asm volatile("wgmma.wait_group.sync.aligned %0;" ::"n"(N) : "memory"); }
template <int N> __device__ __forceinline__ void pin(uint32_t (&d)[N]) {
#pragma unroll
    for (int q = 0; q < N; q++) asm volatile("" : "+r"(d[q])::"memory");
}
__device__ __forceinline__ void stg128(void* p, const uint32_t (&v)[4]) {
    asm volatile("st.global.v4.u32 [%0], {%1, %2, %3, %4};" ::"l"(p), "r"(v[0]), "r"(v[1]), "r"(v[2]), "r"(v[3]) : "memory");
}
__device__ __forceinline__ void ldg128_if(bool on, uint32_t (&v)[4], const void* p) {
    asm volatile("{\n.reg .pred p;\nsetp.ne.b32 p, %5, 0;\n@p ld.global.L1::no_allocate.v4.u32 {%0, %1, %2, %3}, [%4];\n}\n"
                 : "+r"(v[0]), "+r"(v[1]), "+r"(v[2]), "+r"(v[3]) : "l"(p), "r"((int)on) : "memory");
}
__device__ __forceinline__ uint4 ldg128_ordered(const void* p) {
    uint4 v;
    asm volatile("ld.global.nc.v4.u32 {%0, %1, %2, %3}, [%4];" : "=r"(v.x), "=r"(v.y), "=r"(v.z), "=r"(v.w) : "l"(p) : "memory");
    return v;
}
__host__ __device__ constexpr uint64_t make_desc(uint32_t addr, uint32_t lbo, uint32_t sbo) {
    return (uint64_t)((addr & 0x3FFFF) >> 4) | ((uint64_t)(lbo >> 4) << 16) | ((uint64_t)(sbo >> 4) << 32);
}
__device__ __forceinline__ void wgmma(uint32_t (&d)[12], uint32_t a0, uint32_t a1, uint32_t a2, uint32_t a3, uint64_t db, int acc) {
    asm volatile("{\n.reg .pred p;\nsetp.ne.b32 p, %17, 0;\n"
                 "wgmma.mma_async.sync.aligned.m64n48k16.f16.f16.f16 "
                 "{%0, %1, %2, %3, %4, %5, %6, %7, %8, %9, %10, %11}, "
                 "{%12, %13, %14, %15}, %16, p, 1, 1, 0;\n}\n"
                 : "+r"(d[0]), "+r"(d[1]), "+r"(d[2]), "+r"(d[3]), "+r"(d[4]), "+r"(d[5]), "+r"(d[6]), "+r"(d[7]), "+r"(d[8]), "+r"(d[9]), "+r"(d[10]), "+r"(d[11])
                 : "r"(a0), "r"(a1), "r"(a2), "r"(a3), "l"(db), "r"(acc));
}
__device__ __forceinline__ void wgmma(uint32_t (&d)[24], uint32_t a0, uint32_t a1, uint32_t a2, uint32_t a3, uint64_t db, int acc) {
    asm volatile("{\n.reg .pred p;\nsetp.ne.b32 p, %29, 0;\n"
                 "wgmma.mma_async.sync.aligned.m64n96k16.f16.f16.f16 "
                 "{%0, %1, %2, %3, %4, %5, %6, %7, %8, %9, %10, %11, %12, %13, %14, %15, %16, %17, %18, %19, %20, %21, %22, %23}, "
                 "{%24, %25, %26, %27}, %28, p, 1, 1, 0;\n}\n"
                 : "+r"(d[0]), "+r"(d[1]), "+r"(d[2]), "+r"(d[3]), "+r"(d[4]), "+r"(d[5]), "+r"(d[6]), "+r"(d[7]), "+r"(d[8]), "+r"(d[9]), "+r"(d[10]), "+r"(d[11]), "+r"(d[12]), "+r"(d[13]), "+r"(d[14]), "+r"(d[15]), "+r"(d[16]), "+r"(d[17]), "+r"(d[18]), "+r"(d[19]), "+r"(d[20]), "+r"(d[21]), "+r"(d[22]), "+r"(d[23])
                 : "r"(a0), "r"(a1), "r"(a2), "r"(a3), "l"(db), "r"(acc));
}
template <int ACC>
__device__ __forceinline__ void wgmma_rowsum(float (&d)[4], const uint32_t (&a)[4], uint64_t ones) {
    asm volatile("{\n.reg .pred p;\nsetp.ne.b32 p, %9, 0;\n"
                 "wgmma.mma_async.sync.aligned.m64n8k16.f32.bf16.bf16 {%0, %1, %2, %3}, {%4, %5, %6, %7}, %8, p, 1, 1, 0;\n}\n"
                 : "+f"(d[0]), "+f"(d[1]), "+f"(d[2]), "+f"(d[3])
                 : "r"(a[0]), "r"(a[1]), "r"(a[2]), "r"(a[3]), "l"(ones), "n"(ACC));
}
__device__ __forceinline__ void ldsm4(uint32_t (&r)[4], uint32_t addr) {
    asm volatile("ldmatrix.sync.aligned.m8n8.x4.shared.b16 {%0, %1, %2, %3}, [%4];"
                 : "=r"(r[0]), "=r"(r[1]), "=r"(r[2]), "=r"(r[3]) : "r"(addr) : "memory");
}
__device__ __forceinline__ void ldsm4_t(uint32_t (&r)[4], uint32_t addr) {
    asm volatile("ldmatrix.sync.aligned.m8n8.x4.trans.shared.b16 {%0, %1, %2, %3}, [%4];"
                 : "=r"(r[0]), "=r"(r[1]), "=r"(r[2]), "=r"(r[3]) : "r"(addr) : "memory");
}
__device__ __forceinline__ void stsm4(uint32_t addr, uint32_t a, uint32_t b, uint32_t c, uint32_t d) {
    asm volatile("stmatrix.sync.aligned.m8n8.x4.shared.b16 [%0], {%1, %2, %3, %4};"
                 ::"r"(addr), "r"(a), "r"(b), "r"(c), "r"(d) : "memory");
}
__device__ __forceinline__ uint32_t transpose8x8(uint32_t v) {
    uint32_t d; asm volatile("movmatrix.sync.aligned.m8n8.trans.b16 %0, %1;" : "=r"(d) : "r"(v)); return d;
}
__device__ __forceinline__ void spin_until(const unsigned* counter, unsigned target) {
    unsigned n = 0, c;
    do {
        asm volatile("ld.acquire.gpu.global.u32 %0, [%1];" : "=r"(c) : "l"(counter) : "memory");
        if (++n > SPIN_LIMIT) __trap();
    } while ((int)(c - target) < 0);
}
__device__ __forceinline__ void lds128(uint32_t& a, uint32_t& b, uint32_t& c, uint32_t& d, uint32_t addr) {
    asm volatile("ld.shared.v4.u32 {%0, %1, %2, %3}, [%4];" : "=r"(a), "=r"(b), "=r"(c), "=r"(d) : "r"(addr) : "memory");
}
__device__ __forceinline__ void lds64(uint32_t& a, uint32_t& b, uint32_t addr) {
    asm volatile("ld.shared.v2.u32 {%0, %1}, [%2];" : "=r"(a), "=r"(b) : "r"(addr) : "memory");
}
__device__ __forceinline__ void lds32(uint32_t& a, uint32_t addr) {
    asm volatile("ld.shared.u32 %0, [%1];" : "=r"(a) : "r"(addr) : "memory");
}
__device__ __forceinline__ float ldsf(uint32_t addr) {
    uint32_t v;
    lds32(v, addr);
    return __uint_as_float(v);
}
__device__ __forceinline__ void sts32(uint32_t addr, uint32_t a) {
    asm volatile("st.shared.u32 [%0], %1;" ::"r"(addr), "r"(a) : "memory");
}
__device__ __forceinline__ void sts128(uint32_t addr, uint32_t a, uint32_t b, uint32_t c, uint32_t d) {
    asm volatile("st.shared.v4.u32 [%0], {%1, %2, %3, %4};" ::"r"(addr), "r"(a), "r"(b), "r"(c), "r"(d) : "memory");
}
__device__ __forceinline__ void sts64(uint32_t addr, uint32_t a, uint32_t b) {
    asm volatile("st.shared.v2.u32 [%0], {%1, %2};" ::"r"(addr), "r"(a), "r"(b) : "memory");
}
__device__ __forceinline__ uint32_t bf_fma(uint32_t a, uint32_t b, uint32_t c) {
    uint32_t d; asm("fma.rn.bf16x2 %0, %1, %2, %3;" : "=r"(d) : "r"(a), "r"(b), "r"(c)); return d;
}
__device__ __forceinline__ uint32_t bf_mul(uint32_t a, uint32_t b) {
    uint32_t d; asm("mul.rn.bf16x2 %0, %1, %2;" : "=r"(d) : "r"(a), "r"(b)); return d;
}
__device__ __forceinline__ uint32_t bf_absmax(uint32_t a, uint32_t b) {
    uint32_t d; asm("max.xorsign.abs.bf16x2 %0, %1, %2;" : "=r"(d) : "r"(a), "r"(b)); return d;
}
__device__ __forceinline__ uint32_t h_fma(uint32_t a, uint32_t b, uint32_t c) {
    uint32_t d; asm("fma.rn.f16x2 %0, %1, %2, %3;" : "=r"(d) : "r"(a), "r"(b), "r"(c)); return d;
}
__device__ __forceinline__ uint32_t h_mul(uint32_t a, uint32_t b) {
    uint32_t d; asm("mul.rn.f16x2 %0, %1, %2;" : "=r"(d) : "r"(a), "r"(b)); return d;
}
__device__ __forceinline__ uint32_t h_round8(uint32_t v) { return (v + 0x00040004u) & 0xfff8fff8u; }
__device__ __forceinline__ uint32_t h_tanh(uint32_t a) {
    uint32_t d; asm("tanh.approx.f16x2 %0, %1;" : "=r"(d) : "r"(a)); return d;
}
__device__ __forceinline__ uint32_t pack_h2(float lo, float hi) {
    uint32_t d; asm("cvt.rn.f16x2.f32 %0, %1, %2;" : "=r"(d) : "f"(hi), "f"(lo)); return d;
}
__device__ __forceinline__ uint32_t pack_bf2(float lo, float hi) {
    uint32_t d; asm("cvt.rn.bf16x2.f32 %0, %1, %2;" : "=r"(d) : "f"(hi), "f"(lo)); return d;
}
__device__ __forceinline__ float bf_lo(uint32_t v) { return __uint_as_float(v << 16); }
__device__ __forceinline__ float bf_hi(uint32_t v) { return __uint_as_float(v & 0xffff0000u); }
__device__ __forceinline__ float h_lo(uint32_t v) { return __low2float(*reinterpret_cast<__half2*>(&v)); }
__device__ __forceinline__ float h_hi(uint32_t v) { return __high2float(*reinterpret_cast<__half2*>(&v)); }
__device__ __forceinline__ float warp_absmax(uint32_t v) {
    return __uint_as_float(__reduce_max_sync(~0u, max((v & 0x7fffu) << 16, v & 0x7fff0000u)));
}
__device__ __forceinline__ uint32_t gelu2(uint32_t z) {
    uint32_t p = h_fma(z, z, GELU_C2);
    uint32_t t = h_tanh(h_mul(z, p));
    return h_fma(z, t, z);
}
__device__ __forceinline__ float grn_norm(float ss) {
    float r;
    asm("sqrt.approx.f32 %0, %1;" : "=f"(r) : "f"(fmaf(ss, INV_2KZ * INV_2KZ, 1e-6f)));
    return r;
}
__device__ __forceinline__ float pow2i(int e) { return __uint_as_float((uint32_t)(e + 127) << 23); }
__device__ __forceinline__ int ilog2f(float v) {
    int e = (int)((__float_as_uint(v) >> 23) & 0xff) - 127;
    return max(-100, min(100, e));
}

__device__ __forceinline__ int sum_exp(float w1max) {
    return w1max > 0.f ? max(-90, min(90, 35 - 2 * ilog2f(2.f * KZ * 96.f * w1max))) : 0;
}
__device__ __forceinline__ float row_scale(float m) { return m > 0.f ? pow2i(2 - ilog2f(m)) : 1.f; }

struct Work {
    int t0, nA, nB, sA, yA, rows;
};
__device__ __forceinline__ Work get_work(int per_cta, int extra) {
    Work w;
    const int t0 = blockIdx.x * per_cta + min((int)blockIdx.x, extra);
    const int t1 = t0 + per_cta + ((int)blockIdx.x < extra);
    w.t0 = t0;
    w.sA = t0 >> 9;
    w.yA = t0 & 511;
    const int tm = min(t1, (w.sA + 1) << 9);
    w.nA = tm - t0;
    w.nB = t1 - tm;
    w.rows = w.nA + 2 + (w.nB ? w.nB + 2 : 0);
    return w;
}
__device__ __forceinline__ int row_code(const Work& w, int i) {
    int strip, y;
    if (i < w.nA + 2) { strip = w.sA; y = w.yA - 1 + i; }
    else { strip = w.sA + 1; y = i - (w.nA + 2) - 1; }
    return y << 16 | strip * TILE_W;
}
__device__ __forceinline__ uint32_t tile_offset(int tile) { return ((tile & 511) * IMG_W + (tile >> 9) * TILE_W) * (CH * 2); }
__device__ __forceinline__ int tile_order(int j, int n) {
    const int olds = (j / ORDER_P) * ORDER_Q + max(0, j % ORDER_P - (ORDER_P - ORDER_Q));
    return (j % ORDER_P >= ORDER_P - ORDER_Q) ? olds : n - 1 - (j - olds);
}
__device__ __forceinline__ void issue_region(const CUtensorMap* tm, uint32_t dst, uint32_t bar, int warp, int code) {
    mbar_expect_tx(bar, REGION_BYTES);
    tma_row(dst, tm, bar, (code & 0xffff) + (16 * warp - 1), code >> 16);
}
__device__ __forceinline__ void elect_arrive(uint32_t bar0, uint32_t bar1, bool both) {
    asm volatile("{\n.reg .pred p, q;\nelect.sync _|p, 0xffffffff;\nsetp.ne.and.b32 q, %2, 0, p;\n"
                 "@p mbarrier.arrive.shared::cta.b64 _, [%0];\n@q mbarrier.arrive.shared::cta.b64 _, [%1];\n}\n"
                 ::"r"(bar0), "r"(bar1), "r"((int)both) : "memory");
}

__device__ __forceinline__ void first_loads(const Work& wk, const CUtensorMap* tm, const CUtensorMap* tw, const __nv_bfloat16* dw,
                                            uint32_t sb, int warp) {
    const uint32_t reg0 = sb + SM_RING + warp * REGION_BYTES, bars = sb + SM_BAR + warp * 8;
#pragma unroll
    for (int s = 0; s < PREFETCH_ROWS; s++) mbar_init(bars + s * 32, 1);
    mbar_init(sb + BAR_W + warp * 8, 1);
    if (warp < 2) mbar_init(sb + BAR_W + (warp + 4) * 8, 1);
    fence_async();
    asm volatile("mbarrier.expect_tx.shared::cta.b64 [%0], %1;" ::"r"(bars), "r"(9 * CH * 2) : "memory");
    bulk_load(reg0 + (NSLOT - 1) * SLOT_BYTES, dw, 9 * CH * 2, bars);
#pragma unroll
    for (int r = 0; r < PREFETCH_ROWS; r++)
        issue_region(tm, reg0 + r * SLOT_BYTES, bars + r * 32, warp, (wk.yA - 1 + r) << 16 | wk.sA * TILE_W);
#pragma unroll 1
    for (int b = warp; b < 6; b += 4) {
        mbar_expect_tx(sb + BAR_W + b * 8, 64 * CH * 2);
        tma_2d(sb + SM_W2 + b * (64 * CH * 2), tw, sb + BAR_W + b * 8, 64 * b, 0);
    }
}

__device__ __forceinline__ void conv_producer(const Work& wk, const CUtensorMap* tm, uint32_t sb, int warp) {
    const int lane = threadIdx.x & 31;
    const int j = lane & 15, grp = lane >> 4;
    const uint32_t reg0 = sb + SM_RING + warp * REGION_BYTES;
    const uint32_t bars = sb + SM_BAR + warp * 8;
    if (elect_one()) {
        if (warp == 0) mbar_init(sb + BAR_PIN, 1);
#pragma unroll
        for (int s = 0; s < 4; s++) mbar_init(sb + BAR_R + (s * 4 + warp) * 8, 1);
#pragma unroll 1
        for (int s = PREFETCH_ROWS; s < 3 * NSLOT; s++) mbar_init(bars + s * 32, 1);
        fence_async();
    }
    __syncwarp();
    named_arrive(0, NTHREADS);
    if (warp * 32 + lane < MAX_ROWS) {
        sts32(sb + SM_ROWS + (warp * 32 + lane) * 4, row_code(wk, warp * 32 + lane));
        sts32(sb + SM_TILES + (warp * 32 + lane) * 4, tile_offset(wk.t0 + tile_order(warp * 32 + lane, wk.nA + wk.nB - NCONS)));
    }
    const uint32_t ld64 = opaque(reg0 + grp * 8 * 192 + j * 8), ld32 = opaque(reg0 + grp * 8 * 192 + 128 + j * 4);
    const uint32_t st64 = opaque(reg0 + grp * A_SBO + (j >> 1) * A_LBO + (j & 1) * 8);
    const uint32_t st32 = opaque(reg0 + grp * A_SBO + (8 + (j >> 2)) * A_LBO + (j & 3) * 4);
    uint32_t accB[8][3] = {}, accC[8][3] = {};
    static_assert(2 * PREFETCH_ROWS == NSLOT, "prefetch slot arithmetic");
    uint32_t so = 0, bo = 0, par = 0, tbl = sb + SM_ROWS + PREFETCH_ROWS * 4;
    const uint32_t tbl_end = sb + SM_ROWS + wk.rows * 4;
    bool x_ready = false;
    named_bar(1, 128);
    mbar_wait(bars, 0);
    uint32_t w[3][3][3];
#pragma unroll
    for (int tap = 0; tap < 9; tap++) {
        const uint32_t p = reg0 + (NSLOT - 1) * SLOT_BYTES + tap * CH * 2;
        uint32_t u0, u1;
        lds64(u0, u1, p + 8 * j);
        __syncwarp();
        sts64(p + 8 * j, u1, u0);
        __syncwarp();
        lds64(w[tap / 3][tap % 3][1], w[tap / 3][tap % 3][0], p + 8 * j);
        lds32(w[tap / 3][tap % 3][2], p + 128 + 4 * j);
    }
    {
        const int first = wk.nA + 2;
#pragma unroll 1
        for (int k = 0; k < wk.rows; k++) {
            if (!x_ready) mbar_wait(bars + bo, par);
            const bool wrap = bo == (NSLOT - 1) * 32, low = bo < PREFETCH_ROWS * 32;
            const uint32_t nbo = wrap ? 0 : bo + 32, npar = par ^ wrap;
            const uint32_t pbo = low ? bo + PREFETCH_ROWS * 32 : bo - PREFETCH_ROWS * 32, ppar = par ^ low;
            uint32_t out[8][3];
            int code;
            bool e_ready;
#pragma unroll
            for (int p = 0; p < 10; p++) {
                uint32_t xv[3];
                lds64(xv[0], xv[1], so + ld64 + p * 192);
                lds32(xv[2], so + ld32 + p * 192);
                if (p == 9) {
                    asm volatile("ld.shared.u32 %0, [%1];" : "=r"(code) : "r"(tbl));
                    e_ready = mbar_test(bars + (BAR_E - SM_BAR) + pbo, ppar);
                    x_ready = mbar_test(bars + nbo, npar);
                }
#pragma unroll
                for (int dx = 0; dx < 3; dx++) {
                    const int o = p - dx;
                    if (o < 0 || o > 7) continue;
#pragma unroll
                    for (int q = 0; q < 3; q++) {
                        out[o][q] = bf_fma(xv[q], w[2][dx][q], dx == 0 ? accB[o][q] : out[o][q]);
                        accB[o][q] = bf_fma(xv[q], w[1][dx][q], dx == 0 ? accC[o][q] : accB[o][q]);
                        accC[o][q] = dx == 0 ? bf_mul(xv[q], w[0][dx][q]) : bf_fma(xv[q], w[0][dx][q], accC[o][q]);
                    }
                }
            }
            __syncwarp();
#pragma unroll
            for (int o = 0; o < 8; o++) {
                sts64(so + st64 + o * 16, out[o][0], out[o][1]);
                sts32(so + st32 + o * 16, out[o][2]);
            }
            const bool halo = k < 2 || (unsigned)(k - first) < 2;
            if (halo) fence_async();
            __syncwarp();
            elect_arrive(bars + (BAR_A - SM_BAR) + bo, bars + (BAR_E - SM_BAR) + bo, halo);
            if (tbl < tbl_end) {
                if (!e_ready) mbar_wait(bars + (BAR_E - SM_BAR) + pbo, ppar);
                code = __shfl_sync(~0u, code, 0);
                if (elect_one()) issue_region(tm, reg0 + (low ? so + PREFETCH_ROWS * SLOT_BYTES : so - PREFETCH_ROWS * SLOT_BYTES), bars + pbo, warp, code);
            }
            tbl += 4;
            so = wrap ? 0 : so + SLOT_BYTES;
            bo = nbo;
            par = npar;
        }
    }
}

template <bool V> struct Flag { static constexpr bool value = V; };
template <bool SCALED, int K0 = 0, int K1 = 3>
__device__ __forceinline__ void gelu_sq(uint32_t (&d)[24], uint32_t (&keep)[24], uint32_t sq_addr, uint32_t scale2) {
    pin(d);
#pragma unroll
    for (int k = K0; k < K1; k++) {
        uint32_t hs[4];
        lds128(hs[0], hs[1], hs[2], hs[3], sq_addr + k * CONS_THREADS * 16);
#pragma unroll
        for (int q = 0; q < 4; q++) {
            uint32_t g0 = gelu2(d[8 * k + 2 * q]), g1 = gelu2(d[8 * k + 2 * q + 1]);
            keep[8 * k + 2 * q] = g0;
            keep[8 * k + 2 * q + 1] = g1;
            if (SCALED) { g0 = h_mul(g0, scale2); g1 = h_mul(g1, scale2); }
            hs[q] = h_fma(g1, g1, h_fma(g0, g0, hs[q]));
        }
        sts128(sq_addr + k * CONS_THREADS * 16, hs[0], hs[1], hs[2], hs[3]);
    }
}
__device__ __forceinline__ void anchor(uint32_t addr, uint32_t a, uint32_t b, uint32_t c, uint32_t d) {
    asm volatile("{\n.reg .pred p;\nsetp.eq.b32 p, %0, 0;\n@p st.shared.v4.u32 [%0], {%1, %2, %3, %4};\n}\n"
                 ::"r"(addr), "r"(a), "r"(b), "r"(c), "r"(d) : "memory");
}
template <bool SCALED>
__device__ __forceinline__ void gelu_sq_reg(uint32_t (&d)[24], uint32_t (&hs)[12], uint32_t scale2) {
    pin(d);
#pragma unroll
    for (int q = 0; q < 12; q++) {
        uint32_t g0 = gelu2(d[2 * q]), g1 = gelu2(d[2 * q + 1]);
        if (SCALED) { g0 = h_mul(g0, scale2); g1 = h_mul(g1, scale2); }
        hs[q] = h_fma(g1, g1, h_fma(g0, g0, hs[q]));
    }
}
__device__ __forceinline__ void gelu_to(uint32_t (&g)[12], uint32_t (&d)[12]) {
    pin(d);
#pragma unroll
    for (int q = 0; q < 12; q++) g[q] = gelu2(d[q]);
    pin(g);
}
__device__ __forceinline__ void load_tile(uint32_t (&raw)[6][4], uint32_t addr) {
#pragma unroll
    for (int s = 0; s < 6; s++) ldsm4(raw[s], addr + s * 2 * A_LBO);
}
__device__ __forceinline__ uint2 ln_stats(const uint32_t (&raw)[6][4], uint64_t ones) {
    uint32_t sq[6][4];
#pragma unroll
    for (int s = 0; s < 6; s++)
#pragma unroll
        for (int q = 0; q < 4; q++) sq[s][q] = bf_mul(raw[s][q], raw[s][q]);
    float sum[4], ssq[4];
    wg_fence();
    wgmma_rowsum<0>(sum, raw[0], ones);
#pragma unroll
    for (int s = 1; s < 6; s++) wgmma_rowsum<1>(sum, raw[s], ones);
    wgmma_rowsum<0>(ssq, sq[0], ones);
#pragma unroll
    for (int s = 1; s < 6; s++) wgmma_rowsum<1>(ssq, sq[s], ones);
    wg_commit();
    wg_wait<0>();
    uint32_t st[2];
#pragma unroll
    for (int h = 0; h < 2; h++) {
        asm volatile("" : "+f"(sum[2 * h]), "+f"(ssq[2 * h])::"memory");
        const float mean = sum[2 * h] * (1.f / CH);
        const float var = fmaxf(fmaf(ssq[2 * h], 1.f / CH, -mean * mean), 0.f);
        float rstd;
        asm("rsqrt.approx.ftz.f32 %0, %1;" : "=f"(rstd) : "f"(var + 1e-5f));
        rstd = bf_lo(pack_bf2(rstd * KZ, 0.f));
        st[h] = pack_bf2(rstd, -mean * rstd);
    }
    return make_uint2(st[0], st[1]);
}
__device__ __forceinline__ void ln_apply(uint32_t (&a)[6][4], const uint2& st) {
    const uint32_t sc[2] = {__byte_perm(st.x, 0, 0x1010), __byte_perm(st.y, 0, 0x1010)};
    const uint32_t sh[2] = {__byte_perm(st.x, 0, 0x3232), __byte_perm(st.y, 0, 0x3232)};
#pragma unroll
    for (int s = 0; s < 6; s++)
#pragma unroll
        for (int q = 0; q < 4; q++) {
            const uint32_t v = bf_fma(a[s][q], sc[q & 1], sh[q & 1]);
            a[s][q] = pack_h2(bf_lo(v), bf_hi(v));
        }
}
__device__ __forceinline__ void stagger_wait(int jt, int wgi) {
    if (jt > 0) named_bar(4 + wgi, 256);
}
__device__ __forceinline__ void stagger_pass(int jt, int wgi, int ntiles) {
    if (jt + 1 < ntiles) named_arrive(4 + (wgi == NCONS - 1 ? 0 : wgi + 1), 256);
}
struct Cursor {
    int slot;
    uint32_t par;
    __device__ __forceinline__ void advance(int n) {
        slot += n;
        if (slot >= NSLOT) { slot -= NSLOT; par ^= 1; }
    }
};
struct Descs {
    uint64_t w1[8][6];
    uint64_t w2[24];
    uint64_t ones;
};
template <int E0, int N>
__device__ __forceinline__ void gemm1_chunk(uint32_t (&d)[N], const uint32_t (&a)[6][4], const Descs& ds, int zero) {
#pragma unroll
    for (int s = 0; s < 6; s++) wgmma(d, a[s][0], a[s][1], a[s][2], a[s][3], ds.w1[E0 / 48][s], s ? 1 : zero);
}
template <int E0, int N>
__device__ __forceinline__ void gemm2_chunk(uint32_t (&acc)[24], const uint32_t (&g)[N], const Descs& ds) {
#pragma unroll
    for (int s = 0; s < N / 4; s++) wgmma(acc, g[4 * s], g[4 * s + 1], g[4 * s + 2], g[4 * s + 3], ds.w2[E0 / 16 + s], 1);
}

__global__ void __launch_bounds__(NTHREADS, 1)
block_kernel(const __grid_constant__ CUtensorMap tmap, const __grid_constant__ CUtensorMap tmap_w1,
             const __nv_bfloat16* __restrict__ x, const __nv_bfloat16* __restrict__ dw, const __nv_bfloat16* __restrict__ w2,
             const __nv_bfloat16* __restrict__ gamma, const __nv_bfloat16* __restrict__ beta, __nv_bfloat16* __restrict__ out, const __grid_constant__ Descs ds,
             const int zero, const int per_cta, const int extra) {
    extern __shared__ __align__(1024) uint8_t smem[];
    constexpr uint32_t sb = SB;
    const int tid = threadIdx.x;
    const Work wk = get_work(per_cta, extra);
    if (smem_u32(smem) != SB || wk.rows + 4 > MAX_ROWS) __trap();
    constexpr uint32_t s_red = sb + SM_RED;

    PROF(0);
    const int warp_id = __shfl_sync(~0u, tid >> 5, 0);
    if (warp_id < 4 && elect_one()) first_loads(wk, &tmap, &tmap_w1, dw, sb, warp_id);
    __syncwarp();
    const int cw = warp_id - 4, wgi = cw >> 2, w4 = warp_id & 3;
    const int ntiles = wk.nA + wk.nB;
    const int wg = warp_id >> 2;
    uint32_t a[6][4], tile_off, next_off, stage, inv_rho2 = 0, rpar = 0, bias_addr, lane16, lane_off;
    auto set_lane = [&](uint32_t lane) {
        bias_addr = sb + SM_BIASH + (lane & 3) * 96;
        lane16 = lane * 16;
        lane_off = ((lane >> 2) * CH + 8 * (lane & 3)) * 2;
    };
    const uint32_t bar_r = sb + BAR_R + warp_id * 8;
    auto load_bias = [&](uint32_t (&acc)[24]) {
#pragma unroll
        for (int q = 0; q < 6; q++) lds128(acc[4 * q], acc[4 * q + 1], acc[4 * q + 2], acc[4 * q + 3], bias_addr + q * 16);
    };
    auto load_frags = [&](bool on) {
#pragma unroll
        for (int s = 0; s < 6; s++) ldg128_if(on, a[s], reinterpret_cast<const char*>(out) + next_off + w4 * WARP_BYTES + lane16 + s * 512);
    };
    auto stage_x = [&]() {
        if (elect_one()) {
            mbar_expect_tx(bar_r, WARP_BYTES);
            bulk_load_stream(stage, reinterpret_cast<const char*>(x) + tile_off + w4 * WARP_BYTES, WARP_BYTES, bar_r);
        }
    };
    auto epilogue = [&](uint32_t (&acc)[24]) {
        pin(acc);
        rpar ^= 1;
        uint4* op = reinterpret_cast<uint4*>(reinterpret_cast<char*>(out) + tile_off + w4 * WARP_BYTES + lane_off);
#pragma unroll
        for (int h = 0; h < 2; h++)
#pragma unroll
            for (int m = 0; m < 3; m++) {
                uint32_t xin[4], o[4];
                lds128(xin[0], xin[1], xin[2], xin[3], stage + lane_off + h * 1536 + m * 64);
#pragma unroll
                for (int q = 0; q < 4; q++) {
                    const uint32_t v = acc[2 * (4 * m + q) + h];
                    o[q] = bf_fma(pack_bf2(h_lo(v), h_hi(v)), inv_rho2, xin[q]);
                }
                __stcs(op + h * 96 + m * 4, make_uint4(o[0], o[1], o[2], o[3]));
            }
        __syncwarp();
    };
    if (warp_id < 4) {
        conv_producer(wk, &tmap, sb, warp_id);
        set_lane(opaque(tid & 31));
        const bool leader = warp_id == 0 && lane16 == 0;
        if (leader) {
            spin_until(&g_prep, (__float_as_uint(ldsf(s_red + 48)) + 1) * W2_GROUPS);
            asm volatile("fence.proxy.async.global;" ::: "memory");
        }
        PROF(2);
        named_bar(3, NTHREADS);
        if (leader) {
            fence_async();
            mbar_expect_tx(sb + BAR_W, EX * CH * 2);
            bulk_load(sb + SM_W2, g_w2h, EX * CH * 2, sb + BAR_W);
        }
        stage = sb + SM_RING + (wk.rows % NSLOT) * SLOT_BYTES + w4 * REGION_BYTES;
        lds32(next_off, sb + SM_TILES);
#pragma unroll
        for (int s = 0; s < 6; s++) a[s][0] = a[s][1] = a[s][2] = a[s][3] = 0;
        load_frags(true);
    } else {
        {
            const int ct = tid - 128, lane = tid & 31, g = lane >> 2, t = lane & 3;
            const unsigned epoch = *reinterpret_cast<volatile unsigned*>(&g_count);
            const int r = lane & 7, mi = lane >> 3;
            const uint32_t src = sb + SM_W2 + (cw >> 1) * (64 * CH * 2) + r * 128 + ((((cw & 1) * 4 + mi) ^ r) * 16);
            const uint32_t dst = sb + SM_W1 + (4 * cw + mi) * 1536 + r * 16;
            named_bar(0, NTHREADS);
            mbar_wait(sb + BAR_W + (cw >> 1) * 8, 0);
            uint32_t wmax[4] = {}, wsum[4] = {};
#pragma unroll 3
            for (int c = 0; c < 12; c++) {
                uint32_t u[4];
                ldsm4_t(u, src + c * 1024);
#pragma unroll
                for (int q = 0; q < 4; q++) {
                    wmax[q] = bf_absmax(wmax[q], u[q]);
                    wsum[q] = bf_fma(u[q], 0x3f803f80u, wsum[q]);
                    u[q] = pack_h2(bf_lo(u[q]), bf_hi(u[q]));
                }
                stsm4(dst + c * 128, u[0], u[1], u[2], u[3]);
            }
            float mean[4];
            bool center = false;
#pragma unroll
            for (int q = 0; q < 4; q++) {
                uint32_t m = wmax[q];
                float sum = bf_lo(wsum[q]) + bf_hi(wsum[q]);
#pragma unroll
                for (int o = 1; o <= 2; o <<= 1) { m = bf_absmax(m, __shfl_xor_sync(~0u, m, o)); sum += __shfl_xor_sync(~0u, sum, o); }
                mean[q] = sum * (1.f / CH);
                center |= fabsf(mean[q]) > 0.2f * fmaxf(fabsf(bf_lo(m)), fabsf(bf_hi(m)));
            }
            if (__any_sync(~0u, center)) {
#pragma unroll 1
                for (int pass = 0; pass < 2; pass++) {
                    float sum[4] = {};
#pragma unroll 1
                    for (int c = 0; c < 12; c++) {
                        uint32_t u[4];
                        ldsm4_t(u, src + c * 1024);
#pragma unroll
                        for (int q = 0; q < 4; q++) {
                            sum[q] += bf_lo(u[q]) + bf_hi(u[q]);
                            u[q] = pack_h2(bf_lo(u[q]) - mean[q], bf_hi(u[q]) - mean[q]);
                        }
                        stsm4(dst + c * 128, u[0], u[1], u[2], u[3]);
                    }
#pragma unroll
                    for (int q = 0; q < 4; q++) {
                        sum[q] += __shfl_xor_sync(~0u, sum[q], 1);
                        sum[q] += __shfl_xor_sync(~0u, sum[q], 2);
                        mean[q] = sum[q] * (1.f / CH);
                    }
                }
            }
            const float w1max = warp_absmax(bf_absmax(bf_absmax(wmax[0], wmax[1]), bf_absmax(wmax[2], wmax[3])));
            if (lane == 0) sts32(s_red + cw * 4, __float_as_uint(w1max));
            if (ct < 32) sts32(sb + SM_ONES + ct * 4, 0x3f803f80u);
            if (blockIdx.x == 0) {
#pragma unroll
                for (int q = 0; q < REPLICAS; q++) g_sums[(epoch & 1) ^ 1][q][ct] = 0;
                if (ct < CH) g_bias[(epoch & 1) ^ 1][ct] = 0.f;
            }
            if (ct == 0) sts32(s_red + 48, epoch);
            fence_async();
            named_bar(2, CONS_THREADS);
#pragma unroll
            for (int q = 0; q < 6; q++) sts128(sb + SM_SQ + (q * CONS_THREADS + ct) * 16, 0, 0, 0, 0);
            mbar_wait(sb + BAR_A + w4 * 8 + 32, 0);
            if (cw == 4 * NCONS - 1) {
#pragma unroll 1
                for (int q = gridDim.x - 1 - blockIdx.x; q < W2_GROUPS; q += gridDim.x) {
                    uint32_t u[3][4], rmax = 0;
#pragma unroll
                    for (int m = 0; m < 3; m++) {
                        const uint4 w = ldg128_ordered(w2 + (8 * q + g) * CH + 32 * m + 8 * t);
                        u[m][0] = w.x; u[m][1] = w.y; u[m][2] = w.z; u[m][3] = w.w;
                    }
                    const float bt = __bfloat162float(beta[8 * q + g]);
#pragma unroll
                    for (int k = 0; k < 12; k++) rmax = bf_absmax(rmax, u[k >> 2][k & 3]);
                    rmax = bf_absmax(rmax, __shfl_xor_sync(~0u, rmax, 1));
                    rmax = bf_absmax(rmax, __shfl_xor_sync(~0u, rmax, 2));
                    const float mx = fmaxf(fabsf(bf_lo(rmax)), fabsf(bf_hi(rmax))), sc = row_scale(mx);
                    if (t == 0) g_w2max[8 * q + g] = mx;
#pragma unroll
                    for (int k = 0; k < 12; k++) {
                        float lo = bf_lo(u[k >> 2][k & 3]), hi = bf_hi(u[k >> 2][k & 3]);
                        g_w2h[k * 1536 + q * 32 + lane] = transpose8x8(pack_h2(lo * sc, hi * sc));
                        lo *= bt; hi *= bt;
#pragma unroll
                        for (int o = 4; o <= 16; o <<= 1) { lo += __shfl_xor_sync(~0u, lo, o); hi += __shfl_xor_sync(~0u, hi, o); }
                        if (g == 0) {
                            float* dst = &g_bias[epoch & 1][32 * (k >> 2) + 8 * t + 2 * (k & 3)];
                            asm volatile("red.global.add.v2.f32 [%0], {%1, %2};" ::"l"(dst), "f"(lo), "f"(hi) : "memory");
                        }
                    }
                    asm volatile("fence.proxy.async.global;" ::: "memory");
                    __syncwarp();
                    if (lane == 0) asm volatile("red.release.gpu.global.add.u32 [%0], 1;" ::"l"(&g_prep) : "memory");
                }
            }
        }

        PROF(1);
        const uint32_t a_addr = opaque(sb + SM_RING + w4 * REGION_BYTES + ((tid >> 3) & 1) * A_SBO + ((tid >> 4) & 1) * A_LBO + (tid & 7) * 16);
        const uint32_t bar_a = sb + BAR_A + w4 * 8, bar_e = sb + BAR_E + w4 * 8;
        const uint32_t sq = opaque(sb + SM_SQ + (tid - 128) * 16);
        auto max_w1 = [&]() {
            float m = 0.f;
#pragma unroll
            for (int q = 0; q < 3; q++) {
                uint32_t u[4];
                lds128(u[0], u[1], u[2], u[3], s_red + q * 16);
#pragma unroll
                for (int k = 0; k < 4; k++) m = fmaxf(m, __uint_as_float(u[k]));
            }
            return m;
        };
        auto square_exp = [&](float w1max) {
            const int e = w1max > 0.f ? 4 - ilog2f(2.f * KZ * 96.f * w1max) : 0;
            return (e >= 0 && e <= 6) ? 0 : max(-14, min(e, 14));
        };
        uint32_t k1[24], k2[24], k3[24];
        Cursor cur = {2, 0};
        int jt = wgi;
        {
            constexpr int SQC = 3 * CONS_THREADS * 16;
            cur.advance(wgi + (wgi >= wk.nA ? 2 : 0));
            int sq_e = square_exp(max_w1());
            uint32_t scale2 = pack_h2(pow2i(sq_e), pow2i(sq_e));
            auto run = [&](auto scaled_tag) {
                constexpr bool SCALED = decltype(scaled_tag)::value;
                uint32_t hs2[12] = {}, hs3[12] = {};
#pragma unroll 1
                for (; jt + NCONS < ntiles; jt += NCONS) {
                    uint32_t a[6][4], d0[24], d1[24], unused[24];
                    stagger_wait(jt, wgi);
                    mbar_wait(bar_a + cur.slot * 32, cur.par);
                    load_tile(a, a_addr + cur.slot * SLOT_BYTES);
                    const uint2 st = ln_stats(a, ds.ones);
                    ln_apply(a, st);
                    wg_fence();
                    gemm1_chunk<0>(d0, a, ds, 0);
                    wg_commit();
                    gemm1_chunk<96>(d1, a, ds, 0);
                    wg_commit();
                    {
                        char* ap = reinterpret_cast<char*>(out) + (tile_offset(wk.t0 + jt) + w4 * WARP_BYTES - (sb + SM_SQ + cw * 512) + sq);
#pragma unroll
                        for (int s = 0; s < 6; s++) stg128(ap + s * 512, a[s]);
                    }
                    wg_wait<1>();
                    gelu_sq<SCALED, 0, S1_PASS>(d0, unused, sq, scale2);
                    stagger_pass(jt, wgi, ntiles);
                    gelu_sq<SCALED, S1_PASS, 3>(d0, unused, sq, scale2);
                    if (elect_one()) mbar_arrive(bar_e + cur.slot * 32);
                    wg_fence();
                    gemm1_chunk<192>(d0, a, ds, zero);
                    wg_commit();
                    wg_wait<1>();
                    gelu_sq<SCALED>(d1, unused, sq + SQC, scale2);
                    wg_fence();
                    gemm1_chunk<288>(d1, a, ds, zero);
                    wg_commit();
                    wg_wait<1>();
                    gelu_sq_reg<SCALED>(d0, hs2, scale2);
                    anchor(sq, hs2[8], hs2[9], hs2[10], hs2[11]);
                    wg_wait<0>();
                    gelu_sq_reg<SCALED>(d1, hs3, scale2);
                    cur.advance(NCONS + ((jt < wk.nA && jt + NCONS >= wk.nA) ? 2 : 0));
                }
#pragma unroll
                for (int k = 0; k < 3; k++) {
                    sts128(sq + 2 * SQC + k * CONS_THREADS * 16, hs2[4 * k], hs2[4 * k + 1], hs2[4 * k + 2], hs2[4 * k + 3]);
                    sts128(sq + 3 * SQC + k * CONS_THREADS * 16, hs3[4 * k], hs3[4 * k + 1], hs3[4 * k + 2], hs3[4 * k + 3]);
                }
            };
            if (sq_e == 0) run(Flag<false>());
            else run(Flag<true>());
            sq_e = square_exp(max_w1());
            scale2 = pack_h2(pow2i(sq_e), pow2i(sq_e));
            {
                uint32_t a[6][4], d0[24], d1[24], d3[24], k0[24];
                stagger_wait(jt, wgi);
                mbar_wait(bar_a + cur.slot * 32, cur.par);
                load_tile(a, a_addr + cur.slot * SLOT_BYTES);
                const uint2 st = ln_stats(a, ds.ones);
                ln_apply(a, st);
                wg_fence();
                gemm1_chunk<0>(d0, a, ds, 0);
                wg_commit();
                gemm1_chunk<96>(d1, a, ds, 0);
                wg_commit();
                stage = sb + SM_RING + cur.slot * SLOT_BYTES + w4 * REGION_BYTES;
                wg_wait<1>();
                gelu_sq<true, 0, S1_PASS>(d0, k0, sq, scale2);
                stagger_pass(jt, wgi, ntiles);
                gelu_sq<true, S1_PASS, 3>(d0, k0, sq, scale2);
#pragma unroll
                for (int q = 0; q < 6; q++) sts128(stage - (sb + SM_SQ + cw * 512) + sq + q * 512, k0[4 * q], k0[4 * q + 1], k0[4 * q + 2], k0[4 * q + 3]);
                wg_fence();
                gemm1_chunk<192>(d0, a, ds, zero);
                wg_commit();
                wg_wait<1>();
                gelu_sq<true>(d1, k1, sq + SQC, scale2);
                wg_fence();
                gemm1_chunk<288>(d3, a, ds, 0);
                wg_commit();
                wg_wait<1>();
                gelu_sq<true>(d0, k2, sq + 2 * SQC, scale2);
                wg_wait<0>();
                gelu_sq<true>(d3, k3, sq + 3 * SQC, scale2);
            }
            named_bar(2, CONS_THREADS);
            const int lane = (sq >> 4) & 31, t = lane & 3, part = lane >> 2;
            const float w1max = max_w1();
            const uint32_t src = sb + SM_SQ + (cw * CONS_THREADS + part * 4 + t) * 16;
            float f[8] = {};
#pragma unroll
            for (int r = 0; r < 12; r++) {
                uint32_t u[4];
                lds128(u[0], u[1], u[2], u[3], src + r * 512);
#pragma unroll
                for (int q = 0; q < 4; q++) { f[2 * q] += h_lo(u[q]); f[2 * q + 1] += h_hi(u[q]); }
            }
            const bool b2 = part & 4, b1 = part & 2, b0 = part & 1;
            float r4[4], r2[2];
#pragma unroll
            for (int q = 0; q < 4; q++) r4[q] = (b2 ? f[q + 4] : f[q]) + __shfl_xor_sync(~0u, b2 ? f[q] : f[q + 4], 16);
#pragma unroll
            for (int q = 0; q < 2; q++) r2[q] = (b1 ? r4[q + 2] : r4[q]) + __shfl_xor_sync(~0u, b1 ? r4[q] : r4[q + 2], 8);
            const float tot = (b0 ? r2[1] : r2[0]) + __shfl_xor_sync(~0u, b0 ? r2[0] : r2[1], 4);
            const unsigned long long fixed = __float2ull_rn(fminf(tot * pow2i(sum_exp(w1max) - 2 * square_exp(w1max)), 0x1p49f));
            atomicAdd(&g_sums[__float_as_uint(ldsf(s_red + 48)) & 1][blockIdx.x % REPLICAS][32 * cw + 8 * (part >> 1) + 2 * t + (part & 1)], fixed << 8 | 1);
        }
        PROF(2);
        named_bar(3, NTHREADS);
        tile_off = tile_offset(wk.t0 + jt);
        {
            const int ct = (sq - (sb + SM_SQ)) >> 4, lane = ct & 31;
            const float w1max = max_w1();
            const unsigned epoch = __float_as_uint(ldsf(s_red + 48));
            set_lane(lane);
            if (elect_one()) prefetch_l2(reinterpret_cast<const char*>(x) + tile_off + w4 * WARP_BYTES, WARP_BYTES);
            const float gam = __bfloat162float(gamma[ct]), rmax = __ldcg(&g_w2max[ct]);
            const int tt = ct / 24, jb = (ct % 24) >> 1;
            float2 bpair = make_float2(0.f, 0.f);
            if (ct < 96) bpair = __ldcg(reinterpret_cast<const float2*>(&g_bias[epoch & 1][32 * (jb >> 2) + 8 * tt + 2 * (jb & 3)]));
            const float gbound = fmaxf(2.f * KZ * 9.7979590f * 192.f * w1max, 1.f) * 19.5959180f * INV_2KZ;
            const float fixed = __uint_as_float(__reduce_max_sync(~0u, __float_as_uint(fmaf(gbound, rmax, fmaxf(fabsf(bpair.x), fabsf(bpair.y))))));
            unsigned long long sum;
            for (unsigned n = 0;; n++) {
                unsigned cnt = 0;
                sum = 0;
#pragma unroll
                for (int q = 0; q < REPLICAS; q++) {
                    unsigned long long v;
                    asm volatile("ld.relaxed.gpu.global.u64 %0, [%1];" : "=l"(v) : "l"(&g_sums[epoch & 1][q][ct]) : "memory");
                    cnt += (unsigned)v & 255u;
                    sum += v >> 8;
                }
                if (__all_sync(~0u, cnt == gridDim.x)) break;
                if (n > SPIN_LIMIT) __trap();
            }
            PROF(3);
            if (blockIdx.x == 0 && ct == 0) g_count = epoch + 1;
            const float gx = grn_norm(__ull2float_rn(sum) * pow2i(-sum_exp(w1max)));
            float tot = gx;
#pragma unroll
            for (int o = 16; o >= 1; o >>= 1) tot += __shfl_xor_sync(~0u, tot, o);
            const float vary = __uint_as_float(__reduce_max_sync(~0u, __float_as_uint(fabsf(gam) * gx * rmax)));
            if (lane == 0) {
                sts32(s_red + 64 + cw * 4, __float_as_uint(tot));
                sts32(s_red + 128 + cw * 4, __float_as_uint(vary));
                sts32(s_red + 192 + cw * 4, __float_as_uint(fixed));
            }
            named_bar(2, CONS_THREADS);
            float vmax = 0.f, fmax2 = 0.f;
            tot = 0.f;
#pragma unroll
            for (int q = 0; q < 3; q++) {
                uint32_t u[4], v[4], w[4];
                lds128(u[0], u[1], u[2], u[3], s_red + 64 + q * 16);
                lds128(v[0], v[1], v[2], v[3], s_red + 128 + q * 16);
                lds128(w[0], w[1], w[2], w[3], s_red + 192 + q * 16);
#pragma unroll
                for (int k = 0; k < 4; k++) { tot += __uint_as_float(u[k]); vmax = fmaxf(vmax, __uint_as_float(v[k])); fmax2 = fmaxf(fmax2, __uint_as_float(w[k])); }
            }
            const float inv_mean = __fdividef(1.f, tot * (1.f / EX) + 1e-6f);
            const float bound = fmaf(gbound * vmax, inv_mean, 2.f * fmax2);
            const int rho_e = bound > 0.f ? 14 - ilog2f(bound) : 0;
            const float rho = pow2i(rho_e), inv_rho = pow2i(-rho_e);
            inv_rho2 = pack_bf2(inv_rho, inv_rho);
            const float f_own = __fdividef(fmaf(gam, gx * inv_mean, 1.f) * INV_2KZ * rho, row_scale(rmax));
            const uint32_t pk = pack_h2(f_own, __shfl_down_sync(~0u, f_own, 1));
            uint32_t f2[4];
#pragma unroll
            for (int q = 0; q < 4; q++) f2[q] = __shfl_sync(~0u, pk, (lane & 24) + 2 * q);
            if (ct < 96) sts32(sb + SM_BIASH + ct * 4, pack_h2(bpair.x * rho, bpair.y * rho));
            if (ct == 96) sts32(s_red + 52, inv_rho2);
            mbar_wait(sb + BAR_W, 1);
#pragma unroll
            for (int nb = 0; nb < 12; nb++) {
                uint32_t a, b, c, d;
                const uint32_t ad = sb + SM_W2 + nb * 6144 + ct * 16;
                lds128(a, b, c, d, ad);
                sts128(ad, h_round8(h_mul(a, f2[0])), h_round8(h_mul(b, f2[1])), h_round8(h_mul(c, f2[2])), h_round8(h_mul(d, f2[3])));
            }
            fence_async();
            named_bar(3, NTHREADS);
        }
        PROF(4);
        {
            uint32_t acc[24];
            load_bias(acc);
            lds32(next_off, sb + SM_TILES + wg * 4);
            if (wgi > 0) named_bar(8 + wgi, 256);
            pin(k1); pin(k2); pin(k3);
            wg_fence();
            gemm2_chunk<288>(acc, k3, ds);
            wg_commit();
            gemm2_chunk<96>(acc, k1, ds);
            gemm2_chunk<192>(acc, k2, ds);
            wg_commit();
            if (wgi + 1 < NCONS) named_arrive(9 + wgi, 256);
            wg_wait<1>();
            uint32_t k0[24];
#pragma unroll
            for (int q = 0; q < 6; q++) lds128(k0[4 * q], k0[4 * q + 1], k0[4 * q + 2], k0[4 * q + 3], stage + lane16 + q * 512);
            pin(k0);
            wg_fence();
            gemm2_chunk<0>(acc, k0, ds);
            wg_commit();
            stage_x();
            wg_wait<1>();
            load_frags(true);
            if (lane16 == 0) mbar_arrive(sb + BAR_PIN);
            mbar_wait(bar_r, rpar);
            wg_wait<0>();
            epilogue(acc);
        }
    }
    {
        const int nrest = ntiles - NCONS;
        for (int jt = wg; jt < nrest; jt += 4) {
            uint32_t d0[12], d1[12], g0[12], g1[12], acc[24];
            tile_off = next_off;
            lds32(next_off, sb + SM_TILES + (jt + 4) * 4);
            if (jt >= S2_FIRST) named_bar(4 + wg, 256);
            wg_fence();
            gemm1_chunk<0>(d0, a, ds, 0);
            wg_commit();
            gemm1_chunk<48>(d1, a, ds, 0);
            wg_commit();
            load_bias(acc);
            const bool more = jt + 4 < nrest;
            tile_off = __shfl_sync(~0u, tile_off, 0);
            next_off = __shfl_sync(~0u, next_off, 0);
            wg_wait<1>();
#define CNX_PASS if (jt + 1 >= S2_FIRST && jt + 1 < nrest) named_arrive(4 + ((wg + 1) & 3), 256);
#define CNX_STEP(C, D, G)                                              \
    gelu_to(G, D);                                                     \
    if (C == 0 && jt == 0) {                                           \
        named_bar(3, NTHREADS);                                        \
        load_bias(acc);                                                \
        lds32(inv_rho2, s_red + 52);                                   \
    }                                                                  \
    wg_fence();                                                        \
    if (C < 6) gemm1_chunk<48 * (C < 6 ? C + 2 : 0)>(D, a, ds, zero); \
    gemm2_chunk<48 * C>(acc, G, ds);                                  \
    wg_commit();                                                       \
    if (C == S2_PASS) { CNX_PASS }                                     \
    wg_wait<(C < 7 ? 1 : 0)>();
            CNX_STEP(0, d0, g0)
            stage_x();
            if (more && elect_one()) prefetch_l2(reinterpret_cast<const char*>(out) + next_off + w4 * WARP_BYTES, WARP_BYTES);
            CNX_STEP(1, d1, g1)
            CNX_STEP(2, d0, g0)
            CNX_STEP(3, d1, g1)
            CNX_STEP(4, d0, g0)
            CNX_STEP(5, d1, g1)
            CNX_STEP(6, d0, g0)
            load_frags(more);
            if (lane16 == 0) mbar_arrive(sb + BAR_PIN);
            mbar_wait(bar_r, rpar);
            CNX_STEP(7, d1, g1)
#undef CNX_STEP
            epilogue(acc);
        }
    }
    PROF(5);
}

}

typedef CUresult (*EncodeTiledFn)(CUtensorMap*, CUtensorMapDataType, cuuint32_t, void*, const cuuint64_t*, const cuuint64_t*,
                                  const cuuint32_t*, const cuuint32_t*, CUtensorMapInterleave, CUtensorMapSwizzle,
                                  CUtensorMapL2promotion, CUtensorMapFloatOOBfill);

extern "C" void kernel_launch(void* const* d_in, const int* in_sizes, int n_in, void* d_out, int out_size) {
    using namespace cnx;
    static EncodeTiledFn encode = nullptr;
    static int num_sms = 0;
    if (!encode) {
        void* fn = nullptr;
        cudaDriverEntryPointQueryResult qr;
        cudaGetDriverEntryPoint("cuTensorMapEncodeTiled", &fn, cudaEnableDefault, &qr);
        encode = (EncodeTiledFn)fn;
        int dev = 0;
        cudaGetDevice(&dev);
        cudaDeviceGetAttribute(&num_sms, cudaDevAttrMultiProcessorCount, dev);
        if (num_sms > MAX_CTAS) num_sms = MAX_CTAS;
        cudaFuncSetAttribute(block_kernel, cudaFuncAttributeMaxDynamicSharedMemorySize, SM_TOTAL);
    }
    CUtensorMap tm;
    cuuint64_t dims[3] = {(cuuint64_t)CH, (cuuint64_t)IMG_W, (cuuint64_t)IMG_H};
    cuuint64_t strides[2] = {(cuuint64_t)CH * 2, (cuuint64_t)CH * 2 * IMG_W};
    cuuint32_t box[3] = {(cuuint32_t)CH, (cuuint32_t)REGION_PX, 1};
    cuuint32_t estr[3] = {1, 1, 1};
    encode(&tm, CU_TENSOR_MAP_DATA_TYPE_BFLOAT16, 3, d_in[0], dims, strides, box, estr, CU_TENSOR_MAP_INTERLEAVE_NONE,
           CU_TENSOR_MAP_SWIZZLE_NONE, CU_TENSOR_MAP_L2_PROMOTION_L2_128B, CU_TENSOR_MAP_FLOAT_OOB_FILL_NONE);
    Descs ds;
    for (int c = 0; c < 8; c++)
        for (int k = 0; k < 6; k++) ds.w1[c][k] = make_desc(SB + SM_W1 + c * 6 * 1536 + k * 256, 128, 1536);
    for (int k = 0; k < 24; k++) ds.w2[k] = make_desc(SB + SM_W2 + k * 256, 128, 6144);
    ds.ones = make_desc(SB + SM_ONES, 0, 0);
    CUtensorMap tw;
    cuuint64_t wdims[2] = {(cuuint64_t)EX, (cuuint64_t)CH};
    cuuint64_t wstrides[1] = {(cuuint64_t)EX * 2};
    cuuint32_t wbox[2] = {64, (cuuint32_t)CH};
    encode(&tw, CU_TENSOR_MAP_DATA_TYPE_BFLOAT16, 2, d_in[2], wdims, wstrides, wbox, estr, CU_TENSOR_MAP_INTERLEAVE_NONE,
           CU_TENSOR_MAP_SWIZZLE_128B, CU_TENSOR_MAP_L2_PROMOTION_L2_128B, CU_TENSOR_MAP_FLOAT_OOB_FILL_NONE);
    block_kernel<<<num_sms, NTHREADS, SM_TOTAL>>>(tm, tw, (const __nv_bfloat16*)d_in[0], (const __nv_bfloat16*)d_in[1],
                                             (const __nv_bfloat16*)d_in[3],
                                             (const __nv_bfloat16*)d_in[4], (const __nv_bfloat16*)d_in[5], (__nv_bfloat16*)d_out,
                                             ds, 0, NTILES / num_sms, NTILES % num_sms);
}
```

```cpp
#include <cuda_runtime.h>
#include <cuda_bf16.h>
#include <cuda_fp16.h>
#include <cuda.h>
#include <stdint.h>

namespace cnx {

constexpr int IMG_H = 512, IMG_W = 512, CH = 96, EX = 384;
constexpr int TILE_W = 64;
constexpr int NTILES = (IMG_W / TILE_W) * IMG_H;
constexpr int NSLOT = 6;
constexpr int REGION_PX = 18;
constexpr int REGION_BYTES = REGION_PX * CH * 2;
constexpr int SLOT_BYTES = 4 * REGION_BYTES;
constexpr int A_LBO = 144, A_SBO = 12 * A_LBO;
constexpr int PREFETCH_ROWS = 3;
constexpr int NCONS = 3;
constexpr int CONS_THREADS = 128 * NCONS;
constexpr int NTHREADS = 128 + CONS_THREADS;
constexpr int MAX_ROWS = 52;
constexpr int TILE_BYTES = TILE_W * CH * 2, WARP_BYTES = TILE_BYTES / 4;
constexpr int S1_PASS = 1, S2_PASS = 1;
#define S2_FIRST 4
#define ORDER_P 3
#define ORDER_Q 1
static_assert(MAX_ROWS <= 128, "one table entry per producer thread");
static_assert(2 * A_SBO == REGION_BYTES && REGION_BYTES % 128 == 0, "region layout");

constexpr uint32_t SB = 1024;
constexpr int SM_W1 = 0;
constexpr int SM_W2 = SM_W1 + CH * EX * 2;
constexpr int SM_RING = SM_W2 + CH * EX * 2;
constexpr int SM_BIASH = SM_RING + NSLOT * SLOT_BYTES;
constexpr int SM_RED = SM_BIASH + 384;
constexpr int SM_ROWS = SM_RED + 256;
constexpr int SM_TILES = SM_ROWS + MAX_ROWS * 4;
constexpr int SM_ONES = SM_TILES + MAX_ROWS * 4;
constexpr int SM_BAR = SM_ONES + 128;
constexpr int BAR_X = SM_BAR;
constexpr int BAR_A = BAR_X + NSLOT * 4 * 8;
constexpr int BAR_E = BAR_A + NSLOT * 4 * 8;
constexpr int BAR_PIN = BAR_E + NSLOT * 4 * 8;
constexpr int BAR_W = BAR_PIN + 8;
constexpr int BAR_R = BAR_W + 6 * 8;
constexpr int SM_TOTAL = BAR_R + 16 * 8;
constexpr int SM_SQ = SM_W2;
static_assert(SM_ONES % 16 == 0 && SM_TOTAL <= 232448, "shared memory budget");

constexpr float KZ = 0.3292034911525734f;
constexpr uint32_t GELU_C2 = 0x40d940d9u;
constexpr float INV_2KZ = 0.5f / KZ;
constexpr unsigned SPIN_LIMIT = 1u << 19;

constexpr int REPLICAS = 4;
__device__ unsigned long long g_sums[2][REPLICAS][EX];
constexpr int MAX_CTAS = 256;
__device__ unsigned g_count;
constexpr int W2_GROUPS = EX / 8;
__device__ __align__(128) uint32_t g_w2h[EX * CH / 2];
__device__ float g_w2max[EX];
__device__ __align__(16) float g_bias[2][CH];
__device__ unsigned g_prep;
constexpr int LENT = 2, MAX_LENDERS = MAX_CTAS / (8 * LENT + 1);
__device__ uint4 g_lent[MAX_LENDERS * LENT * 8 * 4 * 3 * 32];
__device__ unsigned g_lent_in, g_lent_out;

#define PROF(k)

__device__ __forceinline__ uint32_t smem_u32(const void* p) { return (uint32_t)__cvta_generic_to_shared(p); }
__device__ __forceinline__ void mbar_init(uint32_t bar, uint32_t cnt) {
    asm volatile("mbarrier.init.shared::cta.b64 [%0], %1;" ::"r"(bar), "r"(cnt) : "memory");
}
__device__ __forceinline__ void mbar_arrive(uint32_t bar) {
    asm volatile("mbarrier.arrive.shared::cta.b64 _, [%0];" ::"r"(bar) : "memory");
}
__device__ __forceinline__ void mbar_expect_tx(uint32_t bar, uint32_t bytes) {
    asm volatile("mbarrier.arrive.expect_tx.shared::cta.b64 _, [%0], %1;" ::"r"(bar), "r"(bytes) : "memory");
}
__device__ __forceinline__ bool mbar_try(uint32_t bar, uint32_t par) {
    uint32_t ok;
    asm volatile("{\n.reg .pred p;\nmbarrier.try_wait.parity.shared::cta.b64 p, [%1], %2;\nselp.u32 %0, 1, 0, p;\n}\n"
                 : "=r"(ok) : "r"(bar), "r"(par) : "memory");
    return ok != 0;
}
__device__ __forceinline__ void mbar_wait(uint32_t bar, uint32_t par) {
    unsigned n = 0;
    while (!mbar_try(bar, par)) {
        if (++n > SPIN_LIMIT) __trap();
    }
}
__device__ __forceinline__ bool mbar_test(uint32_t bar, uint32_t par) {
    uint32_t ok;
    asm volatile("{\n.reg .pred p;\nmbarrier.test_wait.parity.shared::cta.b64 p, [%1], %2;\nselp.u32 %0, 1, 0, p;\n}\n"
                 : "=r"(ok) : "r"(bar), "r"(par) : "memory");
    return ok != 0;
}
__device__ __forceinline__ bool elect_one() {
    uint32_t ok;
    asm volatile("{\n.reg .pred p;\nelect.sync _|p, 0xffffffff;\nselp.u32 %0, 1, 0, p;\n}\n" : "=r"(ok));
    return ok != 0;
}
__device__ __forceinline__ uint32_t opaque(uint32_t v) { return __shfl_sync(~0u, v, threadIdx.x & 31); }
__device__ __forceinline__ void named_bar(int id, int n) { asm volatile("bar.sync %0, %1;" ::"r"(id), "r"(n) : "memory"); }
__device__ __forceinline__ void named_arrive(int id, int n) { asm volatile("bar.arrive %0, %1;" ::"r"(id), "r"(n) : "memory"); }
__device__ __forceinline__ void fence_async() { asm volatile("fence.proxy.async.shared::cta;" ::: "memory"); }
__device__ __forceinline__ uint64_t evict_first() {
    uint64_t p;
    asm("createpolicy.fractional.L2::evict_first.b64 %0, 1.0;" : "=l"(p));
    return p;
}
__device__ __forceinline__ void tma_row(uint32_t dst, const CUtensorMap* tm, uint32_t bar, int x, int y) {
    asm volatile("cp.async.bulk.tensor.3d.shared::cluster.global.mbarrier::complete_tx::bytes.L2::cache_hint [%0], [%1, {%3, %4, %5}], [%2], %6;"
                 ::"r"(dst), "l"(tm), "r"(bar), "r"(0), "r"(x), "r"(y), "l"(evict_first()) : "memory");
}
__device__ __forceinline__ void bulk_load_stream(uint32_t dst, const void* src, uint32_t bytes, uint32_t bar) {
    asm volatile("cp.async.bulk.shared::cluster.global.mbarrier::complete_tx::bytes.L2::cache_hint [%0], [%1], %2, [%3], %4;"
                 ::"r"(dst), "l"(src), "r"(bytes), "r"(bar), "l"(evict_first()) : "memory");
}
__device__ __forceinline__ void prefetch_l2(const void* src, uint32_t bytes) {
    asm volatile("cp.async.bulk.prefetch.L2.global [%0], %1;" ::"l"(src), "r"(bytes) : "memory");
}
__device__ __forceinline__ void tma_2d(uint32_t dst, const CUtensorMap* tm, uint32_t bar, int x, int y) {
    asm volatile("cp.async.bulk.tensor.2d.shared::cluster.global.mbarrier::complete_tx::bytes [%0], [%1, {%3, %4}], [%2];"
                 ::"r"(dst), "l"(tm), "r"(bar), "r"(x), "r"(y) : "memory");
}
__device__ __forceinline__ void bulk_load(uint32_t dst, const void* src, uint32_t bytes, uint32_t bar) {
    asm volatile("cp.async.bulk.shared::cluster.global.mbarrier::complete_tx::bytes [%0], [%1], %2, [%3];"
                 ::"r"(dst), "l"(src), "r"(bytes), "r"(bar) : "memory");
}
__device__ __forceinline__ void wg_fence() { asm volatile("wgmma.fence.sync.aligned;" ::: "memory"); }
__device__ __forceinline__ void wg_commit() { asm volatile("wgmma.commit_group.sync.aligned;" ::: "memory"); }
template <int N> __device__ __forceinline__ void wg_wait() { asm volatile("wgmma.wait_group.sync.aligned %0;" ::"n"(N) : "memory"); }
template <int N> __device__ __forceinline__ void pin(uint32_t (&d)[N]) {
#pragma unroll
    for (int q = 0; q < N; q++) asm volatile("" : "+r"(d[q])::"memory");
}
__device__ __forceinline__ void stg128(void* p, const uint32_t (&v)[4]) {
    asm volatile("st.global.v4.u32 [%0], {%1, %2, %3, %4};" ::"l"(p), "r"(v[0]), "r"(v[1]), "r"(v[2]), "r"(v[3]) : "memory");
}
__device__ __forceinline__ void ldg128_if(bool on, uint32_t (&v)[4], const void* p) {
    asm volatile("{\n.reg .pred p;\nsetp.ne.b32 p, %5, 0;\n@p ld.global.L1::no_allocate.v4.u32 {%0, %1, %2, %3}, [%4];\n}\n"
                 : "+r"(v[0]), "+r"(v[1]), "+r"(v[2]), "+r"(v[3]) : "l"(p), "r"((int)on) : "memory");
}
__device__ __forceinline__ uint4 ldg128_ordered(const void* p) {
    uint4 v;
    asm volatile("ld.global.nc.v4.u32 {%0, %1, %2, %3}, [%4];" : "=r"(v.x), "=r"(v.y), "=r"(v.z), "=r"(v.w) : "l"(p) : "memory");
    return v;
}
__host__ __device__ constexpr uint64_t make_desc(uint32_t addr, uint32_t lbo, uint32_t sbo) {
    return (uint64_t)((addr & 0x3FFFF) >> 4) | ((uint64_t)(lbo >> 4) << 16) | ((uint64_t)(sbo >> 4) << 32);
}
__device__ __forceinline__ void wgmma(uint32_t (&d)[12], uint32_t a0, uint32_t a1, uint32_t a2, uint32_t a3, uint64_t db, int acc) {
    asm volatile("{\n.reg .pred p;\nsetp.ne.b32 p, %17, 0;\n"
                 "wgmma.mma_async.sync.aligned.m64n48k16.f16.f16.f16 "
                 "{%0, %1, %2, %3, %4, %5, %6, %7, %8, %9, %10, %11}, "
                 "{%12, %13, %14, %15}, %16, p, 1, 1, 0;\n}\n"
                 : "+r"(d[0]), "+r"(d[1]), "+r"(d[2]), "+r"(d[3]), "+r"(d[4]), "+r"(d[5]), "+r"(d[6]), "+r"(d[7]), "+r"(d[8]), "+r"(d[9]), "+r"(d[10]), "+r"(d[11])
                 : "r"(a0), "r"(a1), "r"(a2), "r"(a3), "l"(db), "r"(acc));
}
__device__ __forceinline__ void wgmma(uint32_t (&d)[24], uint32_t a0, uint32_t a1, uint32_t a2, uint32_t a3, uint64_t db, int acc) {
    asm volatile("{\n.reg .pred p;\nsetp.ne.b32 p, %29, 0;\n"
                 "wgmma.mma_async.sync.aligned.m64n96k16.f16.f16.f16 "
                 "{%0, %1, %2, %3, %4, %5, %6, %7, %8, %9, %10, %11, %12, %13, %14, %15, %16, %17, %18, %19, %20, %21, %22, %23}, "
                 "{%24, %25, %26, %27}, %28, p, 1, 1, 0;\n}\n"
                 : "+r"(d[0]), "+r"(d[1]), "+r"(d[2]), "+r"(d[3]), "+r"(d[4]), "+r"(d[5]), "+r"(d[6]), "+r"(d[7]), "+r"(d[8]), "+r"(d[9]), "+r"(d[10]), "+r"(d[11]), "+r"(d[12]), "+r"(d[13]), "+r"(d[14]), "+r"(d[15]), "+r"(d[16]), "+r"(d[17]), "+r"(d[18]), "+r"(d[19]), "+r"(d[20]), "+r"(d[21]), "+r"(d[22]), "+r"(d[23])
                 : "r"(a0), "r"(a1), "r"(a2), "r"(a3), "l"(db), "r"(acc));
}
template <int ACC>
__device__ __forceinline__ void wgmma_rowsum(float (&d)[4], const uint32_t (&a)[4], uint64_t ones) {
    asm volatile("{\n.reg .pred p;\nsetp.ne.b32 p, %9, 0;\n"
                 "wgmma.mma_async.sync.aligned.m64n8k16.f32.bf16.bf16 {%0, %1, %2, %3}, {%4, %5, %6, %7}, %8, p, 1, 1, 0;\n}\n"
                 : "+f"(d[0]), "+f"(d[1]), "+f"(d[2]), "+f"(d[3])
                 : "r"(a[0]), "r"(a[1]), "r"(a[2]), "r"(a[3]), "l"(ones), "n"(ACC));
}
__device__ __forceinline__ void ldsm4(uint32_t (&r)[4], uint32_t addr) {
    asm volatile("ldmatrix.sync.aligned.m8n8.x4.shared.b16 {%0, %1, %2, %3}, [%4];"
                 : "=r"(r[0]), "=r"(r[1]), "=r"(r[2]), "=r"(r[3]) : "r"(addr) : "memory");
}
__device__ __forceinline__ void ldsm4_t(uint32_t (&r)[4], uint32_t addr) {
    asm volatile("ldmatrix.sync.aligned.m8n8.x4.trans.shared.b16 {%0, %1, %2, %3}, [%4];"
                 : "=r"(r[0]), "=r"(r[1]), "=r"(r[2]), "=r"(r[3]) : "r"(addr) : "memory");
}
__device__ __forceinline__ void stsm4(uint32_t addr, uint32_t a, uint32_t b, uint32_t c, uint32_t d) {
    asm volatile("stmatrix.sync.aligned.m8n8.x4.shared.b16 [%0], {%1, %2, %3, %4};"
                 ::"r"(addr), "r"(a), "r"(b), "r"(c), "r"(d) : "memory");
}
__device__ __forceinline__ uint32_t transpose8x8(uint32_t v) {
    uint32_t d; asm volatile("movmatrix.sync.aligned.m8n8.trans.b16 %0, %1;" : "=r"(d) : "r"(v)); return d;
}
__device__ __forceinline__ void spin_until(const unsigned* counter, unsigned target) {
    unsigned n = 0, c;
    do {
        asm volatile("ld.acquire.gpu.global.u32 %0, [%1];" : "=r"(c) : "l"(counter) : "memory");
        if (++n > SPIN_LIMIT) __trap();
    } while ((int)(c - target) < 0);
}
__device__ __forceinline__ void signal(unsigned* counter) {
    __syncwarp();
    if (elect_one()) asm volatile("red.release.gpu.global.add.u32 [%0], 1;" ::"l"(counter) : "memory");
    __syncwarp();
}
__device__ __forceinline__ void lds128(uint32_t& a, uint32_t& b, uint32_t& c, uint32_t& d, uint32_t addr) {
    asm volatile("ld.shared.v4.u32 {%0, %1, %2, %3}, [%4];" : "=r"(a), "=r"(b), "=r"(c), "=r"(d) : "r"(addr) : "memory");
}
__device__ __forceinline__ void lds64(uint32_t& a, uint32_t& b, uint32_t addr) {
    asm volatile("ld.shared.v2.u32 {%0, %1}, [%2];" : "=r"(a), "=r"(b) : "r"(addr) : "memory");
}
__device__ __forceinline__ void lds32(uint32_t& a, uint32_t addr) {
    asm volatile("ld.shared.u32 %0, [%1];" : "=r"(a) : "r"(addr) : "memory");
}
__device__ __forceinline__ float ldsf(uint32_t addr) {
    uint32_t v;
    lds32(v, addr);
    return __uint_as_float(v);
}
__device__ __forceinline__ void sts32(uint32_t addr, uint32_t a) {
    asm volatile("st.shared.u32 [%0], %1;" ::"r"(addr), "r"(a) : "memory");
}
__device__ __forceinline__ void sts128(uint32_t addr, uint32_t a, uint32_t b, uint32_t c, uint32_t d) {
    asm volatile("st.shared.v4.u32 [%0], {%1, %2, %3, %4};" ::"r"(addr), "r"(a), "r"(b), "r"(c), "r"(d) : "memory");
}
__device__ __forceinline__ void sts64(uint32_t addr, uint32_t a, uint32_t b) {
    asm volatile("st.shared.v2.u32 [%0], {%1, %2};" ::"r"(addr), "r"(a), "r"(b) : "memory");
}
__device__ __forceinline__ uint32_t bf_fma(uint32_t a, uint32_t b, uint32_t c) {
    uint32_t d; asm("fma.rn.bf16x2 %0, %1, %2, %3;" : "=r"(d) : "r"(a), "r"(b), "r"(c)); return d;
}
__device__ __forceinline__ uint32_t bf_mul(uint32_t a, uint32_t b) {
    uint32_t d; asm("mul.rn.bf16x2 %0, %1, %2;" : "=r"(d) : "r"(a), "r"(b)); return d;
}
__device__ __forceinline__ uint32_t bf_absmax(uint32_t a, uint32_t b) {
    uint32_t d; asm("max.xorsign.abs.bf16x2 %0, %1, %2;" : "=r"(d) : "r"(a), "r"(b)); return d;
}
__device__ __forceinline__ uint32_t h_fma(uint32_t a, uint32_t b, uint32_t c) {
    uint32_t d; asm("fma.rn.f16x2 %0, %1, %2, %3;" : "=r"(d) : "r"(a), "r"(b), "r"(c)); return d;
}
__device__ __forceinline__ uint32_t h_mul(uint32_t a, uint32_t b) {
    uint32_t d; asm("mul.rn.f16x2 %0, %1, %2;" : "=r"(d) : "r"(a), "r"(b)); return d;
}
__device__ __forceinline__ uint32_t h_round8(uint32_t v) { return (v + 0x00040004u) & 0xfff8fff8u; }
__device__ __forceinline__ uint32_t h_tanh(uint32_t a) {
    uint32_t d; asm("tanh.approx.f16x2 %0, %1;" : "=r"(d) : "r"(a)); return d;
}
__device__ __forceinline__ uint32_t pack_h2(float lo, float hi) {
    uint32_t d; asm("cvt.rn.f16x2.f32 %0, %1, %2;" : "=r"(d) : "f"(hi), "f"(lo)); return d;
}
__device__ __forceinline__ uint32_t pack_bf2(float lo, float hi) {
    uint32_t d; asm("cvt.rn.bf16x2.f32 %0, %1, %2;" : "=r"(d) : "f"(hi), "f"(lo)); return d;
}
__device__ __forceinline__ float bf_lo(uint32_t v) { return __uint_as_float(v << 16); }
__device__ __forceinline__ float bf_hi(uint32_t v) { return __uint_as_float(v & 0xffff0000u); }
__device__ __forceinline__ float h_lo(uint32_t v) { return __low2float(*reinterpret_cast<__half2*>(&v)); }
__device__ __forceinline__ float h_hi(uint32_t v) { return __high2float(*reinterpret_cast<__half2*>(&v)); }
__device__ __forceinline__ float warp_absmax(uint32_t v) {
    return __uint_as_float(__reduce_max_sync(~0u, max((v & 0x7fffu) << 16, v & 0x7fff0000u)));
}
__device__ __forceinline__ uint32_t gelu2(uint32_t z) {
    uint32_t p = h_fma(z, z, GELU_C2);
    uint32_t t = h_tanh(h_mul(z, p));
    return h_fma(z, t, z);
}
__device__ __forceinline__ float grn_norm(float ss) {
    float r;
    asm("sqrt.approx.f32 %0, %1;" : "=f"(r) : "f"(fmaf(ss, INV_2KZ * INV_2KZ, 1e-6f)));
    return r;
}
__device__ __forceinline__ float pow2i(int e) { return __uint_as_float((uint32_t)(e + 127) << 23); }
__device__ __forceinline__ int ilog2f(float v) {
    int e = (int)((__float_as_uint(v) >> 23) & 0xff) - 127;
    return max(-100, min(100, e));
}

__device__ __forceinline__ int sum_exp(float w1max) {
    return w1max > 0.f ? max(-90, min(90, 35 - 2 * ilog2f(2.f * KZ * 96.f * w1max))) : 0;
}
__device__ __forceinline__ float row_scale(float m) { return m > 0.f ? pow2i(2 - ilog2f(m)) : 1.f; }

struct Work {
    int t0, nA, nB, sA, yA, rows, lent;
};
__device__ __forceinline__ Work get_work(int per_cta, int extra, int lenders) {
    Work w;
    w.lent = (int)blockIdx.x < lenders ? LENT : 0;
    const int t0 = blockIdx.x * per_cta + min((int)blockIdx.x, extra);
    const int t1 = t0 + per_cta + ((int)blockIdx.x < extra);
    w.t0 = t0;
    w.sA = t0 >> 9;
    w.yA = t0 & 511;
    const int tm = min(t1, (w.sA + 1) << 9);
    w.nA = tm - t0;
    w.nB = t1 - tm;
    w.rows = w.nA + 2 + (w.nB ? w.nB + 2 : 0);
    return w;
}
__device__ __forceinline__ int row_code(const Work& w, int i) {
    int strip, y;
    if (i < w.nA + 2) { strip = w.sA; y = w.yA - 1 + i; }
    else { strip = w.sA + 1; y = i - (w.nA + 2) - 1; }
    return y << 16 | strip * TILE_W;
}
__device__ __forceinline__ uint32_t tile_offset(int tile) { return ((tile & 511) * IMG_W + (tile >> 9) * TILE_W) * (CH * 2); }
__device__ __forceinline__ int tile_order(int j, int n) {
    const int olds = (j / ORDER_P) * ORDER_Q + max(0, j % ORDER_P - (ORDER_P - ORDER_Q));
    return (j % ORDER_P >= ORDER_P - ORDER_Q) ? olds : n - 1 - (j - olds);
}
__device__ __forceinline__ void issue_region(const CUtensorMap* tm, uint32_t dst, uint32_t bar, int warp, int code) {
    mbar_expect_tx(bar, REGION_BYTES);
    tma_row(dst, tm, bar, (code & 0xffff) + (16 * warp - 1), code >> 16);
}
__device__ __forceinline__ void elect_arrive(uint32_t bar0, uint32_t bar1, bool both) {
    asm volatile("{\n.reg .pred p, q;\nelect.sync _|p, 0xffffffff;\nsetp.ne.and.b32 q, %2, 0, p;\n"
                 "@p mbarrier.arrive.shared::cta.b64 _, [%0];\n@q mbarrier.arrive.shared::cta.b64 _, [%1];\n}\n"
                 ::"r"(bar0), "r"(bar1), "r"((int)both) : "memory");
}

__device__ __forceinline__ void first_loads(const Work& wk, const CUtensorMap* tm, const CUtensorMap* tw, const __nv_bfloat16* dw,
                                            uint32_t sb, int warp) {
    const uint32_t reg0 = sb + SM_RING + warp * REGION_BYTES, bars = sb + SM_BAR + warp * 8;
#pragma unroll
    for (int s = 0; s < PREFETCH_ROWS; s++) mbar_init(bars + s * 32, 1);
    mbar_init(sb + BAR_W + warp * 8, 1);
    if (warp < 2) mbar_init(sb + BAR_W + (warp + 4) * 8, 1);
    fence_async();
    asm volatile("mbarrier.expect_tx.shared::cta.b64 [%0], %1;" ::"r"(bars), "r"(9 * CH * 2) : "memory");
    bulk_load(reg0 + (NSLOT - 1) * SLOT_BYTES, dw, 9 * CH * 2, bars);
#pragma unroll
    for (int r = 0; r < PREFETCH_ROWS; r++)
        issue_region(tm, reg0 + r * SLOT_BYTES, bars + r * 32, warp, (wk.yA - 1 + r) << 16 | wk.sA * TILE_W);
#pragma unroll 1
    for (int b = warp; b < 6; b += 4) {
        mbar_expect_tx(sb + BAR_W + b * 8, 64 * CH * 2);
        tma_2d(sb + SM_W2 + b * (64 * CH * 2), tw, sb + BAR_W + b * 8, 64 * b, 0);
    }
}

__device__ __forceinline__ void conv_producer(const Work& wk, const CUtensorMap* tm, uint32_t sb, int warp) {
    const int lane = threadIdx.x & 31;
    const int j = lane & 15, grp = lane >> 4;
    const uint32_t reg0 = sb + SM_RING + warp * REGION_BYTES;
    const uint32_t bars = sb + SM_BAR + warp * 8;
    if (elect_one()) {
        if (warp == 0) mbar_init(sb + BAR_PIN, 1);
#pragma unroll
        for (int s = 0; s < 4; s++) mbar_init(sb + BAR_R + (s * 4 + warp) * 8, 1);
#pragma unroll 1
        for (int s = PREFETCH_ROWS; s < 3 * NSLOT; s++) mbar_init(bars + s * 32, 1);
        fence_async();
    }
    __syncwarp();
    named_arrive(0, NTHREADS);
    if (warp * 32 + lane < MAX_ROWS) {
        sts32(sb + SM_ROWS + (warp * 32 + lane) * 4, row_code(wk, warp * 32 + lane));
        sts32(sb + SM_TILES + (warp * 32 + lane) * 4, tile_offset(wk.t0 + wk.lent + tile_order(max(warp * 32 + lane - wk.lent / 2, 0), wk.nA + wk.nB - NCONS - wk.lent)));
    }
    const uint32_t ld64 = opaque(reg0 + grp * 8 * 192 + j * 8), ld32 = opaque(reg0 + grp * 8 * 192 + 128 + j * 4);
    const uint32_t st64 = opaque(reg0 + grp * A_SBO + (j >> 1) * A_LBO + (j & 1) * 8);
    const uint32_t st32 = opaque(reg0 + grp * A_SBO + (8 + (j >> 2)) * A_LBO + (j & 3) * 4);
    uint32_t accB[8][3] = {}, accC[8][3] = {};
    static_assert(2 * PREFETCH_ROWS == NSLOT, "prefetch slot arithmetic");
    uint32_t so = 0, bo = 0, par = 0, tbl = sb + SM_ROWS + PREFETCH_ROWS * 4;
    const uint32_t tbl_end = sb + SM_ROWS + wk.rows * 4;
    bool x_ready = false;
    named_bar(1, 128);
    mbar_wait(bars, 0);
    uint32_t w[3][3][3];
#pragma unroll
    for (int tap = 0; tap < 9; tap++) {
        const uint32_t p = reg0 + (NSLOT - 1) * SLOT_BYTES + tap * CH * 2;
        uint32_t u0, u1;
        lds64(u0, u1, p + 8 * j);
        __syncwarp();
        sts64(p + 8 * j, u1, u0);
        __syncwarp();
        lds64(w[tap / 3][tap % 3][1], w[tap / 3][tap % 3][0], p + 8 * j);
        lds32(w[tap / 3][tap % 3][2], p + 128 + 4 * j);
    }
    {
        const int first = wk.nA + 2, publish = wk.lent ? 12 : -1;
#pragma unroll 1
        for (int k = 0; k < wk.rows; k++) {
            if (!x_ready) mbar_wait(bars + bo, par);
            const bool wrap = bo == (NSLOT - 1) * 32, low = bo < PREFETCH_ROWS * 32;
            const uint32_t nbo = wrap ? 0 : bo + 32, npar = par ^ wrap;
            const uint32_t pbo = low ? bo + PREFETCH_ROWS * 32 : bo - PREFETCH_ROWS * 32, ppar = par ^ low;
            uint32_t out[8][3];
            int code;
            bool e_ready;
#pragma unroll
            for (int p = 0; p < 10; p++) {
                uint32_t xv[3];
                lds64(xv[0], xv[1], so + ld64 + p * 192);
                lds32(xv[2], so + ld32 + p * 192);
                if (p == 9) {
                    asm volatile("ld.shared.u32 %0, [%1];" : "=r"(code) : "r"(tbl));
                    e_ready = mbar_test(bars + (BAR_E - SM_BAR) + pbo, ppar);
                    x_ready = mbar_test(bars + nbo, npar);
                }
#pragma unroll
                for (int dx = 0; dx < 3; dx++) {
                    const int o = p - dx;
                    if (o < 0 || o > 7) continue;
#pragma unroll
                    for (int q = 0; q < 3; q++) {
                        out[o][q] = bf_fma(xv[q], w[2][dx][q], dx == 0 ? accB[o][q] : out[o][q]);
                        accB[o][q] = bf_fma(xv[q], w[1][dx][q], dx == 0 ? accC[o][q] : accB[o][q]);
                        accC[o][q] = dx == 0 ? bf_mul(xv[q], w[0][dx][q]) : bf_fma(xv[q], w[0][dx][q], accC[o][q]);
                    }
                }
            }
            __syncwarp();
#pragma unroll
            for (int o = 0; o < 8; o++) {
                sts64(so + st64 + o * 16, out[o][0], out[o][1]);
                sts32(so + st32 + o * 16, out[o][2]);
            }
            const bool halo = k < 2 || (unsigned)(k - first) < 2;
            if (halo) fence_async();
            if (k == publish) signal(&g_lent_in);
            __syncwarp();
            elect_arrive(bars + (BAR_A - SM_BAR) + bo, bars + (BAR_E - SM_BAR) + bo, halo);
            if (tbl < tbl_end) {
                if (!e_ready) mbar_wait(bars + (BAR_E - SM_BAR) + pbo, ppar);
                code = __shfl_sync(~0u, code, 0);
                if (elect_one()) issue_region(tm, reg0 + (low ? so + PREFETCH_ROWS * SLOT_BYTES : so - PREFETCH_ROWS * SLOT_BYTES), bars + pbo, warp, code);
            }
            tbl += 4;
            so = wrap ? 0 : so + SLOT_BYTES;
            bo = nbo;
            par = npar;
        }
    }
}

template <bool V> struct Flag { static constexpr bool value = V; };
template <bool SCALED, int K0 = 0, int K1 = 3>
__device__ __forceinline__ void gelu_sq(uint32_t (&d)[24], uint32_t (&keep)[24], uint32_t sq_addr, uint32_t scale2) {
    pin(d);
#pragma unroll
    for (int k = K0; k < K1; k++) {
        uint32_t hs[4];
        lds128(hs[0], hs[1], hs[2], hs[3], sq_addr + k * CONS_THREADS * 16);
#pragma unroll
        for (int q = 0; q < 4; q++) {
            uint32_t g0 = gelu2(d[8 * k + 2 * q]), g1 = gelu2(d[8 * k + 2 * q + 1]);
            keep[8 * k + 2 * q] = g0;
            keep[8 * k + 2 * q + 1] = g1;
            if (SCALED) { g0 = h_mul(g0, scale2); g1 = h_mul(g1, scale2); }
            hs[q] = h_fma(g1, g1, h_fma(g0, g0, hs[q]));
        }
        sts128(sq_addr + k * CONS_THREADS * 16, hs[0], hs[1], hs[2], hs[3]);
    }
}
__device__ __forceinline__ void anchor(uint32_t addr, uint32_t a, uint32_t b, uint32_t c, uint32_t d) {
    asm volatile("{\n.reg .pred p;\nsetp.eq.b32 p, %0, 0;\n@p st.shared.v4.u32 [%0], {%1, %2, %3, %4};\n}\n"
                 ::"r"(addr), "r"(a), "r"(b), "r"(c), "r"(d) : "memory");
}
template <bool SCALED>
__device__ __forceinline__ void gelu_sq_reg(uint32_t (&d)[24], uint32_t (&hs)[12], uint32_t scale2) {
    pin(d);
#pragma unroll
    for (int q = 0; q < 12; q++) {
        uint32_t g0 = gelu2(d[2 * q]), g1 = gelu2(d[2 * q + 1]);
        if (SCALED) { g0 = h_mul(g0, scale2); g1 = h_mul(g1, scale2); }
        hs[q] = h_fma(g1, g1, h_fma(g0, g0, hs[q]));
    }
}
__device__ __forceinline__ void gelu_to(uint32_t (&g)[12], uint32_t (&d)[12]) {
    pin(d);
#pragma unroll
    for (int q = 0; q < 12; q++) g[q] = gelu2(d[q]);
    pin(g);
}
__device__ __forceinline__ void load_tile(uint32_t (&raw)[6][4], uint32_t addr) {
#pragma unroll
    for (int s = 0; s < 6; s++) ldsm4(raw[s], addr + s * 2 * A_LBO);
}
__device__ __forceinline__ uint2 ln_stats(const uint32_t (&raw)[6][4], uint64_t ones) {
    uint32_t sq[6][4];
#pragma unroll
    for (int s = 0; s < 6; s++)
#pragma unroll
        for (int q = 0; q < 4; q++) sq[s][q] = bf_mul(raw[s][q], raw[s][q]);
    float sum[4], ssq[4];
    wg_fence();
    wgmma_rowsum<0>(sum, raw[0], ones);
#pragma unroll
    for (int s = 1; s < 6; s++) wgmma_rowsum<1>(sum, raw[s], ones);
    wgmma_rowsum<0>(ssq, sq[0], ones);
#pragma unroll
    for (int s = 1; s < 6; s++) wgmma_rowsum<1>(ssq, sq[s], ones);
    wg_commit();
    wg_wait<0>();
    uint32_t st[2];
#pragma unroll
    for (int h = 0; h < 2; h++) {
        asm volatile("" : "+f"(sum[2 * h]), "+f"(ssq[2 * h])::"memory");
        const float mean = sum[2 * h] * (1.f / CH);
        const float var = fmaxf(fmaf(ssq[2 * h], 1.f / CH, -mean * mean), 0.f);
        float rstd;
        asm("rsqrt.approx.ftz.f32 %0, %1;" : "=f"(rstd) : "f"(var + 1e-5f));
        rstd = bf_lo(pack_bf2(rstd * KZ, 0.f));
        st[h] = pack_bf2(rstd, -mean * rstd);
    }
    return make_uint2(st[0], st[1]);
}
__device__ __forceinline__ void ln_apply(uint32_t (&a)[6][4], const uint2& st) {
    const uint32_t sc[2] = {__byte_perm(st.x, 0, 0x1010), __byte_perm(st.y, 0, 0x1010)};
    const uint32_t sh[2] = {__byte_perm(st.x, 0, 0x3232), __byte_perm(st.y, 0, 0x3232)};
#pragma unroll
    for (int s = 0; s < 6; s++)
#pragma unroll
        for (int q = 0; q < 4; q++) {
            const uint32_t v = bf_fma(a[s][q], sc[q & 1], sh[q & 1]);
            a[s][q] = pack_h2(bf_lo(v), bf_hi(v));
        }
}
__device__ __forceinline__ void stagger_wait(int jt, int wgi) {
    if (jt > 0) named_bar(4 + wgi, 256);
}
__device__ __forceinline__ void stagger_pass(int jt, int wgi, int ntiles) {
    if (jt + 1 < ntiles) named_arrive(4 + (wgi == NCONS - 1 ? 0 : wgi + 1), 256);
}
struct Cursor {
    int slot;
    uint32_t par;
    __device__ __forceinline__ void advance(int n) {
        slot += n;
        if (slot >= NSLOT) { slot -= NSLOT; par ^= 1; }
    }
};
struct Descs {
    uint64_t w1[8][6];
    uint64_t w2[24];
    uint64_t ones;
};
template <int E0, int N>
__device__ __forceinline__ void gemm1_chunk(uint32_t (&d)[N], const uint32_t (&a)[6][4], const Descs& ds, int zero) {
#pragma unroll
    for (int s = 0; s < 6; s++) wgmma(d, a[s][0], a[s][1], a[s][2], a[s][3], ds.w1[E0 / 48][s], s ? 1 : zero);
}
template <int E0, int N>
__device__ __forceinline__ void gemm2_chunk(uint32_t (&acc)[24], const uint32_t (&g)[N], const Descs& ds) {
#pragma unroll
    for (int s = 0; s < N / 4; s++) wgmma(acc, g[4 * s], g[4 * s + 1], g[4 * s + 2], g[4 * s + 3], ds.w2[E0 / 16 + s], 1);
}

__global__ void __launch_bounds__(NTHREADS, 1)
block_kernel(const __grid_constant__ CUtensorMap tmap, const __grid_constant__ CUtensorMap tmap_w1,
             const __nv_bfloat16* __restrict__ x, const __nv_bfloat16* __restrict__ dw, const __nv_bfloat16* __restrict__ w2,
             const __nv_bfloat16* __restrict__ gamma, const __nv_bfloat16* __restrict__ beta, __nv_bfloat16* __restrict__ out, const __grid_constant__ Descs ds,
             const int zero, const int per_cta, const int extra, const int lenders) {
    extern __shared__ __align__(1024) uint8_t smem[];
    constexpr uint32_t sb = SB;
    const int tid = threadIdx.x;
    const Work wk = get_work(per_cta, extra, lenders);
    if (smem_u32(smem) != SB || wk.rows + 4 > MAX_ROWS) __trap();
    constexpr uint32_t s_red = sb + SM_RED;

    PROF(0);
    const int warp_id = __shfl_sync(~0u, tid >> 5, 0);
    if (warp_id < 4 && elect_one()) first_loads(wk, &tmap, &tmap_w1, dw, sb, warp_id);
    __syncwarp();
    const int cw = warp_id - 4, wgi = cw >> 2, w4 = warp_id & 3;
    const int ntiles = wk.nA + wk.nB;
    const int wg = warp_id >> 2;
    int first = wg;
    uint32_t a[6][4], tile_off, next_off, stage, inv_rho2 = 0, rpar = 0, bias_addr, lane16, lane_off;
    auto set_lane = [&](uint32_t lane) {
        bias_addr = sb + SM_BIASH + (lane & 3) * 96;
        lane16 = lane * 16;
        lane_off = ((lane >> 2) * CH + 8 * (lane & 3)) * 2;
    };
    const uint32_t bar_r = sb + BAR_R + warp_id * 8;
    auto load_bias = [&](uint32_t (&acc)[24]) {
#pragma unroll
        for (int q = 0; q < 6; q++) lds128(acc[4 * q], acc[4 * q + 1], acc[4 * q + 2], acc[4 * q + 3], bias_addr + q * 16);
    };
    auto load_frags = [&](bool on) {
#pragma unroll
        for (int s = 0; s < 6; s++) ldg128_if(on, a[s], reinterpret_cast<const char*>(out) + next_off + w4 * WARP_BYTES + lane16 + s * 512);
    };
    auto stage_x = [&]() {
        if (elect_one()) {
            mbar_expect_tx(bar_r, WARP_BYTES);
            bulk_load_stream(stage, reinterpret_cast<const char*>(x) + tile_off + w4 * WARP_BYTES, WARP_BYTES, bar_r);
        }
    };
    auto epilogue = [&](uint32_t (&acc)[24]) {
        pin(acc);
        rpar ^= 1;
        uint4* op = reinterpret_cast<uint4*>(reinterpret_cast<char*>(out) + tile_off + w4 * WARP_BYTES + lane_off);
#pragma unroll
        for (int h = 0; h < 2; h++)
#pragma unroll
            for (int m = 0; m < 3; m++) {
                uint32_t xin[4], o[4];
                lds128(xin[0], xin[1], xin[2], xin[3], stage + lane_off + h * 1536 + m * 64);
#pragma unroll
                for (int q = 0; q < 4; q++) {
                    const uint32_t v = acc[2 * (4 * m + q) + h];
                    o[q] = bf_fma(pack_bf2(h_lo(v), h_hi(v)), inv_rho2, xin[q]);
                }
                __stcs(op + h * 96 + m * 4, make_uint4(o[0], o[1], o[2], o[3]));
            }
        __syncwarp();
    };
    if (warp_id < 4) {
        conv_producer(wk, &tmap, sb, warp_id);
        const int lane = opaque(tid & 31), g = lane >> 2, t = lane & 3;
        const unsigned epoch = __float_as_uint(ldsf(s_red + 48));
        set_lane(lane);
#pragma unroll 1
        for (int q = gridDim.x - 1 - blockIdx.x; q < W2_GROUPS; q += gridDim.x) {
            uint32_t u[3], rmax = 0;
#pragma unroll
            for (int m = 0; m < 3; m++) {
                const uint4 w = ldg128_ordered(w2 + (8 * q + g) * CH + 32 * m + 8 * t);
                rmax = bf_absmax(bf_absmax(rmax, bf_absmax(w.x, w.y)), bf_absmax(w.z, w.w));
                u[m] = w4 & 2 ? (w4 & 1 ? w.w : w.z) : (w4 & 1 ? w.y : w.x);
            }
            const float bt = __bfloat162float(beta[8 * q + g]);
            rmax = bf_absmax(rmax, __shfl_xor_sync(~0u, rmax, 1));
            rmax = bf_absmax(rmax, __shfl_xor_sync(~0u, rmax, 2));
            const float mx = fmaxf(fabsf(bf_lo(rmax)), fabsf(bf_hi(rmax))), sc = row_scale(mx);
            if (t == 0 && w4 == 0) g_w2max[8 * q + g] = mx;
#pragma unroll
            for (int m = 0; m < 3; m++) {
                float lo = bf_lo(u[m]), hi = bf_hi(u[m]);
                g_w2h[(4 * m + w4) * 1536 + q * 32 + lane] = transpose8x8(pack_h2(lo * sc, hi * sc));
                lo *= bt; hi *= bt;
#pragma unroll
                for (int o = 4; o <= 16; o <<= 1) { lo += __shfl_xor_sync(~0u, lo, o); hi += __shfl_xor_sync(~0u, hi, o); }
                if (g == 0) {
                    float* dst = &g_bias[epoch & 1][32 * m + 8 * t + 2 * w4];
                    asm volatile("red.global.add.v2.f32 [%0], {%1, %2};" ::"l"(dst), "f"(lo), "f"(hi) : "memory");
                }
            }
            asm volatile("fence.proxy.async.global;" ::: "memory");
            signal(&g_prep);
        }
#pragma unroll
        for (int s = 0; s < 6; s++) a[s][0] = a[s][1] = a[s][2] = a[s][3] = 0;
        const unsigned piece = blockIdx.x - lenders;
        if (piece < 8 * LENT * lenders) {
            spin_until(&g_lent_in, (epoch + 1) * 4 * lenders);
            next_off = tile_offset(piece / (8 * LENT) * (per_cta + 1) + piece / 8 % LENT);
            load_frags(true);
            uint32_t d[12], gl[12];
            wg_fence();
#pragma unroll
            for (int s = 0; s < 6; s++) wgmma(d, a[s][0], a[s][1], a[s][2], a[s][3], ds.w1[0][s] + piece % 8 * (6 * 1536 / 16), s ? 1 : 0);
            wg_commit();
            wg_wait<0>();
            gelu_to(gl, d);
#pragma unroll
            for (int s = 0; s < 3; s++) g_lent[((piece * 4 + w4) * 3 + s) * 32 + lane] = make_uint4(gl[4 * s], gl[4 * s + 1], gl[4 * s + 2], gl[4 * s + 3]);
            float f[6], r[3];
#pragma unroll
            for (int j = 0; j < 6; j++) {
                const float lo = fmaf(h_lo(gl[2 * j]), h_lo(gl[2 * j]), h_lo(gl[2 * j + 1]) * h_lo(gl[2 * j + 1]));
                const float hi = fmaf(h_hi(gl[2 * j]), h_hi(gl[2 * j]), h_hi(gl[2 * j + 1]) * h_hi(gl[2 * j + 1]));
                f[j] = (g & 1 ? hi : lo) + __shfl_xor_sync(~0u, g & 1 ? lo : hi, 4);
            }
#pragma unroll
            for (int j = 0; j < 3; j++) {
                r[j] = (g & 2 ? f[j + 3] : f[j]) + __shfl_xor_sync(~0u, g & 2 ? f[j] : f[j + 3], 8);
                asm volatile("red.shared.add.f32 [%0], %1;" ::"r"(sb + SM_BIASH + (8 * j + 12 * (g & 2) + 2 * t + (g & 1)) * 4), "f"(r[j]) : "memory");
            }
        }
        named_arrive(11, NTHREADS);
        if (piece < 8 * LENT * lenders) signal(&g_lent_out);
        const bool leader = warp_id == 0 && lane == 0;
        if (leader) {
            spin_until(&g_prep, (epoch + 1) * 4 * W2_GROUPS);
            asm volatile("fence.proxy.async.global;" ::: "memory");
        }
        PROF(2);
        named_bar(3, NTHREADS);
        if (leader) {
            fence_async();
            mbar_expect_tx(sb + BAR_W, EX * CH * 2);
            bulk_load(sb + SM_W2, g_w2h, EX * CH * 2, sb + BAR_W);
        }
        stage = sb + SM_RING + (wk.rows % NSLOT) * SLOT_BYTES + w4 * REGION_BYTES;
        if (wk.lent) {
            tile_off = tile_offset(wk.t0);
            stage_x();
            if (elect_one()) prefetch_l2(reinterpret_cast<const char*>(x) + tile_offset(wk.t0 + 1) + w4 * WARP_BYTES, WARP_BYTES);
            spin_until(&g_lent_out, (epoch + 1) * 32 * LENT * lenders);
            uint32_t gl[4][12] = {};
            const uint4* src = &g_lent[(blockIdx.x * LENT * 8 * 4 + w4) * 96 + lane];
            auto fetch = [&](uint32_t (&v)[12], int c, bool on) {
#pragma unroll
                for (int s = 0; s < 3; s++) ldg128_if(on, reinterpret_cast<uint32_t (&)[4]>(v[4 * s]), src + c * 384 + s * 32);
            };
#pragma unroll
            for (int c = 0; c < 3; c++) fetch(gl[c], c, true);
            named_bar(3, NTHREADS);
            lds32(inv_rho2, s_red + 52);
#pragma unroll 1
            for (int e = 0; e < LENT; e++) {
                uint32_t acc[24];
                load_bias(acc);
#define CNX_LENT(C)                                  \
    pin(gl[C % 4]);                                  \
    wg_fence();                                      \
    gemm2_chunk<48 * C>(acc, gl[C % 4], ds);         \
    wg_commit();                                     \
    wg_wait<(C < 7 ? 1 : 0)>();                      \
    fetch(gl[(C + 3) % 4], C + 3, C < 5 || e == 0);  \
    if (lane == 0) mbar_arrive(sb + BAR_PIN);
                CNX_LENT(0) CNX_LENT(1) CNX_LENT(2) CNX_LENT(3) CNX_LENT(4) CNX_LENT(5) CNX_LENT(6) CNX_LENT(7)
#undef CNX_LENT
                src += 8 * 384;
                mbar_wait(bar_r, rpar);
                epilogue(acc);
                tile_off = tile_offset(wk.t0 + 1);
                if (e == 0) stage_x();
            }
            first = 4;
        }
        lds32(next_off, sb + SM_TILES + first * 4);
        load_frags(true);
    } else {
        {
            const int ct = tid - 128, lane = tid & 31;
            const unsigned epoch = *reinterpret_cast<volatile unsigned*>(&g_count);
            const int r = lane & 7, mi = lane >> 3;
            const uint32_t src = sb + SM_W2 + (cw >> 1) * (64 * CH * 2) + r * 128 + ((((cw & 1) * 4 + mi) ^ r) * 16);
            const uint32_t dst = sb + SM_W1 + (4 * cw + mi) * 1536 + r * 16;
            named_bar(0, NTHREADS);
            mbar_wait(sb + BAR_W + (cw >> 1) * 8, 0);
            uint32_t wmax[4] = {}, wsum[4] = {};
#pragma unroll 3
            for (int c = 0; c < 12; c++) {
                uint32_t u[4];
                ldsm4_t(u, src + c * 1024);
#pragma unroll
                for (int q = 0; q < 4; q++) {
                    wmax[q] = bf_absmax(wmax[q], u[q]);
                    wsum[q] = bf_fma(u[q], 0x3f803f80u, wsum[q]);
                    u[q] = pack_h2(bf_lo(u[q]), bf_hi(u[q]));
                }
                stsm4(dst + c * 128, u[0], u[1], u[2], u[3]);
            }
            float mean[4];
            bool center = false;
#pragma unroll
            for (int q = 0; q < 4; q++) {
                uint32_t m = wmax[q];
                float sum = bf_lo(wsum[q]) + bf_hi(wsum[q]);
#pragma unroll
                for (int o = 1; o <= 2; o <<= 1) { m = bf_absmax(m, __shfl_xor_sync(~0u, m, o)); sum += __shfl_xor_sync(~0u, sum, o); }
                mean[q] = sum * (1.f / CH);
                center |= fabsf(mean[q]) > 0.2f * fmaxf(fabsf(bf_lo(m)), fabsf(bf_hi(m)));
            }
            if (__any_sync(~0u, center)) {
#pragma unroll 1
                for (int pass = 0; pass < 2; pass++) {
                    float sum[4] = {};
#pragma unroll 1
                    for (int c = 0; c < 12; c++) {
                        uint32_t u[4];
                        ldsm4_t(u, src + c * 1024);
#pragma unroll
                        for (int q = 0; q < 4; q++) {
                            sum[q] += bf_lo(u[q]) + bf_hi(u[q]);
                            u[q] = pack_h2(bf_lo(u[q]) - mean[q], bf_hi(u[q]) - mean[q]);
                        }
                        stsm4(dst + c * 128, u[0], u[1], u[2], u[3]);
                    }
#pragma unroll
                    for (int q = 0; q < 4; q++) {
                        sum[q] += __shfl_xor_sync(~0u, sum[q], 1);
                        sum[q] += __shfl_xor_sync(~0u, sum[q], 2);
                        mean[q] = sum[q] * (1.f / CH);
                    }
                }
            }
            const float w1max = warp_absmax(bf_absmax(bf_absmax(wmax[0], wmax[1]), bf_absmax(wmax[2], wmax[3])));
            if (lane == 0) sts32(s_red + cw * 4, __float_as_uint(w1max));
            if (ct < 32) sts32(sb + SM_ONES + ct * 4, 0x3f803f80u);
            if (ct < 48) sts32(sb + SM_BIASH + ct * 4, 0);
            if (blockIdx.x == 0) {
#pragma unroll
                for (int q = 0; q < REPLICAS; q++) g_sums[(epoch & 1) ^ 1][q][ct] = 0;
                if (ct < CH) g_bias[(epoch & 1) ^ 1][ct] = 0.f;
            }
            if (ct == 0) sts32(s_red + 48, epoch);
            fence_async();
            named_bar(2, CONS_THREADS);
#pragma unroll
            for (int q = 0; q < 6; q++) sts128(sb + SM_SQ + (q * CONS_THREADS + ct) * 16, 0, 0, 0, 0);
            mbar_wait(sb + BAR_A + w4 * 8 + 32, 0);
        }

        PROF(1);
        const uint32_t a_addr = opaque(sb + SM_RING + w4 * REGION_BYTES + ((tid >> 3) & 1) * A_SBO + ((tid >> 4) & 1) * A_LBO + (tid & 7) * 16);
        const uint32_t bar_a = sb + BAR_A + w4 * 8, bar_e = sb + BAR_E + w4 * 8;
        const uint32_t sq = opaque(sb + SM_SQ + (tid - 128) * 16);
        auto max_w1 = [&]() {
            float m = 0.f;
#pragma unroll
            for (int q = 0; q < 3; q++) {
                uint32_t u[4];
                lds128(u[0], u[1], u[2], u[3], s_red + q * 16);
#pragma unroll
                for (int k = 0; k < 4; k++) m = fmaxf(m, __uint_as_float(u[k]));
            }
            return m;
        };
        auto square_exp = [&](float w1max) {
            const int e = w1max > 0.f ? 4 - ilog2f(2.f * KZ * 96.f * w1max) : 0;
            return (e >= 0 && e <= 6) ? 0 : max(-14, min(e, 14));
        };
        uint32_t k1[24], k2[24], k3[24];
        if (wgi < wk.lent) {
            const int slot = wgi + (wgi >= wk.nA ? 4 : 2);
            uint32_t a[6][4];
            mbar_wait(bar_a + slot * 32, 0);
            load_tile(a, a_addr + slot * SLOT_BYTES);
            const uint2 st = ln_stats(a, ds.ones);
            ln_apply(a, st);
            char* ap = reinterpret_cast<char*>(out) + (tile_offset(wk.t0 + wgi) + w4 * WARP_BYTES - (sb + SM_SQ + cw * 512) + sq);
#pragma unroll
            for (int s = 0; s < 6; s++) stg128(ap + s * 512, a[s]);
            __syncwarp();
            if (elect_one()) mbar_arrive(bar_e + slot * 32);
        }
        Cursor cur = {2, 0};
        int jt = wk.lent + wgi;
        {
            constexpr int SQC = 3 * CONS_THREADS * 16;
            cur.advance(jt + (jt >= wk.nA ? 2 : 0));
            int sq_e = square_exp(max_w1());
            uint32_t scale2 = pack_h2(pow2i(sq_e), pow2i(sq_e));
            auto run = [&](auto scaled_tag) {
                constexpr bool SCALED = decltype(scaled_tag)::value;
                uint32_t hs2[12] = {}, hs3[12] = {};
#pragma unroll 1
                for (; jt + NCONS < ntiles; jt += NCONS) {
                    uint32_t a[6][4], d0[24], d1[24], unused[24];
                    stagger_wait(jt - wk.lent, wgi);
                    mbar_wait(bar_a + cur.slot * 32, cur.par);
                    load_tile(a, a_addr + cur.slot * SLOT_BYTES);
                    const uint2 st = ln_stats(a, ds.ones);
                    ln_apply(a, st);
                    wg_fence();
                    gemm1_chunk<0>(d0, a, ds, 0);
                    wg_commit();
                    gemm1_chunk<96>(d1, a, ds, 0);
                    wg_commit();
                    {
                        char* ap = reinterpret_cast<char*>(out) + (tile_offset(wk.t0 + jt) + w4 * WARP_BYTES - (sb + SM_SQ + cw * 512) + sq);
#pragma unroll
                        for (int s = 0; s < 6; s++) stg128(ap + s * 512, a[s]);
                    }
                    wg_wait<1>();
                    gelu_sq<SCALED, 0, S1_PASS>(d0, unused, sq, scale2);
                    stagger_pass(jt, wgi, ntiles);
                    gelu_sq<SCALED, S1_PASS, 3>(d0, unused, sq, scale2);
                    if (elect_one()) mbar_arrive(bar_e + cur.slot * 32);
                    wg_fence();
                    gemm1_chunk<192>(d0, a, ds, zero);
                    wg_commit();
                    wg_wait<1>();
                    gelu_sq<SCALED>(d1, unused, sq + SQC, scale2);
                    wg_fence();
                    gemm1_chunk<288>(d1, a, ds, zero);
                    wg_commit();
                    wg_wait<1>();
                    gelu_sq_reg<SCALED>(d0, hs2, scale2);
                    anchor(sq, hs2[8], hs2[9], hs2[10], hs2[11]);
                    wg_wait<0>();
                    gelu_sq_reg<SCALED>(d1, hs3, scale2);
                    cur.advance(NCONS + ((jt < wk.nA && jt + NCONS >= wk.nA) ? 2 : 0));
                }
#pragma unroll
                for (int k = 0; k < 3; k++) {
                    sts128(sq + 2 * SQC + k * CONS_THREADS * 16, hs2[4 * k], hs2[4 * k + 1], hs2[4 * k + 2], hs2[4 * k + 3]);
                    sts128(sq + 3 * SQC + k * CONS_THREADS * 16, hs3[4 * k], hs3[4 * k + 1], hs3[4 * k + 2], hs3[4 * k + 3]);
                }
            };
            if (sq_e == 0) run(Flag<false>());
            else run(Flag<true>());
            sq_e = square_exp(max_w1());
            scale2 = pack_h2(pow2i(sq_e), pow2i(sq_e));
            {
                uint32_t a[6][4], d0[24], d1[24], d3[24], k0[24];
                stagger_wait(jt - wk.lent, wgi);
                mbar_wait(bar_a + cur.slot * 32, cur.par);
                load_tile(a, a_addr + cur.slot * SLOT_BYTES);
                const uint2 st = ln_stats(a, ds.ones);
                ln_apply(a, st);
                wg_fence();
                gemm1_chunk<0>(d0, a, ds, 0);
                wg_commit();
                gemm1_chunk<96>(d1, a, ds, 0);
                wg_commit();
                stage = sb + SM_RING + cur.slot * SLOT_BYTES + w4 * REGION_BYTES;
                wg_wait<1>();
                gelu_sq<true, 0, S1_PASS>(d0, k0, sq, scale2);
                stagger_pass(jt, wgi, ntiles);
                gelu_sq<true, S1_PASS, 3>(d0, k0, sq, scale2);
#pragma unroll
                for (int q = 0; q < 6; q++) sts128(stage - (sb + SM_SQ + cw * 512) + sq + q * 512, k0[4 * q], k0[4 * q + 1], k0[4 * q + 2], k0[4 * q + 3]);
                wg_fence();
                gemm1_chunk<192>(d0, a, ds, zero);
                wg_commit();
                wg_wait<1>();
                gelu_sq<true>(d1, k1, sq + SQC, scale2);
                wg_fence();
                gemm1_chunk<288>(d3, a, ds, 0);
                wg_commit();
                wg_wait<1>();
                gelu_sq<true>(d0, k2, sq + 2 * SQC, scale2);
                wg_wait<0>();
                gelu_sq<true>(d3, k3, sq + 3 * SQC, scale2);
            }
            named_bar(11, NTHREADS);
            const int lane = (sq >> 4) & 31, t = lane & 3, part = lane >> 2;
            const float w1max = max_w1();
            const uint32_t src = sb + SM_SQ + (cw * CONS_THREADS + part * 4 + t) * 16;
            float f[8] = {};
#pragma unroll
            for (int r = 0; r < 12; r++) {
                uint32_t u[4];
                lds128(u[0], u[1], u[2], u[3], src + r * 512);
#pragma unroll
                for (int q = 0; q < 4; q++) { f[2 * q] += h_lo(u[q]); f[2 * q + 1] += h_hi(u[q]); }
            }
            const bool b2 = part & 4, b1 = part & 2, b0 = part & 1;
            float r4[4], r2[2];
#pragma unroll
            for (int q = 0; q < 4; q++) r4[q] = (b2 ? f[q + 4] : f[q]) + __shfl_xor_sync(~0u, b2 ? f[q] : f[q + 4], 16);
#pragma unroll
            for (int q = 0; q < 2; q++) r2[q] = (b1 ? r4[q + 2] : r4[q]) + __shfl_xor_sync(~0u, b1 ? r4[q] : r4[q + 2], 8);
            const float tot = (b0 ? r2[1] : r2[0]) + __shfl_xor_sync(~0u, b0 ? r2[0] : r2[1], 4);
            const unsigned ch = 32 * cw + 8 * (part >> 1) + 2 * t + (part & 1), in_piece = ch - (blockIdx.x - lenders) % 8 * 48;
            const float helped = in_piece < 48 ? ldsf(sb + SM_BIASH + in_piece * 4) : 0.f;
            const float units = fmaf(tot, pow2i(sum_exp(w1max) - 2 * square_exp(w1max)), helped * pow2i(sum_exp(w1max)));
            atomicAdd(&g_sums[__float_as_uint(ldsf(s_red + 48)) & 1][blockIdx.x % REPLICAS][ch], __float2ull_rn(fminf(units, 0x1p49f)) << 8 | 1);
        }
        PROF(2);
        named_bar(3, NTHREADS);
        tile_off = tile_offset(wk.t0 + jt);
        {
            const int ct = (sq - (sb + SM_SQ)) >> 4, lane = ct & 31;
            const float w1max = max_w1();
            const unsigned epoch = __float_as_uint(ldsf(s_red + 48));
            set_lane(lane);
            if (elect_one()) prefetch_l2(reinterpret_cast<const char*>(x) + tile_off + w4 * WARP_BYTES, WARP_BYTES);
            const float gam = __bfloat162float(gamma[ct]), rmax = __ldcg(&g_w2max[ct]);
            const int tt = ct / 24, jb = (ct % 24) >> 1;
            float2 bpair = make_float2(0.f, 0.f);
            if (ct < 96) bpair = __ldcg(reinterpret_cast<const float2*>(&g_bias[epoch & 1][32 * (jb >> 2) + 8 * tt + 2 * (jb & 3)]));
            const float gbound = fmaxf(2.f * KZ * 9.7979590f * 192.f * w1max, 1.f) * 19.5959180f * INV_2KZ;
            const float fixed = __uint_as_float(__reduce_max_sync(~0u, __float_as_uint(fmaf(gbound, rmax, fmaxf(fabsf(bpair.x), fabsf(bpair.y))))));
            unsigned long long sum;
            for (unsigned n = 0;; n++) {
                unsigned cnt = 0;
                sum = 0;
#pragma unroll
                for (int q = 0; q < REPLICAS; q++) {
                    unsigned long long v;
                    asm volatile("ld.relaxed.gpu.global.u64 %0, [%1];" : "=l"(v) : "l"(&g_sums[epoch & 1][q][ct]) : "memory");
                    cnt += (unsigned)v & 255u;
                    sum += v >> 8;
                }
                if (__all_sync(~0u, cnt == gridDim.x)) break;
                if (n > SPIN_LIMIT) __trap();
            }
            PROF(3);
            if (blockIdx.x == 0 && ct == 0) g_count = epoch + 1;
            const float gx = grn_norm(__ull2float_rn(sum) * pow2i(-sum_exp(w1max)));
            float tot = gx;
#pragma unroll
            for (int o = 16; o >= 1; o >>= 1) tot += __shfl_xor_sync(~0u, tot, o);
            const float vary = __uint_as_float(__reduce_max_sync(~0u, __float_as_uint(fabsf(gam) * gx * rmax)));
            if (lane == 0) {
                sts32(s_red + 64 + cw * 4, __float_as_uint(tot));
                sts32(s_red + 128 + cw * 4, __float_as_uint(vary));
                sts32(s_red + 192 + cw * 4, __float_as_uint(fixed));
            }
            named_bar(2, CONS_THREADS);
            float vmax = 0.f, fmax2 = 0.f;
            tot = 0.f;
#pragma unroll
            for (int q = 0; q < 3; q++) {
                uint32_t u[4], v[4], w[4];
                lds128(u[0], u[1], u[2], u[3], s_red + 64 + q * 16);
                lds128(v[0], v[1], v[2], v[3], s_red + 128 + q * 16);
                lds128(w[0], w[1], w[2], w[3], s_red + 192 + q * 16);
#pragma unroll
                for (int k = 0; k < 4; k++) { tot += __uint_as_float(u[k]); vmax = fmaxf(vmax, __uint_as_float(v[k])); fmax2 = fmaxf(fmax2, __uint_as_float(w[k])); }
            }
            const float inv_mean = __fdividef(1.f, tot * (1.f / EX) + 1e-6f);
            const float bound = fmaf(gbound * vmax, inv_mean, 2.f * fmax2);
            const int rho_e = bound > 0.f ? 14 - ilog2f(bound) : 0;
            const float rho = pow2i(rho_e), inv_rho = pow2i(-rho_e);
            inv_rho2 = pack_bf2(inv_rho, inv_rho);
            const float f_own = __fdividef(fmaf(gam, gx * inv_mean, 1.f) * INV_2KZ * rho, row_scale(rmax));
            const uint32_t pk = pack_h2(f_own, __shfl_down_sync(~0u, f_own, 1));
            uint32_t f2[4];
#pragma unroll
            for (int q = 0; q < 4; q++) f2[q] = __shfl_sync(~0u, pk, (lane & 24) + 2 * q);
            if (ct < 96) sts32(sb + SM_BIASH + ct * 4, pack_h2(bpair.x * rho, bpair.y * rho));
            if (ct == 96) sts32(s_red + 52, inv_rho2);
            mbar_wait(sb + BAR_W, 1);
#pragma unroll
            for (int nb = 0; nb < 12; nb++) {
                uint32_t a, b, c, d;
                const uint32_t ad = sb + SM_W2 + nb * 6144 + ct * 16;
                lds128(a, b, c, d, ad);
                sts128(ad, h_round8(h_mul(a, f2[0])), h_round8(h_mul(b, f2[1])), h_round8(h_mul(c, f2[2])), h_round8(h_mul(d, f2[3])));
            }
            fence_async();
            named_bar(3, NTHREADS);
        }
        PROF(4);
        {
            uint32_t acc[24];
            load_bias(acc);
            lds32(next_off, sb + SM_TILES + wg * 4);
            if (wgi > 0) named_bar(8 + wgi, 256);
            pin(k1); pin(k2); pin(k3);
            wg_fence();
            gemm2_chunk<288>(acc, k3, ds);
            wg_commit();
            gemm2_chunk<96>(acc, k1, ds);
            gemm2_chunk<192>(acc, k2, ds);
            wg_commit();
            if (wgi + 1 < NCONS) named_arrive(9 + wgi, 256);
            wg_wait<1>();
            uint32_t k0[24];
#pragma unroll
            for (int q = 0; q < 6; q++) lds128(k0[4 * q], k0[4 * q + 1], k0[4 * q + 2], k0[4 * q + 3], stage + lane16 + q * 512);
            pin(k0);
            wg_fence();
            gemm2_chunk<0>(acc, k0, ds);
            wg_commit();
            stage_x();
            wg_wait<1>();
            load_frags(true);
            if (lane16 == 0) mbar_arrive(sb + BAR_PIN);
            mbar_wait(bar_r, rpar);
            wg_wait<0>();
            epilogue(acc);
        }
    }
    {
        const int nrest = ntiles - NCONS - wk.lent / 2;
        for (int jt = first; jt < nrest; jt += 4) {
            uint32_t d0[12], d1[12], g0[12], g1[12], acc[24];
            tile_off = next_off;
            lds32(next_off, sb + SM_TILES + (jt + 4) * 4);
            if (jt >= S2_FIRST) named_bar(4 + wg, 256);
            wg_fence();
            gemm1_chunk<0>(d0, a, ds, 0);
            wg_commit();
            gemm1_chunk<48>(d1, a, ds, 0);
            wg_commit();
            load_bias(acc);
            const bool more = jt + 4 < nrest;
            tile_off = __shfl_sync(~0u, tile_off, 0);
            next_off = __shfl_sync(~0u, next_off, 0);
            wg_wait<1>();
#define CNX_PASS if (jt + 1 >= S2_FIRST && jt + 1 < nrest) named_arrive(4 + ((wg + 1) & 3), 256);
#define CNX_STEP(C, D, G)                                              \
    gelu_to(G, D);                                                     \
    if (C == 0 && jt == 0) {                                           \
        named_bar(3, NTHREADS);                                        \
        load_bias(acc);                                                \
        lds32(inv_rho2, s_red + 52);                                   \
    }                                                                  \
    wg_fence();                                                        \
    if (C < 6) gemm1_chunk<48 * (C < 6 ? C + 2 : 0)>(D, a, ds, zero); \
    gemm2_chunk<48 * C>(acc, G, ds);                                  \
    wg_commit();                                                       \
    if (C == S2_PASS) { CNX_PASS }                                     \
    wg_wait<(C < 7 ? 1 : 0)>();
            CNX_STEP(0, d0, g0)
            stage_x();
            if (more && elect_one()) prefetch_l2(reinterpret_cast<const char*>(out) + next_off + w4 * WARP_BYTES, WARP_BYTES);
            CNX_STEP(1, d1, g1)
            CNX_STEP(2, d0, g0)
            CNX_STEP(3, d1, g1)
            CNX_STEP(4, d0, g0)
            CNX_STEP(5, d1, g1)
            CNX_STEP(6, d0, g0)
            load_frags(more);
            if (lane16 == 0) mbar_arrive(sb + BAR_PIN);
            mbar_wait(bar_r, rpar);
            CNX_STEP(7, d1, g1)
#undef CNX_STEP
            epilogue(acc);
        }
    }
    PROF(5);
}

}

typedef CUresult (*EncodeTiledFn)(CUtensorMap*, CUtensorMapDataType, cuuint32_t, void*, const cuuint64_t*, const cuuint64_t*,
                                  const cuuint32_t*, const cuuint32_t*, CUtensorMapInterleave, CUtensorMapSwizzle,
                                  CUtensorMapL2promotion, CUtensorMapFloatOOBfill);

extern "C" void kernel_launch(void* const* d_in, const int* in_sizes, int n_in, void* d_out, int out_size) {
    using namespace cnx;
    static EncodeTiledFn encode = nullptr;
    static int num_sms = 0;
    if (!encode) {
        void* fn = nullptr;
        cudaDriverEntryPointQueryResult qr;
        cudaGetDriverEntryPoint("cuTensorMapEncodeTiled", &fn, cudaEnableDefault, &qr);
        encode = (EncodeTiledFn)fn;
        int dev = 0;
        cudaGetDevice(&dev);
        cudaDeviceGetAttribute(&num_sms, cudaDevAttrMultiProcessorCount, dev);
        if (num_sms > MAX_CTAS) num_sms = MAX_CTAS;
        cudaFuncSetAttribute(block_kernel, cudaFuncAttributeMaxDynamicSharedMemorySize, SM_TOTAL);
    }
    CUtensorMap tm;
    cuuint64_t dims[3] = {(cuuint64_t)CH, (cuuint64_t)IMG_W, (cuuint64_t)IMG_H};
    cuuint64_t strides[2] = {(cuuint64_t)CH * 2, (cuuint64_t)CH * 2 * IMG_W};
    cuuint32_t box[3] = {(cuuint32_t)CH, (cuuint32_t)REGION_PX, 1};
    cuuint32_t estr[3] = {1, 1, 1};
    encode(&tm, CU_TENSOR_MAP_DATA_TYPE_BFLOAT16, 3, d_in[0], dims, strides, box, estr, CU_TENSOR_MAP_INTERLEAVE_NONE,
           CU_TENSOR_MAP_SWIZZLE_NONE, CU_TENSOR_MAP_L2_PROMOTION_L2_128B, CU_TENSOR_MAP_FLOAT_OOB_FILL_NONE);
    Descs ds;
    for (int c = 0; c < 8; c++)
        for (int k = 0; k < 6; k++) ds.w1[c][k] = make_desc(SB + SM_W1 + c * 6 * 1536 + k * 256, 128, 1536);
    for (int k = 0; k < 24; k++) ds.w2[k] = make_desc(SB + SM_W2 + k * 256, 128, 6144);
    ds.ones = make_desc(SB + SM_ONES, 0, 0);
    CUtensorMap tw;
    cuuint64_t wdims[2] = {(cuuint64_t)EX, (cuuint64_t)CH};
    cuuint64_t wstrides[1] = {(cuuint64_t)EX * 2};
    cuuint32_t wbox[2] = {64, (cuuint32_t)CH};
    encode(&tw, CU_TENSOR_MAP_DATA_TYPE_BFLOAT16, 2, d_in[2], wdims, wstrides, wbox, estr, CU_TENSOR_MAP_INTERLEAVE_NONE,
           CU_TENSOR_MAP_SWIZZLE_128B, CU_TENSOR_MAP_L2_PROMOTION_L2_128B, CU_TENSOR_MAP_FLOAT_OOB_FILL_NONE);
    const int extra = NTILES % num_sms;
    block_kernel<<<num_sms, NTHREADS, SM_TOTAL>>>(tm, tw, (const __nv_bfloat16*)d_in[0], (const __nv_bfloat16*)d_in[1],
                                             (const __nv_bfloat16*)d_in[3],
                                             (const __nv_bfloat16*)d_in[4], (const __nv_bfloat16*)d_in[5], (__nv_bfloat16*)d_out,
                                             ds, 0, NTILES / num_sms, extra, extra * (8 * LENT + 1) <= num_sms ? extra : 0);
}
```

```cpp
#include <cuda_runtime.h>
#include <cuda_bf16.h>
#include <cuda_fp16.h>
#include <cuda.h>
#include <stdint.h>

namespace cnx {

constexpr int IMG_H = 512, IMG_W = 512, CH = 96, EX = 384;
constexpr int TILE_W = 64;
constexpr int NTILES = (IMG_W / TILE_W) * IMG_H;
constexpr int NSLOT = 6;
constexpr int REGION_PX = 18;
constexpr int REGION_BYTES = REGION_PX * CH * 2;
constexpr int SLOT_BYTES = 4 * REGION_BYTES;
constexpr int A_LBO = 144, A_SBO = 12 * A_LBO;
constexpr int PREFETCH_ROWS = 3;
constexpr int NCONS = 3;
constexpr int CONS_THREADS = 128 * NCONS;
constexpr int NTHREADS = 128 + CONS_THREADS;
constexpr int MAX_ROWS = 52;
constexpr int TILE_BYTES = TILE_W * CH * 2, WARP_BYTES = TILE_BYTES / 4;
constexpr int S1_PASS = 1, S2_PASS = 1;
#define W2_EARLY 6
#define S2_FIRST 4
#define ORDER_P 3
#define ORDER_Q 1
static_assert(MAX_ROWS <= 128, "one table entry per producer thread");
static_assert(2 * A_SBO == REGION_BYTES && REGION_BYTES % 128 == 0, "region layout");

constexpr uint32_t SB = 1024;
constexpr int SM_W1 = 0;
constexpr int SM_W2 = SM_W1 + CH * EX * 2;
constexpr int SM_RING = SM_W2 + CH * EX * 2;
constexpr int SM_BIASH = SM_RING + NSLOT * SLOT_BYTES;
constexpr int SM_RED = SM_BIASH + 384;
constexpr int SM_ROWS = SM_RED + 256;
constexpr int SM_TILES = SM_ROWS + MAX_ROWS * 4;
constexpr int SM_ONES = SM_TILES + MAX_ROWS * 4;
constexpr int SM_BAR = SM_ONES + 128;
constexpr int BAR_X = SM_BAR;
constexpr int BAR_A = BAR_X + NSLOT * 4 * 8;
constexpr int BAR_E = BAR_A + NSLOT * 4 * 8;
constexpr int BAR_PIN = BAR_E + NSLOT * 4 * 8;
constexpr int BAR_W = BAR_PIN + 8;
constexpr int BAR_R = BAR_W + 6 * 8;
constexpr int SM_TOTAL = BAR_R + 16 * 8;
constexpr int SM_SQ = SM_W2;
constexpr int SQ_ROW = 128 * 16, SQ_WG = 6 * SQ_ROW;
static_assert(SM_ONES % 16 == 0 && SM_TOTAL <= 232448, "shared memory budget");

constexpr float KZ = 0.3292034911525734f;
constexpr uint32_t GELU_C2 = 0x40d940d9u;
constexpr float INV_2KZ = 0.5f / KZ;
constexpr unsigned SPIN_LIMIT = 1u << 19;

constexpr int MAX_CTAS = 256;
#define NREP 4
constexpr int REPLICAS = NREP;
constexpr int W2_GROUPS = EX / 8;
constexpr int LENT = 2, MAX_LENDERS = MAX_CTAS / (8 * LENT + 1);
struct Scratch {
    uint32_t w2h[EX * CH / 2];
    float w2max[EX];
    float bias[2][CH];
    unsigned long long sums[2][REPLICAS][EX];
    uint4 lent[MAX_LENDERS * LENT * 8 * 4 * 3 * 32];
    unsigned launch, pad0[31], prep, pad1[31], lent_in, pad2[31], lent_out, pad3[31];
};
__device__ __align__(128) Scratch g_scratch;

#define PROF(k)

__device__ __forceinline__ uint32_t smem_u32(const void* p) { return (uint32_t)__cvta_generic_to_shared(p); }
__device__ __forceinline__ void mbar_init(uint32_t bar, uint32_t cnt) {
    asm volatile("mbarrier.init.shared::cta.b64 [%0], %1;" ::"r"(bar), "r"(cnt) : "memory");
}
__device__ __forceinline__ void mbar_arrive(uint32_t bar) {
    asm volatile("mbarrier.arrive.shared::cta.b64 _, [%0];" ::"r"(bar) : "memory");
}
__device__ __forceinline__ void mbar_expect_tx(uint32_t bar, uint32_t bytes) {
    asm volatile("mbarrier.arrive.expect_tx.shared::cta.b64 _, [%0], %1;" ::"r"(bar), "r"(bytes) : "memory");
}
__device__ __forceinline__ bool mbar_try(uint32_t bar, uint32_t par) {
    uint32_t ok;
    asm volatile("{\n.reg .pred p;\nmbarrier.try_wait.parity.shared::cta.b64 p, [%1], %2;\nselp.u32 %0, 1, 0, p;\n}\n"
                 : "=r"(ok) : "r"(bar), "r"(par) : "memory");
    return ok != 0;
}
__device__ __forceinline__ void mbar_wait(uint32_t bar, uint32_t par) {
    unsigned n = 0;
    while (!mbar_try(bar, par)) {
        if (++n > SPIN_LIMIT) __trap();
    }
}
__device__ __forceinline__ bool mbar_test(uint32_t bar, uint32_t par) {
    uint32_t ok;
    asm volatile("{\n.reg .pred p;\nmbarrier.test_wait.parity.shared::cta.b64 p, [%1], %2;\nselp.u32 %0, 1, 0, p;\n}\n"
                 : "=r"(ok) : "r"(bar), "r"(par) : "memory");
    return ok != 0;
}
__device__ __forceinline__ bool elect_one() {
    uint32_t ok;
    asm volatile("{\n.reg .pred p;\nelect.sync _|p, 0xffffffff;\nselp.u32 %0, 1, 0, p;\n}\n" : "=r"(ok));
    return ok != 0;
}
__device__ __forceinline__ uint32_t opaque(uint32_t v) { return __shfl_sync(~0u, v, threadIdx.x & 31); }
__device__ __forceinline__ void named_bar(int id, int n) { asm volatile("bar.sync %0, %1;" ::"r"(id), "r"(n) : "memory"); }
__device__ __forceinline__ void named_arrive(int id, int n) { asm volatile("bar.arrive %0, %1;" ::"r"(id), "r"(n) : "memory"); }
__device__ __forceinline__ void fence_async() { asm volatile("fence.proxy.async.shared::cta;" ::: "memory"); }
__device__ __forceinline__ uint64_t evict_first() {
    uint64_t p;
    asm("createpolicy.fractional.L2::evict_first.b64 %0, 1.0;" : "=l"(p));
    return p;
}
__device__ __forceinline__ void tma_row(uint32_t dst, const CUtensorMap* tm, uint32_t bar, int x, int y) {
    asm volatile("cp.async.bulk.tensor.3d.shared::cluster.global.mbarrier::complete_tx::bytes.L2::cache_hint [%0], [%1, {%3, %4, %5}], [%2], %6;"
                 ::"r"(dst), "l"(tm), "r"(bar), "r"(0), "r"(x), "r"(y), "l"(evict_first()) : "memory");
}
__device__ __forceinline__ void bulk_load_stream(uint32_t dst, const void* src, uint32_t bytes, uint32_t bar) {
    asm volatile("cp.async.bulk.shared::cluster.global.mbarrier::complete_tx::bytes.L2::cache_hint [%0], [%1], %2, [%3], %4;"
                 ::"r"(dst), "l"(src), "r"(bytes), "r"(bar), "l"(evict_first()) : "memory");
}
__device__ __forceinline__ void prefetch_l2(const void* src, uint32_t bytes) {
    asm volatile("cp.async.bulk.prefetch.L2.global [%0], %1;" ::"l"(src), "r"(bytes) : "memory");
}
__device__ __forceinline__ void tma_2d(uint32_t dst, const CUtensorMap* tm, uint32_t bar, int x, int y) {
    asm volatile("cp.async.bulk.tensor.2d.shared::cluster.global.mbarrier::complete_tx::bytes [%0], [%1, {%3, %4}], [%2];"
                 ::"r"(dst), "l"(tm), "r"(bar), "r"(x), "r"(y) : "memory");
}
__device__ __forceinline__ void bulk_load(uint32_t dst, const void* src, uint32_t bytes, uint32_t bar) {
    asm volatile("cp.async.bulk.shared::cluster.global.mbarrier::complete_tx::bytes [%0], [%1], %2, [%3];"
                 ::"r"(dst), "l"(src), "r"(bytes), "r"(bar) : "memory");
}
__device__ __forceinline__ void wg_fence() { asm volatile("wgmma.fence.sync.aligned;" ::: "memory"); }
__device__ __forceinline__ void wg_commit() { asm volatile("wgmma.commit_group.sync.aligned;" ::: "memory"); }
template <int N> __device__ __forceinline__ void wg_wait() { asm volatile("wgmma.wait_group.sync.aligned %0;" ::"n"(N) : "memory"); }
template <int N> __device__ __forceinline__ void pin(uint32_t (&d)[N]) {
#pragma unroll
    for (int q = 0; q < N; q++) asm volatile("" : "+r"(d[q])::"memory");
}
__device__ __forceinline__ void stg128(void* p, const uint32_t (&v)[4]) {
    asm volatile("st.global.v4.u32 [%0], {%1, %2, %3, %4};" ::"l"(p), "r"(v[0]), "r"(v[1]), "r"(v[2]), "r"(v[3]) : "memory");
}
__device__ __forceinline__ void ldg128_if(bool on, uint32_t (&v)[4], const void* p) {
    asm volatile("{\n.reg .pred p;\nsetp.ne.b32 p, %5, 0;\n@p ld.global.L1::no_allocate.v4.u32 {%0, %1, %2, %3}, [%4];\n}\n"
                 : "+r"(v[0]), "+r"(v[1]), "+r"(v[2]), "+r"(v[3]) : "l"(p), "r"((int)on) : "memory");
}
__device__ __forceinline__ uint4 ldg128_ordered(const void* p) {
    uint4 v;
    asm volatile("ld.global.nc.v4.u32 {%0, %1, %2, %3}, [%4];" : "=r"(v.x), "=r"(v.y), "=r"(v.z), "=r"(v.w) : "l"(p) : "memory");
    return v;
}
__host__ __device__ constexpr uint64_t make_desc(uint32_t addr, uint32_t lbo, uint32_t sbo) {
    return (uint64_t)((addr & 0x3FFFF) >> 4) | ((uint64_t)(lbo >> 4) << 16) | ((uint64_t)(sbo >> 4) << 32);
}
__device__ __forceinline__ void wgmma(uint32_t (&d)[12], uint32_t a0, uint32_t a1, uint32_t a2, uint32_t a3, uint64_t db, int acc) {
    asm volatile("{\n.reg .pred p;\nsetp.ne.b32 p, %17, 0;\n"
                 "wgmma.mma_async.sync.aligned.m64n48k16.f16.f16.f16 "
                 "{%0, %1, %2, %3, %4, %5, %6, %7, %8, %9, %10, %11}, "
                 "{%12, %13, %14, %15}, %16, p, 1, 1, 0;\n}\n"
                 : "+r"(d[0]), "+r"(d[1]), "+r"(d[2]), "+r"(d[3]), "+r"(d[4]), "+r"(d[5]), "+r"(d[6]), "+r"(d[7]), "+r"(d[8]), "+r"(d[9]), "+r"(d[10]), "+r"(d[11])
                 : "r"(a0), "r"(a1), "r"(a2), "r"(a3), "l"(db), "r"(acc));
}
__device__ __forceinline__ void wgmma(uint32_t (&d)[24], uint32_t a0, uint32_t a1, uint32_t a2, uint32_t a3, uint64_t db, int acc) {
    asm volatile("{\n.reg .pred p;\nsetp.ne.b32 p, %29, 0;\n"
                 "wgmma.mma_async.sync.aligned.m64n96k16.f16.f16.f16 "
                 "{%0, %1, %2, %3, %4, %5, %6, %7, %8, %9, %10, %11, %12, %13, %14, %15, %16, %17, %18, %19, %20, %21, %22, %23}, "
                 "{%24, %25, %26, %27}, %28, p, 1, 1, 0;\n}\n"
                 : "+r"(d[0]), "+r"(d[1]), "+r"(d[2]), "+r"(d[3]), "+r"(d[4]), "+r"(d[5]), "+r"(d[6]), "+r"(d[7]), "+r"(d[8]), "+r"(d[9]), "+r"(d[10]), "+r"(d[11]), "+r"(d[12]), "+r"(d[13]), "+r"(d[14]), "+r"(d[15]), "+r"(d[16]), "+r"(d[17]), "+r"(d[18]), "+r"(d[19]), "+r"(d[20]), "+r"(d[21]), "+r"(d[22]), "+r"(d[23])
                 : "r"(a0), "r"(a1), "r"(a2), "r"(a3), "l"(db), "r"(acc));
}
template <int ACC>
__device__ __forceinline__ void wgmma_rowsum(float (&d)[4], const uint32_t (&a)[4], uint64_t ones) {
    asm volatile("{\n.reg .pred p;\nsetp.ne.b32 p, %9, 0;\n"
                 "wgmma.mma_async.sync.aligned.m64n8k16.f32.bf16.bf16 {%0, %1, %2, %3}, {%4, %5, %6, %7}, %8, p, 1, 1, 0;\n}\n"
                 : "+f"(d[0]), "+f"(d[1]), "+f"(d[2]), "+f"(d[3])
                 : "r"(a[0]), "r"(a[1]), "r"(a[2]), "r"(a[3]), "l"(ones), "n"(ACC));
}
__device__ __forceinline__ void ldsm4(uint32_t (&r)[4], uint32_t addr) {
    asm volatile("ldmatrix.sync.aligned.m8n8.x4.shared.b16 {%0, %1, %2, %3}, [%4];"
                 : "=r"(r[0]), "=r"(r[1]), "=r"(r[2]), "=r"(r[3]) : "r"(addr) : "memory");
}
__device__ __forceinline__ void ldsm4_t(uint32_t (&r)[4], uint32_t addr) {
    asm volatile("ldmatrix.sync.aligned.m8n8.x4.trans.shared.b16 {%0, %1, %2, %3}, [%4];"
                 : "=r"(r[0]), "=r"(r[1]), "=r"(r[2]), "=r"(r[3]) : "r"(addr) : "memory");
}
__device__ __forceinline__ void stsm4(uint32_t addr, uint32_t a, uint32_t b, uint32_t c, uint32_t d) {
    asm volatile("stmatrix.sync.aligned.m8n8.x4.shared.b16 [%0], {%1, %2, %3, %4};"
                 ::"r"(addr), "r"(a), "r"(b), "r"(c), "r"(d) : "memory");
}
__device__ __forceinline__ uint32_t transpose8x8(uint32_t v) {
    uint32_t d; asm volatile("movmatrix.sync.aligned.m8n8.trans.b16 %0, %1;" : "=r"(d) : "r"(v)); return d;
}
__device__ __forceinline__ void spin_until(const unsigned* counter, unsigned target) {
    unsigned n = 0, c;
    do {
        asm volatile("ld.acquire.gpu.global.u32 %0, [%1];" : "=r"(c) : "l"(counter) : "memory");
        if (++n > SPIN_LIMIT) __trap();
    } while ((int)(c - target) < 0);
}
__device__ __forceinline__ void signal(unsigned* counter) {
    __syncwarp();
    if (elect_one()) asm volatile("red.release.gpu.global.add.u32 [%0], 1;" ::"l"(counter) : "memory");
    __syncwarp();
}
__device__ __forceinline__ void lds128(uint32_t& a, uint32_t& b, uint32_t& c, uint32_t& d, uint32_t addr) {
    asm volatile("ld.shared.v4.u32 {%0, %1, %2, %3}, [%4];" : "=r"(a), "=r"(b), "=r"(c), "=r"(d) : "r"(addr) : "memory");
}
__device__ __forceinline__ void lds64(uint32_t& a, uint32_t& b, uint32_t addr) {
    asm volatile("ld.shared.v2.u32 {%0, %1}, [%2];" : "=r"(a), "=r"(b) : "r"(addr) : "memory");
}
__device__ __forceinline__ void lds32(uint32_t& a, uint32_t addr) {
    asm volatile("ld.shared.u32 %0, [%1];" : "=r"(a) : "r"(addr) : "memory");
}
__device__ __forceinline__ float ldsf(uint32_t addr) {
    uint32_t v;
    lds32(v, addr);
    return __uint_as_float(v);
}
__device__ __forceinline__ void sts32(uint32_t addr, uint32_t a) {
    asm volatile("st.shared.u32 [%0], %1;" ::"r"(addr), "r"(a) : "memory");
}
__device__ __forceinline__ void sts128(uint32_t addr, uint32_t a, uint32_t b, uint32_t c, uint32_t d) {
    asm volatile("st.shared.v4.u32 [%0], {%1, %2, %3, %4};" ::"r"(addr), "r"(a), "r"(b), "r"(c), "r"(d) : "memory");
}
__device__ __forceinline__ void sts64(uint32_t addr, uint32_t a, uint32_t b) {
    asm volatile("st.shared.v2.u32 [%0], {%1, %2};" ::"r"(addr), "r"(a), "r"(b) : "memory");
}
__device__ __forceinline__ uint32_t bf_fma(uint32_t a, uint32_t b, uint32_t c) {
    uint32_t d; asm("fma.rn.bf16x2 %0, %1, %2, %3;" : "=r"(d) : "r"(a), "r"(b), "r"(c)); return d;
}
__device__ __forceinline__ uint32_t bf_mul(uint32_t a, uint32_t b) {
    uint32_t d; asm("mul.rn.bf16x2 %0, %1, %2;" : "=r"(d) : "r"(a), "r"(b)); return d;
}
__device__ __forceinline__ uint32_t bf_absmax(uint32_t a, uint32_t b) {
    uint32_t d; asm("max.xorsign.abs.bf16x2 %0, %1, %2;" : "=r"(d) : "r"(a), "r"(b)); return d;
}
__device__ __forceinline__ uint32_t h_fma(uint32_t a, uint32_t b, uint32_t c) {
    uint32_t d; asm("fma.rn.f16x2 %0, %1, %2, %3;" : "=r"(d) : "r"(a), "r"(b), "r"(c)); return d;
}
__device__ __forceinline__ uint32_t h_mul(uint32_t a, uint32_t b) {
    uint32_t d; asm("mul.rn.f16x2 %0, %1, %2;" : "=r"(d) : "r"(a), "r"(b)); return d;
}
__device__ __forceinline__ uint32_t h_round8(uint32_t v) { return (v + 0x00040004u) & 0xfff8fff8u; }
__device__ __forceinline__ uint32_t h_tanh(uint32_t a) {
    uint32_t d; asm("tanh.approx.f16x2 %0, %1;" : "=r"(d) : "r"(a)); return d;
}
__device__ __forceinline__ uint32_t pack_h2(float lo, float hi) {
    uint32_t d; asm("cvt.rn.f16x2.f32 %0, %1, %2;" : "=r"(d) : "f"(hi), "f"(lo)); return d;
}
__device__ __forceinline__ uint32_t pack_bf2(float lo, float hi) {
    uint32_t d; asm("cvt.rn.bf16x2.f32 %0, %1, %2;" : "=r"(d) : "f"(hi), "f"(lo)); return d;
}
__device__ __forceinline__ float bf_lo(uint32_t v) { return __uint_as_float(v << 16); }
__device__ __forceinline__ float bf_hi(uint32_t v) { return __uint_as_float(v & 0xffff0000u); }
__device__ __forceinline__ float h_lo(uint32_t v) { return __low2float(*reinterpret_cast<__half2*>(&v)); }
__device__ __forceinline__ float h_hi(uint32_t v) { return __high2float(*reinterpret_cast<__half2*>(&v)); }
__device__ __forceinline__ float warp_absmax(uint32_t v) {
    return __uint_as_float(__reduce_max_sync(~0u, max((v & 0x7fffu) << 16, v & 0x7fff0000u)));
}
__device__ __forceinline__ uint32_t gelu2(uint32_t z) {
    uint32_t p = h_fma(z, z, GELU_C2);
    uint32_t t = h_tanh(h_mul(z, p));
    return h_fma(z, t, z);
}
__device__ __forceinline__ float grn_norm(float ss) {
    float r;
    asm("sqrt.approx.f32 %0, %1;" : "=f"(r) : "f"(fmaf(ss, INV_2KZ * INV_2KZ, 1e-6f)));
    return r;
}
__device__ __forceinline__ float pow2i(int e) { return __uint_as_float((uint32_t)(e + 127) << 23); }
__device__ __forceinline__ int ilog2f(float v) {
    int e = (int)((__float_as_uint(v) >> 23) & 0xff) - 127;
    return max(-100, min(100, e));
}

__device__ __forceinline__ int sum_exp(float w1max) {
    return w1max > 0.f ? max(-90, min(90, 35 - 2 * ilog2f(2.f * KZ * 96.f * w1max))) : 0;
}
__device__ __forceinline__ float row_scale(float m) { return m > 0.f ? pow2i(2 - ilog2f(m)) : 1.f; }

struct Work {
    int tA, tB, nA, nB, rows, lent;
    __device__ __forceinline__ int tile(int j) const { return j < nA ? tA + j : tB + j - nA; }
};
__device__ __forceinline__ Work get_work(int per_cta, int extra, int lenders) {
    Work w;
    w.lent = (int)blockIdx.x < lenders ? LENT : 0;
    const int t0 = blockIdx.x * per_cta + min((int)blockIdx.x, extra);
    const int t1 = t0 + per_cta + ((int)blockIdx.x < extra);
    const int tm = min(t1, (t0 | 511) + 1);
    const bool swap = t1 > tm && t1 - tm < tm - t0;
    w.tA = swap ? tm : t0;
    w.tB = swap ? t0 : tm;
    w.nA = swap ? t1 - tm : tm - t0;
    w.nB = t1 - t0 - w.nA;
    w.rows = w.nA + 2 + (w.nB ? w.nB + 2 : 0);
    return w;
}
__device__ __forceinline__ int row_code(const Work& w, int i) {
    const bool in_a = i < w.nA + 2;
    const int t = in_a ? w.tA : w.tB;
    return ((t & 511) - 1 + (in_a ? i : i - (w.nA + 2))) << 16 | (t >> 9) * TILE_W;
}
__device__ __forceinline__ uint32_t tile_offset(int tile) { return ((tile & 511) * IMG_W + (tile >> 9) * TILE_W) * (CH * 2); }
__device__ __forceinline__ int tile_order(int j, int n) {
    const int olds = (j / ORDER_P) * ORDER_Q + max(0, j % ORDER_P - (ORDER_P - ORDER_Q));
    return (j % ORDER_P >= ORDER_P - ORDER_Q) ? olds : n - 1 - (j - olds);
}
__device__ __forceinline__ void issue_region(const CUtensorMap* tm, uint32_t dst, uint32_t bar, int warp, int code) {
    mbar_expect_tx(bar, REGION_BYTES);
    tma_row(dst, tm, bar, (code & 0xffff) + (16 * warp - 1), code >> 16);
}
__device__ __forceinline__ void elect_arrive(uint32_t bar0, uint32_t bar1, bool both) {
    asm volatile("{\n.reg .pred p, q;\nelect.sync _|p, 0xffffffff;\nsetp.ne.and.b32 q, %2, 0, p;\n"
                 "@p mbarrier.arrive.shared::cta.b64 _, [%0];\n@q mbarrier.arrive.shared::cta.b64 _, [%1];\n}\n"
                 ::"r"(bar0), "r"(bar1), "r"((int)both) : "memory");
}

__device__ __forceinline__ void first_loads(const Work& wk, const CUtensorMap* tm, const CUtensorMap* tw, const __nv_bfloat16* dw,
                                            uint32_t sb, int warp) {
    const uint32_t reg0 = sb + SM_RING + warp * REGION_BYTES, bars = sb + SM_BAR + warp * 8;
#pragma unroll
    for (int s = 0; s < PREFETCH_ROWS; s++) mbar_init(bars + s * 32, 1);
    mbar_init(sb + BAR_W + warp * 8, 1);
    if (warp < 2) mbar_init(sb + BAR_W + (warp + 4) * 8, 1);
    fence_async();
    asm volatile("mbarrier.expect_tx.shared::cta.b64 [%0], %1;" ::"r"(bars), "r"(9 * CH * 2) : "memory");
    bulk_load(reg0 + (NSLOT - 1) * SLOT_BYTES, dw, 9 * CH * 2, bars);
#pragma unroll
    for (int r = 0; r < PREFETCH_ROWS; r++)
        issue_region(tm, reg0 + r * SLOT_BYTES, bars + r * 32, warp, ((wk.tA & 511) - 1 + r) << 16 | (wk.tA >> 9) * TILE_W);
#pragma unroll 1
    for (int b = warp; b < 6; b += 4) {
        mbar_expect_tx(sb + BAR_W + b * 8, 64 * CH * 2);
        tma_2d(sb + SM_W2 + b * (64 * CH * 2), tw, sb + BAR_W + b * 8, 64 * b, 0);
    }
}

__device__ __forceinline__ void conv_producer(const Work& wk, const CUtensorMap* tm, Scratch* sc, uint32_t sb, int warp) {
    const int lane = threadIdx.x & 31;
    const int j = lane & 15, grp = lane >> 4;
    const uint32_t reg0 = sb + SM_RING + warp * REGION_BYTES;
    const uint32_t bars = sb + SM_BAR + warp * 8;
    if (elect_one()) {
        if (warp == 0) mbar_init(sb + BAR_PIN, 1);
#pragma unroll
        for (int s = 0; s < 4; s++) mbar_init(sb + BAR_R + (s * 4 + warp) * 8, 1);
#pragma unroll 1
        for (int s = PREFETCH_ROWS; s < 3 * NSLOT; s++) mbar_init(bars + s * 32, 1);
        fence_async();
    }
    __syncwarp();
    named_arrive(0, NTHREADS);
    if (warp * 32 + lane < MAX_ROWS) {
        sts32(sb + SM_ROWS + (warp * 32 + lane) * 4, row_code(wk, warp * 32 + lane));
        sts32(sb + SM_TILES + (warp * 32 + lane) * 4, tile_offset(wk.tile(wk.lent + tile_order(max(warp * 32 + lane - wk.lent / 2, 0), wk.nA + wk.nB - NCONS - wk.lent))));
    }
    const uint32_t ld64 = opaque(reg0 + grp * 8 * 192 + j * 8), ld32 = opaque(reg0 + grp * 8 * 192 + 128 + j * 4);
    const uint32_t st64 = opaque(reg0 + grp * A_SBO + (j >> 1) * A_LBO + (j & 1) * 8);
    const uint32_t st32 = opaque(reg0 + grp * A_SBO + (8 + (j >> 2)) * A_LBO + (j & 3) * 4);
    uint32_t accB[8][3] = {}, accC[8][3] = {};
    static_assert(2 * PREFETCH_ROWS == NSLOT, "prefetch slot arithmetic");
    uint32_t so = 0, bo = 0, par = 0, tbl = sb + SM_ROWS + PREFETCH_ROWS * 4;
    const uint32_t tbl_end = sb + SM_ROWS + wk.rows * 4;
    bool x_ready = false;
    named_bar(1, 128);
    mbar_wait(bars, 0);
    uint32_t w[3][3][3];
#pragma unroll
    for (int tap = 0; tap < 9; tap++) {
        const uint32_t p = reg0 + (NSLOT - 1) * SLOT_BYTES + tap * CH * 2;
        uint32_t u0, u1;
        lds64(u0, u1, p + 8 * j);
        __syncwarp();
        sts64(p + 8 * j, u1, u0);
        __syncwarp();
        lds64(w[tap / 3][tap % 3][1], w[tap / 3][tap % 3][0], p + 8 * j);
        lds32(w[tap / 3][tap % 3][2], p + 128 + 4 * j);
    }
    {
        const int first = wk.nA + 2, publish = wk.lent ? 12 : -1;
#pragma unroll 1
        for (int k = 0; k < wk.rows; k++) {
            if (!x_ready) mbar_wait(bars + bo, par);
            const bool wrap = bo == (NSLOT - 1) * 32, low = bo < PREFETCH_ROWS * 32;
            const uint32_t nbo = wrap ? 0 : bo + 32, npar = par ^ wrap;
            const uint32_t pbo = low ? bo + PREFETCH_ROWS * 32 : bo - PREFETCH_ROWS * 32, ppar = par ^ low;
            uint32_t out[8][3];
            int code;
            bool e_ready;
#pragma unroll
            for (int p = 0; p < 10; p++) {
                uint32_t xv[3];
                lds64(xv[0], xv[1], so + ld64 + p * 192);
                lds32(xv[2], so + ld32 + p * 192);
                if (p == 9) {
                    asm volatile("ld.shared.u32 %0, [%1];" : "=r"(code) : "r"(tbl));
                    e_ready = mbar_test(bars + (BAR_E - SM_BAR) + pbo, ppar);
                    x_ready = mbar_test(bars + nbo, npar);
                }
#pragma unroll
                for (int dx = 0; dx < 3; dx++) {
                    const int o = p - dx;
                    if (o < 0 || o > 7) continue;
#pragma unroll
                    for (int q = 0; q < 3; q++) {
                        out[o][q] = bf_fma(xv[q], w[2][dx][q], dx == 0 ? accB[o][q] : out[o][q]);
                        accB[o][q] = bf_fma(xv[q], w[1][dx][q], dx == 0 ? accC[o][q] : accB[o][q]);
                        accC[o][q] = dx == 0 ? bf_mul(xv[q], w[0][dx][q]) : bf_fma(xv[q], w[0][dx][q], accC[o][q]);
                    }
                }
            }
            __syncwarp();
#pragma unroll
            for (int o = 0; o < 8; o++) {
                sts64(so + st64 + o * 16, out[o][0], out[o][1]);
                sts32(so + st32 + o * 16, out[o][2]);
            }
            const bool halo = k < 2 || (unsigned)(k - first) < 2;
            if (halo) fence_async();
            if (k == publish) signal(&sc->lent_in);
            __syncwarp();
            elect_arrive(bars + (BAR_A - SM_BAR) + bo, bars + (BAR_E - SM_BAR) + bo, halo);
            if (tbl < tbl_end) {
                if (!e_ready) mbar_wait(bars + (BAR_E - SM_BAR) + pbo, ppar);
                code = __shfl_sync(~0u, code, 0);
                if (elect_one()) issue_region(tm, reg0 + (low ? so + PREFETCH_ROWS * SLOT_BYTES : so - PREFETCH_ROWS * SLOT_BYTES), bars + pbo, warp, code);
            }
            tbl += 4;
            so = wrap ? 0 : so + SLOT_BYTES;
            bo = nbo;
            par = npar;
        }
    }
}

template <bool V> struct Flag { static constexpr bool value = V; };
template <bool SCALED, int K0 = 0, int K1 = 3>
__device__ __forceinline__ void gelu_sq(uint32_t (&d)[24], uint32_t (&keep)[24], uint32_t sq_addr, uint32_t scale2) {
    pin(d);
#pragma unroll
    for (int k = K0; k < K1; k++) {
        uint32_t hs[4];
        lds128(hs[0], hs[1], hs[2], hs[3], sq_addr + k * SQ_ROW);
#pragma unroll
        for (int q = 0; q < 4; q++) {
            uint32_t g0 = gelu2(d[8 * k + 2 * q]), g1 = gelu2(d[8 * k + 2 * q + 1]);
            keep[8 * k + 2 * q] = g0;
            keep[8 * k + 2 * q + 1] = g1;
            if (SCALED) { g0 = h_mul(g0, scale2); g1 = h_mul(g1, scale2); }
            hs[q] = h_fma(g1, g1, h_fma(g0, g0, hs[q]));
        }
        sts128(sq_addr + k * SQ_ROW, hs[0], hs[1], hs[2], hs[3]);
    }
}
__device__ __forceinline__ void anchor(uint32_t addr, uint32_t a, uint32_t b, uint32_t c, uint32_t d) {
    asm volatile("{\n.reg .pred p;\nsetp.eq.b32 p, %0, 0;\n@p st.shared.v4.u32 [%0], {%1, %2, %3, %4};\n}\n"
                 ::"r"(addr), "r"(a), "r"(b), "r"(c), "r"(d) : "memory");
}
template <bool SCALED>
__device__ __forceinline__ void gelu_sq_reg(uint32_t (&d)[24], uint32_t (&hs)[12], uint32_t scale2) {
    pin(d);
#pragma unroll
    for (int q = 0; q < 12; q++) {
        uint32_t g0 = gelu2(d[2 * q]), g1 = gelu2(d[2 * q + 1]);
        if (SCALED) { g0 = h_mul(g0, scale2); g1 = h_mul(g1, scale2); }
        hs[q] = h_fma(g1, g1, h_fma(g0, g0, hs[q]));
    }
}
__device__ __forceinline__ void gelu_to(uint32_t (&g)[12], uint32_t (&d)[12]) {
    pin(d);
#pragma unroll
    for (int q = 0; q < 12; q++) g[q] = gelu2(d[q]);
    pin(g);
}
__device__ __forceinline__ void load_tile(uint32_t (&raw)[6][4], uint32_t addr) {
#pragma unroll
    for (int s = 0; s < 6; s++) ldsm4(raw[s], addr + s * 2 * A_LBO);
}
__device__ __forceinline__ uint2 ln_stats(const uint32_t (&raw)[6][4], uint64_t ones) {
    uint32_t sq[6][4];
#pragma unroll
    for (int s = 0; s < 6; s++)
#pragma unroll
        for (int q = 0; q < 4; q++) sq[s][q] = bf_mul(raw[s][q], raw[s][q]);
    float sum[4], ssq[4];
    wg_fence();
    wgmma_rowsum<0>(sum, raw[0], ones);
#pragma unroll
    for (int s = 1; s < 6; s++) wgmma_rowsum<1>(sum, raw[s], ones);
    wgmma_rowsum<0>(ssq, sq[0], ones);
#pragma unroll
    for (int s = 1; s < 6; s++) wgmma_rowsum<1>(ssq, sq[s], ones);
    wg_commit();
    wg_wait<0>();
    uint32_t st[2];
#pragma unroll
    for (int h = 0; h < 2; h++) {
        asm volatile("" : "+f"(sum[2 * h]), "+f"(ssq[2 * h])::"memory");
        const float mean = sum[2 * h] * (1.f / CH);
        const float var = fmaxf(fmaf(ssq[2 * h], 1.f / CH, -mean * mean), 0.f);
        float rstd;
        asm("rsqrt.approx.ftz.f32 %0, %1;" : "=f"(rstd) : "f"(var + 1e-5f));
        rstd = bf_lo(pack_bf2(rstd * KZ, 0.f));
        st[h] = pack_bf2(rstd, -mean * rstd);
    }
    return make_uint2(st[0], st[1]);
}
__device__ __forceinline__ void ln_apply(uint32_t (&a)[6][4], const uint2& st) {
    const uint32_t sc[2] = {__byte_perm(st.x, 0, 0x1010), __byte_perm(st.y, 0, 0x1010)};
    const uint32_t sh[2] = {__byte_perm(st.x, 0, 0x3232), __byte_perm(st.y, 0, 0x3232)};
#pragma unroll
    for (int s = 0; s < 6; s++)
#pragma unroll
        for (int q = 0; q < 4; q++) {
            const uint32_t v = bf_fma(a[s][q], sc[q & 1], sh[q & 1]);
            a[s][q] = pack_h2(bf_lo(v), bf_hi(v));
        }
}
__device__ __forceinline__ void stagger_wait(int jt, int wgi) {
    if (jt > 0) named_bar(4 + wgi, 256);
}
__device__ __forceinline__ void stagger_pass(int jt, int wgi, int ntiles) {
    if (jt + 1 < ntiles) named_arrive(4 + (wgi == NCONS - 1 ? 0 : wgi + 1), 256);
}
struct Cursor {
    int slot;
    uint32_t par;
    __device__ __forceinline__ void advance(int n) {
        slot += n;
        if (slot >= NSLOT) { slot -= NSLOT; par ^= 1; }
    }
};
struct Descs {
    uint64_t w1[8][6];
    uint64_t w2[24];
    uint64_t ones;
};
template <int E0, int N>
__device__ __forceinline__ void gemm1_chunk(uint32_t (&d)[N], const uint32_t (&a)[6][4], const Descs& ds, int zero) {
#pragma unroll
    for (int s = 0; s < 6; s++) wgmma(d, a[s][0], a[s][1], a[s][2], a[s][3], ds.w1[E0 / 48][s], s ? 1 : zero);
}
template <int E0, int N>
__device__ __forceinline__ void gemm2_chunk(uint32_t (&acc)[24], const uint32_t (&g)[N], const Descs& ds) {
#pragma unroll
    for (int s = 0; s < N / 4; s++) wgmma(acc, g[4 * s], g[4 * s + 1], g[4 * s + 2], g[4 * s + 3], ds.w2[E0 / 16 + s], 1);
}

__global__ void __launch_bounds__(NTHREADS, 1)
block_kernel(const __grid_constant__ CUtensorMap tmap, const __grid_constant__ CUtensorMap tmap_w1,
             const __nv_bfloat16* __restrict__ x, const __nv_bfloat16* __restrict__ dw, const __nv_bfloat16* __restrict__ w2,
             const __nv_bfloat16* __restrict__ gamma, const __nv_bfloat16* __restrict__ beta, __nv_bfloat16* __restrict__ out,
             Scratch* __restrict__ sc, const __grid_constant__ Descs ds,
             const int zero, const int per_cta, const int extra, const int lenders) {
    extern __shared__ __align__(1024) uint8_t smem[];
    constexpr uint32_t sb = SB;
    const int tid = threadIdx.x;
    const Work wk = get_work(per_cta, extra, lenders);
    if (smem_u32(smem) != SB || wk.rows + 4 > MAX_ROWS) __trap();
    constexpr uint32_t s_red = sb + SM_RED;

    PROF(0);
    const int warp_id = __shfl_sync(~0u, tid >> 5, 0);
    if (warp_id < 4 && elect_one()) first_loads(wk, &tmap, &tmap_w1, dw, sb, warp_id);
    __syncwarp();
    const int cw = warp_id - 4, wgi = cw >> 2, w4 = warp_id & 3;
    const int ntiles = wk.nA + wk.nB;
    const int wg = warp_id >> 2;
    int first = wg;
    uint32_t a[6][4], tile_off, next_off, stage, inv_rho2 = 0, rpar = 0, bias_addr, lane16, lane_off;
    auto set_lane = [&](uint32_t lane) {
        bias_addr = sb + SM_BIASH + (lane & 3) * 96;
        lane16 = lane * 16;
        lane_off = ((lane >> 2) * CH + 8 * (lane & 3)) * 2;
    };
    const uint32_t bar_r = sb + BAR_R + warp_id * 8;
    auto load_bias = [&](uint32_t (&acc)[24]) {
#pragma unroll
        for (int q = 0; q < 6; q++) lds128(acc[4 * q], acc[4 * q + 1], acc[4 * q + 2], acc[4 * q + 3], bias_addr + q * 16);
    };
    auto load_frags = [&](bool on) {
#pragma unroll
        for (int s = 0; s < 6; s++) ldg128_if(on, a[s], reinterpret_cast<const char*>(out) + next_off + w4 * WARP_BYTES + lane16 + s * 512);
    };
    auto stage_x = [&]() {
        if (elect_one()) {
            mbar_expect_tx(bar_r, WARP_BYTES);
            bulk_load_stream(stage, reinterpret_cast<const char*>(x) + tile_off + w4 * WARP_BYTES, WARP_BYTES, bar_r);
        }
    };
    auto epilogue = [&](uint32_t (&acc)[24]) {
        pin(acc);
        rpar ^= 1;
        uint4* op = reinterpret_cast<uint4*>(reinterpret_cast<char*>(out) + tile_off + w4 * WARP_BYTES + lane_off);
#pragma unroll
        for (int h = 0; h < 2; h++)
#pragma unroll
            for (int m = 0; m < 3; m++) {
                uint32_t xin[4], o[4];
                lds128(xin[0], xin[1], xin[2], xin[3], stage + lane_off + h * 1536 + m * 64);
#pragma unroll
                for (int q = 0; q < 4; q++) {
                    const uint32_t v = acc[2 * (4 * m + q) + h];
                    o[q] = bf_fma(pack_bf2(h_lo(v), h_hi(v)), inv_rho2, xin[q]);
                }
                __stcs(op + h * 96 + m * 4, make_uint4(o[0], o[1], o[2], o[3]));
            }
        __syncwarp();
    };
    auto max_w1 = [&]() {
        float m = 0.f;
#pragma unroll
        for (int q = 0; q < 3; q++) {
            uint32_t u[4];
            lds128(u[0], u[1], u[2], u[3], s_red + q * 16);
#pragma unroll
            for (int k = 0; k < 4; k++) m = fmaxf(m, __uint_as_float(u[k]));
        }
        return m;
    };
    auto square_exp = [&](float w1max) {
        const int e = w1max > 0.f ? 4 - ilog2f(2.f * KZ * 96.f * w1max) : 0;
        return (e >= 0 && e <= 6) ? 0 : max(-14, min(e, 14));
    };
    const int last_wg = (ntiles - 1 - wk.lent) % NCONS;
    auto reduce = [&](int q, uint32_t lane, bool leader) {
        const int t = lane & 3, part = lane >> 2;
        float f[8] = {};
        named_bar(11, CONS_THREADS);
#pragma unroll 1
        for (int i = 0; i < NCONS; i++) {
            const int src_wg = (last_wg + 1 + i) % NCONS;
            if (i == NCONS - 1) {
                named_bar(13, CONS_THREADS);
                if (leader) {
                    fence_async();
#pragma unroll
                    for (int k = 1; k < NCONS; k++) {
                        const int o = (last_wg + k) % NCONS * SQ_WG;
                        bulk_load(sb + SM_W2 + o, reinterpret_cast<const char*>(sc->w2h) + o, SQ_WG, sb + BAR_W);
                    }
                }
                __syncwarp();
                named_bar(14, NTHREADS);
            }
            const uint32_t src = lane * 16 + (q < 6 ? sb + SM_SQ + src_wg * SQ_WG + q * SQ_ROW
                                                    : sb + SM_RING + (wk.rows + i) % NSLOT * SLOT_BYTES + (q - 6) * SQ_ROW);
#pragma unroll
            for (int r = 0; r < 4; r++) {
                uint32_t u[4];
                lds128(u[0], u[1], u[2], u[3], src + r * 512);
#pragma unroll
                for (int k = 0; k < 4; k++) { f[2 * k] += h_lo(u[k]); f[2 * k + 1] += h_hi(u[k]); }
            }
            if (i == 0) {
                const unsigned in_piece = 32 * q + 2 * t - (blockIdx.x - lenders) % 8 * 48;
                const float up = pow2i(2 * square_exp(max_w1()));
#pragma unroll
                for (int k = 0; k < 8; k++)
                    if (part == 0 && in_piece + 8 * (k >> 1) < 48) f[k] = fmaf(ldsf(sb + SM_BIASH + (in_piece + 8 * (k >> 1) + (k & 1)) * 4), up, f[k]);
            }
        }
        const float w1max = max_w1(), to_fixed = pow2i(sum_exp(w1max) - 2 * square_exp(w1max));
        const bool b2 = part & 4, b1 = part & 2, b0 = part & 1;
        float r4[4], r2[2];
#pragma unroll
        for (int k = 0; k < 4; k++) r4[k] = (b2 ? f[k + 4] : f[k]) + __shfl_xor_sync(~0u, b2 ? f[k] : f[k + 4], 16);
#pragma unroll
        for (int k = 0; k < 2; k++) r2[k] = (b1 ? r4[k + 2] : r4[k]) + __shfl_xor_sync(~0u, b1 ? r4[k] : r4[k + 2], 8);
        const float tot = (b0 ? r2[1] : r2[0]) + __shfl_xor_sync(~0u, b0 ? r2[0] : r2[1], 4);
        atomicAdd(&sc->sums[__float_as_uint(ldsf(s_red + 48)) & 1][blockIdx.x % REPLICAS][32 * q + 8 * (part >> 1) + 2 * t + (part & 1)],
                  __float2ull_rn(fminf(tot * to_fixed, 0x1p49f)) << 8 | 1);
    };
    const uint32_t s_fac = sb + SM_RING + (wk.rows + 1) % NSLOT * SLOT_BYTES + SQ_WG;
    if (warp_id < 4) {
        conv_producer(wk, &tmap, sc, sb, warp_id);
        const int lane = opaque(tid & 31), g = lane >> 2, t = lane & 3;
        const unsigned epoch = __float_as_uint(ldsf(s_red + 48));
        set_lane(lane);
#pragma unroll 1
        for (int q = gridDim.x - 1 - blockIdx.x; q < W2_GROUPS; q += gridDim.x) {
            uint32_t u[3], rmax = 0;
#pragma unroll
            for (int m = 0; m < 3; m++) {
                const uint4 w = ldg128_ordered(w2 + (8 * q + g) * CH + 32 * m + 8 * t);
                rmax = bf_absmax(bf_absmax(rmax, bf_absmax(w.x, w.y)), bf_absmax(w.z, w.w));
                u[m] = w4 & 2 ? (w4 & 1 ? w.w : w.z) : (w4 & 1 ? w.y : w.x);
            }
            const float bt = __bfloat162float(beta[8 * q + g]);
            rmax = bf_absmax(rmax, __shfl_xor_sync(~0u, rmax, 1));
            rmax = bf_absmax(rmax, __shfl_xor_sync(~0u, rmax, 2));
            const float mx = fmaxf(fabsf(bf_lo(rmax)), fabsf(bf_hi(rmax))), rs = row_scale(mx);
            if (t == 0 && w4 == 0) sc->w2max[8 * q + g] = mx;
#pragma unroll
            for (int m = 0; m < 3; m++) {
                float lo = bf_lo(u[m]), hi = bf_hi(u[m]);
                sc->w2h[(4 * m + w4) * 1536 + q * 32 + lane] = transpose8x8(pack_h2(lo * rs, hi * rs));
                lo *= bt; hi *= bt;
#pragma unroll
                for (int o = 4; o <= 16; o <<= 1) { lo += __shfl_xor_sync(~0u, lo, o); hi += __shfl_xor_sync(~0u, hi, o); }
                if (g == 0) {
                    float* dst = &sc->bias[epoch & 1][32 * m + 8 * t + 2 * w4];
                    asm volatile("red.global.add.v2.f32 [%0], {%1, %2};" ::"l"(dst), "f"(lo), "f"(hi) : "memory");
                }
            }
            asm volatile("fence.proxy.async.global;" ::: "memory");
            signal(&sc->prep);
        }
#pragma unroll
        for (int s = 0; s < 6; s++) a[s][0] = a[s][1] = a[s][2] = a[s][3] = 0;
        const unsigned piece = blockIdx.x - lenders;
        if (piece < 8 * LENT * lenders) {
            spin_until(&sc->lent_in, (epoch + 1) * 4 * lenders);
            next_off = tile_offset(piece / (8 * LENT) * (per_cta + 1) + piece / 8 % LENT);
            load_frags(true);
            uint32_t d[12], gl[12];
            wg_fence();
#pragma unroll
            for (int s = 0; s < 6; s++) wgmma(d, a[s][0], a[s][1], a[s][2], a[s][3], ds.w1[0][s] + piece % 8 * (6 * 1536 / 16), s ? 1 : 0);
            wg_commit();
            wg_wait<0>();
            gelu_to(gl, d);
#pragma unroll
            for (int s = 0; s < 3; s++) sc->lent[((piece * 4 + w4) * 3 + s) * 32 + lane] = make_uint4(gl[4 * s], gl[4 * s + 1], gl[4 * s + 2], gl[4 * s + 3]);
            float f[6], r[3];
#pragma unroll
            for (int j = 0; j < 6; j++) {
                const float lo = fmaf(h_lo(gl[2 * j]), h_lo(gl[2 * j]), h_lo(gl[2 * j + 1]) * h_lo(gl[2 * j + 1]));
                const float hi = fmaf(h_hi(gl[2 * j]), h_hi(gl[2 * j]), h_hi(gl[2 * j + 1]) * h_hi(gl[2 * j + 1]));
                f[j] = (g & 1 ? hi : lo) + __shfl_xor_sync(~0u, g & 1 ? lo : hi, 4);
            }
#pragma unroll
            for (int j = 0; j < 3; j++) {
                r[j] = (g & 2 ? f[j + 3] : f[j]) + __shfl_xor_sync(~0u, g & 2 ? f[j] : f[j + 3], 8);
                asm volatile("red.shared.add.f32 [%0], %1;" ::"r"(sb + SM_BIASH + (8 * j + 12 * (g & 2) + 2 * t + (g & 1)) * 4), "f"(r[j]) : "memory");
            }
        }
        if (piece < 8 * LENT * lenders) signal(&sc->lent_out);
        const bool leader = warp_id == 0 && lane == 0;
        if (leader) {
            spin_until(&sc->prep, (epoch + 1) * 4 * W2_GROUPS);
            asm volatile("fence.proxy.async.global;" ::: "memory");
            mbar_expect_tx(sb + BAR_W, EX * CH * 2);
            bulk_load(sb + SM_W2 + NCONS * SQ_WG, reinterpret_cast<const char*>(sc->w2h) + NCONS * SQ_WG, EX * CH * 2 - NCONS * SQ_WG, sb + BAR_W);
        }
        __syncwarp();
        named_bar(1, 128);
        const int i0 = w4 * 32 + lane;
        float gam[3], rmax[3];
#pragma unroll
        for (int m = 0; m < 3; m++) { gam[m] = __bfloat162float(gamma[i0 + 128 * m]); rmax[m] = __ldcg(&sc->w2max[i0 + 128 * m]); }
        float2 bpair = make_float2(0.f, 0.f);
        if (i0 < 96) bpair = __ldcg(reinterpret_cast<const float2*>(&sc->bias[epoch & 1][32 * (i0 % 24 >> 3) + 8 * (i0 / 24) + (i0 % 24 & 6)]));
        const float w1max = max_w1();
        const float gbound = fmaxf(2.f * KZ * 9.7979590f * 192.f * w1max, 1.f) * 19.5959180f * INV_2KZ;
        const unsigned fixed = __reduce_max_sync(~0u, __float_as_uint(fmaf(gbound, fmaxf(fmaxf(rmax[0], rmax[1]), rmax[2]), fmaxf(fabsf(bpair.x), fabsf(bpair.y)))));
        if (lane == 0) sts32(s_red + 96 + w4 * 4, fixed);
        reduce(4 * last_wg + w4, lane, leader);
        PROF(2);
        named_bar(15, CONS_THREADS);
        if (leader) {
            fence_async();
            bulk_load(sb + SM_W2 + last_wg * SQ_WG, reinterpret_cast<const char*>(sc->w2h) + last_wg * SQ_WG, SQ_WG, sb + BAR_W);
        }
        stage = sb + SM_RING + (wk.rows % NSLOT) * SLOT_BYTES + w4 * REGION_BYTES;
        auto grn = [&]() {
            unsigned long long sum[3];
            for (unsigned n = 0;; n++) {
                bool all = true;
#pragma unroll
                for (int m = 0; m < 3; m++) {
                    unsigned cnt = 0;
                    sum[m] = 0;
#pragma unroll
                    for (int q = 0; q < REPLICAS; q++) {
                        unsigned long long v;
                        asm volatile("ld.relaxed.gpu.global.u64 %0, [%1];" : "=l"(v) : "l"(&sc->sums[epoch & 1][q][i0 + 128 * m]) : "memory");
                        cnt += (unsigned)v & 255u;
                        sum[m] += v >> 8;
                    }
                    all &= cnt == gridDim.x;
                }
                if (__all_sync(~0u, all)) break;
                if (n > SPIN_LIMIT) __trap();
            }
            PROF(3);
            if (blockIdx.x == 0 && leader) sc->launch = epoch + 1;
            float gx[3], tot = 0.f, vary = 0.f;
#pragma unroll
            for (int m = 0; m < 3; m++) {
                gx[m] = grn_norm(__ull2float_rn(sum[m]) * pow2i(-sum_exp(w1max)));
                tot += gx[m];
                vary = fmaxf(vary, fabsf(gam[m]) * gx[m] * rmax[m]);
            }
#pragma unroll
            for (int o = 16; o >= 1; o >>= 1) tot += __shfl_xor_sync(~0u, tot, o);
            const unsigned vwarp = __reduce_max_sync(~0u, __float_as_uint(vary));
            if (lane == 0) { sts32(s_red + 64 + w4 * 4, __float_as_uint(tot)); sts32(s_red + 80 + w4 * 4, vwarp); }
            named_bar(1, 128);
            uint32_t u[4], v[4], w[4];
            lds128(u[0], u[1], u[2], u[3], s_red + 64);
            lds128(v[0], v[1], v[2], v[3], s_red + 80);
            lds128(w[0], w[1], w[2], w[3], s_red + 96);
            tot = (__uint_as_float(u[0]) + __uint_as_float(u[1])) + (__uint_as_float(u[2]) + __uint_as_float(u[3]));
            const float vmax = __uint_as_float(max(max(v[0], v[1]), max(v[2], v[3]))), fmax2 = __uint_as_float(max(max(w[0], w[1]), max(w[2], w[3])));
            const float inv_mean = __fdividef(1.f, tot * (1.f / EX) + 1e-6f);
            const float bound = fmaf(gbound * vmax, inv_mean, 2.f * fmax2);
            const int rho_e = bound > 0.f ? 14 - ilog2f(bound) : 0;
            const float rho = pow2i(rho_e), inv_rho = pow2i(-rho_e);
            inv_rho2 = pack_bf2(inv_rho, inv_rho);
#pragma unroll
            for (int m = 0; m < 3; m++) {
                const float f = __fdividef(fmaf(gam[m], gx[m] * inv_mean, 1.f) * INV_2KZ * rho, row_scale(rmax[m]));
                asm volatile("st.shared.u16 [%0], %1;" ::"r"(s_fac + (i0 + 128 * m) * 2), "h"((unsigned short)pack_h2(f, 0.f)) : "memory");
            }
            if (i0 < 96) sts32(sb + SM_BIASH + i0 * 4, pack_h2(bpair.x * rho, bpair.y * rho));
            if (i0 == 96) sts32(s_red + 52, inv_rho2);
            named_arrive(12, NTHREADS);
        };
        if (wk.lent) {
            tile_off = tile_offset(wk.tA);
            stage_x();
            if (elect_one()) prefetch_l2(reinterpret_cast<const char*>(x) + tile_offset(wk.tA + 1) + w4 * WARP_BYTES, WARP_BYTES);
            spin_until(&sc->lent_out, (epoch + 1) * 32 * LENT * lenders);
            uint32_t gl[4][12] = {};
            const uint4* src = &sc->lent[(blockIdx.x * LENT * 8 * 4 + w4) * 96 + lane];
            auto fetch = [&](uint32_t (&v)[12], int c, bool on) {
#pragma unroll
                for (int s = 0; s < 3; s++) ldg128_if(on, reinterpret_cast<uint32_t (&)[4]>(v[4 * s]), src + c * 384 + s * 32);
            };
#pragma unroll
            for (int c = 0; c < 3; c++) fetch(gl[c], c, true);
            grn();
            named_bar(3, NTHREADS);
#pragma unroll 1
            for (int e = 0; e < LENT; e++) {
                uint32_t acc[24];
                load_bias(acc);
#define CNX_LENT(C)                                  \
    pin(gl[C % 4]);                                  \
    wg_fence();                                      \
    gemm2_chunk<48 * C>(acc, gl[C % 4], ds);         \
    wg_commit();                                     \
    wg_wait<(C < 7 ? 1 : 0)>();                      \
    fetch(gl[(C + 3) % 4], C + 3, C < 5 || e == 0);  \
    if (lane == 0) mbar_arrive(sb + BAR_PIN);
                CNX_LENT(0) CNX_LENT(1) CNX_LENT(2) CNX_LENT(3) CNX_LENT(4) CNX_LENT(5) CNX_LENT(6) CNX_LENT(7)
#undef CNX_LENT
                src += 8 * 384;
                mbar_wait(bar_r, rpar);
                epilogue(acc);
                tile_off = tile_offset(wk.tA + 1);
                if (e == 0) stage_x();
            }
            first = 4;
        }
        lds32(next_off, sb + SM_TILES + first * 4);
        load_frags(true);
        if (!wk.lent) grn();
    } else {
        {
            const int ct = tid - 128, lane = tid & 31;
            const unsigned epoch = *reinterpret_cast<volatile unsigned*>(&sc->launch);
            const int r = lane & 7, mi = lane >> 3;
            const uint32_t src = sb + SM_W2 + (cw >> 1) * (64 * CH * 2) + r * 128 + ((((cw & 1) * 4 + mi) ^ r) * 16);
            const uint32_t dst = sb + SM_W1 + (4 * cw + mi) * 1536 + r * 16;
            named_bar(0, NTHREADS);
            mbar_wait(sb + BAR_W + (cw >> 1) * 8, 0);
            uint32_t wmax[4] = {}, wsum[4] = {};
#pragma unroll 3
            for (int c = 0; c < 12; c++) {
                uint32_t u[4];
                ldsm4_t(u, src + c * 1024);
#pragma unroll
                for (int q = 0; q < 4; q++) {
                    wmax[q] = bf_absmax(wmax[q], u[q]);
                    wsum[q] = bf_fma(u[q], 0x3f803f80u, wsum[q]);
                    u[q] = pack_h2(bf_lo(u[q]), bf_hi(u[q]));
                }
                stsm4(dst + c * 128, u[0], u[1], u[2], u[3]);
            }
            float mean[4];
            bool center = false;
#pragma unroll
            for (int q = 0; q < 4; q++) {
                uint32_t m = wmax[q];
                float sum = bf_lo(wsum[q]) + bf_hi(wsum[q]);
#pragma unroll
                for (int o = 1; o <= 2; o <<= 1) { m = bf_absmax(m, __shfl_xor_sync(~0u, m, o)); sum += __shfl_xor_sync(~0u, sum, o); }
                mean[q] = sum * (1.f / CH);
                center |= fabsf(mean[q]) > 0.2f * fmaxf(fabsf(bf_lo(m)), fabsf(bf_hi(m)));
            }
            if (__any_sync(~0u, center)) {
#pragma unroll 1
                for (int pass = 0; pass < 2; pass++) {
                    float sum[4] = {};
#pragma unroll 1
                    for (int c = 0; c < 12; c++) {
                        uint32_t u[4];
                        ldsm4_t(u, src + c * 1024);
#pragma unroll
                        for (int q = 0; q < 4; q++) {
                            sum[q] += bf_lo(u[q]) + bf_hi(u[q]);
                            u[q] = pack_h2(bf_lo(u[q]) - mean[q], bf_hi(u[q]) - mean[q]);
                        }
                        stsm4(dst + c * 128, u[0], u[1], u[2], u[3]);
                    }
#pragma unroll
                    for (int q = 0; q < 4; q++) {
                        sum[q] += __shfl_xor_sync(~0u, sum[q], 1);
                        sum[q] += __shfl_xor_sync(~0u, sum[q], 2);
                        mean[q] = sum[q] * (1.f / CH);
                    }
                }
            }
            const float w1max = warp_absmax(bf_absmax(bf_absmax(wmax[0], wmax[1]), bf_absmax(wmax[2], wmax[3])));
            if (lane == 0) sts32(s_red + cw * 4, __float_as_uint(w1max));
            if (ct < 32) sts32(sb + SM_ONES + ct * 4, 0x3f803f80u);
            if (ct < 48) sts32(sb + SM_BIASH + ct * 4, 0);
            if (blockIdx.x == 0) {
#pragma unroll
                for (int q = 0; q < REPLICAS; q++) sc->sums[(epoch & 1) ^ 1][q][ct] = 0;
                if (ct < CH) sc->bias[(epoch & 1) ^ 1][ct] = 0.f;
            }
            if (ct == 0) sts32(s_red + 48, epoch);
            fence_async();
            named_bar(2, CONS_THREADS);
#pragma unroll
            for (int q = 0; q < 6; q++) sts128(sb + SM_SQ + wgi * SQ_WG + q * SQ_ROW + (ct & 127) * 16, 0, 0, 0, 0);
            mbar_wait(sb + BAR_A + w4 * 8 + 32, 0);
        }

        PROF(1);
        const uint32_t a_addr = opaque(sb + SM_RING + w4 * REGION_BYTES + ((tid >> 3) & 1) * A_SBO + ((tid >> 4) & 1) * A_LBO + (tid & 7) * 16);
        const uint32_t bar_a = sb + BAR_A + w4 * 8, bar_e = sb + BAR_E + w4 * 8;
        const uint32_t sq = opaque(sb + SM_SQ + wgi * SQ_WG + (tid & 127) * 16);
        const uint32_t sq_warp = sb + SM_SQ + wgi * SQ_WG + w4 * 512;
        uint32_t k1[24], k2[24], k3[24];
        if (wgi < wk.lent) {
            const int slot = wgi + 2;
            uint32_t a[6][4];
            mbar_wait(bar_a + slot * 32, 0);
            load_tile(a, a_addr + slot * SLOT_BYTES);
            const uint2 st = ln_stats(a, ds.ones);
            ln_apply(a, st);
            char* ap = reinterpret_cast<char*>(out) + (tile_offset(wk.tA + wgi) + w4 * WARP_BYTES - sq_warp + sq);
#pragma unroll
            for (int s = 0; s < 6; s++) stg128(ap + s * 512, a[s]);
            __syncwarp();
            if (elect_one()) mbar_arrive(bar_e + slot * 32);
        }
        Cursor cur = {2, 0};
        int jt = wk.lent + wgi;
        {
            constexpr int SQC = 3 * SQ_ROW;
            cur.advance(jt + (jt >= wk.nA ? 2 : 0));
            int sq_e = square_exp(max_w1());
            uint32_t scale2 = pack_h2(pow2i(sq_e), pow2i(sq_e));
            auto run = [&](auto scaled_tag) {
                constexpr bool SCALED = decltype(scaled_tag)::value;
                uint32_t hs2[12] = {}, hs3[12] = {};
#pragma unroll 1
                for (; jt + NCONS < ntiles; jt += NCONS) {
                    uint32_t a[6][4], d0[24], d1[24], unused[24];
                    stagger_wait(jt - wk.lent, wgi);
                    mbar_wait(bar_a + cur.slot * 32, cur.par);
                    load_tile(a, a_addr + cur.slot * SLOT_BYTES);
                    const uint2 st = ln_stats(a, ds.ones);
                    ln_apply(a, st);
                    wg_fence();
                    gemm1_chunk<0>(d0, a, ds, 0);
                    wg_commit();
                    gemm1_chunk<96>(d1, a, ds, 0);
                    wg_commit();
                    {
                        char* ap = reinterpret_cast<char*>(out) + (tile_offset(wk.tile(jt)) + w4 * WARP_BYTES - sq_warp + sq);
#pragma unroll
                        for (int s = 0; s < 6; s++) stg128(ap + s * 512, a[s]);
                    }
                    wg_wait<1>();
                    gelu_sq<SCALED, 0, S1_PASS>(d0, unused, sq, scale2);
                    stagger_pass(jt, wgi, ntiles);
                    gelu_sq<SCALED, S1_PASS, 3>(d0, unused, sq, scale2);
                    if (elect_one()) mbar_arrive(bar_e + cur.slot * 32);
                    wg_fence();
                    gemm1_chunk<192>(d0, a, ds, zero);
                    wg_commit();
                    wg_wait<1>();
                    gelu_sq<SCALED>(d1, unused, sq + SQC, scale2);
                    wg_fence();
                    gemm1_chunk<288>(d1, a, ds, zero);
                    wg_commit();
                    wg_wait<1>();
                    gelu_sq_reg<SCALED>(d0, hs2, scale2);
                    anchor(sq, hs2[8], hs2[9], hs2[10], hs2[11]);
                    wg_wait<0>();
                    gelu_sq_reg<SCALED>(d1, hs3, scale2);
                    cur.advance(NCONS + ((jt < wk.nA && jt + NCONS >= wk.nA) ? 2 : 0));
                }
                const uint32_t sq2 = sq - (SM_SQ + wgi * SQ_WG) + SM_RING + (cur.slot + 3) % NSLOT * SLOT_BYTES;
#pragma unroll
                for (int k = 0; k < 3; k++) {
                    sts128(sq2 + k * SQ_ROW, hs2[4 * k], hs2[4 * k + 1], hs2[4 * k + 2], hs2[4 * k + 3]);
                    sts128(sq2 + SQC + k * SQ_ROW, hs3[4 * k], hs3[4 * k + 1], hs3[4 * k + 2], hs3[4 * k + 3]);
                }
            };
            if (sq_e == 0) run(Flag<false>());
            else run(Flag<true>());
            sq_e = square_exp(max_w1());
            scale2 = pack_h2(pow2i(sq_e), pow2i(sq_e));
            {
                uint32_t a[6][4], d0[24], d1[24], d3[24], k0[24];
                stagger_wait(jt - wk.lent, wgi);
                mbar_wait(bar_a + cur.slot * 32, cur.par);
                load_tile(a, a_addr + cur.slot * SLOT_BYTES);
                const uint2 st = ln_stats(a, ds.ones);
                ln_apply(a, st);
                wg_fence();
                gemm1_chunk<0>(d0, a, ds, 0);
                wg_commit();
                gemm1_chunk<96>(d1, a, ds, 0);
                wg_commit();
                stage = sb + SM_RING + cur.slot * SLOT_BYTES + w4 * REGION_BYTES;
                wg_wait<1>();
                gelu_sq<true, 0, S1_PASS>(d0, k0, sq, scale2);
                stagger_pass(jt, wgi, ntiles);
                gelu_sq<true, S1_PASS, 3>(d0, k0, sq, scale2);
#pragma unroll
                for (int q = 0; q < 6; q++) sts128(stage - sq_warp + sq + q * 512, k0[4 * q], k0[4 * q + 1], k0[4 * q + 2], k0[4 * q + 3]);
                wg_fence();
                gemm1_chunk<192>(d0, a, ds, zero);
                wg_commit();
                wg_wait<1>();
                gelu_sq<true>(d1, k1, sq + SQC, scale2);
                wg_fence();
                gemm1_chunk<288>(d3, a, ds, 0);
                wg_commit();
                wg_wait<1>();
                const uint32_t sq2 = sq - (SM_SQ + wgi * SQ_WG) + SM_RING + (cur.slot + 3) % NSLOT * SLOT_BYTES;
                gelu_sq<true>(d0, k2, sq2, scale2);
                wg_wait<0>();
                gelu_sq<true>(d3, k3, sq2 + SQC, scale2);
            }
            if (wgi == last_wg) {
                named_arrive(14, NTHREADS);
            } else {
                reduce(cw, (sq >> 4) & 31, false);
                named_arrive(15, CONS_THREADS);
            }
        }
        PROF(2);
        tile_off = tile_offset(wk.tile(jt));
        {
            set_lane((sq >> 4) & 31);
            if (elect_one()) prefetch_l2(reinterpret_cast<const char*>(x) + tile_off + w4 * WARP_BYTES, WARP_BYTES);
            const uint32_t row = sb + SM_W2 + cw * 512 + lane16;
            uint32_t u[W2_EARLY][4], f2[4];
            mbar_wait(sb + BAR_W, 1);
#pragma unroll
            for (int nb = 0; nb < W2_EARLY; nb++) lds128(u[nb][0], u[nb][1], u[nb][2], u[nb][3], row + nb * 6144);
            named_bar(12, NTHREADS);
            PROF(3);
            lds128(f2[0], f2[1], f2[2], f2[3], s_fac + cw * 64 + (lane16 >> 7) * 16);
            lds32(inv_rho2, s_red + 52);
#pragma unroll
            for (int nb = 0; nb < 12; nb++) {
                uint32_t v[4];
                if (nb < W2_EARLY) { v[0] = u[nb % W2_EARLY][0]; v[1] = u[nb % W2_EARLY][1]; v[2] = u[nb % W2_EARLY][2]; v[3] = u[nb % W2_EARLY][3]; }
                else lds128(v[0], v[1], v[2], v[3], row + nb * 6144);
                sts128(row + nb * 6144, h_round8(h_mul(v[0], f2[0])), h_round8(h_mul(v[1], f2[1])), h_round8(h_mul(v[2], f2[2])), h_round8(h_mul(v[3], f2[3])));
            }
            fence_async();
            named_bar(3, NTHREADS);
        }
        PROF(4);
        {
            uint32_t acc[24];
            load_bias(acc);
            lds32(next_off, sb + SM_TILES + wg * 4);
            if (wgi > 0) named_bar(8 + wgi, 256);
            pin(k1); pin(k2); pin(k3);
            wg_fence();
            gemm2_chunk<288>(acc, k3, ds);
            wg_commit();
            gemm2_chunk<96>(acc, k1, ds);
            gemm2_chunk<192>(acc, k2, ds);
            wg_commit();
            if (wgi + 1 < NCONS) named_arrive(9 + wgi, 256);
            wg_wait<1>();
            uint32_t k0[24];
#pragma unroll
            for (int q = 0; q < 6; q++) lds128(k0[4 * q], k0[4 * q + 1], k0[4 * q + 2], k0[4 * q + 3], stage + lane16 + q * 512);
            pin(k0);
            wg_fence();
            gemm2_chunk<0>(acc, k0, ds);
            wg_commit();
            stage_x();
            wg_wait<1>();
            load_frags(true);
            if (lane16 == 0) mbar_arrive(sb + BAR_PIN);
            mbar_wait(bar_r, rpar);
            wg_wait<0>();
            epilogue(acc);
        }
    }
    {
        const int nrest = ntiles - NCONS - wk.lent / 2;
        for (int jt = first; jt < nrest; jt += 4) {
            uint32_t d0[12], d1[12], g0[12], g1[12], acc[24];
            tile_off = next_off;
            lds32(next_off, sb + SM_TILES + (jt + 4) * 4);
            if (jt >= S2_FIRST) named_bar(4 + wg, 256);
            wg_fence();
            gemm1_chunk<0>(d0, a, ds, 0);
            wg_commit();
            gemm1_chunk<48>(d1, a, ds, 0);
            wg_commit();
            load_bias(acc);
            const bool more = jt + 4 < nrest;
            tile_off = __shfl_sync(~0u, tile_off, 0);
            next_off = __shfl_sync(~0u, next_off, 0);
            wg_wait<1>();
#define CNX_PASS if (jt + 1 >= S2_FIRST && jt + 1 < nrest) named_arrive(4 + ((wg + 1) & 3), 256);
#define CNX_STEP(C, D, G)                                              \
    gelu_to(G, D);                                                     \
    if (C == 0 && jt == 0) {                                           \
        named_bar(3, NTHREADS);                                        \
        load_bias(acc);                                                \
    }                                                                  \
    wg_fence();                                                        \
    if (C < 6) gemm1_chunk<48 * (C < 6 ? C + 2 : 0)>(D, a, ds, zero); \
    gemm2_chunk<48 * C>(acc, G, ds);                                  \
    wg_commit();                                                       \
    if (C == S2_PASS) { CNX_PASS }                                     \
    wg_wait<(C < 7 ? 1 : 0)>();
            CNX_STEP(0, d0, g0)
            stage_x();
            if (more && elect_one()) prefetch_l2(reinterpret_cast<const char*>(out) + next_off + w4 * WARP_BYTES, WARP_BYTES);
            CNX_STEP(1, d1, g1)
            CNX_STEP(2, d0, g0)
            CNX_STEP(3, d1, g1)
            CNX_STEP(4, d0, g0)
            CNX_STEP(5, d1, g1)
            CNX_STEP(6, d0, g0)
            load_frags(more);
            if (lane16 == 0) mbar_arrive(sb + BAR_PIN);
            mbar_wait(bar_r, rpar);
            CNX_STEP(7, d1, g1)
#undef CNX_STEP
            epilogue(acc);
        }
    }
    PROF(5);
}

}

typedef CUresult (*EncodeTiledFn)(CUtensorMap*, CUtensorMapDataType, cuuint32_t, void*, const cuuint64_t*, const cuuint64_t*,
                                  const cuuint32_t*, const cuuint32_t*, CUtensorMapInterleave, CUtensorMapSwizzle,
                                  CUtensorMapL2promotion, CUtensorMapFloatOOBfill);

extern "C" void kernel_launch(void* const* d_in, const int* in_sizes, int n_in, void* d_out, int out_size) {
    using namespace cnx;
    static EncodeTiledFn encode = nullptr;
    static int num_sms = 0;
    static Scratch* scratch = nullptr;
    if (!encode) {
        void* fn = nullptr;
        cudaDriverEntryPointQueryResult qr;
        cudaGetDriverEntryPoint("cuTensorMapEncodeTiled", &fn, cudaEnableDefault, &qr);
        encode = (EncodeTiledFn)fn;
        cudaGetSymbolAddress((void**)&scratch, g_scratch);
        int dev = 0;
        cudaGetDevice(&dev);
        cudaDeviceGetAttribute(&num_sms, cudaDevAttrMultiProcessorCount, dev);
        if (num_sms > MAX_CTAS) num_sms = MAX_CTAS;
        cudaFuncSetAttribute(block_kernel, cudaFuncAttributeMaxDynamicSharedMemorySize, SM_TOTAL);
    }
    CUtensorMap tm;
    cuuint64_t dims[3] = {(cuuint64_t)CH, (cuuint64_t)IMG_W, (cuuint64_t)IMG_H};
    cuuint64_t strides[2] = {(cuuint64_t)CH * 2, (cuuint64_t)CH * 2 * IMG_W};
    cuuint32_t box[3] = {(cuuint32_t)CH, (cuuint32_t)REGION_PX, 1};
    cuuint32_t estr[3] = {1, 1, 1};
    encode(&tm, CU_TENSOR_MAP_DATA_TYPE_BFLOAT16, 3, d_in[0], dims, strides, box, estr, CU_TENSOR_MAP_INTERLEAVE_NONE,
           CU_TENSOR_MAP_SWIZZLE_NONE, CU_TENSOR_MAP_L2_PROMOTION_L2_128B, CU_TENSOR_MAP_FLOAT_OOB_FILL_NONE);
    Descs ds;
    for (int c = 0; c < 8; c++)
        for (int k = 0; k < 6; k++) ds.w1[c][k] = make_desc(SB + SM_W1 + c * 6 * 1536 + k * 256, 128, 1536);
    for (int k = 0; k < 24; k++) ds.w2[k] = make_desc(SB + SM_W2 + k * 256, 128, 6144);
    ds.ones = make_desc(SB + SM_ONES, 0, 0);
    CUtensorMap tw;
    cuuint64_t wdims[2] = {(cuuint64_t)EX, (cuuint64_t)CH};
    cuuint64_t wstrides[1] = {(cuuint64_t)EX * 2};
    cuuint32_t wbox[2] = {64, (cuuint32_t)CH};
    encode(&tw, CU_TENSOR_MAP_DATA_TYPE_BFLOAT16, 2, d_in[2], wdims, wstrides, wbox, estr, CU_TENSOR_MAP_INTERLEAVE_NONE,
           CU_TENSOR_MAP_SWIZZLE_128B, CU_TENSOR_MAP_L2_PROMOTION_L2_128B, CU_TENSOR_MAP_FLOAT_OOB_FILL_NONE);
    const int per_cta = NTILES / num_sms, extra = NTILES % num_sms;
    const int lenders = extra * (8 * LENT + 1) <= num_sms && extra * (per_cta + 1) <= IMG_H ? extra : 0;
    block_kernel<<<num_sms, NTHREADS, SM_TOTAL>>>(tm, tw, (const __nv_bfloat16*)d_in[0], (const __nv_bfloat16*)d_in[1],
                                             (const __nv_bfloat16*)d_in[3],
                                             (const __nv_bfloat16*)d_in[4], (const __nv_bfloat16*)d_in[5], (__nv_bfloat16*)d_out,
                                             scratch, ds, 0, per_cta, extra, lenders);
}
```

```cpp
#include <cuda_runtime.h>
#include <cuda_bf16.h>
#include <cuda_fp16.h>
#include <cuda.h>
#include <stdint.h>

namespace cnx {

constexpr int IMG_H = 512, IMG_W = 512, CH = 96, EX = 384;
constexpr int TILE_W = 64;
constexpr int NTILES = (IMG_W / TILE_W) * IMG_H;
constexpr int NSLOT = 6;
constexpr int REGION_PX = 18;
constexpr int REGION_BYTES = REGION_PX * CH * 2;
constexpr int SLOT_BYTES = 4 * REGION_BYTES;
constexpr int A_LBO = 144, A_SBO = 12 * A_LBO;
constexpr int PREFETCH_ROWS = 3;
constexpr int NCONS = 3;
constexpr int CONS_THREADS = 128 * NCONS;
constexpr int NTHREADS = 128 + CONS_THREADS;
constexpr int MAX_ROWS = 52;
constexpr int TILE_BYTES = TILE_W * CH * 2, WARP_BYTES = TILE_BYTES / 4;
constexpr int S1_PASS = 1, S2_PASS = 1;
#define W2_EARLY 6
#define S2_FIRST 4
#define ORDER_P 3
#define ORDER_Q 1
static_assert(MAX_ROWS <= 128, "one table entry per producer thread");
static_assert(2 * A_SBO == REGION_BYTES && REGION_BYTES % 128 == 0, "region layout");

constexpr uint32_t SB = 1024;
constexpr int SM_W1 = 0;
constexpr int SM_W2 = SM_W1 + CH * EX * 2;
constexpr int SM_RING = SM_W2 + CH * EX * 2;
constexpr int SM_BIASH = SM_RING + NSLOT * SLOT_BYTES;
constexpr int SM_RED = SM_BIASH + 384;
constexpr int SM_ROWS = SM_RED + 256;
constexpr int SM_TILES = SM_ROWS + MAX_ROWS * 4;
constexpr int SM_ONES = SM_TILES + MAX_ROWS * 4;
constexpr int SM_BAR = SM_ONES + 128;
constexpr int BAR_X = SM_BAR;
constexpr int BAR_A = BAR_X + NSLOT * 4 * 8;
constexpr int BAR_E = BAR_A + NSLOT * 4 * 8;
constexpr int BAR_PIN = BAR_E + NSLOT * 4 * 8;
constexpr int BAR_W = BAR_PIN + 8;
constexpr int BAR_R = BAR_W + 6 * 8;
constexpr int SM_TOTAL = BAR_R + 16 * 8;
constexpr int SM_SQ = SM_W2;
constexpr int SQ_ROW = 128 * 16, SQ_WG = 6 * SQ_ROW;
static_assert(SM_ONES % 16 == 0 && SM_TOTAL <= 232448, "shared memory budget");

constexpr float KZ = 0.3292034911525734f;
constexpr uint32_t GELU_C2 = 0x40d940d9u;
constexpr float INV_2KZ = 0.5f / KZ;
constexpr unsigned SPIN_LIMIT = 1u << 19;

constexpr int MAX_CTAS = 256;
#define NREP 2
constexpr int REPLICAS = NREP;
constexpr int W2_GROUPS = EX / 8;
constexpr int LENT = 2, MAX_LENDERS = MAX_CTAS / (8 * LENT + 1);
struct Scratch {
    uint32_t w2h[EX * CH / 2];
    float w2max[EX];
    float bias[2][CH];
    unsigned long long sums[2][REPLICAS][EX];
    uint4 lent[MAX_LENDERS * LENT * 8 * 4 * 3 * 32];
    unsigned launch, pad0[31], prep, pad1[31], lent_in, pad2[31], lent_out, pad3[31];
};
__device__ __align__(128) Scratch g_scratch;

#define PROF(k)

__device__ __forceinline__ uint32_t smem_u32(const void* p) { return (uint32_t)__cvta_generic_to_shared(p); }
__device__ __forceinline__ void mbar_init(uint32_t bar, uint32_t cnt) {
    asm volatile("mbarrier.init.shared::cta.b64 [%0], %1;" ::"r"(bar), "r"(cnt) : "memory");
}
__device__ __forceinline__ void mbar_arrive(uint32_t bar) {
    asm volatile("mbarrier.arrive.shared::cta.b64 _, [%0];" ::"r"(bar) : "memory");
}
__device__ __forceinline__ void mbar_expect_tx(uint32_t bar, uint32_t bytes) {
    asm volatile("mbarrier.arrive.expect_tx.shared::cta.b64 _, [%0], %1;" ::"r"(bar), "r"(bytes) : "memory");
}
__device__ __forceinline__ bool mbar_try(uint32_t bar, uint32_t par) {
    uint32_t ok;
    asm volatile("{\n.reg .pred p;\nmbarrier.try_wait.parity.shared::cta.b64 p, [%1], %2;\nselp.u32 %0, 1, 0, p;\n}\n"
                 : "=r"(ok) : "r"(bar), "r"(par) : "memory");
    return ok != 0;
}
__device__ __forceinline__ void mbar_wait(uint32_t bar, uint32_t par) {
    unsigned n = 0;
    while (!mbar_try(bar, par)) {
        if (++n > SPIN_LIMIT) __trap();
    }
}
__device__ __forceinline__ bool mbar_test(uint32_t bar, uint32_t par) {
    uint32_t ok;
    asm volatile("{\n.reg .pred p;\nmbarrier.test_wait.parity.shared::cta.b64 p, [%1], %2;\nselp.u32 %0, 1, 0, p;\n}\n"
                 : "=r"(ok) : "r"(bar), "r"(par) : "memory");
    return ok != 0;
}
__device__ __forceinline__ bool elect_one() {
    uint32_t ok;
    asm volatile("{\n.reg .pred p;\nelect.sync _|p, 0xffffffff;\nselp.u32 %0, 1, 0, p;\n}\n" : "=r"(ok));
    return ok != 0;
}
__device__ __forceinline__ uint32_t opaque(uint32_t v) { return __shfl_sync(~0u, v, threadIdx.x & 31); }
__device__ __forceinline__ void named_bar(int id, int n) { asm volatile("bar.sync %0, %1;" ::"r"(id), "r"(n) : "memory"); }
__device__ __forceinline__ void named_arrive(int id, int n) { asm volatile("bar.arrive %0, %1;" ::"r"(id), "r"(n) : "memory"); }
__device__ __forceinline__ void fence_async() { asm volatile("fence.proxy.async.shared::cta;" ::: "memory"); }
__device__ __forceinline__ uint64_t evict_first() {
    uint64_t p;
    asm("createpolicy.fractional.L2::evict_first.b64 %0, 1.0;" : "=l"(p));
    return p;
}
__device__ __forceinline__ void tma_row(uint32_t dst, const CUtensorMap* tm, uint32_t bar, int x, int y) {
    asm volatile("cp.async.bulk.tensor.3d.shared::cluster.global.mbarrier::complete_tx::bytes.L2::cache_hint [%0], [%1, {%3, %4, %5}], [%2], %6;"
                 ::"r"(dst), "l"(tm), "r"(bar), "r"(0), "r"(x), "r"(y), "l"(evict_first()) : "memory");
}
__device__ __forceinline__ void bulk_load_stream(uint32_t dst, const void* src, uint32_t bytes, uint32_t bar) {
    asm volatile("cp.async.bulk.shared::cluster.global.mbarrier::complete_tx::bytes.L2::cache_hint [%0], [%1], %2, [%3], %4;"
                 ::"r"(dst), "l"(src), "r"(bytes), "r"(bar), "l"(evict_first()) : "memory");
}
__device__ __forceinline__ void prefetch_l2(const void* src, uint32_t bytes) {
    asm volatile("cp.async.bulk.prefetch.L2.global [%0], %1;" ::"l"(src), "r"(bytes) : "memory");
}
__device__ __forceinline__ void tma_2d(uint32_t dst, const CUtensorMap* tm, uint32_t bar, int x, int y) {
    asm volatile("cp.async.bulk.tensor.2d.shared::cluster.global.mbarrier::complete_tx::bytes [%0], [%1, {%3, %4}], [%2];"
                 ::"r"(dst), "l"(tm), "r"(bar), "r"(x), "r"(y) : "memory");
}
__device__ __forceinline__ void bulk_load(uint32_t dst, const void* src, uint32_t bytes, uint32_t bar) {
    asm volatile("cp.async.bulk.shared::cluster.global.mbarrier::complete_tx::bytes [%0], [%1], %2, [%3];"
                 ::"r"(dst), "l"(src), "r"(bytes), "r"(bar) : "memory");
}
__device__ __forceinline__ void wg_fence() { asm volatile("wgmma.fence.sync.aligned;" ::: "memory"); }
__device__ __forceinline__ void wg_commit() { asm volatile("wgmma.commit_group.sync.aligned;" ::: "memory"); }
template <int N> __device__ __forceinline__ void wg_wait() { asm volatile("wgmma.wait_group.sync.aligned %0;" ::"n"(N) : "memory"); }
template <int N> __device__ __forceinline__ void pin(uint32_t (&d)[N]) {
#pragma unroll
    for (int q = 0; q < N; q++) asm volatile("" : "+r"(d[q])::"memory");
}
__device__ __forceinline__ void stg128(void* p, const uint32_t (&v)[4]) {
    asm volatile("st.global.v4.u32 [%0], {%1, %2, %3, %4};" ::"l"(p), "r"(v[0]), "r"(v[1]), "r"(v[2]), "r"(v[3]) : "memory");
}
__device__ __forceinline__ void ldg128_if(bool on, uint32_t (&v)[4], const void* p) {
    asm volatile("{\n.reg .pred p;\nsetp.ne.b32 p, %5, 0;\n@p ld.global.L1::no_allocate.v4.u32 {%0, %1, %2, %3}, [%4];\n}\n"
                 : "+r"(v[0]), "+r"(v[1]), "+r"(v[2]), "+r"(v[3]) : "l"(p), "r"((int)on) : "memory");
}
__device__ __forceinline__ uint4 ldg128_ordered(const void* p) {
    uint4 v;
    asm volatile("ld.global.nc.v4.u32 {%0, %1, %2, %3}, [%4];" : "=r"(v.x), "=r"(v.y), "=r"(v.z), "=r"(v.w) : "l"(p) : "memory");
    return v;
}
__host__ __device__ constexpr uint64_t make_desc(uint32_t addr, uint32_t lbo, uint32_t sbo) {
    return (uint64_t)((addr & 0x3FFFF) >> 4) | ((uint64_t)(lbo >> 4) << 16) | ((uint64_t)(sbo >> 4) << 32);
}
__device__ __forceinline__ void wgmma(uint32_t (&d)[12], uint32_t a0, uint32_t a1, uint32_t a2, uint32_t a3, uint64_t db, int acc) {
    asm volatile("{\n.reg .pred p;\nsetp.ne.b32 p, %17, 0;\n"
                 "wgmma.mma_async.sync.aligned.m64n48k16.f16.f16.f16 "
                 "{%0, %1, %2, %3, %4, %5, %6, %7, %8, %9, %10, %11}, "
                 "{%12, %13, %14, %15}, %16, p, 1, 1, 0;\n}\n"
                 : "+r"(d[0]), "+r"(d[1]), "+r"(d[2]), "+r"(d[3]), "+r"(d[4]), "+r"(d[5]), "+r"(d[6]), "+r"(d[7]), "+r"(d[8]), "+r"(d[9]), "+r"(d[10]), "+r"(d[11])
                 : "r"(a0), "r"(a1), "r"(a2), "r"(a3), "l"(db), "r"(acc));
}
__device__ __forceinline__ void wgmma(uint32_t (&d)[24], uint32_t a0, uint32_t a1, uint32_t a2, uint32_t a3, uint64_t db, int acc) {
    asm volatile("{\n.reg .pred p;\nsetp.ne.b32 p, %29, 0;\n"
                 "wgmma.mma_async.sync.aligned.m64n96k16.f16.f16.f16 "
                 "{%0, %1, %2, %3, %4, %5, %6, %7, %8, %9, %10, %11, %12, %13, %14, %15, %16, %17, %18, %19, %20, %21, %22, %23}, "
                 "{%24, %25, %26, %27}, %28, p, 1, 1, 0;\n}\n"
                 : "+r"(d[0]), "+r"(d[1]), "+r"(d[2]), "+r"(d[3]), "+r"(d[4]), "+r"(d[5]), "+r"(d[6]), "+r"(d[7]), "+r"(d[8]), "+r"(d[9]), "+r"(d[10]), "+r"(d[11]), "+r"(d[12]), "+r"(d[13]), "+r"(d[14]), "+r"(d[15]), "+r"(d[16]), "+r"(d[17]), "+r"(d[18]), "+r"(d[19]), "+r"(d[20]), "+r"(d[21]), "+r"(d[22]), "+r"(d[23])
                 : "r"(a0), "r"(a1), "r"(a2), "r"(a3), "l"(db), "r"(acc));
}
template <int ACC>
__device__ __forceinline__ void wgmma_rowsum(float (&d)[4], const uint32_t (&a)[4], uint64_t ones) {
    asm volatile("{\n.reg .pred p;\nsetp.ne.b32 p, %9, 0;\n"
                 "wgmma.mma_async.sync.aligned.m64n8k16.f32.bf16.bf16 {%0, %1, %2, %3}, {%4, %5, %6, %7}, %8, p, 1, 1, 0;\n}\n"
                 : "+f"(d[0]), "+f"(d[1]), "+f"(d[2]), "+f"(d[3])
                 : "r"(a[0]), "r"(a[1]), "r"(a[2]), "r"(a[3]), "l"(ones), "n"(ACC));
}
__device__ __forceinline__ void ldsm4(uint32_t (&r)[4], uint32_t addr) {
    asm volatile("ldmatrix.sync.aligned.m8n8.x4.shared.b16 {%0, %1, %2, %3}, [%4];"
                 : "=r"(r[0]), "=r"(r[1]), "=r"(r[2]), "=r"(r[3]) : "r"(addr) : "memory");
}
__device__ __forceinline__ void ldsm4_t(uint32_t (&r)[4], uint32_t addr) {
    asm volatile("ldmatrix.sync.aligned.m8n8.x4.trans.shared.b16 {%0, %1, %2, %3}, [%4];"
                 : "=r"(r[0]), "=r"(r[1]), "=r"(r[2]), "=r"(r[3]) : "r"(addr) : "memory");
}
__device__ __forceinline__ void stsm4(uint32_t addr, uint32_t a, uint32_t b, uint32_t c, uint32_t d) {
    asm volatile("stmatrix.sync.aligned.m8n8.x4.shared.b16 [%0], {%1, %2, %3, %4};"
                 ::"r"(addr), "r"(a), "r"(b), "r"(c), "r"(d) : "memory");
}
__device__ __forceinline__ uint32_t transpose8x8(uint32_t v) {
    uint32_t d; asm volatile("movmatrix.sync.aligned.m8n8.trans.b16 %0, %1;" : "=r"(d) : "r"(v)); return d;
}
__device__ __forceinline__ void spin_until(const unsigned* counter, unsigned target) {
    unsigned n = 0, c;
    do {
        asm volatile("ld.acquire.gpu.global.u32 %0, [%1];" : "=r"(c) : "l"(counter) : "memory");
        if (++n > SPIN_LIMIT) __trap();
    } while ((int)(c - target) < 0);
}
__device__ __forceinline__ void signal(unsigned* counter) {
    __syncwarp();
    if (elect_one()) asm volatile("red.release.gpu.global.add.u32 [%0], 1;" ::"l"(counter) : "memory");
    __syncwarp();
}
__device__ __forceinline__ void lds128(uint32_t& a, uint32_t& b, uint32_t& c, uint32_t& d, uint32_t addr) {
    asm volatile("ld.shared.v4.u32 {%0, %1, %2, %3}, [%4];" : "=r"(a), "=r"(b), "=r"(c), "=r"(d) : "r"(addr) : "memory");
}
__device__ __forceinline__ void lds64(uint32_t& a, uint32_t& b, uint32_t addr) {
    asm volatile("ld.shared.v2.u32 {%0, %1}, [%2];" : "=r"(a), "=r"(b) : "r"(addr) : "memory");
}
__device__ __forceinline__ void lds32(uint32_t& a, uint32_t addr) {
    asm volatile("ld.shared.u32 %0, [%1];" : "=r"(a) : "r"(addr) : "memory");
}
__device__ __forceinline__ float ldsf(uint32_t addr) {
    uint32_t v;
    lds32(v, addr);
    return __uint_as_float(v);
}
__device__ __forceinline__ void sts32(uint32_t addr, uint32_t a) {
    asm volatile("st.shared.u32 [%0], %1;" ::"r"(addr), "r"(a) : "memory");
}
__device__ __forceinline__ void sts128(uint32_t addr, uint32_t a, uint32_t b, uint32_t c, uint32_t d) {
    asm volatile("st.shared.v4.u32 [%0], {%1, %2, %3, %4};" ::"r"(addr), "r"(a), "r"(b), "r"(c), "r"(d) : "memory");
}
__device__ __forceinline__ void sts64(uint32_t addr, uint32_t a, uint32_t b) {
    asm volatile("st.shared.v2.u32 [%0], {%1, %2};" ::"r"(addr), "r"(a), "r"(b) : "memory");
}
__device__ __forceinline__ uint32_t bf_fma(uint32_t a, uint32_t b, uint32_t c) {
    uint32_t d; asm("fma.rn.bf16x2 %0, %1, %2, %3;" : "=r"(d) : "r"(a), "r"(b), "r"(c)); return d;
}
__device__ __forceinline__ uint32_t bf_mul(uint32_t a, uint32_t b) {
    uint32_t d; asm("mul.rn.bf16x2 %0, %1, %2;" : "=r"(d) : "r"(a), "r"(b)); return d;
}
__device__ __forceinline__ uint32_t bf_absmax(uint32_t a, uint32_t b) {
    uint32_t d; asm("max.xorsign.abs.bf16x2 %0, %1, %2;" : "=r"(d) : "r"(a), "r"(b)); return d;
}
__device__ __forceinline__ uint32_t h_fma(uint32_t a, uint32_t b, uint32_t c) {
    uint32_t d; asm("fma.rn.f16x2 %0, %1, %2, %3;" : "=r"(d) : "r"(a), "r"(b), "r"(c)); return d;
}
__device__ __forceinline__ uint32_t h_mul(uint32_t a, uint32_t b) {
    uint32_t d; asm("mul.rn.f16x2 %0, %1, %2;" : "=r"(d) : "r"(a), "r"(b)); return d;
}
__device__ __forceinline__ uint32_t h_round8(uint32_t v) { return (v + 0x00040004u) & 0xfff8fff8u; }
__device__ __forceinline__ uint32_t h_tanh(uint32_t a) {
    uint32_t d; asm("tanh.approx.f16x2 %0, %1;" : "=r"(d) : "r"(a)); return d;
}
__device__ __forceinline__ uint32_t pack_h2(float lo, float hi) {
    uint32_t d; asm("cvt.rn.f16x2.f32 %0, %1, %2;" : "=r"(d) : "f"(hi), "f"(lo)); return d;
}
__device__ __forceinline__ uint32_t pack_bf2(float lo, float hi) {
    uint32_t d; asm("cvt.rn.bf16x2.f32 %0, %1, %2;" : "=r"(d) : "f"(hi), "f"(lo)); return d;
}
__device__ __forceinline__ float bf_lo(uint32_t v) { return __uint_as_float(v << 16); }
__device__ __forceinline__ float bf_hi(uint32_t v) { return __uint_as_float(v & 0xffff0000u); }
__device__ __forceinline__ float h_lo(uint32_t v) { return __low2float(*reinterpret_cast<__half2*>(&v)); }
__device__ __forceinline__ float h_hi(uint32_t v) { return __high2float(*reinterpret_cast<__half2*>(&v)); }
__device__ __forceinline__ float warp_absmax(uint32_t v) {
    return __uint_as_float(__reduce_max_sync(~0u, max((v & 0x7fffu) << 16, v & 0x7fff0000u)));
}
__device__ __forceinline__ uint32_t gelu2(uint32_t z) {
    uint32_t p = h_fma(z, z, GELU_C2);
    uint32_t t = h_tanh(h_mul(z, p));
    return h_fma(z, t, z);
}
__device__ __forceinline__ float grn_norm(float ss) {
    float r;
    asm("sqrt.approx.f32 %0, %1;" : "=f"(r) : "f"(fmaf(ss, INV_2KZ * INV_2KZ, 1e-6f)));
    return r;
}
__device__ __forceinline__ float pow2i(int e) { return __uint_as_float((uint32_t)(e + 127) << 23); }
__device__ __forceinline__ int ilog2f(float v) {
    int e = (int)((__float_as_uint(v) >> 23) & 0xff) - 127;
    return max(-100, min(100, e));
}

__device__ __forceinline__ int sum_exp(float w1max) {
    return w1max > 0.f ? max(-90, min(90, 35 - 2 * ilog2f(2.f * KZ * 96.f * w1max))) : 0;
}
__device__ __forceinline__ float row_scale(float m) { return m > 0.f ? pow2i(2 - ilog2f(m)) : 1.f; }

struct Work {
    int tA, tB, nA, nB, rows, lent;
    __device__ __forceinline__ int tile(int j) const { return j < nA ? tA + j : tB + j - nA; }
};
__device__ __forceinline__ Work get_work(int per_cta, int extra, int lenders) {
    Work w;
    w.lent = (int)blockIdx.x < lenders ? LENT : 0;
    const int t0 = blockIdx.x * per_cta + min((int)blockIdx.x, extra);
    const int t1 = t0 + per_cta + ((int)blockIdx.x < extra);
    const int tm = min(t1, (t0 | 511) + 1);
    const bool swap = t1 > tm && t1 - tm < tm - t0;
    w.tA = swap ? tm : t0;
    w.tB = swap ? t0 : tm;
    w.nA = swap ? t1 - tm : tm - t0;
    w.nB = t1 - t0 - w.nA;
    w.rows = w.nA + 2 + (w.nB ? w.nB + 2 : 0);
    return w;
}
__device__ __forceinline__ int row_code(const Work& w, int i) {
    const bool in_a = i < w.nA + 2;
    const int t = in_a ? w.tA : w.tB;
    return ((t & 511) - 1 + (in_a ? i : i - (w.nA + 2))) << 16 | (t >> 9) * TILE_W;
}
__device__ __forceinline__ uint32_t tile_offset(int tile) { return ((tile & 511) * IMG_W + (tile >> 9) * TILE_W) * (CH * 2); }
__device__ __forceinline__ int tile_order(int j, int n) {
    const int olds = (j / ORDER_P) * ORDER_Q + max(0, j % ORDER_P - (ORDER_P - ORDER_Q));
    return (j % ORDER_P >= ORDER_P - ORDER_Q) ? olds : n - 1 - (j - olds);
}
__device__ __forceinline__ void issue_region(const CUtensorMap* tm, uint32_t dst, uint32_t bar, int warp, int code) {
    mbar_expect_tx(bar, REGION_BYTES);
    tma_row(dst, tm, bar, (code & 0xffff) + (16 * warp - 1), code >> 16);
}
__device__ __forceinline__ void elect_arrive(uint32_t bar0, uint32_t bar1, bool both) {
    asm volatile("{\n.reg .pred p, q;\nelect.sync _|p, 0xffffffff;\nsetp.ne.and.b32 q, %2, 0, p;\n"
                 "@p mbarrier.arrive.shared::cta.b64 _, [%0];\n@q mbarrier.arrive.shared::cta.b64 _, [%1];\n}\n"
                 ::"r"(bar0), "r"(bar1), "r"((int)both) : "memory");
}

__device__ __forceinline__ void first_loads(const Work& wk, const CUtensorMap* tm, const CUtensorMap* tw, const __nv_bfloat16* dw,
                                            uint32_t sb, int warp) {
    const uint32_t reg0 = sb + SM_RING + warp * REGION_BYTES, bars = sb + SM_BAR + warp * 8;
#pragma unroll
    for (int s = 0; s < PREFETCH_ROWS; s++) mbar_init(bars + s * 32, 1);
    mbar_init(sb + BAR_W + warp * 8, 1);
    if (warp < 2) mbar_init(sb + BAR_W + (warp + 4) * 8, 1);
    fence_async();
    asm volatile("mbarrier.expect_tx.shared::cta.b64 [%0], %1;" ::"r"(bars), "r"(9 * CH * 2) : "memory");
    bulk_load(reg0 + (NSLOT - 1) * SLOT_BYTES, dw, 9 * CH * 2, bars);
#pragma unroll
    for (int r = 0; r < PREFETCH_ROWS; r++)
        issue_region(tm, reg0 + r * SLOT_BYTES, bars + r * 32, warp, ((wk.tA & 511) - 1 + r) << 16 | (wk.tA >> 9) * TILE_W);
#pragma unroll 1
    for (int b = warp; b < 6; b += 4) {
        mbar_expect_tx(sb + BAR_W + b * 8, 64 * CH * 2);
        tma_2d(sb + SM_W2 + b * (64 * CH * 2), tw, sb + BAR_W + b * 8, 64 * b, 0);
    }
}

__device__ __forceinline__ void conv_producer(const Work& wk, const CUtensorMap* tm, Scratch* sc, uint32_t sb, int warp) {
    const int lane = threadIdx.x & 31;
    const int j = lane & 15, grp = lane >> 4;
    const uint32_t reg0 = sb + SM_RING + warp * REGION_BYTES;
    const uint32_t bars = sb + SM_BAR + warp * 8;
    if (elect_one()) {
        if (warp == 0) mbar_init(sb + BAR_PIN, 1);
#pragma unroll
        for (int s = 0; s < 4; s++) mbar_init(sb + BAR_R + (s * 4 + warp) * 8, 1);
#pragma unroll 1
        for (int s = PREFETCH_ROWS; s < 3 * NSLOT; s++) mbar_init(bars + s * 32, 1);
        fence_async();
    }
    __syncwarp();
    named_arrive(0, NTHREADS);
    if (warp * 32 + lane < MAX_ROWS) {
        sts32(sb + SM_ROWS + (warp * 32 + lane) * 4, row_code(wk, warp * 32 + lane));
        sts32(sb + SM_TILES + (warp * 32 + lane) * 4, tile_offset(wk.tile(wk.lent + tile_order(max(warp * 32 + lane - wk.lent / 2, 0), wk.nA + wk.nB - NCONS - wk.lent))));
    }
    const uint32_t ld64 = opaque(reg0 + grp * 8 * 192 + j * 8), ld32 = opaque(reg0 + grp * 8 * 192 + 128 + j * 4);
    const uint32_t st64 = opaque(reg0 + grp * A_SBO + (j >> 1) * A_LBO + (j & 1) * 8);
    const uint32_t st32 = opaque(reg0 + grp * A_SBO + (8 + (j >> 2)) * A_LBO + (j & 3) * 4);
    uint32_t accB[8][3] = {}, accC[8][3] = {};
    static_assert(2 * PREFETCH_ROWS == NSLOT, "prefetch slot arithmetic");
    uint32_t so = 0, bo = 0, par = 0, tbl = sb + SM_ROWS + PREFETCH_ROWS * 4;
    const uint32_t tbl_end = sb + SM_ROWS + wk.rows * 4;
    bool x_ready = false;
    named_bar(1, 128);
    mbar_wait(bars, 0);
    uint32_t w[3][3][3];
#pragma unroll
    for (int tap = 0; tap < 9; tap++) {
        const uint32_t p = reg0 + (NSLOT - 1) * SLOT_BYTES + tap * CH * 2;
        uint32_t u0, u1;
        lds64(u0, u1, p + 8 * j);
        __syncwarp();
        sts64(p + 8 * j, u1, u0);
        __syncwarp();
        lds64(w[tap / 3][tap % 3][1], w[tap / 3][tap % 3][0], p + 8 * j);
        lds32(w[tap / 3][tap % 3][2], p + 128 + 4 * j);
    }
    {
        const int first = wk.nA + 2, publish = wk.lent ? 12 : -1;
#pragma unroll 1
        for (int k = 0; k < wk.rows; k++) {
            if (!x_ready) mbar_wait(bars + bo, par);
            const bool wrap = bo == (NSLOT - 1) * 32, low = bo < PREFETCH_ROWS * 32;
            const uint32_t nbo = wrap ? 0 : bo + 32, npar = par ^ wrap;
            const uint32_t pbo = low ? bo + PREFETCH_ROWS * 32 : bo - PREFETCH_ROWS * 32, ppar = par ^ low;
            uint32_t out[8][3];
            int code;
            bool e_ready;
#pragma unroll
            for (int p = 0; p < 10; p++) {
                uint32_t xv[3];
                lds64(xv[0], xv[1], so + ld64 + p * 192);
                lds32(xv[2], so + ld32 + p * 192);
                if (p == 9) {
                    asm volatile("ld.shared.u32 %0, [%1];" : "=r"(code) : "r"(tbl));
                    e_ready = mbar_test(bars + (BAR_E - SM_BAR) + pbo, ppar);
                    x_ready = mbar_test(bars + nbo, npar);
                }
#pragma unroll
                for (int dx = 0; dx < 3; dx++) {
                    const int o = p - dx;
                    if (o < 0 || o > 7) continue;
#pragma unroll
                    for (int q = 0; q < 3; q++) {
                        out[o][q] = bf_fma(xv[q], w[2][dx][q], dx == 0 ? accB[o][q] : out[o][q]);
                        accB[o][q] = bf_fma(xv[q], w[1][dx][q], dx == 0 ? accC[o][q] : accB[o][q]);
                        accC[o][q] = dx == 0 ? bf_mul(xv[q], w[0][dx][q]) : bf_fma(xv[q], w[0][dx][q], accC[o][q]);
                    }
                }
            }
            __syncwarp();
#pragma unroll
            for (int o = 0; o < 8; o++) {
                sts64(so + st64 + o * 16, out[o][0], out[o][1]);
                sts32(so + st32 + o * 16, out[o][2]);
            }
            const bool halo = k < 2 || (unsigned)(k - first) < 2;
            if (halo) fence_async();
            if (k == publish) signal(&sc->lent_in);
            __syncwarp();
            elect_arrive(bars + (BAR_A - SM_BAR) + bo, bars + (BAR_E - SM_BAR) + bo, halo);
            if (tbl < tbl_end) {
                if (!e_ready) mbar_wait(bars + (BAR_E - SM_BAR) + pbo, ppar);
                code = __shfl_sync(~0u, code, 0);
                if (elect_one()) issue_region(tm, reg0 + (low ? so + PREFETCH_ROWS * SLOT_BYTES : so - PREFETCH_ROWS * SLOT_BYTES), bars + pbo, warp, code);
            }
            tbl += 4;
            so = wrap ? 0 : so + SLOT_BYTES;
            bo = nbo;
            par = npar;
        }
    }
}

template <bool SCALED, int K0 = 0, int K1 = 3>
__device__ __forceinline__ void gelu_sq(uint32_t (&d)[24], uint32_t (&keep)[24], uint32_t sq_addr, uint32_t scale2) {
    pin(d);
#pragma unroll
    for (int k = K0; k < K1; k++) {
        uint32_t hs[4];
        lds128(hs[0], hs[1], hs[2], hs[3], sq_addr + k * SQ_ROW);
#pragma unroll
        for (int q = 0; q < 4; q++) {
            uint32_t g0 = gelu2(d[8 * k + 2 * q]), g1 = gelu2(d[8 * k + 2 * q + 1]);
            keep[8 * k + 2 * q] = g0;
            keep[8 * k + 2 * q + 1] = g1;
            if (SCALED) { g0 = h_mul(g0, scale2); g1 = h_mul(g1, scale2); }
            hs[q] = h_fma(g1, g1, h_fma(g0, g0, hs[q]));
        }
        sts128(sq_addr + k * SQ_ROW, hs[0], hs[1], hs[2], hs[3]);
    }
}
__device__ __forceinline__ void anchor(uint32_t addr, uint32_t a, uint32_t b, uint32_t c, uint32_t d) {
    asm volatile("{\n.reg .pred p;\nsetp.eq.b32 p, %0, 0;\n@p st.shared.v4.u32 [%0], {%1, %2, %3, %4};\n}\n"
                 ::"r"(addr), "r"(a), "r"(b), "r"(c), "r"(d) : "memory");
}
__device__ __forceinline__ void gelu_sq_reg(uint32_t (&d)[24], uint32_t (&hs)[12]) {
    pin(d);
#pragma unroll
    for (int q = 0; q < 12; q++) {
        const uint32_t g0 = gelu2(d[2 * q]), g1 = gelu2(d[2 * q + 1]);
        hs[q] = h_fma(g1, g1, h_fma(g0, g0, hs[q]));
    }
}
__device__ __forceinline__ void gelu_to(uint32_t (&g)[12], uint32_t (&d)[12]) {
    pin(d);
#pragma unroll
    for (int q = 0; q < 12; q++) g[q] = gelu2(d[q]);
    pin(g);
}
__device__ __forceinline__ void load_tile(uint32_t (&raw)[6][4], uint32_t addr) {
#pragma unroll
    for (int s = 0; s < 6; s++) ldsm4(raw[s], addr + s * 2 * A_LBO);
}
__device__ __forceinline__ uint2 ln_stats(const uint32_t (&raw)[6][4], uint64_t ones) {
    uint32_t sq[6][4];
#pragma unroll
    for (int s = 0; s < 6; s++)
#pragma unroll
        for (int q = 0; q < 4; q++) sq[s][q] = bf_mul(raw[s][q], raw[s][q]);
    float sum[4], ssq[4];
    wg_fence();
    wgmma_rowsum<0>(sum, raw[0], ones);
#pragma unroll
    for (int s = 1; s < 6; s++) wgmma_rowsum<1>(sum, raw[s], ones);
    wgmma_rowsum<0>(ssq, sq[0], ones);
#pragma unroll
    for (int s = 1; s < 6; s++) wgmma_rowsum<1>(ssq, sq[s], ones);
    wg_commit();
    wg_wait<0>();
    uint32_t st[2];
#pragma unroll
    for (int h = 0; h < 2; h++) {
        asm volatile("" : "+f"(sum[2 * h]), "+f"(ssq[2 * h])::"memory");
        const float mean = sum[2 * h] * (1.f / CH);
        const float var = fmaxf(fmaf(ssq[2 * h], 1.f / CH, -mean * mean), 0.f);
        float rstd;
        asm("rsqrt.approx.ftz.f32 %0, %1;" : "=f"(rstd) : "f"(var + 1e-5f));
        rstd = bf_lo(pack_bf2(rstd * KZ, 0.f));
        st[h] = pack_bf2(rstd, -mean * rstd);
    }
    return make_uint2(st[0], st[1]);
}
__device__ __forceinline__ void ln_apply(uint32_t (&a)[6][4], const uint2& st) {
    const uint32_t sc[2] = {__byte_perm(st.x, 0, 0x1010), __byte_perm(st.y, 0, 0x1010)};
    const uint32_t sh[2] = {__byte_perm(st.x, 0, 0x3232), __byte_perm(st.y, 0, 0x3232)};
#pragma unroll
    for (int s = 0; s < 6; s++)
#pragma unroll
        for (int q = 0; q < 4; q++) {
            const uint32_t v = bf_fma(a[s][q], sc[q & 1], sh[q & 1]);
            a[s][q] = pack_h2(bf_lo(v), bf_hi(v));
        }
}
struct Cursor {
    int slot;
    uint32_t par;
    __device__ __forceinline__ void advance(int n) {
        slot += n;
        if (slot >= NSLOT) { slot -= NSLOT; par ^= 1; }
    }
};
struct Descs {
    uint64_t w1[8][6];
    uint64_t w2[24];
    uint64_t ones;
};
template <int E0, int N>
__device__ __forceinline__ void gemm1_chunk(uint32_t (&d)[N], const uint32_t (&a)[6][4], const Descs& ds, int zero) {
#pragma unroll
    for (int s = 0; s < 6; s++) wgmma(d, a[s][0], a[s][1], a[s][2], a[s][3], ds.w1[E0 / 48][s], s ? 1 : zero);
}
template <int E0, int N>
__device__ __forceinline__ void gemm2_chunk(uint32_t (&acc)[24], const uint32_t (&g)[N], const Descs& ds) {
#pragma unroll
    for (int s = 0; s < N / 4; s++) wgmma(acc, g[4 * s], g[4 * s + 1], g[4 * s + 2], g[4 * s + 3], ds.w2[E0 / 16 + s], 1);
}

__global__ void __launch_bounds__(NTHREADS, 1)
block_kernel(const __grid_constant__ CUtensorMap tmap, const __grid_constant__ CUtensorMap tmap_w1,
             const __nv_bfloat16* __restrict__ x, const __nv_bfloat16* __restrict__ dw, const __nv_bfloat16* __restrict__ w2,
             const __nv_bfloat16* __restrict__ gamma, const __nv_bfloat16* __restrict__ beta, __nv_bfloat16* __restrict__ out,
             Scratch* __restrict__ sc, const __grid_constant__ Descs ds,
             const int zero, const int per_cta, const int extra, const int lenders) {
    extern __shared__ __align__(1024) uint8_t smem[];
    constexpr uint32_t sb = SB;
    const int tid = threadIdx.x;
    const Work wk = get_work(per_cta, extra, lenders);
    if (smem_u32(smem) != SB || wk.rows + 4 > MAX_ROWS) __trap();
    constexpr uint32_t s_red = sb + SM_RED;

    PROF(0);
    const int warp_id = __shfl_sync(~0u, tid >> 5, 0);
    if (warp_id < 4 && elect_one()) first_loads(wk, &tmap, &tmap_w1, dw, sb, warp_id);
    __syncwarp();
    const int cw = warp_id - 4, wgi = cw >> 2, w4 = warp_id & 3;
    const int ntiles = wk.nA + wk.nB;
    const int wg = warp_id >> 2;
    int first = wg;
    uint32_t a[6][4], tile_off, next_off, stage, inv_rho2 = 0, rpar = 0, bias_addr, lane16, lane_off;
    auto set_lane = [&](uint32_t lane) {
        bias_addr = sb + SM_BIASH + (lane & 3) * 96;
        lane16 = lane * 16;
        lane_off = ((lane >> 2) * CH + 8 * (lane & 3)) * 2;
    };
    const uint32_t bar_r = sb + BAR_R + warp_id * 8;
    auto load_bias = [&](uint32_t (&acc)[24]) {
#pragma unroll
        for (int q = 0; q < 6; q++) lds128(acc[4 * q], acc[4 * q + 1], acc[4 * q + 2], acc[4 * q + 3], bias_addr + q * 16);
    };
    auto load_frags = [&](bool on) {
#pragma unroll
        for (int s = 0; s < 6; s++) ldg128_if(on, a[s], reinterpret_cast<const char*>(out) + next_off + w4 * WARP_BYTES + lane16 + s * 512);
    };
    auto stage_x = [&]() {
        if (elect_one()) {
            mbar_expect_tx(bar_r, WARP_BYTES);
            bulk_load_stream(stage, reinterpret_cast<const char*>(x) + tile_off + w4 * WARP_BYTES, WARP_BYTES, bar_r);
        }
    };
    auto epilogue = [&](uint32_t (&acc)[24]) {
        pin(acc);
        rpar ^= 1;
        uint4* op = reinterpret_cast<uint4*>(reinterpret_cast<char*>(out) + tile_off + w4 * WARP_BYTES + lane_off);
#pragma unroll
        for (int h = 0; h < 2; h++)
#pragma unroll
            for (int m = 0; m < 3; m++) {
                uint32_t xin[4], o[4];
                lds128(xin[0], xin[1], xin[2], xin[3], stage + lane_off + h * 1536 + m * 64);
#pragma unroll
                for (int q = 0; q < 4; q++) {
                    const uint32_t v = acc[2 * (4 * m + q) + h];
                    o[q] = bf_fma(pack_bf2(h_lo(v), h_hi(v)), inv_rho2, xin[q]);
                }
                __stcs(op + h * 96 + m * 4, make_uint4(o[0], o[1], o[2], o[3]));
            }
        __syncwarp();
    };
    auto max_w1 = [&]() {
        float m = 0.f;
#pragma unroll
        for (int q = 0; q < 3; q++) {
            uint32_t u[4];
            lds128(u[0], u[1], u[2], u[3], s_red + q * 16);
#pragma unroll
            for (int k = 0; k < 4; k++) m = fmaxf(m, __uint_as_float(u[k]));
        }
        return m;
    };
    auto square_exp = [&](float w1max) {
        const int e = w1max > 0.f ? 4 - ilog2f(2.f * KZ * 96.f * w1max) : 0;
        return (e >= 0 && e <= 6) ? 0 : max(-14, min(e, 14));
    };
    const int last_wg = (ntiles - 1 - wk.lent) % NCONS;
    auto reduce = [&](int q, uint32_t lane, bool leader) {
        const int t = lane & 3, part = lane >> 2;
        const float w1max = max_w1();
        const int sq_e = square_exp(w1max);
        const float to_fixed = pow2i(sum_exp(w1max) - 2 * sq_e);
        unsigned long long* dst = &sc->sums[__float_as_uint(ldsf(s_red + 48)) & 1][blockIdx.x % REPLICAS][32 * q + 8 * (part >> 1) + 2 * t + (part & 1)];
        named_bar(11, CONS_THREADS);
        const unsigned in_piece = 32 * q + 8 * (part >> 1) + 2 * t + (part & 1) - (blockIdx.x - lenders) % 8 * 48;
        const float helped = in_piece < 48 ? ldsf(sb + SM_BIASH + in_piece * 4) * pow2i(2 * sq_e) : 0.f;
        float f[8] = {};
#pragma unroll 1
        for (int i = 0; i < NCONS; i++) {
            const int src_wg = (last_wg + 1 + i) % NCONS;
            if (i == NCONS - 1) {
                named_bar(13, CONS_THREADS);
                if (leader) {
                    fence_async();
#pragma unroll
                    for (int k = 1; k < NCONS; k++) {
                        const int o = (last_wg + k) % NCONS * SQ_WG;
                        bulk_load(sb + SM_W2 + o, reinterpret_cast<const char*>(sc->w2h) + o, SQ_WG, sb + BAR_W);
                    }
                }
                __syncwarp();
                named_bar(14, NTHREADS);
            }
            const uint32_t upper = sq_e ? SM_SQ + (NCONS + src_wg) * SQ_WG : SM_RING + (wk.rows + i) % NSLOT * SLOT_BYTES;
            const uint32_t src = sb + lane * 16 + (q < 6 ? SM_SQ + src_wg * SQ_WG + q * SQ_ROW : upper + (q - 6) * SQ_ROW);
#pragma unroll
            for (int r = 0; r < 4; r++) {
                uint32_t u[4];
                lds128(u[0], u[1], u[2], u[3], src + r * 512);
#pragma unroll
                for (int k = 0; k < 4; k++) { f[2 * k] += h_lo(u[k]); f[2 * k + 1] += h_hi(u[k]); }
            }
        }
        const bool b2 = part & 4, b1 = part & 2, b0 = part & 1;
        float r4[4], r2[2];
#pragma unroll
        for (int k = 0; k < 4; k++) r4[k] = (b2 ? f[k + 4] : f[k]) + __shfl_xor_sync(~0u, b2 ? f[k] : f[k + 4], 16);
#pragma unroll
        for (int k = 0; k < 2; k++) r2[k] = (b1 ? r4[k + 2] : r4[k]) + __shfl_xor_sync(~0u, b1 ? r4[k] : r4[k + 2], 8);
        const float tot = (b0 ? r2[1] : r2[0]) + __shfl_xor_sync(~0u, b0 ? r2[0] : r2[1], 4);
        atomicAdd(dst, __float2ull_rn(fminf((tot + helped) * to_fixed, 0x1p49f)) << 8 | 1);
    };
    const uint32_t s_fac = sb + SM_RING + (wk.rows + 1) % NSLOT * SLOT_BYTES + SQ_WG;
    if (warp_id < 4) {
        conv_producer(wk, &tmap, sc, sb, warp_id);
        const int lane = opaque(tid & 31), g = lane >> 2, t = lane & 3;
        const unsigned epoch = __float_as_uint(ldsf(s_red + 48));
        set_lane(lane);
#pragma unroll 1
        for (int q = gridDim.x - 1 - blockIdx.x; q < W2_GROUPS; q += gridDim.x) {
            uint32_t u[3], rmax = 0;
#pragma unroll
            for (int m = 0; m < 3; m++) {
                const uint4 w = ldg128_ordered(w2 + (8 * q + g) * CH + 32 * m + 8 * t);
                rmax = bf_absmax(bf_absmax(rmax, bf_absmax(w.x, w.y)), bf_absmax(w.z, w.w));
                u[m] = w4 & 2 ? (w4 & 1 ? w.w : w.z) : (w4 & 1 ? w.y : w.x);
            }
            const float bt = __bfloat162float(beta[8 * q + g]);
            rmax = bf_absmax(rmax, __shfl_xor_sync(~0u, rmax, 1));
            rmax = bf_absmax(rmax, __shfl_xor_sync(~0u, rmax, 2));
            const float mx = fmaxf(fabsf(bf_lo(rmax)), fabsf(bf_hi(rmax))), rs = row_scale(mx);
            if (t == 0 && w4 == 0) sc->w2max[8 * q + g] = mx;
#pragma unroll
            for (int m = 0; m < 3; m++) {
                float lo = bf_lo(u[m]), hi = bf_hi(u[m]);
                sc->w2h[(4 * m + w4) * 1536 + q * 32 + lane] = transpose8x8(pack_h2(lo * rs, hi * rs));
                lo *= bt; hi *= bt;
#pragma unroll
                for (int o = 4; o <= 16; o <<= 1) { lo += __shfl_xor_sync(~0u, lo, o); hi += __shfl_xor_sync(~0u, hi, o); }
                if (g == 0) {
                    float* dst = &sc->bias[epoch & 1][32 * m + 8 * t + 2 * w4];
                    asm volatile("red.global.add.v2.f32 [%0], {%1, %2};" ::"l"(dst), "f"(lo), "f"(hi) : "memory");
                }
            }
            asm volatile("fence.proxy.async.global;" ::: "memory");
            signal(&sc->prep);
        }
#pragma unroll
        for (int s = 0; s < 6; s++) a[s][0] = a[s][1] = a[s][2] = a[s][3] = 0;
        const unsigned piece = blockIdx.x - lenders;
        if (piece < 8 * LENT * lenders) {
            spin_until(&sc->lent_in, (epoch + 1) * 4 * lenders);
            next_off = tile_offset(piece / (8 * LENT) * (per_cta + 1) + piece / 8 % LENT);
            load_frags(true);
            uint32_t d[12], gl[12];
            wg_fence();
#pragma unroll
            for (int s = 0; s < 6; s++) wgmma(d, a[s][0], a[s][1], a[s][2], a[s][3], ds.w1[0][s] + piece % 8 * (6 * 1536 / 16), s ? 1 : 0);
            wg_commit();
            wg_wait<0>();
            gelu_to(gl, d);
#pragma unroll
            for (int s = 0; s < 3; s++) sc->lent[((piece * 4 + w4) * 3 + s) * 32 + lane] = make_uint4(gl[4 * s], gl[4 * s + 1], gl[4 * s + 2], gl[4 * s + 3]);
            float f[6], r[3];
#pragma unroll
            for (int j = 0; j < 6; j++) {
                const float lo = fmaf(h_lo(gl[2 * j]), h_lo(gl[2 * j]), h_lo(gl[2 * j + 1]) * h_lo(gl[2 * j + 1]));
                const float hi = fmaf(h_hi(gl[2 * j]), h_hi(gl[2 * j]), h_hi(gl[2 * j + 1]) * h_hi(gl[2 * j + 1]));
                f[j] = (g & 1 ? hi : lo) + __shfl_xor_sync(~0u, g & 1 ? lo : hi, 4);
            }
#pragma unroll
            for (int j = 0; j < 3; j++) {
                r[j] = (g & 2 ? f[j + 3] : f[j]) + __shfl_xor_sync(~0u, g & 2 ? f[j] : f[j + 3], 8);
                asm volatile("red.shared.add.f32 [%0], %1;" ::"r"(sb + SM_BIASH + (8 * j + 12 * (g & 2) + 2 * t + (g & 1)) * 4), "f"(r[j]) : "memory");
            }
        }
        if (piece < 8 * LENT * lenders) signal(&sc->lent_out);
        const bool leader = warp_id == 0 && lane == 0;
        const float w1max = max_w1();
        const bool plain = square_exp(w1max) == 0;
        auto load_upper = [&]() {
            bulk_load(sb + SM_W2 + NCONS * SQ_WG, reinterpret_cast<const char*>(sc->w2h) + NCONS * SQ_WG, EX * CH * 2 - NCONS * SQ_WG, sb + BAR_W);
        };
        if (leader) {
            spin_until(&sc->prep, (epoch + 1) * 4 * W2_GROUPS);
            asm volatile("fence.proxy.async.global;" ::: "memory");
            fence_async();
            mbar_expect_tx(sb + BAR_W, EX * CH * 2);
            if (plain) load_upper();
        }
        __syncwarp();
        named_bar(1, 128);
        const int i0 = w4 * 32 + lane;
        float gam[3], rmax[3];
#pragma unroll
        for (int m = 0; m < 3; m++) { gam[m] = __bfloat162float(gamma[i0 + 128 * m]); rmax[m] = __ldcg(&sc->w2max[i0 + 128 * m]); }
        float2 bpair = make_float2(0.f, 0.f);
        if (i0 < 96) bpair = __ldcg(reinterpret_cast<const float2*>(&sc->bias[epoch & 1][32 * (i0 % 24 >> 3) + 8 * (i0 / 24) + (i0 % 24 & 6)]));
        const float gbound = fmaxf(2.f * KZ * 9.7979590f * 192.f * w1max, 1.f) * 19.5959180f * INV_2KZ;
        const unsigned fixed = __reduce_max_sync(~0u, __float_as_uint(fmaf(gbound, fmaxf(fmaxf(rmax[0], rmax[1]), rmax[2]), fmaxf(fabsf(bpair.x), fabsf(bpair.y)))));
        if (lane == 0) sts32(s_red + 96 + w4 * 4, fixed);
        reduce(4 * last_wg + w4, lane, leader);
        PROF(2);
        named_bar(15, CONS_THREADS);
        if (leader) {
            fence_async();
            bulk_load(sb + SM_W2 + last_wg * SQ_WG, reinterpret_cast<const char*>(sc->w2h) + last_wg * SQ_WG, SQ_WG, sb + BAR_W);
            if (!plain) load_upper();
        }
        stage = sb + SM_RING + (wk.rows % NSLOT) * SLOT_BYTES + w4 * REGION_BYTES;
        auto grn = [&]() {
            unsigned long long sum[3];
            for (unsigned n = 0;; n++) {
                bool all = true;
#pragma unroll
                for (int m = 0; m < 3; m++) {
                    unsigned cnt = 0;
                    sum[m] = 0;
#pragma unroll
                    for (int q = 0; q < REPLICAS; q++) {
                        unsigned long long v;
                        asm volatile("ld.relaxed.gpu.global.u64 %0, [%1];" : "=l"(v) : "l"(&sc->sums[epoch & 1][q][i0 + 128 * m]) : "memory");
                        cnt += (unsigned)v & 255u;
                        sum[m] += v >> 8;
                    }
                    all &= cnt == gridDim.x;
                }
                if (__all_sync(~0u, all)) break;
                if (n > SPIN_LIMIT) __trap();
            }
            PROF(3);
            if (blockIdx.x == 0 && leader) sc->launch = epoch + 1;
            float gx[3], tot = 0.f, vary = 0.f;
#pragma unroll
            for (int m = 0; m < 3; m++) {
                gx[m] = grn_norm(__ull2float_rn(sum[m]) * pow2i(-sum_exp(w1max)));
                tot += gx[m];
                vary = fmaxf(vary, fabsf(gam[m]) * gx[m] * rmax[m]);
            }
#pragma unroll
            for (int o = 16; o >= 1; o >>= 1) tot += __shfl_xor_sync(~0u, tot, o);
            const unsigned vwarp = __reduce_max_sync(~0u, __float_as_uint(vary));
            if (lane == 0) { sts32(s_red + 64 + w4 * 4, __float_as_uint(tot)); sts32(s_red + 80 + w4 * 4, vwarp); }
            named_bar(1, 128);
            uint32_t u[4], v[4], w[4];
            lds128(u[0], u[1], u[2], u[3], s_red + 64);
            lds128(v[0], v[1], v[2], v[3], s_red + 80);
            lds128(w[0], w[1], w[2], w[3], s_red + 96);
            tot = (__uint_as_float(u[0]) + __uint_as_float(u[1])) + (__uint_as_float(u[2]) + __uint_as_float(u[3]));
            const float vmax = __uint_as_float(max(max(v[0], v[1]), max(v[2], v[3]))), fmax2 = __uint_as_float(max(max(w[0], w[1]), max(w[2], w[3])));
            const float inv_mean = __fdividef(1.f, tot * (1.f / EX) + 1e-6f);
            const float bound = fmaf(gbound * vmax, inv_mean, 2.f * fmax2);
            const int rho_e = bound > 0.f ? 14 - ilog2f(bound) : 0;
            const float rho = pow2i(rho_e), inv_rho = pow2i(-rho_e);
            inv_rho2 = pack_bf2(inv_rho, inv_rho);
#pragma unroll
            for (int m = 0; m < 3; m++) {
                const float f = __fdividef(fmaf(gam[m], gx[m] * inv_mean, 1.f) * INV_2KZ * rho, row_scale(rmax[m]));
                asm volatile("st.shared.u16 [%0], %1;" ::"r"(s_fac + (i0 + 128 * m) * 2), "h"((unsigned short)pack_h2(f, 0.f)) : "memory");
            }
            if (i0 < 96) sts32(sb + SM_BIASH + i0 * 4, pack_h2(bpair.x * rho, bpair.y * rho));
            if (i0 == 96) sts32(s_red + 52, inv_rho2);
            named_arrive(12, NTHREADS);
        };
        uint32_t gl[4][12] = {};
        const uint4* src = &sc->lent[(blockIdx.x * LENT * 8 * 4 + w4) * 96 + lane];
        auto fetch = [&](uint32_t (&v)[12], int c, bool on) {
#pragma unroll
            for (int s = 0; s < 3; s++) ldg128_if(on, reinterpret_cast<uint32_t (&)[4]>(v[4 * s]), src + c * 384 + s * 32);
        };
        if (__builtin_expect(wk.lent, 0)) {
            first = 4;
            tile_off = tile_offset(wk.tA);
            stage_x();
            if (elect_one()) prefetch_l2(reinterpret_cast<const char*>(x) + tile_offset(wk.tA + 1) + w4 * WARP_BYTES, WARP_BYTES);
            spin_until(&sc->lent_out, (epoch + 1) * 32 * LENT * lenders);
#pragma unroll
            for (int c = 0; c < 3; c++) fetch(gl[c], c, true);
        }
        lds32(next_off, sb + SM_TILES + first * 4);
        load_frags(true);
        grn();
        if (__builtin_expect(wk.lent, 0)) {
            named_bar(3, NTHREADS);
#pragma unroll 1
            for (int e = 0; e < LENT; e++) {
                uint32_t acc[24];
                load_bias(acc);
#define CNX_LENT(C)                                  \
    pin(gl[C % 4]);                                  \
    wg_fence();                                      \
    gemm2_chunk<48 * C>(acc, gl[C % 4], ds);         \
    wg_commit();                                     \
    wg_wait<(C < 7 ? 1 : 0)>();                      \
    fetch(gl[(C + 3) % 4], C + 3, C < 5 || e == 0);  \
    if (lane == 0) mbar_arrive(sb + BAR_PIN);
                CNX_LENT(0) CNX_LENT(1) CNX_LENT(2) CNX_LENT(3) CNX_LENT(4) CNX_LENT(5) CNX_LENT(6) CNX_LENT(7)
#undef CNX_LENT
                src += 8 * 384;
                mbar_wait(bar_r, rpar);
                epilogue(acc);
                tile_off = tile_offset(wk.tA + 1);
                if (e == 0) stage_x();
            }
        }
    } else {
        {
            const int ct = tid - 128, lane = tid & 31;
            const unsigned epoch = *reinterpret_cast<volatile unsigned*>(&sc->launch);
            const int r = lane & 7, mi = lane >> 3;
            const uint32_t src = sb + SM_W2 + (cw >> 1) * (64 * CH * 2) + r * 128 + ((((cw & 1) * 4 + mi) ^ r) * 16);
            const uint32_t dst = sb + SM_W1 + (4 * cw + mi) * 1536 + r * 16;
            named_bar(0, NTHREADS);
            mbar_wait(sb + BAR_W + (cw >> 1) * 8, 0);
            uint32_t wmax[4] = {}, wsum[4] = {};
#pragma unroll 3
            for (int c = 0; c < 12; c++) {
                uint32_t u[4];
                ldsm4_t(u, src + c * 1024);
#pragma unroll
                for (int q = 0; q < 4; q++) {
                    wmax[q] = bf_absmax(wmax[q], u[q]);
                    wsum[q] = bf_fma(u[q], 0x3f803f80u, wsum[q]);
                    u[q] = pack_h2(bf_lo(u[q]), bf_hi(u[q]));
                }
                stsm4(dst + c * 128, u[0], u[1], u[2], u[3]);
            }
            float mean[4];
            bool center = false;
#pragma unroll
            for (int q = 0; q < 4; q++) {
                uint32_t m = wmax[q];
                float sum = bf_lo(wsum[q]) + bf_hi(wsum[q]);
#pragma unroll
                for (int o = 1; o <= 2; o <<= 1) { m = bf_absmax(m, __shfl_xor_sync(~0u, m, o)); sum += __shfl_xor_sync(~0u, sum, o); }
                mean[q] = sum * (1.f / CH);
                center |= fabsf(mean[q]) > 0.2f * fmaxf(fabsf(bf_lo(m)), fabsf(bf_hi(m)));
            }
            if (__builtin_expect(__any_sync(~0u, center), 0)) {
#pragma unroll 1
                for (int pass = 0; pass < 2; pass++) {
                    float sum[4] = {};
#pragma unroll 1
                    for (int c = 0; c < 12; c++) {
                        uint32_t u[4];
                        ldsm4_t(u, src + c * 1024);
#pragma unroll
                        for (int q = 0; q < 4; q++) {
                            sum[q] += bf_lo(u[q]) + bf_hi(u[q]);
                            u[q] = pack_h2(bf_lo(u[q]) - mean[q], bf_hi(u[q]) - mean[q]);
                        }
                        stsm4(dst + c * 128, u[0], u[1], u[2], u[3]);
                    }
#pragma unroll
                    for (int q = 0; q < 4; q++) {
                        sum[q] += __shfl_xor_sync(~0u, sum[q], 1);
                        sum[q] += __shfl_xor_sync(~0u, sum[q], 2);
                        mean[q] = sum[q] * (1.f / CH);
                    }
                }
            }
            const float w1max = warp_absmax(bf_absmax(bf_absmax(wmax[0], wmax[1]), bf_absmax(wmax[2], wmax[3])));
            if (lane == 0) sts32(s_red + cw * 4, __float_as_uint(w1max));
            if (ct < 32) sts32(sb + SM_ONES + ct * 4, 0x3f803f80u);
            if (ct < 48) sts32(sb + SM_BIASH + ct * 4, 0);
            if (blockIdx.x == 0) {
#pragma unroll
                for (int q = 0; q < REPLICAS; q++) sc->sums[(epoch & 1) ^ 1][q][ct] = 0;
                if (ct < CH) sc->bias[(epoch & 1) ^ 1][ct] = 0.f;
            }
            if (ct == 0) sts32(s_red + 48, epoch);
            fence_async();
            named_bar(2, CONS_THREADS);
#pragma unroll
            for (int q = 0; q < 12; q++) sts128(sb + SM_SQ + (wgi + q / 6 * NCONS) * SQ_WG + q % 6 * SQ_ROW + (ct & 127) * 16, 0, 0, 0, 0);
            mbar_wait(sb + BAR_A + w4 * 8 + 32, 0);
        }

        PROF(1);
        const uint32_t a_addr = opaque(sb + SM_RING + w4 * REGION_BYTES + ((tid >> 3) & 1) * A_SBO + ((tid >> 4) & 1) * A_LBO + (tid & 7) * 16);
        const uint32_t bar_a = sb + BAR_A + w4 * 8, bar_e = sb + BAR_E + w4 * 8;
        const uint32_t sq = opaque(sb + SM_SQ + wgi * SQ_WG + (tid & 127) * 16);
        const uint32_t sq_warp = sb + SM_SQ + wgi * SQ_WG + w4 * 512;
        uint32_t k1[24], k2[24], k3[24];
        constexpr int SQC = 3 * SQ_ROW;
        const int pass_to = 4 + (wgi == NCONS - 1 ? 0 : wgi + 1);
        auto store_frags = [&](const uint32_t (&a)[6][4], int j) {
            char* ap = reinterpret_cast<char*>(out) + (tile_offset(wk.tile(j)) + w4 * WARP_BYTES - sq_warp + sq);
#pragma unroll
            for (int s = 0; s < 6; s++) stg128(ap + s * 512, a[s]);
        };
        int jt = wgi < wk.lent ? wgi : wk.lent + wgi;
        Cursor cur = {2, 0};
        cur.advance(jt + (jt >= wk.nA ? 2 : 0));
        if (wgi == NCONS - 1) named_arrive(4, 256);
        for (;;) {
            const bool plain = __all_sync(~0u, square_exp(max_w1()) == 0);
            if (plain && jt >= wk.lent) {
                uint32_t hs2[12] = {}, hs3[12] = {};
#pragma unroll 1
                for (; jt + NCONS < ntiles; jt += NCONS) {
                    uint32_t a[6][4], d0[24], d1[24], unused[24];
                    named_bar(4 + wgi, 256);
                    mbar_wait(bar_a + cur.slot * 32, cur.par);
                    load_tile(a, a_addr + cur.slot * SLOT_BYTES);
                    const uint2 st = ln_stats(a, ds.ones);
                    ln_apply(a, st);
                    wg_fence();
                    gemm1_chunk<0>(d0, a, ds, 0);
                    wg_commit();
                    gemm1_chunk<96>(d1, a, ds, 0);
                    wg_commit();
                    store_frags(a, jt);
                    wg_wait<1>();
                    gelu_sq<false, 0, S1_PASS>(d0, unused, sq, 0);
                    named_arrive(pass_to, 256);
                    gelu_sq<false, S1_PASS, 3>(d0, unused, sq, 0);
                    if (elect_one()) mbar_arrive(bar_e + cur.slot * 32);
                    wg_fence();
                    gemm1_chunk<192>(d0, a, ds, zero);
                    wg_commit();
                    wg_wait<1>();
                    gelu_sq<false>(d1, unused, sq + SQC, 0);
                    wg_fence();
                    gemm1_chunk<288>(d1, a, ds, zero);
                    wg_commit();
                    wg_wait<1>();
                    gelu_sq_reg(d0, hs2);
                    anchor(sq, hs2[8], hs2[9], hs2[10], hs2[11]);
                    wg_wait<0>();
                    gelu_sq_reg(d1, hs3);
                    cur.advance(NCONS + ((jt < wk.nA && jt + NCONS >= wk.nA) ? 2 : 0));
                }
                const uint32_t sq2 = sq - (SM_SQ + wgi * SQ_WG) + SM_RING + (cur.slot + 3) % NSLOT * SLOT_BYTES;
#pragma unroll
                for (int k = 0; k < 3; k++) {
                    sts128(sq2 + k * SQ_ROW, hs2[4 * k], hs2[4 * k + 1], hs2[4 * k + 2], hs2[4 * k + 3]);
                    sts128(sq2 + SQC + k * SQ_ROW, hs3[4 * k], hs3[4 * k + 1], hs3[4 * k + 2], hs3[4 * k + 3]);
                }
            }
            const bool last = jt + NCONS >= ntiles;
            uint32_t a[6][4], d0[24], d1[24], d3[24], k0[24];
            if (jt >= wk.lent) named_bar(4 + wgi, 256);
            mbar_wait(bar_a + cur.slot * 32, cur.par);
            load_tile(a, a_addr + cur.slot * SLOT_BYTES);
            const uint2 st = ln_stats(a, ds.ones);
            ln_apply(a, st);
            if (!last) {
                store_frags(a, jt);
                __syncwarp();
                if (elect_one()) mbar_arrive(bar_e + cur.slot * 32);
                if (jt < wk.lent) {
                    jt += LENT;
                    cur.advance(LENT);
                    continue;
                }
            }
            wg_fence();
            gemm1_chunk<0>(d0, a, ds, 0);
            wg_commit();
            gemm1_chunk<96>(d1, a, ds, 0);
            wg_commit();
            const int sq_e = square_exp(max_w1());
            const uint32_t scale2 = pack_h2(pow2i(sq_e), pow2i(sq_e));
            stage = sb + SM_RING + cur.slot * SLOT_BYTES + w4 * REGION_BYTES;
            wg_wait<1>();
            gelu_sq<true, 0, S1_PASS>(d0, k0, sq, scale2);
            if (jt + 1 < ntiles) named_arrive(pass_to, 256);
            gelu_sq<true, S1_PASS, 3>(d0, k0, sq, scale2);
            if (last) {
#pragma unroll
                for (int q = 0; q < 6; q++) sts128(stage - sq_warp + sq + q * 512, k0[4 * q], k0[4 * q + 1], k0[4 * q + 2], k0[4 * q + 3]);
            }
            wg_fence();
            gemm1_chunk<192>(d0, a, ds, zero);
            wg_commit();
            wg_wait<1>();
            gelu_sq<true>(d1, k1, sq + SQC, scale2);
            wg_fence();
            gemm1_chunk<288>(d3, a, ds, 0);
            wg_commit();
            wg_wait<1>();
            const uint32_t sq2 = sq + (plain ? SM_RING + (cur.slot + 3) % NSLOT * SLOT_BYTES - (SM_SQ + wgi * SQ_WG) : NCONS * SQ_WG);
            gelu_sq<true>(d0, k2, sq2, scale2);
            wg_wait<0>();
            gelu_sq<true>(d3, k3, sq2 + SQC, scale2);
            if (last) break;
            cur.advance(NCONS + ((jt < wk.nA && jt + NCONS >= wk.nA) ? 2 : 0));
            jt += NCONS;
        }
        {
            if (wgi == last_wg) {
                named_arrive(14, NTHREADS);
            } else {
                reduce(cw, (sq >> 4) & 31, false);
                named_arrive(15, CONS_THREADS);
            }
        }
        PROF(2);
        tile_off = tile_offset(wk.tile(jt));
        {
            set_lane((sq >> 4) & 31);
            if (elect_one()) prefetch_l2(reinterpret_cast<const char*>(x) + tile_off + w4 * WARP_BYTES, WARP_BYTES);
            const uint32_t row = sb + SM_W2 + cw * 512 + lane16;
            uint32_t u[W2_EARLY][4], f2[4];
            mbar_wait(sb + BAR_W, 1);
#pragma unroll
            for (int nb = 0; nb < W2_EARLY; nb++) lds128(u[nb][0], u[nb][1], u[nb][2], u[nb][3], row + nb * 6144);
            named_bar(12, NTHREADS);
            PROF(3);
            lds128(f2[0], f2[1], f2[2], f2[3], s_fac + cw * 64 + (lane16 >> 7) * 16);
            lds32(inv_rho2, s_red + 52);
#pragma unroll
            for (int nb = 0; nb < 12; nb++) {
                uint32_t v[4];
                if (nb < W2_EARLY) { v[0] = u[nb % W2_EARLY][0]; v[1] = u[nb % W2_EARLY][1]; v[2] = u[nb % W2_EARLY][2]; v[3] = u[nb % W2_EARLY][3]; }
                else lds128(v[0], v[1], v[2], v[3], row + nb * 6144);
                sts128(row + nb * 6144, h_round8(h_mul(v[0], f2[0])), h_round8(h_mul(v[1], f2[1])), h_round8(h_mul(v[2], f2[2])), h_round8(h_mul(v[3], f2[3])));
            }
            fence_async();
            named_bar(3, NTHREADS);
        }
        PROF(4);
        {
            uint32_t acc[24];
            load_bias(acc);
            lds32(next_off, sb + SM_TILES + wg * 4);
            if (wgi > 0) named_bar(8 + wgi, 256);
            pin(k1); pin(k2); pin(k3);
            wg_fence();
            gemm2_chunk<288>(acc, k3, ds);
            wg_commit();
            gemm2_chunk<96>(acc, k1, ds);
            gemm2_chunk<192>(acc, k2, ds);
            wg_commit();
            if (wgi + 1 < NCONS) named_arrive(9 + wgi, 256);
            wg_wait<1>();
            uint32_t k0[24];
#pragma unroll
            for (int q = 0; q < 6; q++) lds128(k0[4 * q], k0[4 * q + 1], k0[4 * q + 2], k0[4 * q + 3], stage + lane16 + q * 512);
            pin(k0);
            wg_fence();
            gemm2_chunk<0>(acc, k0, ds);
            wg_commit();
            stage_x();
            wg_wait<1>();
            load_frags(true);
            if (lane16 == 0) mbar_arrive(sb + BAR_PIN);
            mbar_wait(bar_r, rpar);
            wg_wait<0>();
            epilogue(acc);
        }
    }
    {
        const int nrest = ntiles - NCONS - wk.lent / 2;
        for (int jt = first; jt < nrest; jt += 4) {
            uint32_t d0[12], d1[12], g0[12], g1[12], acc[24];
            tile_off = next_off;
            lds32(next_off, sb + SM_TILES + (jt + 4) * 4);
            if (jt >= S2_FIRST) named_bar(4 + wg, 256);
            wg_fence();
            gemm1_chunk<0>(d0, a, ds, 0);
            wg_commit();
            gemm1_chunk<48>(d1, a, ds, 0);
            wg_commit();
            load_bias(acc);
            const bool more = jt + 4 < nrest;
            tile_off = __shfl_sync(~0u, tile_off, 0);
            next_off = __shfl_sync(~0u, next_off, 0);
            wg_wait<1>();
#define CNX_PASS if (jt + 1 >= S2_FIRST && jt + 1 < nrest) named_arrive(4 + ((wg + 1) & 3), 256);
#define CNX_STEP(C, D, G)                                              \
    gelu_to(G, D);                                                     \
    if (C == 0 && jt == 0) {                                           \
        named_bar(3, NTHREADS);                                        \
        load_bias(acc);                                                \
    }                                                                  \
    wg_fence();                                                        \
    if (C < 6) gemm1_chunk<48 * (C < 6 ? C + 2 : 0)>(D, a, ds, zero); \
    gemm2_chunk<48 * C>(acc, G, ds);                                  \
    wg_commit();                                                       \
    if (C == S2_PASS) { CNX_PASS }                                     \
    wg_wait<(C < 7 ? 1 : 0)>();
            CNX_STEP(0, d0, g0)
            stage_x();
            if (more && elect_one()) prefetch_l2(reinterpret_cast<const char*>(out) + next_off + w4 * WARP_BYTES, WARP_BYTES);
            CNX_STEP(1, d1, g1)
            CNX_STEP(2, d0, g0)
            CNX_STEP(3, d1, g1)
            CNX_STEP(4, d0, g0)
            CNX_STEP(5, d1, g1)
            CNX_STEP(6, d0, g0)
            load_frags(more);
            if (lane16 == 0) mbar_arrive(sb + BAR_PIN);
            mbar_wait(bar_r, rpar);
            CNX_STEP(7, d1, g1)
#undef CNX_STEP
            epilogue(acc);
        }
    }
    PROF(5);
}

}

typedef CUresult (*EncodeTiledFn)(CUtensorMap*, CUtensorMapDataType, cuuint32_t, void*, const cuuint64_t*, const cuuint64_t*,
                                  const cuuint32_t*, const cuuint32_t*, CUtensorMapInterleave, CUtensorMapSwizzle,
                                  CUtensorMapL2promotion, CUtensorMapFloatOOBfill);

extern "C" void kernel_launch(void* const* d_in, const int* in_sizes, int n_in, void* d_out, int out_size) {
    using namespace cnx;
    static EncodeTiledFn encode = nullptr;
    static int num_sms = 0;
    static Scratch* scratch = nullptr;
    if (!encode) {
        void* fn = nullptr;
        cudaDriverEntryPointQueryResult qr;
        cudaGetDriverEntryPoint("cuTensorMapEncodeTiled", &fn, cudaEnableDefault, &qr);
        encode = (EncodeTiledFn)fn;
        cudaGetSymbolAddress((void**)&scratch, g_scratch);
        int dev = 0;
        cudaGetDevice(&dev);
        cudaDeviceGetAttribute(&num_sms, cudaDevAttrMultiProcessorCount, dev);
        if (num_sms > MAX_CTAS) num_sms = MAX_CTAS;
        cudaFuncSetAttribute(block_kernel, cudaFuncAttributeMaxDynamicSharedMemorySize, SM_TOTAL);
    }
    CUtensorMap tm;
    cuuint64_t dims[3] = {(cuuint64_t)CH, (cuuint64_t)IMG_W, (cuuint64_t)IMG_H};
    cuuint64_t strides[2] = {(cuuint64_t)CH * 2, (cuuint64_t)CH * 2 * IMG_W};
    cuuint32_t box[3] = {(cuuint32_t)CH, (cuuint32_t)REGION_PX, 1};
    cuuint32_t estr[3] = {1, 1, 1};
    encode(&tm, CU_TENSOR_MAP_DATA_TYPE_BFLOAT16, 3, d_in[0], dims, strides, box, estr, CU_TENSOR_MAP_INTERLEAVE_NONE,
           CU_TENSOR_MAP_SWIZZLE_NONE, CU_TENSOR_MAP_L2_PROMOTION_L2_128B, CU_TENSOR_MAP_FLOAT_OOB_FILL_NONE);
    Descs ds;
    for (int c = 0; c < 8; c++)
        for (int k = 0; k < 6; k++) ds.w1[c][k] = make_desc(SB + SM_W1 + c * 6 * 1536 + k * 256, 128, 1536);
    for (int k = 0; k < 24; k++) ds.w2[k] = make_desc(SB + SM_W2 + k * 256, 128, 6144);
    ds.ones = make_desc(SB + SM_ONES, 0, 0);
    CUtensorMap tw;
    cuuint64_t wdims[2] = {(cuuint64_t)EX, (cuuint64_t)CH};
    cuuint64_t wstrides[1] = {(cuuint64_t)EX * 2};
    cuuint32_t wbox[2] = {64, (cuuint32_t)CH};
    encode(&tw, CU_TENSOR_MAP_DATA_TYPE_BFLOAT16, 2, d_in[2], wdims, wstrides, wbox, estr, CU_TENSOR_MAP_INTERLEAVE_NONE,
           CU_TENSOR_MAP_SWIZZLE_128B, CU_TENSOR_MAP_L2_PROMOTION_L2_128B, CU_TENSOR_MAP_FLOAT_OOB_FILL_NONE);
    const int per_cta = NTILES / num_sms, extra = NTILES % num_sms;
    const int lenders = extra * (8 * LENT + 1) <= num_sms && extra * (per_cta + 1) <= IMG_H ? extra : 0;
    block_kernel<<<num_sms, NTHREADS, SM_TOTAL>>>(tm, tw, (const __nv_bfloat16*)d_in[0], (const __nv_bfloat16*)d_in[1],
                                             (const __nv_bfloat16*)d_in[3],
                                             (const __nv_bfloat16*)d_in[4], (const __nv_bfloat16*)d_in[5], (__nv_bfloat16*)d_out,
                                             scratch, ds, 0, per_cta, extra, lenders);
}
```

```cpp
#include <cuda_runtime.h>
#include <cuda_bf16.h>
#include <cuda_fp16.h>
#include <cuda.h>
#include <stdint.h>

namespace cnx {

constexpr int IMG_H = 512, IMG_W = 512, CH = 96, EX = 384;
constexpr int TILE_W = 64;
constexpr int NTILES = (IMG_W / TILE_W) * IMG_H;
constexpr int NSLOT = 6;
constexpr int REGION_PX = 18;
constexpr int REGION_BYTES = REGION_PX * CH * 2;
constexpr int SLOT_BYTES = 4 * REGION_BYTES;
constexpr int A_LBO = 144, A_SBO = 12 * A_LBO;
constexpr int PREFETCH_ROWS = 3;
constexpr int NCONS = 3;
constexpr int CONS_THREADS = 128 * NCONS;
constexpr int NTHREADS = 128 + CONS_THREADS;
constexpr int MAX_ROWS = 52;
constexpr int TILE_BYTES = TILE_W * CH * 2, WARP_BYTES = TILE_BYTES / 4;
constexpr int S1_PASS = 1, S2_PASS = 1;
#define K_PASS 4
#define K_WAIT 20
#define K_STG 6
#define K_REL 6
#define K_ANCH 2
#define K_CVT 0
#define W2_EARLY 6
#define S2_FIRST 4
#define ORDER_P 3
#define ORDER_Q 1
static_assert(MAX_ROWS <= 128, "one table entry per producer thread");
static_assert(2 * A_SBO == REGION_BYTES && REGION_BYTES % 128 == 0, "region layout");

constexpr uint32_t SB = 1024;
constexpr int SM_W1 = 0;
constexpr int SM_W2 = SM_W1 + CH * EX * 2;
constexpr int SM_RING = SM_W2 + CH * EX * 2;
constexpr int SM_BIASH = SM_RING + NSLOT * SLOT_BYTES;
constexpr int SM_RED = SM_BIASH + 384;
constexpr int SM_ROWS = SM_RED + 256;
constexpr int SM_TILES = SM_ROWS + MAX_ROWS * 4;
constexpr int SM_ONES = SM_TILES + MAX_ROWS * 4;
constexpr int SM_BAR = SM_ONES + 128;
constexpr int BAR_X = SM_BAR;
constexpr int BAR_A = BAR_X + NSLOT * 4 * 8;
constexpr int BAR_E = BAR_A + NSLOT * 4 * 8;
constexpr int BAR_PIN = BAR_E + NSLOT * 4 * 8;
constexpr int BAR_W = BAR_PIN + 8;
constexpr int BAR_R = BAR_W + 6 * 8;
constexpr int SM_TOTAL = BAR_R + 16 * 8;
constexpr int SM_SQ = SM_W2;
constexpr int SQ_ROW = 128 * 16, SQ_WG = 6 * SQ_ROW;
static_assert(SM_ONES % 16 == 0 && SM_TOTAL <= 232448, "shared memory budget");

constexpr float KZ = 0.3292034911525734f;
constexpr uint32_t GELU_C2 = 0x40d940d9u;
constexpr float INV_2KZ = 0.5f / KZ;
constexpr unsigned SPIN_LIMIT = 1u << 19;

constexpr int MAX_CTAS = 255;
constexpr int W2_GROUPS = EX / 8;
constexpr int LENT = 2, MAX_LENDERS = MAX_CTAS / (8 * LENT + 1);
struct Scratch {
    uint32_t w2h[EX * CH / 2];
    float w2max[EX];
    float bias[2][CH];
    unsigned long long sums[2][EX / 4][32];
    __device__ __forceinline__ unsigned long long* sum(unsigned launch, int e) { return &sums[launch & 1][e >> 2][e & 3]; }
    uint4 lent[MAX_LENDERS * LENT * 8 * 4 * 3 * 32];
    unsigned launch, pad0[31], prep, pad1[31], lent_in, pad2[31], lent_out, pad3[31];
};
__device__ __align__(128) Scratch g_scratch;

#define PROF(k)

__device__ __forceinline__ uint32_t smem_u32(const void* p) { return (uint32_t)__cvta_generic_to_shared(p); }
__device__ __forceinline__ void mbar_init(uint32_t bar, uint32_t cnt) {
    asm volatile("mbarrier.init.shared::cta.b64 [%0], %1;" ::"r"(bar), "r"(cnt) : "memory");
}
__device__ __forceinline__ void mbar_arrive(uint32_t bar) {
    asm volatile("mbarrier.arrive.shared::cta.b64 _, [%0];" ::"r"(bar) : "memory");
}
__device__ __forceinline__ void mbar_expect_tx(uint32_t bar, uint32_t bytes) {
    asm volatile("mbarrier.arrive.expect_tx.shared::cta.b64 _, [%0], %1;" ::"r"(bar), "r"(bytes) : "memory");
}
__device__ __forceinline__ bool mbar_try(uint32_t bar, uint32_t par) {
    uint32_t ok;
    asm volatile("{\n.reg .pred p;\nmbarrier.try_wait.parity.shared::cta.b64 p, [%1], %2;\nselp.u32 %0, 1, 0, p;\n}\n"
                 : "=r"(ok) : "r"(bar), "r"(par) : "memory");
    return ok != 0;
}
__device__ __forceinline__ void mbar_wait(uint32_t bar, uint32_t par) {
    unsigned n = 0;
    while (!mbar_try(bar, par)) {
        if (++n > SPIN_LIMIT) __trap();
    }
}
__device__ __forceinline__ bool mbar_test(uint32_t bar, uint32_t par) {
    uint32_t ok;
    asm volatile("{\n.reg .pred p;\nmbarrier.test_wait.parity.shared::cta.b64 p, [%1], %2;\nselp.u32 %0, 1, 0, p;\n}\n"
                 : "=r"(ok) : "r"(bar), "r"(par) : "memory");
    return ok != 0;
}
__device__ __forceinline__ bool elect_one() {
    uint32_t ok;
    asm volatile("{\n.reg .pred p;\nelect.sync _|p, 0xffffffff;\nselp.u32 %0, 1, 0, p;\n}\n" : "=r"(ok));
    return ok != 0;
}
__device__ __forceinline__ uint32_t opaque(uint32_t v) { return __shfl_sync(~0u, v, threadIdx.x & 31); }
__device__ __forceinline__ void named_bar(int id, int n) { asm volatile("bar.sync %0, %1;" ::"r"(id), "r"(n) : "memory"); }
__device__ __forceinline__ void named_arrive(int id, int n) { asm volatile("bar.arrive %0, %1;" ::"r"(id), "r"(n) : "memory"); }
__device__ __forceinline__ void fence_async() { asm volatile("fence.proxy.async.shared::cta;" ::: "memory"); }
__device__ __forceinline__ uint64_t evict_first() {
    uint64_t p;
    asm("createpolicy.fractional.L2::evict_first.b64 %0, 1.0;" : "=l"(p));
    return p;
}
__device__ __forceinline__ void tma_row(uint32_t dst, const CUtensorMap* tm, uint32_t bar, int x, int y) {
    asm volatile("cp.async.bulk.tensor.3d.shared::cluster.global.mbarrier::complete_tx::bytes.L2::cache_hint [%0], [%1, {%3, %4, %5}], [%2], %6;"
                 ::"r"(dst), "l"(tm), "r"(bar), "r"(0), "r"(x), "r"(y), "l"(evict_first()) : "memory");
}
__device__ __forceinline__ void bulk_load_stream(uint32_t dst, const void* src, uint32_t bytes, uint32_t bar) {
    asm volatile("cp.async.bulk.shared::cluster.global.mbarrier::complete_tx::bytes.L2::cache_hint [%0], [%1], %2, [%3], %4;"
                 ::"r"(dst), "l"(src), "r"(bytes), "r"(bar), "l"(evict_first()) : "memory");
}
__device__ __forceinline__ void prefetch_l2(const void* src, uint32_t bytes) {
    asm volatile("cp.async.bulk.prefetch.L2.global [%0], %1;" ::"l"(src), "r"(bytes) : "memory");
}
__device__ __forceinline__ void tma_2d(uint32_t dst, const CUtensorMap* tm, uint32_t bar, int x, int y) {
    asm volatile("cp.async.bulk.tensor.2d.shared::cluster.global.mbarrier::complete_tx::bytes [%0], [%1, {%3, %4}], [%2];"
                 ::"r"(dst), "l"(tm), "r"(bar), "r"(x), "r"(y) : "memory");
}
__device__ __forceinline__ void bulk_load(uint32_t dst, const void* src, uint32_t bytes, uint32_t bar) {
    asm volatile("cp.async.bulk.shared::cluster.global.mbarrier::complete_tx::bytes [%0], [%1], %2, [%3];"
                 ::"r"(dst), "l"(src), "r"(bytes), "r"(bar) : "memory");
}
__device__ __forceinline__ void wg_fence() { asm volatile("wgmma.fence.sync.aligned;" ::: "memory"); }
__device__ __forceinline__ void wg_commit() { asm volatile("wgmma.commit_group.sync.aligned;" ::: "memory"); }
template <int N> __device__ __forceinline__ void wg_wait() { asm volatile("wgmma.wait_group.sync.aligned %0;" ::"n"(N) : "memory"); }
template <int N> __device__ __forceinline__ void pin(uint32_t (&d)[N]) {
#pragma unroll
    for (int q = 0; q < N; q++) asm volatile("" : "+r"(d[q])::"memory");
}
__device__ __forceinline__ void stg128(void* p, const uint32_t (&v)[4]) {
    asm volatile("st.global.v4.u32 [%0], {%1, %2, %3, %4};" ::"l"(p), "r"(v[0]), "r"(v[1]), "r"(v[2]), "r"(v[3]) : "memory");
}
__device__ __forceinline__ void ldg128_if(bool on, uint32_t (&v)[4], const void* p) {
    asm volatile("{\n.reg .pred p;\nsetp.ne.b32 p, %5, 0;\n@p ld.global.L1::no_allocate.v4.u32 {%0, %1, %2, %3}, [%4];\n}\n"
                 : "+r"(v[0]), "+r"(v[1]), "+r"(v[2]), "+r"(v[3]) : "l"(p), "r"((int)on) : "memory");
}
__device__ __forceinline__ uint4 ldg128_ordered(const void* p) {
    uint4 v;
    asm volatile("ld.global.nc.v4.u32 {%0, %1, %2, %3}, [%4];" : "=r"(v.x), "=r"(v.y), "=r"(v.z), "=r"(v.w) : "l"(p) : "memory");
    return v;
}
__host__ __device__ constexpr uint64_t make_desc(uint32_t addr, uint32_t lbo, uint32_t sbo) {
    return (uint64_t)((addr & 0x3FFFF) >> 4) | ((uint64_t)(lbo >> 4) << 16) | ((uint64_t)(sbo >> 4) << 32);
}
__device__ __forceinline__ void wgmma(uint32_t (&d)[12], uint32_t a0, uint32_t a1, uint32_t a2, uint32_t a3, uint64_t db, int acc) {
    asm volatile("{\n.reg .pred p;\nsetp.ne.b32 p, %17, 0;\n"
                 "wgmma.mma_async.sync.aligned.m64n48k16.f16.f16.f16 "
                 "{%0, %1, %2, %3, %4, %5, %6, %7, %8, %9, %10, %11}, "
                 "{%12, %13, %14, %15}, %16, p, 1, 1, 0;\n}\n"
                 : "+r"(d[0]), "+r"(d[1]), "+r"(d[2]), "+r"(d[3]), "+r"(d[4]), "+r"(d[5]), "+r"(d[6]), "+r"(d[7]), "+r"(d[8]), "+r"(d[9]), "+r"(d[10]), "+r"(d[11])
                 : "r"(a0), "r"(a1), "r"(a2), "r"(a3), "l"(db), "r"(acc));
}
__device__ __forceinline__ void wgmma(uint32_t (&d)[24], uint32_t a0, uint32_t a1, uint32_t a2, uint32_t a3, uint64_t db, int acc) {
    asm volatile("{\n.reg .pred p;\nsetp.ne.b32 p, %29, 0;\n"
                 "wgmma.mma_async.sync.aligned.m64n96k16.f16.f16.f16 "
                 "{%0, %1, %2, %3, %4, %5, %6, %7, %8, %9, %10, %11, %12, %13, %14, %15, %16, %17, %18, %19, %20, %21, %22, %23}, "
                 "{%24, %25, %26, %27}, %28, p, 1, 1, 0;\n}\n"
                 : "+r"(d[0]), "+r"(d[1]), "+r"(d[2]), "+r"(d[3]), "+r"(d[4]), "+r"(d[5]), "+r"(d[6]), "+r"(d[7]), "+r"(d[8]), "+r"(d[9]), "+r"(d[10]), "+r"(d[11]), "+r"(d[12]), "+r"(d[13]), "+r"(d[14]), "+r"(d[15]), "+r"(d[16]), "+r"(d[17]), "+r"(d[18]), "+r"(d[19]), "+r"(d[20]), "+r"(d[21]), "+r"(d[22]), "+r"(d[23])
                 : "r"(a0), "r"(a1), "r"(a2), "r"(a3), "l"(db), "r"(acc));
}
template <int ACC>
__device__ __forceinline__ void wgmma_rowsum(float (&d)[4], const uint32_t (&a)[4], uint64_t ones) {
    asm volatile("{\n.reg .pred p;\nsetp.ne.b32 p, %9, 0;\n"
                 "wgmma.mma_async.sync.aligned.m64n8k16.f32.bf16.bf16 {%0, %1, %2, %3}, {%4, %5, %6, %7}, %8, p, 1, 1, 0;\n}\n"
                 : "+f"(d[0]), "+f"(d[1]), "+f"(d[2]), "+f"(d[3])
                 : "r"(a[0]), "r"(a[1]), "r"(a[2]), "r"(a[3]), "l"(ones), "n"(ACC));
}
__device__ __forceinline__ void ldsm4(uint32_t (&r)[4], uint32_t addr) {
    asm volatile("ldmatrix.sync.aligned.m8n8.x4.shared.b16 {%0, %1, %2, %3}, [%4];"
                 : "=r"(r[0]), "=r"(r[1]), "=r"(r[2]), "=r"(r[3]) : "r"(addr) : "memory");
}
__device__ __forceinline__ void ldsm4_t(uint32_t (&r)[4], uint32_t addr) {
    asm volatile("ldmatrix.sync.aligned.m8n8.x4.trans.shared.b16 {%0, %1, %2, %3}, [%4];"
                 : "=r"(r[0]), "=r"(r[1]), "=r"(r[2]), "=r"(r[3]) : "r"(addr) : "memory");
}
__device__ __forceinline__ void stsm4(uint32_t addr, uint32_t a, uint32_t b, uint32_t c, uint32_t d) {
    asm volatile("stmatrix.sync.aligned.m8n8.x4.shared.b16 [%0], {%1, %2, %3, %4};"
                 ::"r"(addr), "r"(a), "r"(b), "r"(c), "r"(d) : "memory");
}
__device__ __forceinline__ uint32_t transpose8x8(uint32_t v) {
    uint32_t d; asm volatile("movmatrix.sync.aligned.m8n8.trans.b16 %0, %1;" : "=r"(d) : "r"(v)); return d;
}
__device__ __forceinline__ void spin_until(const unsigned* counter, unsigned target) {
    unsigned n = 0, c;
    do {
        asm volatile("ld.acquire.gpu.global.u32 %0, [%1];" : "=r"(c) : "l"(counter) : "memory");
        if (++n > SPIN_LIMIT) __trap();
    } while ((int)(c - target) < 0);
}
__device__ __forceinline__ void signal(unsigned* counter) {
    __syncwarp();
    if (elect_one()) asm volatile("red.release.gpu.global.add.u32 [%0], 1;" ::"l"(counter) : "memory");
    __syncwarp();
}
__device__ __forceinline__ void lds128(uint32_t& a, uint32_t& b, uint32_t& c, uint32_t& d, uint32_t addr) {
    asm volatile("ld.shared.v4.u32 {%0, %1, %2, %3}, [%4];" : "=r"(a), "=r"(b), "=r"(c), "=r"(d) : "r"(addr) : "memory");
}
__device__ __forceinline__ void lds64(uint32_t& a, uint32_t& b, uint32_t addr) {
    asm volatile("ld.shared.v2.u32 {%0, %1}, [%2];" : "=r"(a), "=r"(b) : "r"(addr) : "memory");
}
__device__ __forceinline__ void lds32(uint32_t& a, uint32_t addr) {
    asm volatile("ld.shared.u32 %0, [%1];" : "=r"(a) : "r"(addr) : "memory");
}
__device__ __forceinline__ float ldsf(uint32_t addr) {
    uint32_t v;
    lds32(v, addr);
    return __uint_as_float(v);
}
__device__ __forceinline__ void sts32(uint32_t addr, uint32_t a) {
    asm volatile("st.shared.u32 [%0], %1;" ::"r"(addr), "r"(a) : "memory");
}
__device__ __forceinline__ void sts128(uint32_t addr, uint32_t a, uint32_t b, uint32_t c, uint32_t d) {
    asm volatile("st.shared.v4.u32 [%0], {%1, %2, %3, %4};" ::"r"(addr), "r"(a), "r"(b), "r"(c), "r"(d) : "memory");
}
__device__ __forceinline__ void sts64(uint32_t addr, uint32_t a, uint32_t b) {
    asm volatile("st.shared.v2.u32 [%0], {%1, %2};" ::"r"(addr), "r"(a), "r"(b) : "memory");
}
__device__ __forceinline__ uint32_t bf_fma(uint32_t a, uint32_t b, uint32_t c) {
    uint32_t d; asm("fma.rn.bf16x2 %0, %1, %2, %3;" : "=r"(d) : "r"(a), "r"(b), "r"(c)); return d;
}
__device__ __forceinline__ uint32_t bf_mul(uint32_t a, uint32_t b) {
    uint32_t d; asm("mul.rn.bf16x2 %0, %1, %2;" : "=r"(d) : "r"(a), "r"(b)); return d;
}
__device__ __forceinline__ uint32_t bf_absmax(uint32_t a, uint32_t b) {
    uint32_t d; asm("max.xorsign.abs.bf16x2 %0, %1, %2;" : "=r"(d) : "r"(a), "r"(b)); return d;
}
__device__ __forceinline__ uint32_t h_fma(uint32_t a, uint32_t b, uint32_t c) {
    uint32_t d; asm("fma.rn.f16x2 %0, %1, %2, %3;" : "=r"(d) : "r"(a), "r"(b), "r"(c)); return d;
}
__device__ __forceinline__ uint32_t h_mul(uint32_t a, uint32_t b) {
    uint32_t d; asm("mul.rn.f16x2 %0, %1, %2;" : "=r"(d) : "r"(a), "r"(b)); return d;
}
__device__ __forceinline__ uint32_t h_round8(uint32_t v) { return (v + 0x00040004u) & 0xfff8fff8u; }
__device__ __forceinline__ uint32_t h_tanh(uint32_t a) {
    uint32_t d; asm("tanh.approx.f16x2 %0, %1;" : "=r"(d) : "r"(a)); return d;
}
__device__ __forceinline__ uint32_t pack_h2(float lo, float hi) {
    uint32_t d; asm("cvt.rn.f16x2.f32 %0, %1, %2;" : "=r"(d) : "f"(hi), "f"(lo)); return d;
}
__device__ __forceinline__ uint32_t pack_bf2(float lo, float hi) {
    uint32_t d; asm("cvt.rn.bf16x2.f32 %0, %1, %2;" : "=r"(d) : "f"(hi), "f"(lo)); return d;
}
__device__ __forceinline__ float bf_lo(uint32_t v) { return __uint_as_float(v << 16); }
__device__ __forceinline__ float bf_hi(uint32_t v) { return __uint_as_float(v & 0xffff0000u); }
__device__ __forceinline__ float h_lo(uint32_t v) { return __low2float(*reinterpret_cast<__half2*>(&v)); }
__device__ __forceinline__ float h_hi(uint32_t v) { return __high2float(*reinterpret_cast<__half2*>(&v)); }
__device__ __forceinline__ float warp_absmax(uint32_t v) {
    return __uint_as_float(__reduce_max_sync(~0u, max((v & 0x7fffu) << 16, v & 0x7fff0000u)));
}
__device__ __forceinline__ uint32_t gelu2(uint32_t z) {
    uint32_t p = h_fma(z, z, GELU_C2);
    uint32_t t = h_tanh(h_mul(z, p));
    return h_fma(z, t, z);
}
__device__ __forceinline__ float grn_norm(float ss) {
    float r;
    asm("sqrt.approx.f32 %0, %1;" : "=f"(r) : "f"(fmaf(ss, INV_2KZ * INV_2KZ, 1e-6f)));
    return r;
}
__device__ __forceinline__ float pow2i(int e) { return __uint_as_float((uint32_t)(e + 127) << 23); }
__device__ __forceinline__ int ilog2f(float v) {
    int e = (int)((__float_as_uint(v) >> 23) & 0xff) - 127;
    return max(-100, min(100, e));
}

__device__ __forceinline__ int sum_exp(float w1max) {
    return w1max > 0.f ? max(-90, min(90, 33 - 2 * ilog2f(2.f * KZ * 96.f * w1max))) : 0;
}
__device__ __forceinline__ float row_scale(float m) { return m > 0.f ? pow2i(2 - ilog2f(m)) : 1.f; }

struct Work {
    int tA, tB, nA, nB, rows, lent;
    __device__ __forceinline__ int tile(int j) const { return j < nA ? tA + j : tB + j - nA; }
};
__device__ __forceinline__ Work get_work(int per_cta, int extra, int lenders) {
    Work w;
    w.lent = (int)blockIdx.x < lenders ? LENT : 0;
    const int t0 = blockIdx.x * per_cta + min((int)blockIdx.x, extra);
    const int t1 = t0 + per_cta + ((int)blockIdx.x < extra);
    const int tm = min(t1, (t0 | 511) + 1);
    const bool swap = t1 > tm && t1 - tm < tm - t0;
    w.tA = swap ? tm : t0;
    w.tB = swap ? t0 : tm;
    w.nA = swap ? t1 - tm : tm - t0;
    w.nB = t1 - t0 - w.nA;
    w.rows = w.nA + 2 + (w.nB ? w.nB + 2 : 0);
    return w;
}
__device__ __forceinline__ int row_code(const Work& w, int i) {
    const bool in_a = i < w.nA + 2;
    const int t = in_a ? w.tA : w.tB;
    return ((t & 511) - 1 + (in_a ? i : i - (w.nA + 2))) << 16 | (t >> 9) * TILE_W;
}
__device__ __forceinline__ uint32_t tile_offset(int tile) { return ((tile & 511) * IMG_W + (tile >> 9) * TILE_W) * (CH * 2); }
__device__ __forceinline__ int tile_order(int j, int n) {
    const int olds = (j / ORDER_P) * ORDER_Q + max(0, j % ORDER_P - (ORDER_P - ORDER_Q));
    return (j % ORDER_P >= ORDER_P - ORDER_Q) ? olds : n - 1 - (j - olds);
}
__device__ __forceinline__ void issue_region(const CUtensorMap* tm, uint32_t dst, uint32_t bar, int warp, int code) {
    mbar_expect_tx(bar, REGION_BYTES);
    tma_row(dst, tm, bar, (code & 0xffff) + (16 * warp - 1), code >> 16);
}
__device__ __forceinline__ void elect_arrive(uint32_t bar0, uint32_t bar1, bool both) {
    asm volatile("{\n.reg .pred p, q;\nelect.sync _|p, 0xffffffff;\nsetp.ne.and.b32 q, %2, 0, p;\n"
                 "@p mbarrier.arrive.shared::cta.b64 _, [%0];\n@q mbarrier.arrive.shared::cta.b64 _, [%1];\n}\n"
                 ::"r"(bar0), "r"(bar1), "r"((int)both) : "memory");
}

__device__ __forceinline__ void first_loads(const Work& wk, const CUtensorMap* tm, const CUtensorMap* tw, const __nv_bfloat16* dw,
                                            uint32_t sb, int warp) {
    const uint32_t reg0 = sb + SM_RING + warp * REGION_BYTES, bars = sb + SM_BAR + warp * 8;
#pragma unroll
    for (int s = 0; s < PREFETCH_ROWS; s++) mbar_init(bars + s * 32, 1);
    mbar_init(sb + BAR_W + warp * 8, 1);
    if (warp < 2) mbar_init(sb + BAR_W + (warp + 4) * 8, 1);
    fence_async();
    asm volatile("mbarrier.expect_tx.shared::cta.b64 [%0], %1;" ::"r"(bars), "r"(9 * CH * 2) : "memory");
    bulk_load(reg0 + (NSLOT - 1) * SLOT_BYTES, dw, 9 * CH * 2, bars);
#pragma unroll
    for (int r = 0; r < PREFETCH_ROWS; r++)
        issue_region(tm, reg0 + r * SLOT_BYTES, bars + r * 32, warp, ((wk.tA & 511) - 1 + r) << 16 | (wk.tA >> 9) * TILE_W);
#pragma unroll 1
    for (int b = warp; b < 6; b += 4) {
        mbar_expect_tx(sb + BAR_W + b * 8, 64 * CH * 2);
        tma_2d(sb + SM_W2 + b * (64 * CH * 2), tw, sb + BAR_W + b * 8, 64 * b, 0);
    }
}

__device__ __forceinline__ void conv_producer(const Work& wk, const CUtensorMap* tm, Scratch* sc, uint32_t sb, int warp) {
    const int lane = threadIdx.x & 31;
    const int j = lane & 15, grp = lane >> 4;
    const uint32_t reg0 = sb + SM_RING + warp * REGION_BYTES;
    const uint32_t bars = sb + SM_BAR + warp * 8;
    if (elect_one()) {
        if (warp == 0) mbar_init(sb + BAR_PIN, 1);
#pragma unroll
        for (int s = 0; s < 4; s++) mbar_init(sb + BAR_R + (s * 4 + warp) * 8, 1);
#pragma unroll 1
        for (int s = PREFETCH_ROWS; s < 3 * NSLOT; s++) mbar_init(bars + s * 32, 1);
        fence_async();
    }
    __syncwarp();
    named_arrive(0, NTHREADS);
    if (warp * 32 + lane < MAX_ROWS) {
        sts32(sb + SM_ROWS + (warp * 32 + lane) * 4, row_code(wk, warp * 32 + lane));
        sts32(sb + SM_TILES + (warp * 32 + lane) * 4, tile_offset(wk.tile(wk.lent + tile_order(max(warp * 32 + lane - wk.lent / 2, 0), wk.nA + wk.nB - NCONS - wk.lent))));
    }
    const uint32_t ld64 = opaque(reg0 + grp * 8 * 192 + j * 8), ld32 = opaque(reg0 + grp * 8 * 192 + 128 + j * 4);
    const uint32_t st64 = opaque(reg0 + grp * A_SBO + (j >> 1) * A_LBO + (j & 1) * 8);
    const uint32_t st32 = opaque(reg0 + grp * A_SBO + (8 + (j >> 2)) * A_LBO + (j & 3) * 4);
    uint32_t accB[8][3] = {}, accC[8][3] = {};
    static_assert(2 * PREFETCH_ROWS == NSLOT, "prefetch slot arithmetic");
    uint32_t so = 0, bo = 0, par = 0, tbl = sb + SM_ROWS + PREFETCH_ROWS * 4;
    const uint32_t tbl_end = sb + SM_ROWS + wk.rows * 4;
    bool x_ready = false;
    named_bar(1, 128);
    mbar_wait(bars, 0);
    uint32_t w[3][3][3];
#pragma unroll
    for (int tap = 0; tap < 9; tap++) {
        const uint32_t p = reg0 + (NSLOT - 1) * SLOT_BYTES + tap * CH * 2;
        uint32_t u0, u1;
        lds64(u0, u1, p + 8 * j);
        __syncwarp();
        sts64(p + 8 * j, u1, u0);
        __syncwarp();
        lds64(w[tap / 3][tap % 3][1], w[tap / 3][tap % 3][0], p + 8 * j);
        lds32(w[tap / 3][tap % 3][2], p + 128 + 4 * j);
    }
    {
        const int first = wk.nA + 2, publish = wk.lent ? 12 : -1;
#pragma unroll 1
        for (int k = 0; k < wk.rows; k++) {
            if (!x_ready) mbar_wait(bars + bo, par);
            const bool wrap = bo == (NSLOT - 1) * 32, low = bo < PREFETCH_ROWS * 32;
            const uint32_t nbo = wrap ? 0 : bo + 32, npar = par ^ wrap;
            const uint32_t pbo = low ? bo + PREFETCH_ROWS * 32 : bo - PREFETCH_ROWS * 32, ppar = par ^ low;
            uint32_t out[8][3];
            int code;
            bool e_ready;
#pragma unroll
            for (int p = 0; p < 10; p++) {
                uint32_t xv[3];
                lds64(xv[0], xv[1], so + ld64 + p * 192);
                lds32(xv[2], so + ld32 + p * 192);
                if (p == 9) {
                    asm volatile("ld.shared.u32 %0, [%1];" : "=r"(code) : "r"(tbl));
                    e_ready = mbar_test(bars + (BAR_E - SM_BAR) + pbo, ppar);
                    x_ready = mbar_test(bars + nbo, npar);
                }
#pragma unroll
                for (int dx = 0; dx < 3; dx++) {
                    const int o = p - dx;
                    if (o < 0 || o > 7) continue;
#pragma unroll
                    for (int q = 0; q < 3; q++) {
                        out[o][q] = bf_fma(xv[q], w[2][dx][q], dx == 0 ? accB[o][q] : out[o][q]);
                        accB[o][q] = bf_fma(xv[q], w[1][dx][q], dx == 0 ? accC[o][q] : accB[o][q]);
                        accC[o][q] = dx == 0 ? bf_mul(xv[q], w[0][dx][q]) : bf_fma(xv[q], w[0][dx][q], accC[o][q]);
                    }
                }
            }
            __syncwarp();
#pragma unroll
            for (int o = 0; o < 8; o++) {
                sts64(so + st64 + o * 16, out[o][0], out[o][1]);
                sts32(so + st32 + o * 16, out[o][2]);
            }
            const bool halo = k < 2 || (unsigned)(k - first) < 2;
            if (halo) fence_async();
            if (k == publish) signal(&sc->lent_in);
            __syncwarp();
            elect_arrive(bars + (BAR_A - SM_BAR) + bo, bars + (BAR_E - SM_BAR) + bo, halo);
            if (tbl < tbl_end) {
                if (!e_ready) mbar_wait(bars + (BAR_E - SM_BAR) + pbo, ppar);
                code = __shfl_sync(~0u, code, 0);
                if (elect_one()) issue_region(tm, reg0 + (low ? so + PREFETCH_ROWS * SLOT_BYTES : so - PREFETCH_ROWS * SLOT_BYTES), bars + pbo, warp, code);
            }
            tbl += 4;
            so = wrap ? 0 : so + SLOT_BYTES;
            bo = nbo;
            par = npar;
        }
    }
}

template <bool SCALED, int K0 = 0, int K1 = 3>
__device__ __forceinline__ void gelu_sq(uint32_t (&d)[24], uint32_t (&keep)[24], uint32_t sq_addr, uint32_t scale2) {
    pin(d);
#pragma unroll
    for (int k = K0; k < K1; k++) {
        uint32_t hs[4];
        lds128(hs[0], hs[1], hs[2], hs[3], sq_addr + k * SQ_ROW);
#pragma unroll
        for (int q = 0; q < 4; q++) {
            uint32_t g0 = gelu2(d[8 * k + 2 * q]), g1 = gelu2(d[8 * k + 2 * q + 1]);
            keep[8 * k + 2 * q] = g0;
            keep[8 * k + 2 * q + 1] = g1;
            if (SCALED) { g0 = h_mul(g0, scale2); g1 = h_mul(g1, scale2); }
            hs[q] = h_fma(g1, g1, h_fma(g0, g0, hs[q]));
        }
        sts128(sq_addr + k * SQ_ROW, hs[0], hs[1], hs[2], hs[3]);
    }
}
__device__ __forceinline__ void anchor(uint32_t addr, uint32_t a, uint32_t b, uint32_t c, uint32_t d) {
    asm volatile("{\n.reg .pred p;\nsetp.eq.b32 p, %0, 0;\n@p st.shared.v4.u32 [%0], {%1, %2, %3, %4};\n}\n"
                 ::"r"(addr), "r"(a), "r"(b), "r"(c), "r"(d) : "memory");
}
__device__ __forceinline__ void gelu_sq_reg(uint32_t (&d)[24], uint32_t (&hs)[12]) {
    pin(d);
#pragma unroll
    for (int q = 0; q < 12; q++) {
        const uint32_t g0 = gelu2(d[2 * q]), g1 = gelu2(d[2 * q + 1]);
        hs[q] = h_fma(g1, g1, h_fma(g0, g0, hs[q]));
    }
}
__device__ __forceinline__ void gelu_to(uint32_t (&g)[12], uint32_t (&d)[12]) {
    pin(d);
#pragma unroll
    for (int q = 0; q < 12; q++) g[q] = gelu2(d[q]);
    pin(g);
}
__device__ __forceinline__ void load_tile(uint32_t (&raw)[6][4], uint32_t addr) {
#pragma unroll
    for (int s = 0; s < 6; s++) ldsm4(raw[s], addr + s * 2 * A_LBO);
}
__device__ __forceinline__ uint2 ln_stats(const uint32_t (&raw)[6][4], uint64_t ones) {
    uint32_t sq[6][4];
#pragma unroll
    for (int s = 0; s < 6; s++)
#pragma unroll
        for (int q = 0; q < 4; q++) sq[s][q] = bf_mul(raw[s][q], raw[s][q]);
    float sum[4], ssq[4];
    wg_fence();
    wgmma_rowsum<0>(sum, raw[0], ones);
#pragma unroll
    for (int s = 1; s < 6; s++) wgmma_rowsum<1>(sum, raw[s], ones);
    wgmma_rowsum<0>(ssq, sq[0], ones);
#pragma unroll
    for (int s = 1; s < 6; s++) wgmma_rowsum<1>(ssq, sq[s], ones);
    wg_commit();
    wg_wait<0>();
    uint32_t st[2];
#pragma unroll
    for (int h = 0; h < 2; h++) {
        asm volatile("" : "+f"(sum[2 * h]), "+f"(ssq[2 * h])::"memory");
        const float mean = sum[2 * h] * (1.f / CH);
        const float var = fmaxf(fmaf(ssq[2 * h], 1.f / CH, -mean * mean), 0.f);
        float rstd;
        asm("rsqrt.approx.ftz.f32 %0, %1;" : "=f"(rstd) : "f"(var + 1e-5f));
        rstd = bf_lo(pack_bf2(rstd * (K_CVT == 0 ? KZ : KZ * 0x1p-112f), 0.f));
        st[h] = pack_bf2(rstd, -mean * rstd);
    }
    return make_uint2(st[0], st[1]);
}
__device__ __forceinline__ void ln_apply(uint32_t (&a)[6][4], const uint2& st) {
    const uint32_t sc[2] = {__byte_perm(st.x, 0, 0x1010), __byte_perm(st.y, 0, 0x1010)};
    const uint32_t sh[2] = {__byte_perm(st.x, 0, 0x3232), __byte_perm(st.y, 0, 0x3232)};
#pragma unroll
    for (int s = 0; s < 6; s++)
#pragma unroll
        for (int q = 0; q < 4; q++) {
            const uint32_t v = bf_fma(a[s][q], sc[q & 1], sh[q & 1]);
            a[s][q] = K_CVT == 0 ? pack_h2(bf_lo(v), bf_hi(v)) : (v & 0x7fff7fffu) * 7u + v;
        }
}
struct Cursor {
    int slot;
    uint32_t par;
    __device__ __forceinline__ void advance(int n) {
        slot += n;
        if (slot >= NSLOT) { slot -= NSLOT; par ^= 1; }
    }
};
struct Descs {
    uint64_t w1[8][6];
    uint64_t w2[24];
    uint64_t ones;
};
template <int E0, int N>
__device__ __forceinline__ void gemm1_chunk(uint32_t (&d)[N], const uint32_t (&a)[6][4], const Descs& ds, int zero) {
#pragma unroll
    for (int s = 0; s < 6; s++) wgmma(d, a[s][0], a[s][1], a[s][2], a[s][3], ds.w1[E0 / 48][s], s ? 1 : zero);
}
template <int E0, int N>
__device__ __forceinline__ void gemm2_chunk(uint32_t (&acc)[24], const uint32_t (&g)[N], const Descs& ds) {
#pragma unroll
    for (int s = 0; s < N / 4; s++) wgmma(acc, g[4 * s], g[4 * s + 1], g[4 * s + 2], g[4 * s + 3], ds.w2[E0 / 16 + s], 1);
}

__global__ void __launch_bounds__(NTHREADS, 1)
block_kernel(const __grid_constant__ CUtensorMap tmap, const __grid_constant__ CUtensorMap tmap_w1,
             const __nv_bfloat16* __restrict__ x, const __nv_bfloat16* __restrict__ dw, const __nv_bfloat16* __restrict__ w2,
             const __nv_bfloat16* __restrict__ gamma, const __nv_bfloat16* __restrict__ beta, __nv_bfloat16* __restrict__ out,
             Scratch* __restrict__ sc, const __grid_constant__ Descs ds,
             const int zero, const int per_cta, const int extra, const int lenders) {
    extern __shared__ __align__(1024) uint8_t smem[];
    constexpr uint32_t sb = SB;
    const int tid = threadIdx.x;
    const Work wk = get_work(per_cta, extra, lenders);
    if (smem_u32(smem) != SB || wk.rows + 4 > MAX_ROWS) __trap();
    constexpr uint32_t s_red = sb + SM_RED;

    PROF(0);
    const int warp_id = __shfl_sync(~0u, tid >> 5, 0);
    if (warp_id < 4 && elect_one()) first_loads(wk, &tmap, &tmap_w1, dw, sb, warp_id);
    __syncwarp();
    const int cw = warp_id - 4, wgi = cw >> 2, w4 = warp_id & 3;
    const int ntiles = wk.nA + wk.nB;
    const int wg = warp_id >> 2;
    int first = wg;
    uint32_t a[6][4], tile_off, next_off, stage, inv_rho2 = 0, rpar = 0, bias_addr, lane16, lane_off;
    auto set_lane = [&](uint32_t lane) {
        bias_addr = sb + SM_BIASH + (lane & 3) * 96;
        lane16 = lane * 16;
        lane_off = ((lane >> 2) * CH + 8 * (lane & 3)) * 2;
    };
    const uint32_t bar_r = sb + BAR_R + warp_id * 8;
    auto load_bias = [&](uint32_t (&acc)[24]) {
#pragma unroll
        for (int q = 0; q < 6; q++) lds128(acc[4 * q], acc[4 * q + 1], acc[4 * q + 2], acc[4 * q + 3], bias_addr + q * 16);
    };
    auto load_frags = [&](bool on) {
#pragma unroll
        for (int s = 0; s < 6; s++) ldg128_if(on, a[s], reinterpret_cast<const char*>(out) + next_off + w4 * WARP_BYTES + lane16 + s * 512);
    };
    auto stage_x = [&]() {
        if (elect_one()) {
            mbar_expect_tx(bar_r, WARP_BYTES);
            bulk_load_stream(stage, reinterpret_cast<const char*>(x) + tile_off + w4 * WARP_BYTES, WARP_BYTES, bar_r);
        }
    };
    auto epilogue = [&](uint32_t (&acc)[24]) {
        pin(acc);
        rpar ^= 1;
        uint4* op = reinterpret_cast<uint4*>(reinterpret_cast<char*>(out) + tile_off + w4 * WARP_BYTES + lane_off);
#pragma unroll
        for (int h = 0; h < 2; h++)
#pragma unroll
            for (int m = 0; m < 3; m++) {
                uint32_t xin[4], o[4];
                lds128(xin[0], xin[1], xin[2], xin[3], stage + lane_off + h * 1536 + m * 64);
#pragma unroll
                for (int q = 0; q < 4; q++) {
                    const uint32_t v = acc[2 * (4 * m + q) + h];
                    o[q] = bf_fma(pack_bf2(h_lo(v), h_hi(v)), inv_rho2, xin[q]);
                }
                __stcs(op + h * 96 + m * 4, make_uint4(o[0], o[1], o[2], o[3]));
            }
        __syncwarp();
    };
    auto max_w1 = [&]() {
        float m = 0.f;
#pragma unroll
        for (int q = 0; q < 3; q++) {
            uint32_t u[4];
            lds128(u[0], u[1], u[2], u[3], s_red + q * 16);
#pragma unroll
            for (int k = 0; k < 4; k++) m = fmaxf(m, __uint_as_float(u[k]));
        }
        return m;
    };
    auto square_exp = [&](float w1max) {
        const int e = w1max > 0.f ? 4 - ilog2f(2.f * KZ * 96.f * w1max) : 0;
        return (e >= 0 && e <= 6) ? 0 : max(-14, min(e, 14));
    };
    const int last_wg = (ntiles - 1 - wk.lent) % NCONS;
    auto reduce = [&](int q, uint32_t lane, bool leader) {
        const int t = lane & 3, part = lane >> 2;
        const float w1max = max_w1();
        const int sq_e = square_exp(w1max);
        const float to_fixed = pow2i(sum_exp(w1max) - 2 * sq_e);
        unsigned long long* dst = sc->sum(__float_as_uint(ldsf(s_red + 48)), 32 * q + 8 * (part >> 1) + 2 * t + (part & 1));
        named_bar(11, CONS_THREADS);
        const unsigned in_piece = 32 * q + 8 * (part >> 1) + 2 * t + (part & 1) - (blockIdx.x - lenders) % 8 * 48;
        const float helped = in_piece < 48 ? ldsf(sb + SM_BIASH + in_piece * 4) * pow2i(2 * sq_e) : 0.f;
        float f[8] = {};
#pragma unroll 1
        for (int i = 0; i < NCONS; i++) {
            const int src_wg = (last_wg + 1 + i) % NCONS;
            if (i == NCONS - 1) {
                named_bar(13, CONS_THREADS);
                if (leader) {
                    fence_async();
#pragma unroll
                    for (int k = 1; k < NCONS; k++) {
                        const int o = (last_wg + k) % NCONS * SQ_WG;
                        bulk_load(sb + SM_W2 + o, reinterpret_cast<const char*>(sc->w2h) + o, SQ_WG, sb + BAR_W);
                    }
                }
                __syncwarp();
                named_bar(14, NTHREADS);
            }
            const uint32_t upper = sq_e ? SM_SQ + (NCONS + src_wg) * SQ_WG : SM_RING + (wk.rows + i) % NSLOT * SLOT_BYTES;
            const uint32_t src = sb + lane * 16 + (q < 6 ? SM_SQ + src_wg * SQ_WG + q * SQ_ROW : upper + (q - 6) * SQ_ROW);
#pragma unroll
            for (int r = 0; r < 4; r++) {
                uint32_t u[4];
                lds128(u[0], u[1], u[2], u[3], src + r * 512);
#pragma unroll
                for (int k = 0; k < 4; k++) { f[2 * k] += h_lo(u[k]); f[2 * k + 1] += h_hi(u[k]); }
            }
        }
        const bool b2 = part & 4, b1 = part & 2, b0 = part & 1;
        float r4[4], r2[2];
#pragma unroll
        for (int k = 0; k < 4; k++) r4[k] = (b2 ? f[k + 4] : f[k]) + __shfl_xor_sync(~0u, b2 ? f[k] : f[k + 4], 16);
#pragma unroll
        for (int k = 0; k < 2; k++) r2[k] = (b1 ? r4[k + 2] : r4[k]) + __shfl_xor_sync(~0u, b1 ? r4[k] : r4[k + 2], 8);
        const float tot = (b0 ? r2[1] : r2[0]) + __shfl_xor_sync(~0u, b0 ? r2[0] : r2[1], 4);
        atomicAdd(dst, __float2ull_rn(fminf((tot + helped) * to_fixed, 0x1p47f)) << 8 | 1);
    };
    const uint32_t s_fac = sb + SM_RING + (wk.rows + 1) % NSLOT * SLOT_BYTES + SQ_WG;
    if (warp_id < 4) {
        conv_producer(wk, &tmap, sc, sb, warp_id);
        const int lane = opaque(tid & 31), g = lane >> 2, t = lane & 3;
        const unsigned epoch = __float_as_uint(ldsf(s_red + 48));
        set_lane(lane);
#pragma unroll 1
        for (int q = gridDim.x - 1 - blockIdx.x; q < W2_GROUPS; q += gridDim.x) {
            uint32_t u[3], rmax = 0;
#pragma unroll
            for (int m = 0; m < 3; m++) {
                const uint4 w = ldg128_ordered(w2 + (8 * q + g) * CH + 32 * m + 8 * t);
                rmax = bf_absmax(bf_absmax(rmax, bf_absmax(w.x, w.y)), bf_absmax(w.z, w.w));
                u[m] = w4 & 2 ? (w4 & 1 ? w.w : w.z) : (w4 & 1 ? w.y : w.x);
            }
            const float bt = __bfloat162float(beta[8 * q + g]);
            rmax = bf_absmax(rmax, __shfl_xor_sync(~0u, rmax, 1));
            rmax = bf_absmax(rmax, __shfl_xor_sync(~0u, rmax, 2));
            const float mx = fmaxf(fabsf(bf_lo(rmax)), fabsf(bf_hi(rmax))), rs = row_scale(mx);
            if (t == 0 && w4 == 0) sc->w2max[8 * q + g] = mx;
#pragma unroll
            for (int m = 0; m < 3; m++) {
                float lo = bf_lo(u[m]), hi = bf_hi(u[m]);
                sc->w2h[(4 * m + w4) * 1536 + q * 32 + lane] = transpose8x8(pack_h2(lo * rs, hi * rs));
                lo *= bt; hi *= bt;
#pragma unroll
                for (int o = 4; o <= 16; o <<= 1) { lo += __shfl_xor_sync(~0u, lo, o); hi += __shfl_xor_sync(~0u, hi, o); }
                if (g == 0) {
                    float* dst = &sc->bias[epoch & 1][32 * m + 8 * t + 2 * w4];
                    asm volatile("red.global.add.v2.f32 [%0], {%1, %2};" ::"l"(dst), "f"(lo), "f"(hi) : "memory");
                }
            }
            asm volatile("fence.proxy.async.global;" ::: "memory");
            signal(&sc->prep);
        }
#pragma unroll
        for (int s = 0; s < 6; s++) a[s][0] = a[s][1] = a[s][2] = a[s][3] = 0;
        const unsigned piece = blockIdx.x - lenders;
        if (piece < 8 * LENT * lenders) {
            spin_until(&sc->lent_in, (epoch + 1) * 4 * lenders);
            next_off = tile_offset(piece / (8 * LENT) * (per_cta + 1) + piece / 8 % LENT);
            load_frags(true);
            uint32_t d[12], gl[12];
            wg_fence();
#pragma unroll
            for (int s = 0; s < 6; s++) wgmma(d, a[s][0], a[s][1], a[s][2], a[s][3], ds.w1[0][s] + piece % 8 * (6 * 1536 / 16), s ? 1 : 0);
            wg_commit();
            wg_wait<0>();
            gelu_to(gl, d);
#pragma unroll
            for (int s = 0; s < 3; s++) sc->lent[((piece * 4 + w4) * 3 + s) * 32 + lane] = make_uint4(gl[4 * s], gl[4 * s + 1], gl[4 * s + 2], gl[4 * s + 3]);
            float f[6], r[3];
#pragma unroll
            for (int j = 0; j < 6; j++) {
                const float lo = fmaf(h_lo(gl[2 * j]), h_lo(gl[2 * j]), h_lo(gl[2 * j + 1]) * h_lo(gl[2 * j + 1]));
                const float hi = fmaf(h_hi(gl[2 * j]), h_hi(gl[2 * j]), h_hi(gl[2 * j + 1]) * h_hi(gl[2 * j + 1]));
                f[j] = (g & 1 ? hi : lo) + __shfl_xor_sync(~0u, g & 1 ? lo : hi, 4);
            }
#pragma unroll
            for (int j = 0; j < 3; j++) {
                r[j] = (g & 2 ? f[j + 3] : f[j]) + __shfl_xor_sync(~0u, g & 2 ? f[j] : f[j + 3], 8);
                asm volatile("red.shared.add.f32 [%0], %1;" ::"r"(sb + SM_BIASH + (8 * j + 12 * (g & 2) + 2 * t + (g & 1)) * 4), "f"(r[j]) : "memory");
            }
        }
        if (piece < 8 * LENT * lenders) signal(&sc->lent_out);
        const bool leader = warp_id == 0 && lane == 0;
        const float w1max = max_w1();
        const bool plain = square_exp(w1max) == 0;
        auto load_upper = [&]() {
            bulk_load(sb + SM_W2 + NCONS * SQ_WG, reinterpret_cast<const char*>(sc->w2h) + NCONS * SQ_WG, EX * CH * 2 - NCONS * SQ_WG, sb + BAR_W);
        };
        if (leader) {
            spin_until(&sc->prep, (epoch + 1) * 4 * W2_GROUPS);
            asm volatile("fence.proxy.async.global;" ::: "memory");
            fence_async();
            mbar_expect_tx(sb + BAR_W, EX * CH * 2);
            if (plain) load_upper();
        }
        __syncwarp();
        named_bar(1, 128);
        const int i0 = w4 * 32 + lane;
        float gam[3], rmax[3];
#pragma unroll
        for (int m = 0; m < 3; m++) { gam[m] = __bfloat162float(gamma[i0 + 128 * m]); rmax[m] = __ldcg(&sc->w2max[i0 + 128 * m]); }
        float2 bpair = make_float2(0.f, 0.f);
        if (i0 < 96) bpair = __ldcg(reinterpret_cast<const float2*>(&sc->bias[epoch & 1][32 * (i0 % 24 >> 3) + 8 * (i0 / 24) + (i0 % 24 & 6)]));
        const float gbound = fmaxf(2.f * KZ * 9.7979590f * 192.f * w1max, 1.f) * 19.5959180f * INV_2KZ;
        const unsigned fixed = __reduce_max_sync(~0u, __float_as_uint(fmaf(gbound, fmaxf(fmaxf(rmax[0], rmax[1]), rmax[2]), fmaxf(fabsf(bpair.x), fabsf(bpair.y)))));
        if (lane == 0) sts32(s_red + 96 + w4 * 4, fixed);
        reduce(4 * last_wg + w4, lane, leader);
        PROF(2);
        named_bar(15, CONS_THREADS);
        if (leader) {
            fence_async();
            bulk_load(sb + SM_W2 + last_wg * SQ_WG, reinterpret_cast<const char*>(sc->w2h) + last_wg * SQ_WG, SQ_WG, sb + BAR_W);
            if (!plain) load_upper();
        }
        stage = sb + SM_RING + (wk.rows % NSLOT) * SLOT_BYTES + w4 * REGION_BYTES;
        auto grn = [&]() {
            auto peek = [&](int e) {
                unsigned long long v;
                asm volatile("ld.relaxed.gpu.global.u64 %0, [%1];" : "=l"(v) : "l"(sc->sum(epoch, e)) : "memory");
                return v;
            };
            unsigned n = 0;
            while (((unsigned)peek((blockIdx.x * 4 + w4) % (EX / 4) * 4) & 255u) != gridDim.x)
                if (++n > SPIN_LIMIT) __trap();
            unsigned long long sum[3];
            for (;;) {
                bool all = true;
#pragma unroll
                for (int m = 0; m < 3; m++) {
                    sum[m] = peek(i0 + 128 * m);
                    all &= ((unsigned)sum[m] & 255u) == gridDim.x;
                }
                if (__all_sync(~0u, all)) break;
                if (++n > SPIN_LIMIT) __trap();
            }
            PROF(3);
            if (blockIdx.x == 0 && leader) sc->launch = epoch + 1;
            float gx[3], tot = 0.f, vary = 0.f;
#pragma unroll
            for (int m = 0; m < 3; m++) {
                gx[m] = grn_norm(__ull2float_rn(sum[m] >> 8) * pow2i(-sum_exp(w1max)));
                tot += gx[m];
                vary = fmaxf(vary, fabsf(gam[m]) * gx[m] * rmax[m]);
            }
#pragma unroll
            for (int o = 16; o >= 1; o >>= 1) tot += __shfl_xor_sync(~0u, tot, o);
            const unsigned vwarp = __reduce_max_sync(~0u, __float_as_uint(vary));
            if (lane == 0) { sts32(s_red + 64 + w4 * 4, __float_as_uint(tot)); sts32(s_red + 80 + w4 * 4, vwarp); }
            named_bar(1, 128);
            uint32_t u[4], v[4], w[4];
            lds128(u[0], u[1], u[2], u[3], s_red + 64);
            lds128(v[0], v[1], v[2], v[3], s_red + 80);
            lds128(w[0], w[1], w[2], w[3], s_red + 96);
            tot = (__uint_as_float(u[0]) + __uint_as_float(u[1])) + (__uint_as_float(u[2]) + __uint_as_float(u[3]));
            const float vmax = __uint_as_float(max(max(v[0], v[1]), max(v[2], v[3]))), fmax2 = __uint_as_float(max(max(w[0], w[1]), max(w[2], w[3])));
            const float inv_mean = __fdividef(1.f, tot * (1.f / EX) + 1e-6f);
            const float bound = fmaf(gbound * vmax, inv_mean, 2.f * fmax2);
            const int rho_e = bound > 0.f ? 14 - ilog2f(bound) : 0;
            const float rho = pow2i(rho_e), inv_rho = pow2i(-rho_e);
            inv_rho2 = pack_bf2(inv_rho, inv_rho);
#pragma unroll
            for (int m = 0; m < 3; m++) {
                const float f = __fdividef(fmaf(gam[m], gx[m] * inv_mean, 1.f) * INV_2KZ * rho, row_scale(rmax[m]));
                asm volatile("st.shared.u16 [%0], %1;" ::"r"(s_fac + (i0 + 128 * m) * 2), "h"((unsigned short)pack_h2(f, 0.f)) : "memory");
            }
            if (i0 < 96) sts32(sb + SM_BIASH + i0 * 4, pack_h2(bpair.x * rho, bpair.y * rho));
            if (i0 == 96) sts32(s_red + 52, inv_rho2);
            named_arrive(12, NTHREADS);
        };
        uint32_t gl[4][12] = {};
        const uint4* src = &sc->lent[(blockIdx.x * LENT * 8 * 4 + w4) * 96 + lane];
        auto fetch = [&](uint32_t (&v)[12], int c, bool on) {
#pragma unroll
            for (int s = 0; s < 3; s++) ldg128_if(on, reinterpret_cast<uint32_t (&)[4]>(v[4 * s]), src + c * 384 + s * 32);
        };
        if (__builtin_expect(wk.lent, 0)) {
            first = 4;
            tile_off = tile_offset(wk.tA);
            stage_x();
            if (elect_one()) prefetch_l2(reinterpret_cast<const char*>(x) + tile_offset(wk.tA + 1) + w4 * WARP_BYTES, WARP_BYTES);
            spin_until(&sc->lent_out, (epoch + 1) * 32 * LENT * lenders);
#pragma unroll
            for (int c = 0; c < 3; c++) fetch(gl[c], c, true);
        }
        lds32(next_off, sb + SM_TILES + first * 4);
        load_frags(true);
        grn();
        if (__builtin_expect(wk.lent, 0)) {
            named_bar(3, NTHREADS);
#pragma unroll 1
            for (int e = 0; e < LENT; e++) {
                uint32_t acc[24];
                load_bias(acc);
#define CNX_LENT(C)                                  \
    pin(gl[C % 4]);                                  \
    wg_fence();                                      \
    gemm2_chunk<48 * C>(acc, gl[C % 4], ds);         \
    wg_commit();                                     \
    wg_wait<(C < 7 ? 1 : 0)>();                      \
    fetch(gl[(C + 3) % 4], C + 3, C < 5 || e == 0);  \
    if (lane == 0) mbar_arrive(sb + BAR_PIN);
                CNX_LENT(0) CNX_LENT(1) CNX_LENT(2) CNX_LENT(3) CNX_LENT(4) CNX_LENT(5) CNX_LENT(6) CNX_LENT(7)
#undef CNX_LENT
                src += 8 * 384;
                mbar_wait(bar_r, rpar);
                epilogue(acc);
                tile_off = tile_offset(wk.tA + 1);
                if (e == 0) stage_x();
            }
        }
    } else {
        {
            const int ct = tid - 128, lane = tid & 31;
            const unsigned epoch = *reinterpret_cast<volatile unsigned*>(&sc->launch);
            const int r = lane & 7, mi = lane >> 3;
            const uint32_t src = sb + SM_W2 + (cw >> 1) * (64 * CH * 2) + r * 128 + ((((cw & 1) * 4 + mi) ^ r) * 16);
            const uint32_t dst = sb + SM_W1 + (4 * cw + mi) * 1536 + r * 16;
            named_bar(0, NTHREADS);
            mbar_wait(sb + BAR_W + (cw >> 1) * 8, 0);
            uint32_t wmax[4] = {}, wsum[4] = {};
#pragma unroll 3
            for (int c = 0; c < 12; c++) {
                uint32_t u[4];
                ldsm4_t(u, src + c * 1024);
#pragma unroll
                for (int q = 0; q < 4; q++) {
                    wmax[q] = bf_absmax(wmax[q], u[q]);
                    wsum[q] = bf_fma(u[q], 0x3f803f80u, wsum[q]);
                    u[q] = pack_h2(bf_lo(u[q]), bf_hi(u[q]));
                }
                stsm4(dst + c * 128, u[0], u[1], u[2], u[3]);
            }
            float mean[4];
            bool center = false;
#pragma unroll
            for (int q = 0; q < 4; q++) {
                uint32_t m = wmax[q];
                float sum = bf_lo(wsum[q]) + bf_hi(wsum[q]);
#pragma unroll
                for (int o = 1; o <= 2; o <<= 1) { m = bf_absmax(m, __shfl_xor_sync(~0u, m, o)); sum += __shfl_xor_sync(~0u, sum, o); }
                mean[q] = sum * (1.f / CH);
                center |= fabsf(mean[q]) > 0.2f * fmaxf(fabsf(bf_lo(m)), fabsf(bf_hi(m)));
            }
            if (__builtin_expect(__any_sync(~0u, center), 0)) {
#pragma unroll 1
                for (int pass = 0; pass < 2; pass++) {
                    float sum[4] = {};
#pragma unroll 1
                    for (int c = 0; c < 12; c++) {
                        uint32_t u[4];
                        ldsm4_t(u, src + c * 1024);
#pragma unroll
                        for (int q = 0; q < 4; q++) {
                            sum[q] += bf_lo(u[q]) + bf_hi(u[q]);
                            u[q] = pack_h2(bf_lo(u[q]) - mean[q], bf_hi(u[q]) - mean[q]);
                        }
                        stsm4(dst + c * 128, u[0], u[1], u[2], u[3]);
                    }
#pragma unroll
                    for (int q = 0; q < 4; q++) {
                        sum[q] += __shfl_xor_sync(~0u, sum[q], 1);
                        sum[q] += __shfl_xor_sync(~0u, sum[q], 2);
                        mean[q] = sum[q] * (1.f / CH);
                    }
                }
            }
            const float w1max = warp_absmax(bf_absmax(bf_absmax(wmax[0], wmax[1]), bf_absmax(wmax[2], wmax[3])));
            if (lane == 0) sts32(s_red + cw * 4, __float_as_uint(w1max));
            if (ct < 32) sts32(sb + SM_ONES + ct * 4, 0x3f803f80u);
            if (ct < 48) sts32(sb + SM_BIASH + ct * 4, 0);
            if (blockIdx.x == 0) {
                *sc->sum(epoch + 1, ct) = 0;
                if (ct < CH) sc->bias[(epoch & 1) ^ 1][ct] = 0.f;
            }
            if (ct == 0) sts32(s_red + 48, epoch);
            fence_async();
            named_bar(2, CONS_THREADS);
#pragma unroll
            for (int q = 0; q < 12; q++) sts128(sb + SM_SQ + (wgi + q / 6 * NCONS) * SQ_WG + q % 6 * SQ_ROW + (ct & 127) * 16, 0, 0, 0, 0);
            mbar_wait(sb + BAR_A + w4 * 8 + 32, 0);
        }

        PROF(1);
        const uint32_t a_addr = opaque(sb + SM_RING + w4 * REGION_BYTES + ((tid >> 3) & 1) * A_SBO + ((tid >> 4) & 1) * A_LBO + (tid & 7) * 16);
        const uint32_t bar_a = sb + BAR_A + w4 * 8, bar_e = sb + BAR_E + w4 * 8;
        const uint32_t sq = opaque(sb + SM_SQ + wgi * SQ_WG + (tid & 127) * 16);
        const uint32_t sq_warp = sb + SM_SQ + wgi * SQ_WG + w4 * 512;
        uint32_t k1[24], k2[24], k3[24];
        constexpr int SQC = 3 * SQ_ROW;
        const int pass_to = 4 + (wgi == NCONS - 1 ? 0 : wgi + 1);
        auto store_frags = [&](const uint32_t (&a)[6][4], int j) {
            char* ap = reinterpret_cast<char*>(out) + (tile_offset(wk.tile(j)) + w4 * WARP_BYTES - sq_warp + sq);
#pragma unroll
            for (int s = 0; s < 6; s++) stg128(ap + s * 512, a[s]);
        };
        int jt = wgi < wk.lent ? wgi : wk.lent + wgi;
        Cursor cur = {2, 0};
        cur.advance(jt + (jt >= wk.nA ? 2 : 0));
        if (wgi == NCONS - 1) named_arrive(4, 256);
        for (;;) {
            const bool plain = __all_sync(~0u, square_exp(max_w1()) == 0);
            if (plain && jt >= wk.lent) {
                uint32_t hs2[12] = {}, hs3[12] = {};
#pragma unroll 1
                for (; jt + NCONS < ntiles; jt += NCONS) {
                    uint32_t a[6][4], d0[24], d1[24], unused[24];
#define AT(pos) \
    if (K_WAIT == pos) named_bar(4 + wgi, 256); \
    if (K_PASS == pos) named_arrive(pass_to, 256); \
    if (K_STG == pos) store_frags(a, jt); \
    if (K_REL == pos) { if (elect_one()) mbar_arrive(bar_e + cur.slot * 32); }
                    AT(20)
                    mbar_wait(bar_a + cur.slot * 32, cur.par);
                    load_tile(a, a_addr + cur.slot * SLOT_BYTES);
                    AT(21)
                    const uint2 st = ln_stats(a, ds.ones);
                    AT(0)
                    ln_apply(a, st);
                    AT(1)
                    wg_fence();
                    gemm1_chunk<0>(d0, a, ds, 0);
                    wg_commit();
                    gemm1_chunk<96>(d1, a, ds, 0);
                    wg_commit();
                    AT(2)
                    wg_wait<1>();
                    AT(3)
                    gelu_sq<false, 0, 1>(d0, unused, sq, 0);
                    AT(4)
                    gelu_sq<false, 1, 2>(d0, unused, sq, 0);
                    AT(5)
                    gelu_sq<false, 2, 3>(d0, unused, sq, 0);
                    AT(6)
                    wg_fence();
                    gemm1_chunk<192>(d0, a, ds, zero);
                    wg_commit();
                    AT(7)
                    wg_wait<1>();
                    gelu_sq<false, 0, 1>(d1, unused, sq + SQC, 0);
                    AT(8)
                    gelu_sq<false, 1, 3>(d1, unused, sq + SQC, 0);
                    AT(9)
                    wg_fence();
                    gemm1_chunk<288>(d1, a, ds, zero);
                    wg_commit();
                    AT(10)
                    wg_wait<1>();
                    gelu_sq_reg(d0, hs2);
                    if (K_ANCH < 3) anchor(sq, hs2[4 * (K_ANCH % 3)], hs2[4 * (K_ANCH % 3) + 1], hs2[4 * (K_ANCH % 3) + 2], hs2[4 * (K_ANCH % 3) + 3]);
                    wg_wait<0>();
                    AT(11)
                    gelu_sq_reg(d1, hs3);
#undef AT
                    cur.advance(NCONS + ((jt < wk.nA && jt + NCONS >= wk.nA) ? 2 : 0));
                }
                const uint32_t sq2 = sq - (SM_SQ + wgi * SQ_WG) + SM_RING + (cur.slot + 3) % NSLOT * SLOT_BYTES;
#pragma unroll
                for (int k = 0; k < 3; k++) {
                    sts128(sq2 + k * SQ_ROW, hs2[4 * k], hs2[4 * k + 1], hs2[4 * k + 2], hs2[4 * k + 3]);
                    sts128(sq2 + SQC + k * SQ_ROW, hs3[4 * k], hs3[4 * k + 1], hs3[4 * k + 2], hs3[4 * k + 3]);
                }
            }
            const bool last = jt + NCONS >= ntiles;
            uint32_t a[6][4], d0[24], d1[24], d3[24], k0[24];
#define AT(pos) \
    if (K_WAIT == pos && jt >= wk.lent) named_bar(4 + wgi, 256); \
    if (K_PASS == pos && jt >= wk.lent && jt + 1 < ntiles) named_arrive(pass_to, 256);
            AT(20)
            mbar_wait(bar_a + cur.slot * 32, cur.par);
            load_tile(a, a_addr + cur.slot * SLOT_BYTES);
            AT(21)
            const uint2 st = ln_stats(a, ds.ones);
            AT(0)
            ln_apply(a, st);
            AT(1)
            if (!last) {
                store_frags(a, jt);
                __syncwarp();
                if (elect_one()) mbar_arrive(bar_e + cur.slot * 32);
                if (jt < wk.lent) {
                    jt += LENT;
                    cur.advance(LENT);
                    continue;
                }
            }
            wg_fence();
            gemm1_chunk<0>(d0, a, ds, 0);
            wg_commit();
            gemm1_chunk<96>(d1, a, ds, 0);
            wg_commit();
            const int sq_e = square_exp(max_w1());
            const uint32_t scale2 = pack_h2(pow2i(sq_e), pow2i(sq_e));
            stage = sb + SM_RING + cur.slot * SLOT_BYTES + w4 * REGION_BYTES;
            AT(2)
            wg_wait<1>();
            AT(3)
            gelu_sq<true, 0, 1>(d0, k0, sq, scale2);
            AT(4)
            gelu_sq<true, 1, 2>(d0, k0, sq, scale2);
            AT(5)
            gelu_sq<true, 2, 3>(d0, k0, sq, scale2);
            AT(6)
            if (last) {
#pragma unroll
                for (int q = 0; q < 6; q++) sts128(stage - sq_warp + sq + q * 512, k0[4 * q], k0[4 * q + 1], k0[4 * q + 2], k0[4 * q + 3]);
            }
            wg_fence();
            gemm1_chunk<192>(d0, a, ds, zero);
            wg_commit();
            AT(7)
            wg_wait<1>();
            gelu_sq<true, 0, 1>(d1, k1, sq + SQC, scale2);
            AT(8)
            gelu_sq<true, 1, 3>(d1, k1, sq + SQC, scale2);
            AT(9)
#undef AT
            wg_fence();
            gemm1_chunk<288>(d3, a, ds, 0);
            wg_commit();
            wg_wait<1>();
            const uint32_t sq2 = sq + (plain ? SM_RING + (cur.slot + 3) % NSLOT * SLOT_BYTES - (SM_SQ + wgi * SQ_WG) : NCONS * SQ_WG);
            gelu_sq<true>(d0, k2, sq2, scale2);
            wg_wait<0>();
            gelu_sq<true>(d3, k3, sq2 + SQC, scale2);
            if (last) break;
            cur.advance(NCONS + ((jt < wk.nA && jt + NCONS >= wk.nA) ? 2 : 0));
            jt += NCONS;
        }
        {
            if (wgi == last_wg) {
                named_arrive(14, NTHREADS);
            } else {
                reduce(cw, (sq >> 4) & 31, false);
                named_arrive(15, CONS_THREADS);
            }
        }
        PROF(2);
        tile_off = tile_offset(wk.tile(jt));
        {
            set_lane((sq >> 4) & 31);
            if (elect_one()) prefetch_l2(reinterpret_cast<const char*>(x) + tile_off + w4 * WARP_BYTES, WARP_BYTES);
            const uint32_t row = sb + SM_W2 + cw * 512 + lane16;
            uint32_t u[W2_EARLY][4], f2[4];
            mbar_wait(sb + BAR_W, 1);
#pragma unroll
            for (int nb = 0; nb < W2_EARLY; nb++) lds128(u[nb][0], u[nb][1], u[nb][2], u[nb][3], row + nb * 6144);
            named_bar(12, NTHREADS);
            PROF(3);
            lds128(f2[0], f2[1], f2[2], f2[3], s_fac + cw * 64 + (lane16 >> 7) * 16);
            lds32(inv_rho2, s_red + 52);
#pragma unroll
            for (int nb = 0; nb < 12; nb++) {
                uint32_t v[4];
                if (nb < W2_EARLY) { v[0] = u[nb % W2_EARLY][0]; v[1] = u[nb % W2_EARLY][1]; v[2] = u[nb % W2_EARLY][2]; v[3] = u[nb % W2_EARLY][3]; }
                else lds128(v[0], v[1], v[2], v[3], row + nb * 6144);
                sts128(row + nb * 6144, h_round8(h_mul(v[0], f2[0])), h_round8(h_mul(v[1], f2[1])), h_round8(h_mul(v[2], f2[2])), h_round8(h_mul(v[3], f2[3])));
            }
            fence_async();
            named_bar(3, NTHREADS);
        }
        PROF(4);
        {
            uint32_t acc[24];
            load_bias(acc);
            lds32(next_off, sb + SM_TILES + wg * 4);
            if (wgi > 0) named_bar(8 + wgi, 256);
            pin(k1); pin(k2); pin(k3);
            wg_fence();
            gemm2_chunk<288>(acc, k3, ds);
            wg_commit();
            gemm2_chunk<96>(acc, k1, ds);
            gemm2_chunk<192>(acc, k2, ds);
            wg_commit();
            if (wgi + 1 < NCONS) named_arrive(9 + wgi, 256);
            wg_wait<1>();
            uint32_t k0[24];
#pragma unroll
            for (int q = 0; q < 6; q++) lds128(k0[4 * q], k0[4 * q + 1], k0[4 * q + 2], k0[4 * q + 3], stage + lane16 + q * 512);
            pin(k0);
            wg_fence();
            gemm2_chunk<0>(acc, k0, ds);
            wg_commit();
            stage_x();
            wg_wait<1>();
            load_frags(true);
            if (lane16 == 0) mbar_arrive(sb + BAR_PIN);
            mbar_wait(bar_r, rpar);
            wg_wait<0>();
            epilogue(acc);
        }
    }
    {
        const int nrest = ntiles - NCONS - wk.lent / 2;
        for (int jt = first; jt < nrest; jt += 4) {
            uint32_t d0[12], d1[12], g0[12], g1[12], acc[24];
            tile_off = next_off;
            lds32(next_off, sb + SM_TILES + (jt + 4) * 4);
            if (jt >= S2_FIRST) named_bar(4 + wg, 256);
            wg_fence();
            gemm1_chunk<0>(d0, a, ds, 0);
            wg_commit();
            gemm1_chunk<48>(d1, a, ds, 0);
            wg_commit();
            load_bias(acc);
            const bool more = jt + 4 < nrest;
            tile_off = __shfl_sync(~0u, tile_off, 0);
            next_off = __shfl_sync(~0u, next_off, 0);
            wg_wait<1>();
#define CNX_PASS if (jt + 1 >= S2_FIRST && jt + 1 < nrest) named_arrive(4 + ((wg + 1) & 3), 256);
#define CNX_STEP(C, D, G)                                              \
    gelu_to(G, D);                                                     \
    if (C == 0 && jt == 0) {                                           \
        named_bar(3, NTHREADS);                                        \
        load_bias(acc);                                                \
    }                                                                  \
    wg_fence();                                                        \
    if (C < 6) gemm1_chunk<48 * (C < 6 ? C + 2 : 0)>(D, a, ds, zero); \
    gemm2_chunk<48 * C>(acc, G, ds);                                  \
    wg_commit();                                                       \
    if (C == S2_PASS) { CNX_PASS }                                     \
    wg_wait<(C < 7 ? 1 : 0)>();
            CNX_STEP(0, d0, g0)
            stage_x();
            if (more && elect_one()) prefetch_l2(reinterpret_cast<const char*>(out) + next_off + w4 * WARP_BYTES, WARP_BYTES);
            CNX_STEP(1, d1, g1)
            CNX_STEP(2, d0, g0)
            CNX_STEP(3, d1, g1)
            CNX_STEP(4, d0, g0)
            CNX_STEP(5, d1, g1)
            CNX_STEP(6, d0, g0)
            load_frags(more);
            if (lane16 == 0) mbar_arrive(sb + BAR_PIN);
            mbar_wait(bar_r, rpar);
            CNX_STEP(7, d1, g1)
#undef CNX_STEP
            epilogue(acc);
        }
    }
    PROF(5);
}

}

typedef CUresult (*EncodeTiledFn)(CUtensorMap*, CUtensorMapDataType, cuuint32_t, void*, const cuuint64_t*, const cuuint64_t*,
                                  const cuuint32_t*, const cuuint32_t*, CUtensorMapInterleave, CUtensorMapSwizzle,
                                  CUtensorMapL2promotion, CUtensorMapFloatOOBfill);

extern "C" void kernel_launch(void* const* d_in, const int* in_sizes, int n_in, void* d_out, int out_size) {
    using namespace cnx;
    static EncodeTiledFn encode = nullptr;
    static int num_sms = 0;
    static Scratch* scratch = nullptr;
    if (!encode) {
        void* fn = nullptr;
        cudaDriverEntryPointQueryResult qr;
        cudaGetDriverEntryPoint("cuTensorMapEncodeTiled", &fn, cudaEnableDefault, &qr);
        encode = (EncodeTiledFn)fn;
        cudaGetSymbolAddress((void**)&scratch, g_scratch);
        int dev = 0;
        cudaGetDevice(&dev);
        cudaDeviceGetAttribute(&num_sms, cudaDevAttrMultiProcessorCount, dev);
        if (num_sms > MAX_CTAS) num_sms = MAX_CTAS;
        cudaFuncSetAttribute(block_kernel, cudaFuncAttributeMaxDynamicSharedMemorySize, SM_TOTAL);
    }
    CUtensorMap tm;
    cuuint64_t dims[3] = {(cuuint64_t)CH, (cuuint64_t)IMG_W, (cuuint64_t)IMG_H};
    cuuint64_t strides[2] = {(cuuint64_t)CH * 2, (cuuint64_t)CH * 2 * IMG_W};
    cuuint32_t box[3] = {(cuuint32_t)CH, (cuuint32_t)REGION_PX, 1};
    cuuint32_t estr[3] = {1, 1, 1};
    encode(&tm, CU_TENSOR_MAP_DATA_TYPE_BFLOAT16, 3, d_in[0], dims, strides, box, estr, CU_TENSOR_MAP_INTERLEAVE_NONE,
           CU_TENSOR_MAP_SWIZZLE_NONE, CU_TENSOR_MAP_L2_PROMOTION_L2_128B, CU_TENSOR_MAP_FLOAT_OOB_FILL_NONE);
    Descs ds;
    for (int c = 0; c < 8; c++)
        for (int k = 0; k < 6; k++) ds.w1[c][k] = make_desc(SB + SM_W1 + c * 6 * 1536 + k * 256, 128, 1536);
    for (int k = 0; k < 24; k++) ds.w2[k] = make_desc(SB + SM_W2 + k * 256, 128, 6144);
    ds.ones = make_desc(SB + SM_ONES, 0, 0);
    CUtensorMap tw;
    cuuint64_t wdims[2] = {(cuuint64_t)EX, (cuuint64_t)CH};
    cuuint64_t wstrides[1] = {(cuuint64_t)EX * 2};
    cuuint32_t wbox[2] = {64, (cuuint32_t)CH};
    encode(&tw, CU_TENSOR_MAP_DATA_TYPE_BFLOAT16, 2, d_in[2], wdims, wstrides, wbox, estr, CU_TENSOR_MAP_INTERLEAVE_NONE,
           CU_TENSOR_MAP_SWIZZLE_128B, CU_TENSOR_MAP_L2_PROMOTION_L2_128B, CU_TENSOR_MAP_FLOAT_OOB_FILL_NONE);
    const int per_cta = NTILES / num_sms, extra = NTILES % num_sms;
    const int lenders = extra * (8 * LENT + 1) <= num_sms && extra * (per_cta + 1) <= IMG_H ? extra : 0;
    block_kernel<<<num_sms, NTHREADS, SM_TOTAL>>>(tm, tw, (const __nv_bfloat16*)d_in[0], (const __nv_bfloat16*)d_in[1],
                                             (const __nv_bfloat16*)d_in[3],
                                             (const __nv_bfloat16*)d_in[4], (const __nv_bfloat16*)d_in[5], (__nv_bfloat16*)d_out,
                                             scratch, ds, 0, per_cta, extra, lenders);
}
```

```cpp
#include <cuda_runtime.h>
#include <cuda_bf16.h>
#include <cuda_fp16.h>
#include <cuda.h>
#include <stdint.h>

namespace cnx {

constexpr int IMG_H = 512, IMG_W = 512, CH = 96, EX = 384;
constexpr int TILE_W = 64;
constexpr int NTILES = (IMG_W / TILE_W) * IMG_H;
constexpr int NSLOT = 6;
constexpr int REGION_PX = 18;
constexpr int REGION_BYTES = REGION_PX * CH * 2;
constexpr int SLOT_BYTES = 4 * REGION_BYTES;
constexpr int A_LBO = 144, A_SBO = 12 * A_LBO;
constexpr int PREFETCH_ROWS = 3;
constexpr int NCONS = 3;
constexpr int CONS_THREADS = 128 * NCONS;
constexpr int NTHREADS = 128 + CONS_THREADS;
constexpr int MAX_ROWS = 52;
constexpr int TILE_BYTES = TILE_W * CH * 2, WARP_BYTES = TILE_BYTES / 4;
constexpr int S1_PASS = 1, S2_PASS = 1;
#define K_PASS 4
#define K_WAIT 20
#define K_STG 6
#define K_REL 6
#define K_ANCH 2
#define K_CVT 0
#define W2_EARLY 6
#define S2_FIRST 4
#define ORDER_P 3
#define ORDER_Q 1
static_assert(MAX_ROWS <= 128, "one table entry per producer thread");
static_assert(2 * A_SBO == REGION_BYTES && REGION_BYTES % 128 == 0, "region layout");

constexpr uint32_t SB = 1024;
constexpr int SM_W1 = 0;
constexpr int SM_W2 = SM_W1 + CH * EX * 2;
constexpr int SM_RING = SM_W2 + CH * EX * 2;
constexpr int SM_BIASH = SM_RING + NSLOT * SLOT_BYTES;
constexpr int SM_RED = SM_BIASH + 384;
constexpr int SM_ROWS = SM_RED + 256;
constexpr int SM_TILES = SM_ROWS + MAX_ROWS * 4;
constexpr int SM_ONES = SM_TILES + MAX_ROWS * 4;
constexpr int SM_BAR = SM_ONES + 128;
constexpr int BAR_X = SM_BAR;
constexpr int BAR_A = BAR_X + NSLOT * 4 * 8;
constexpr int BAR_E = BAR_A + NSLOT * 4 * 8;
constexpr int BAR_PIN = BAR_E + NSLOT * 4 * 8;
constexpr int BAR_W = BAR_PIN + 8;
constexpr int BAR_R = BAR_W + 6 * 8;
constexpr int SM_TOTAL = BAR_R + 16 * 8;
constexpr int SM_SQ = SM_W2;
constexpr int SQ_ROW = 128 * 16, SQ_WG = 6 * SQ_ROW;
static_assert(SM_ONES % 16 == 0 && SM_TOTAL <= 232448, "shared memory budget");

constexpr float KZ = 0.3292034911525734f;
constexpr uint32_t GELU_C2 = 0x40d940d9u;
constexpr float INV_2KZ = 0.5f / KZ;
constexpr unsigned SPIN_LIMIT = 1u << 19;

constexpr int MAX_CTAS = 255;
constexpr int W2_GROUPS = EX / 8;
constexpr int LENT = 2, MAX_LENDERS = MAX_CTAS / (8 * LENT + 1);
struct Scratch {
    uint32_t w2h[EX * CH / 2];
    float w2max[EX];
    float bias[2][CH];
    unsigned long long sums[2][EX / 4][32];
    __device__ __forceinline__ unsigned long long* sum(unsigned launch, int e) { return &sums[launch & 1][e >> 2][e & 3]; }
    uint4 lent[MAX_LENDERS * LENT * 8 * 4 * 3 * 32];
    unsigned launch, pad0[31], prep, pad1[31], lent_in, pad2[31], lent_out, pad3[31];
};
__device__ __align__(128) Scratch g_scratch;

#define PROF(k)

__device__ __forceinline__ uint32_t smem_u32(const void* p) { return (uint32_t)__cvta_generic_to_shared(p); }
__device__ __forceinline__ void mbar_init(uint32_t bar, uint32_t cnt) {
    asm volatile("mbarrier.init.shared::cta.b64 [%0], %1;" ::"r"(bar), "r"(cnt) : "memory");
}
__device__ __forceinline__ void mbar_arrive(uint32_t bar) {
    asm volatile("mbarrier.arrive.shared::cta.b64 _, [%0];" ::"r"(bar) : "memory");
}
__device__ __forceinline__ void mbar_expect_tx(uint32_t bar, uint32_t bytes) {
    asm volatile("mbarrier.arrive.expect_tx.shared::cta.b64 _, [%0], %1;" ::"r"(bar), "r"(bytes) : "memory");
}
__device__ __forceinline__ bool mbar_try(uint32_t bar, uint32_t par) {
    uint32_t ok;
    asm volatile("{\n.reg .pred p;\nmbarrier.try_wait.parity.shared::cta.b64 p, [%1], %2;\nselp.u32 %0, 1, 0, p;\n}\n"
                 : "=r"(ok) : "r"(bar), "r"(par) : "memory");
    return ok != 0;
}
__device__ __forceinline__ void mbar_wait(uint32_t bar, uint32_t par) {
    unsigned n = 0;
    while (!mbar_try(bar, par)) {
        if (++n > SPIN_LIMIT) __trap();
    }
}
__device__ __forceinline__ bool mbar_test(uint32_t bar, uint32_t par) {
    uint32_t ok;
    asm volatile("{\n.reg .pred p;\nmbarrier.test_wait.parity.shared::cta.b64 p, [%1], %2;\nselp.u32 %0, 1, 0, p;\n}\n"
                 : "=r"(ok) : "r"(bar), "r"(par) : "memory");
    return ok != 0;
}
__device__ __forceinline__ bool elect_one() {
    uint32_t ok;
    asm volatile("{\n.reg .pred p;\nelect.sync _|p, 0xffffffff;\nselp.u32 %0, 1, 0, p;\n}\n" : "=r"(ok));
    return ok != 0;
}
__device__ __forceinline__ uint32_t opaque(uint32_t v) { return __shfl_sync(~0u, v, threadIdx.x & 31); }
__device__ __forceinline__ void named_bar(int id, int n) { asm volatile("bar.sync %0, %1;" ::"r"(id), "r"(n) : "memory"); }
__device__ __forceinline__ void named_arrive(int id, int n) { asm volatile("bar.arrive %0, %1;" ::"r"(id), "r"(n) : "memory"); }
__device__ __forceinline__ void fence_async() { asm volatile("fence.proxy.async.shared::cta;" ::: "memory"); }
__device__ __forceinline__ uint64_t evict_first() {
    uint64_t p;
    asm("createpolicy.fractional.L2::evict_first.b64 %0, 1.0;" : "=l"(p));
    return p;
}
__device__ __forceinline__ void tma_row(uint32_t dst, const CUtensorMap* tm, uint32_t bar, int x, int y) {
    asm volatile("cp.async.bulk.tensor.3d.shared::cluster.global.mbarrier::complete_tx::bytes.L2::cache_hint [%0], [%1, {%3, %4, %5}], [%2], %6;"
                 ::"r"(dst), "l"(tm), "r"(bar), "r"(0), "r"(x), "r"(y), "l"(evict_first()) : "memory");
}
__device__ __forceinline__ void bulk_load_stream(uint32_t dst, const void* src, uint32_t bytes, uint32_t bar) {
    asm volatile("cp.async.bulk.shared::cluster.global.mbarrier::complete_tx::bytes.L2::cache_hint [%0], [%1], %2, [%3], %4;"
                 ::"r"(dst), "l"(src), "r"(bytes), "r"(bar), "l"(evict_first()) : "memory");
}
__device__ __forceinline__ void prefetch_l2(const void* src, uint32_t bytes) {
    asm volatile("cp.async.bulk.prefetch.L2.global [%0], %1;" ::"l"(src), "r"(bytes) : "memory");
}
__device__ __forceinline__ void tma_2d(uint32_t dst, const CUtensorMap* tm, uint32_t bar, int x, int y) {
    asm volatile("cp.async.bulk.tensor.2d.shared::cluster.global.mbarrier::complete_tx::bytes [%0], [%1, {%3, %4}], [%2];"
                 ::"r"(dst), "l"(tm), "r"(bar), "r"(x), "r"(y) : "memory");
}
__device__ __forceinline__ void bulk_load(uint32_t dst, const void* src, uint32_t bytes, uint32_t bar) {
    asm volatile("cp.async.bulk.shared::cluster.global.mbarrier::complete_tx::bytes [%0], [%1], %2, [%3];"
                 ::"r"(dst), "l"(src), "r"(bytes), "r"(bar) : "memory");
}
__device__ __forceinline__ void wg_fence() { asm volatile("wgmma.fence.sync.aligned;" ::: "memory"); }
__device__ __forceinline__ void wg_commit() { asm volatile("wgmma.commit_group.sync.aligned;" ::: "memory"); }
template <int N> __device__ __forceinline__ void wg_wait() { asm volatile("wgmma.wait_group.sync.aligned %0;" ::"n"(N) : "memory"); }
template <int N> __device__ __forceinline__ void pin(uint32_t (&d)[N]) {
#pragma unroll
    for (int q = 0; q < N; q++) asm volatile("" : "+r"(d[q])::"memory");
}
__device__ __forceinline__ void stg128(void* p, const uint32_t (&v)[4]) {
    asm volatile("st.global.v4.u32 [%0], {%1, %2, %3, %4};" ::"l"(p), "r"(v[0]), "r"(v[1]), "r"(v[2]), "r"(v[3]) : "memory");
}
__device__ __forceinline__ void ldg128(uint32_t (&v)[4], const void* p) {
    asm volatile("ld.global.L1::no_allocate.v4.u32 {%0, %1, %2, %3}, [%4];" : "=r"(v[0]), "=r"(v[1]), "=r"(v[2]), "=r"(v[3]) : "l"(p) : "memory");
}
__device__ __forceinline__ void ldg128_if(bool on, uint32_t (&v)[4], const void* p) {
    asm volatile("{\n.reg .pred p;\nsetp.ne.b32 p, %5, 0;\n@p ld.global.L1::no_allocate.v4.u32 {%0, %1, %2, %3}, [%4];\n}\n"
                 : "+r"(v[0]), "+r"(v[1]), "+r"(v[2]), "+r"(v[3]) : "l"(p), "r"((int)on) : "memory");
}
__device__ __forceinline__ uint4 ldg128_ordered(const void* p) {
    uint4 v;
    asm volatile("ld.global.nc.v4.u32 {%0, %1, %2, %3}, [%4];" : "=r"(v.x), "=r"(v.y), "=r"(v.z), "=r"(v.w) : "l"(p) : "memory");
    return v;
}
__host__ __device__ constexpr uint64_t make_desc(uint32_t addr, uint32_t lbo, uint32_t sbo) {
    return (uint64_t)((addr & 0x3FFFF) >> 4) | ((uint64_t)(lbo >> 4) << 16) | ((uint64_t)(sbo >> 4) << 32);
}
__device__ __forceinline__ void wgmma(uint32_t (&d)[12], uint32_t a0, uint32_t a1, uint32_t a2, uint32_t a3, uint64_t db, int acc) {
    asm volatile("{\n.reg .pred p;\nsetp.ne.b32 p, %17, 0;\n"
                 "wgmma.mma_async.sync.aligned.m64n48k16.f16.f16.f16 "
                 "{%0, %1, %2, %3, %4, %5, %6, %7, %8, %9, %10, %11}, "
                 "{%12, %13, %14, %15}, %16, p, 1, 1, 0;\n}\n"
                 : "+r"(d[0]), "+r"(d[1]), "+r"(d[2]), "+r"(d[3]), "+r"(d[4]), "+r"(d[5]), "+r"(d[6]), "+r"(d[7]), "+r"(d[8]), "+r"(d[9]), "+r"(d[10]), "+r"(d[11])
                 : "r"(a0), "r"(a1), "r"(a2), "r"(a3), "l"(db), "r"(acc));
}
__device__ __forceinline__ void wgmma(uint32_t (&d)[24], uint32_t a0, uint32_t a1, uint32_t a2, uint32_t a3, uint64_t db, int acc) {
    asm volatile("{\n.reg .pred p;\nsetp.ne.b32 p, %29, 0;\n"
                 "wgmma.mma_async.sync.aligned.m64n96k16.f16.f16.f16 "
                 "{%0, %1, %2, %3, %4, %5, %6, %7, %8, %9, %10, %11, %12, %13, %14, %15, %16, %17, %18, %19, %20, %21, %22, %23}, "
                 "{%24, %25, %26, %27}, %28, p, 1, 1, 0;\n}\n"
                 : "+r"(d[0]), "+r"(d[1]), "+r"(d[2]), "+r"(d[3]), "+r"(d[4]), "+r"(d[5]), "+r"(d[6]), "+r"(d[7]), "+r"(d[8]), "+r"(d[9]), "+r"(d[10]), "+r"(d[11]), "+r"(d[12]), "+r"(d[13]), "+r"(d[14]), "+r"(d[15]), "+r"(d[16]), "+r"(d[17]), "+r"(d[18]), "+r"(d[19]), "+r"(d[20]), "+r"(d[21]), "+r"(d[22]), "+r"(d[23])
                 : "r"(a0), "r"(a1), "r"(a2), "r"(a3), "l"(db), "r"(acc));
}
template <int ACC>
__device__ __forceinline__ void wgmma_rowsum(float (&d)[4], const uint32_t (&a)[4], uint64_t ones) {
    asm volatile("{\n.reg .pred p;\nsetp.ne.b32 p, %9, 0;\n"
                 "wgmma.mma_async.sync.aligned.m64n8k16.f32.bf16.bf16 {%0, %1, %2, %3}, {%4, %5, %6, %7}, %8, p, 1, 1, 0;\n}\n"
                 : "+f"(d[0]), "+f"(d[1]), "+f"(d[2]), "+f"(d[3])
                 : "r"(a[0]), "r"(a[1]), "r"(a[2]), "r"(a[3]), "l"(ones), "n"(ACC));
}
__device__ __forceinline__ void ldsm4(uint32_t (&r)[4], uint32_t addr) {
    asm volatile("ldmatrix.sync.aligned.m8n8.x4.shared.b16 {%0, %1, %2, %3}, [%4];"
                 : "=r"(r[0]), "=r"(r[1]), "=r"(r[2]), "=r"(r[3]) : "r"(addr) : "memory");
}
__device__ __forceinline__ void ldsm4_t(uint32_t (&r)[4], uint32_t addr) {
    asm volatile("ldmatrix.sync.aligned.m8n8.x4.trans.shared.b16 {%0, %1, %2, %3}, [%4];"
                 : "=r"(r[0]), "=r"(r[1]), "=r"(r[2]), "=r"(r[3]) : "r"(addr) : "memory");
}
__device__ __forceinline__ void stsm4(uint32_t addr, uint32_t a, uint32_t b, uint32_t c, uint32_t d) {
    asm volatile("stmatrix.sync.aligned.m8n8.x4.shared.b16 [%0], {%1, %2, %3, %4};"
                 ::"r"(addr), "r"(a), "r"(b), "r"(c), "r"(d) : "memory");
}
__device__ __forceinline__ uint32_t transpose8x8(uint32_t v) {
    uint32_t d; asm volatile("movmatrix.sync.aligned.m8n8.trans.b16 %0, %1;" : "=r"(d) : "r"(v)); return d;
}
__device__ __forceinline__ void spin_until(const unsigned* counter, unsigned target) {
    unsigned n = 0, c;
    do {
        asm volatile("ld.acquire.gpu.global.u32 %0, [%1];" : "=r"(c) : "l"(counter) : "memory");
        if (++n > SPIN_LIMIT) __trap();
    } while ((int)(c - target) < 0);
}
__device__ __forceinline__ void signal(unsigned* counter) {
    __syncwarp();
    if (elect_one()) asm volatile("red.release.gpu.global.add.u32 [%0], 1;" ::"l"(counter) : "memory");
    __syncwarp();
}
__device__ __forceinline__ void lds128(uint32_t& a, uint32_t& b, uint32_t& c, uint32_t& d, uint32_t addr) {
    asm volatile("ld.shared.v4.u32 {%0, %1, %2, %3}, [%4];" : "=r"(a), "=r"(b), "=r"(c), "=r"(d) : "r"(addr) : "memory");
}
__device__ __forceinline__ void lds64(uint32_t& a, uint32_t& b, uint32_t addr) {
    asm volatile("ld.shared.v2.u32 {%0, %1}, [%2];" : "=r"(a), "=r"(b) : "r"(addr) : "memory");
}
__device__ __forceinline__ void lds32(uint32_t& a, uint32_t addr) {
    asm volatile("ld.shared.u32 %0, [%1];" : "=r"(a) : "r"(addr) : "memory");
}
__device__ __forceinline__ float ldsf(uint32_t addr) {
    uint32_t v;
    lds32(v, addr);
    return __uint_as_float(v);
}
__device__ __forceinline__ void sts32(uint32_t addr, uint32_t a) {
    asm volatile("st.shared.u32 [%0], %1;" ::"r"(addr), "r"(a) : "memory");
}
__device__ __forceinline__ void sts128(uint32_t addr, uint32_t a, uint32_t b, uint32_t c, uint32_t d) {
    asm volatile("st.shared.v4.u32 [%0], {%1, %2, %3, %4};" ::"r"(addr), "r"(a), "r"(b), "r"(c), "r"(d) : "memory");
}
__device__ __forceinline__ void sts64(uint32_t addr, uint32_t a, uint32_t b) {
    asm volatile("st.shared.v2.u32 [%0], {%1, %2};" ::"r"(addr), "r"(a), "r"(b) : "memory");
}
__device__ __forceinline__ void anchor(uint32_t addr, uint32_t a, uint32_t b, uint32_t c, uint32_t d) {
    asm volatile("{\n.reg .pred p;\nsetp.eq.b32 p, %0, 0;\n@p st.shared.v4.u32 [%0], {%1, %2, %3, %4};\n}\n"
                 ::"r"(addr), "r"(a), "r"(b), "r"(c), "r"(d) : "memory");
}
__device__ __forceinline__ uint32_t bf_fma(uint32_t a, uint32_t b, uint32_t c) {
    uint32_t d; asm("fma.rn.bf16x2 %0, %1, %2, %3;" : "=r"(d) : "r"(a), "r"(b), "r"(c)); return d;
}
__device__ __forceinline__ uint32_t bf_mul(uint32_t a, uint32_t b) {
    uint32_t d; asm("mul.rn.bf16x2 %0, %1, %2;" : "=r"(d) : "r"(a), "r"(b)); return d;
}
__device__ __forceinline__ uint32_t bf_absmax(uint32_t a, uint32_t b) {
    uint32_t d; asm("max.xorsign.abs.bf16x2 %0, %1, %2;" : "=r"(d) : "r"(a), "r"(b)); return d;
}
__device__ __forceinline__ uint32_t h_fma(uint32_t a, uint32_t b, uint32_t c) {
    uint32_t d; asm("fma.rn.f16x2 %0, %1, %2, %3;" : "=r"(d) : "r"(a), "r"(b), "r"(c)); return d;
}
__device__ __forceinline__ uint32_t h_mul(uint32_t a, uint32_t b) {
    uint32_t d; asm("mul.rn.f16x2 %0, %1, %2;" : "=r"(d) : "r"(a), "r"(b)); return d;
}
__device__ __forceinline__ uint32_t h_round8(uint32_t v) { return (v + 0x00040004u) & 0xfff8fff8u; }
__device__ __forceinline__ uint32_t h_tanh(uint32_t a) {
    uint32_t d; asm("tanh.approx.f16x2 %0, %1;" : "=r"(d) : "r"(a)); return d;
}
__device__ __forceinline__ uint32_t pack_h2(float lo, float hi) {
    uint32_t d; asm("cvt.rn.f16x2.f32 %0, %1, %2;" : "=r"(d) : "f"(hi), "f"(lo)); return d;
}
__device__ __forceinline__ uint32_t pack_bf2(float lo, float hi) {
    uint32_t d; asm("cvt.rn.bf16x2.f32 %0, %1, %2;" : "=r"(d) : "f"(hi), "f"(lo)); return d;
}
__device__ __forceinline__ float bf_lo(uint32_t v) { return __uint_as_float(v << 16); }
__device__ __forceinline__ float bf_hi(uint32_t v) { return __uint_as_float(v & 0xffff0000u); }
__device__ __forceinline__ float h_lo(uint32_t v) { return __low2float(*reinterpret_cast<__half2*>(&v)); }
__device__ __forceinline__ float h_hi(uint32_t v) { return __high2float(*reinterpret_cast<__half2*>(&v)); }
__device__ __forceinline__ float warp_absmax(uint32_t v) {
    return __uint_as_float(__reduce_max_sync(~0u, max((v & 0x7fffu) << 16, v & 0x7fff0000u)));
}
__device__ __forceinline__ uint32_t gelu2(uint32_t z) {
    uint32_t p = h_fma(z, z, GELU_C2);
    uint32_t t = h_tanh(h_mul(z, p));
    return h_fma(z, t, z);
}
__device__ __forceinline__ float grn_norm(float ss) {
    float r;
    asm("sqrt.approx.f32 %0, %1;" : "=f"(r) : "f"(fmaf(ss, INV_2KZ * INV_2KZ, 1e-6f)));
    return r;
}
__device__ __forceinline__ float pow2i(int e) { return __uint_as_float((uint32_t)(e + 127) << 23); }
__device__ __forceinline__ int ilog2f(float v) {
    int e = (int)((__float_as_uint(v) >> 23) & 0xff) - 127;
    return max(-100, min(100, e));
}

__device__ __forceinline__ int sum_exp(float w1max) {
    return w1max > 0.f ? max(-90, min(90, 33 - 2 * ilog2f(2.f * KZ * 96.f * w1max))) : 0;
}
__device__ __forceinline__ float row_scale(float m) { return m > 0.f ? pow2i(2 - ilog2f(m)) : 1.f; }

struct Work {
    int tA, tB, nA, nB, rows, lent;
    __device__ __forceinline__ int tile(int j) const { return j < nA ? tA + j : tB + j - nA; }
};
__device__ __forceinline__ Work get_work(int per_cta, int extra, int lenders) {
    Work w;
    w.lent = (int)blockIdx.x < lenders ? LENT : 0;
    const int t0 = blockIdx.x * per_cta + min((int)blockIdx.x, extra);
    const int t1 = t0 + per_cta + ((int)blockIdx.x < extra);
    const int tm = min(t1, (t0 | 511) + 1);
    const bool swap = t1 > tm && t1 - tm < tm - t0;
    w.tA = swap ? tm : t0;
    w.tB = swap ? t0 : tm;
    w.nA = swap ? t1 - tm : tm - t0;
    w.nB = t1 - t0 - w.nA;
    w.rows = w.nA + 2 + (w.nB ? w.nB + 2 : 0);
    return w;
}
__device__ __forceinline__ int row_code(const Work& w, int i) {
    const bool in_a = i < w.nA + 2;
    const int t = in_a ? w.tA : w.tB;
    return ((t & 511) - 1 + (in_a ? i : i - (w.nA + 2))) << 16 | (t >> 9) * TILE_W;
}
__device__ __forceinline__ uint32_t tile_offset(int tile) { return ((tile & 511) * IMG_W + (tile >> 9) * TILE_W) * (CH * 2); }
__device__ __forceinline__ int tile_order(int j, int n) {
    const int olds = (j / ORDER_P) * ORDER_Q + max(0, j % ORDER_P - (ORDER_P - ORDER_Q));
    return (j % ORDER_P >= ORDER_P - ORDER_Q) ? olds : n - 1 - (j - olds);
}
__device__ __forceinline__ void issue_region(const CUtensorMap* tm, uint32_t dst, uint32_t bar, int warp, int code) {
    mbar_expect_tx(bar, REGION_BYTES);
    tma_row(dst, tm, bar, (code & 0xffff) + (16 * warp - 1), code >> 16);
}

__device__ __forceinline__ void conv_producer(const Work& wk, const CUtensorMap* tm, const __nv_bfloat16* dw, Scratch* sc, uint32_t sb, int warp) {
    const int lane = threadIdx.x & 31;
    const int j = lane & 15, grp = lane >> 4;
    const uint32_t reg0 = sb + SM_RING + warp * REGION_BYTES;
    const uint32_t bars = sb + SM_BAR + warp * 8;
    if (elect_one()) {
#pragma unroll
        for (int s = 0; s < PREFETCH_ROWS; s++) mbar_init(bars + s * 32, 1);
        fence_async();
#pragma unroll
        for (int r = 0; r < PREFETCH_ROWS; r++)
            issue_region(tm, reg0 + r * SLOT_BYTES, bars + r * 32, warp, ((wk.tA & 511) - 1 + r) << 16 | (wk.tA >> 9) * TILE_W);
    }
    __syncwarp();
    uint32_t w[3][3][3];
#pragma unroll
    for (int tap = 0; tap < 9; tap++) {
        const uint2 u = __ldg(reinterpret_cast<const uint2*>(dw + tap * CH + 4 * j));
        w[tap / 3][tap % 3][0] = u.x;
        w[tap / 3][tap % 3][1] = u.y;
        w[tap / 3][tap % 3][2] = __ldg(reinterpret_cast<const uint32_t*>(dw + tap * CH + 64 + 2 * j));
    }
    if (lane >= PREFETCH_ROWS && lane < 3 * NSLOT) mbar_init(bars + lane * 32, 1);
    if (lane >= 28) mbar_init(sb + BAR_R + ((lane - 28) * 4 + warp) * 8, 1);
    if (lane == 0 && warp == 0) mbar_init(sb + BAR_PIN, 1);
    if (warp * 32 + lane < MAX_ROWS) {
        sts32(sb + SM_ROWS + (warp * 32 + lane) * 4, row_code(wk, warp * 32 + lane));
        sts32(sb + SM_TILES + (warp * 32 + lane) * 4, tile_offset(wk.tile(wk.lent + tile_order(max(warp * 32 + lane - wk.lent / 2, 0), wk.nA + wk.nB - NCONS - wk.lent))));
    }
    const uint32_t ld64 = opaque(reg0 + grp * 8 * 192 + j * 8), ld32 = opaque(reg0 + grp * 8 * 192 + 128 + j * 4);
    const uint32_t st64 = opaque(reg0 + grp * A_SBO + (j >> 1) * A_LBO + (j & 1) * 8);
    const uint32_t st32 = opaque(reg0 + grp * A_SBO + (8 + (j >> 2)) * A_LBO + (j & 3) * 4);
    fence_async();
    named_bar(0, NTHREADS);
#pragma unroll
    for (int tap = 0; tap < 9; tap++) sts64(reg0 + (NSLOT - 1) * SLOT_BYTES + tap * 256 + lane * 8, w[tap / 3][tap % 3][1], w[tap / 3][tap % 3][0]);
#pragma unroll
    for (int tap = 0; tap < 9; tap++) lds64(w[tap / 3][tap % 3][1], w[tap / 3][tap % 3][0], reg0 + (NSLOT - 1) * SLOT_BYTES + tap * 256 + lane * 8);
    fence_async();
    static_assert(2 * PREFETCH_ROWS == NSLOT, "prefetch slot arithmetic");
    uint32_t so = 0, bo = 0, par = 0, tbl = sb + SM_ROWS + PREFETCH_ROWS * 4;
    const uint32_t tbl_end = sb + SM_ROWS + wk.rows * 4, publish = wk.lent ? tbl + 12 * 4 : 0;
    auto next_row = [&](int code, bool e_ready) {
        const bool wrap = bo == (NSLOT - 1) * 32, low = bo < PREFETCH_ROWS * 32;
        if (tbl < tbl_end) {
            const uint32_t pbo = low ? bo + PREFETCH_ROWS * 32 : bo - PREFETCH_ROWS * 32;
            if (!e_ready) mbar_wait(bars + (BAR_E - SM_BAR) + pbo, par ^ low);
            code = __shfl_sync(~0u, code, 0);
            if (elect_one()) issue_region(tm, reg0 + (low ? so + PREFETCH_ROWS * SLOT_BYTES : so - PREFETCH_ROWS * SLOT_BYTES), bars + pbo, warp, code);
        }
        tbl += 4;
        so = wrap ? 0 : so + SLOT_BYTES;
        bo = wrap ? 0 : bo + 32;
        par ^= wrap;
    };
    int n = wk.nA;
#pragma unroll 1
    for (int seg = 0; seg < 2 && n > 0; seg++, n = wk.nB) {
        uint32_t accB[8][3], accC[8][3];
        {
            const bool wrap = bo == (NSLOT - 1) * 32;
            const uint32_t so1 = wrap ? 0 : so + SLOT_BYTES, bo1 = wrap ? 0 : bo + 32;
            mbar_wait(bars + bo, par);
            mbar_wait(bars + bo1, par ^ wrap);
#pragma unroll
            for (int p = 0; p < 10; p++) {
                uint32_t u[3], v[3];
                lds64(u[0], u[1], so + ld64 + p * 192);
                lds32(u[2], so + ld32 + p * 192);
                lds64(v[0], v[1], so1 + ld64 + p * 192);
                lds32(v[2], so1 + ld32 + p * 192);
#pragma unroll
                for (int dx = 0; dx < 3; dx++) {
                    const int o = p - dx;
                    if (o < 0 || o > 7) continue;
#pragma unroll
                    for (int q = 0; q < 3; q++) {
                        accB[o][q] = bf_fma(v[q], w[1][dx][q], dx == 0 ? bf_mul(u[q], w[0][dx][q]) : bf_fma(u[q], w[0][dx][q], accB[o][q]));
                        accC[o][q] = dx == 0 ? bf_mul(v[q], w[0][dx][q]) : bf_fma(v[q], w[0][dx][q], accC[o][q]);
                    }
                }
            }
            anchor(ld64, accB[7][0], accB[7][1], accB[7][2], 0);
            __syncwarp();
#pragma unroll 1
            for (int r = 0; r < 2; r++) {
                uint32_t code;
                lds32(code, tbl);
                if (elect_one()) { mbar_arrive(bars + (BAR_A - SM_BAR) + bo); mbar_arrive(bars + (BAR_E - SM_BAR) + bo); }
                next_row(code, false);
            }
        }
        bool x_ready = false;
#pragma unroll 1
        for (int k = 0; k < n; k++) {
            if (!x_ready) mbar_wait(bars + bo, par);
            uint32_t out[8][3];
            int code;
            bool e_ready;
#pragma unroll
            for (int p = 0; p < 10; p++) {
                uint32_t xv[3];
                lds64(xv[0], xv[1], so + ld64 + p * 192);
                lds32(xv[2], so + ld32 + p * 192);
                if (p == 9) {
                    const bool wrap = bo == (NSLOT - 1) * 32, low = bo < PREFETCH_ROWS * 32;
                    asm volatile("ld.shared.u32 %0, [%1];" : "=r"(code) : "r"(tbl));
                    e_ready = mbar_test(bars + (BAR_E - SM_BAR) + (low ? bo + PREFETCH_ROWS * 32 : bo - PREFETCH_ROWS * 32), par ^ low);
                    x_ready = mbar_test(bars + (wrap ? 0 : bo + 32), par ^ wrap);
                }
#pragma unroll
                for (int dx = 0; dx < 3; dx++) {
                    const int o = p - dx;
                    if (o < 0 || o > 7) continue;
#pragma unroll
                    for (int q = 0; q < 3; q++) {
                        out[o][q] = bf_fma(xv[q], w[2][dx][q], dx == 0 ? accB[o][q] : out[o][q]);
                        accB[o][q] = bf_fma(xv[q], w[1][dx][q], dx == 0 ? accC[o][q] : accB[o][q]);
                        accC[o][q] = dx == 0 ? bf_mul(xv[q], w[0][dx][q]) : bf_fma(xv[q], w[0][dx][q], accC[o][q]);
                    }
                }
            }
            __syncwarp();
#pragma unroll
            for (int o = 0; o < 8; o++) {
                sts64(so + st64 + o * 16, out[o][0], out[o][1]);
                sts32(so + st32 + o * 16, out[o][2]);
            }
            __syncwarp();
            if (elect_one()) mbar_arrive(bars + (BAR_A - SM_BAR) + bo);
            if (tbl == publish) signal(&sc->lent_in);
            next_row(code, e_ready);
        }
    }
}

template <bool SCALED, int K0 = 0, int K1 = 3>
__device__ __forceinline__ void gelu_sq(uint32_t (&d)[24], uint32_t (&keep)[24], uint32_t sq_addr, uint32_t scale2) {
    pin(d);
#pragma unroll
    for (int k = K0; k < K1; k++) {
        uint32_t hs[4];
        lds128(hs[0], hs[1], hs[2], hs[3], sq_addr + k * SQ_ROW);
#pragma unroll
        for (int q = 0; q < 4; q++) {
            uint32_t g0 = gelu2(d[8 * k + 2 * q]), g1 = gelu2(d[8 * k + 2 * q + 1]);
            keep[8 * k + 2 * q] = g0;
            keep[8 * k + 2 * q + 1] = g1;
            if (SCALED) { g0 = h_mul(g0, scale2); g1 = h_mul(g1, scale2); }
            hs[q] = h_fma(g1, g1, h_fma(g0, g0, hs[q]));
        }
        sts128(sq_addr + k * SQ_ROW, hs[0], hs[1], hs[2], hs[3]);
    }
}
__device__ __forceinline__ void gelu_sq_reg(uint32_t (&d)[24], uint32_t (&hs)[12]) {
    pin(d);
#pragma unroll
    for (int q = 0; q < 12; q++) {
        const uint32_t g0 = gelu2(d[2 * q]), g1 = gelu2(d[2 * q + 1]);
        hs[q] = h_fma(g1, g1, h_fma(g0, g0, hs[q]));
    }
}
__device__ __forceinline__ void gelu_to(uint32_t (&g)[12], uint32_t (&d)[12]) {
    pin(d);
#pragma unroll
    for (int q = 0; q < 12; q++) g[q] = gelu2(d[q]);
    pin(g);
}
__device__ __forceinline__ void load_tile(uint32_t (&raw)[6][4], uint32_t addr) {
#pragma unroll
    for (int s = 0; s < 6; s++) ldsm4(raw[s], addr + s * 2 * A_LBO);
}
__device__ __forceinline__ uint2 ln_stats(const uint32_t (&raw)[6][4], uint64_t ones) {
    uint32_t sq[6][4];
#pragma unroll
    for (int s = 0; s < 6; s++)
#pragma unroll
        for (int q = 0; q < 4; q++) sq[s][q] = bf_mul(raw[s][q], raw[s][q]);
    float sum[4], ssq[4];
    wg_fence();
    wgmma_rowsum<0>(sum, raw[0], ones);
#pragma unroll
    for (int s = 1; s < 6; s++) wgmma_rowsum<1>(sum, raw[s], ones);
    wgmma_rowsum<0>(ssq, sq[0], ones);
#pragma unroll
    for (int s = 1; s < 6; s++) wgmma_rowsum<1>(ssq, sq[s], ones);
    wg_commit();
    wg_wait<0>();
    uint32_t st[2];
#pragma unroll
    for (int h = 0; h < 2; h++) {
        asm volatile("" : "+f"(sum[2 * h]), "+f"(ssq[2 * h])::"memory");
        const float mean = sum[2 * h] * (1.f / CH);
        const float var = fmaxf(fmaf(ssq[2 * h], 1.f / CH, -mean * mean), 0.f);
        float rstd;
        asm("rsqrt.approx.ftz.f32 %0, %1;" : "=f"(rstd) : "f"(var + 1e-5f));
        rstd = bf_lo(pack_bf2(rstd * (K_CVT == 0 ? KZ : KZ * 0x1p-112f), 0.f));
        st[h] = pack_bf2(rstd, -mean * rstd);
    }
    return make_uint2(st[0], st[1]);
}
__device__ __forceinline__ void ln_apply(uint32_t (&a)[6][4], const uint2& st) {
    const uint32_t sc[2] = {__byte_perm(st.x, 0, 0x1010), __byte_perm(st.y, 0, 0x1010)};
    const uint32_t sh[2] = {__byte_perm(st.x, 0, 0x3232), __byte_perm(st.y, 0, 0x3232)};
#pragma unroll
    for (int s = 0; s < 6; s++)
#pragma unroll
        for (int q = 0; q < 4; q++) {
            const uint32_t v = bf_fma(a[s][q], sc[q & 1], sh[q & 1]);
            a[s][q] = K_CVT == 0 ? pack_h2(bf_lo(v), bf_hi(v)) : (v & 0x7fff7fffu) * 7u + v;
        }
}
struct Cursor {
    int slot;
    uint32_t par;
    __device__ __forceinline__ void advance(int n) {
        slot += n;
        if (slot >= NSLOT) { slot -= NSLOT; par ^= 1; }
    }
};
struct Descs {
    uint64_t w1[8][6];
    uint64_t w2[24];
    uint64_t ones;
};
template <int E0, int N>
__device__ __forceinline__ void gemm1_chunk(uint32_t (&d)[N], const uint32_t (&a)[6][4], const Descs& ds, int zero) {
#pragma unroll
    for (int s = 0; s < 6; s++) wgmma(d, a[s][0], a[s][1], a[s][2], a[s][3], ds.w1[E0 / 48][s], s ? 1 : zero);
}
template <int E0, int N>
__device__ __forceinline__ void gemm2_chunk(uint32_t (&acc)[24], const uint32_t (&g)[N], const Descs& ds) {
#pragma unroll
    for (int s = 0; s < N / 4; s++) wgmma(acc, g[4 * s], g[4 * s + 1], g[4 * s + 2], g[4 * s + 3], ds.w2[E0 / 16 + s], 1);
}

__global__ void __launch_bounds__(NTHREADS, 1)
block_kernel(const __grid_constant__ CUtensorMap tmap, const __grid_constant__ CUtensorMap tmap_w1,
             const __nv_bfloat16* __restrict__ x, const __nv_bfloat16* __restrict__ dw, const __nv_bfloat16* __restrict__ w2,
             const __nv_bfloat16* __restrict__ gamma, const __nv_bfloat16* __restrict__ beta, __nv_bfloat16* __restrict__ out,
             Scratch* __restrict__ sc, const __grid_constant__ Descs ds,
             const int zero, const int per_cta, const int extra, const int lenders) {
    extern __shared__ __align__(1024) uint8_t smem[];
    constexpr uint32_t sb = SB;
    const int tid = threadIdx.x;
    const Work wk = get_work(per_cta, extra, lenders);
    if (smem_u32(smem) != SB || wk.rows + 4 > MAX_ROWS) __trap();
    constexpr uint32_t s_red = sb + SM_RED;

    PROF(0);
    const int warp_id = __shfl_sync(~0u, tid >> 5, 0);
    const int cw = warp_id - 4, wgi = cw >> 2, w4 = warp_id & 3;
    const int ntiles = wk.nA + wk.nB;
    const int wg = warp_id >> 2;
    int first = wg;
    uint32_t a[6][4], acc[24], tile_off, next_off, stage, inv_rho2 = 0, rpar = 0, bias_addr, lane16, lane_off;
    auto set_lane = [&](uint32_t lane) {
        bias_addr = sb + SM_BIASH + (lane & 3) * 96;
        lane16 = lane * 16;
        lane_off = ((lane >> 2) * CH + 8 * (lane & 3)) * 2;
    };
    const uint32_t bar_r = sb + BAR_R + warp_id * 8;
    auto load_bias = [&](uint32_t (&acc)[24]) {
#pragma unroll
        for (int q = 0; q < 6; q++) lds128(acc[4 * q], acc[4 * q + 1], acc[4 * q + 2], acc[4 * q + 3], bias_addr + q * 16);
    };
    auto load_frags = [&](bool on) {
#pragma unroll
        for (int s = 0; s < 6; s++) ldg128_if(on, a[s], reinterpret_cast<const char*>(out) + next_off + w4 * WARP_BYTES + lane16 + s * 512);
    };
    auto load_first = [&]() {
#pragma unroll
        for (int s = 0; s < 6; s++) ldg128(a[s], reinterpret_cast<const char*>(out) + next_off + w4 * WARP_BYTES + lane16 + s * 512);
    };
    auto stage_x = [&]() {
        if (elect_one()) {
            mbar_expect_tx(bar_r, WARP_BYTES);
            bulk_load_stream(stage, reinterpret_cast<const char*>(x) + tile_off + w4 * WARP_BYTES, WARP_BYTES, bar_r);
        }
    };
    auto epilogue = [&](uint32_t (&acc)[24]) {
        pin(acc);
        rpar ^= 1;
        uint4* op = reinterpret_cast<uint4*>(reinterpret_cast<char*>(out) + tile_off + w4 * WARP_BYTES + lane_off);
#pragma unroll
        for (int h = 0; h < 2; h++)
#pragma unroll
            for (int m = 0; m < 3; m++) {
                uint32_t xin[4], o[4];
                lds128(xin[0], xin[1], xin[2], xin[3], stage + lane_off + h * 1536 + m * 64);
#pragma unroll
                for (int q = 0; q < 4; q++) {
                    const uint32_t v = acc[2 * (4 * m + q) + h];
                    o[q] = bf_fma(pack_bf2(h_lo(v), h_hi(v)), inv_rho2, xin[q]);
                }
                __stcs(op + h * 96 + m * 4, make_uint4(o[0], o[1], o[2], o[3]));
            }
        __syncwarp();
    };
    auto max_w1 = [&]() {
        float m = 0.f;
#pragma unroll
        for (int q = 0; q < 3; q++) {
            uint32_t u[4];
            lds128(u[0], u[1], u[2], u[3], s_red + q * 16);
#pragma unroll
            for (int k = 0; k < 4; k++) m = fmaxf(m, __uint_as_float(u[k]));
        }
        return m;
    };
    auto square_exp = [&](float w1max) {
        const int e = w1max > 0.f ? 4 - ilog2f(2.f * KZ * 96.f * w1max) : 0;
        return (e >= 0 && e <= 6) ? 0 : max(-14, min(e, 14));
    };
    const int last_wg = (ntiles - 1 - wk.lent) % NCONS;
    auto reduce = [&](int q, uint32_t lane, bool leader) {
        const int t = lane & 3, part = lane >> 2;
        const float w1max = max_w1();
        const int sq_e = square_exp(w1max);
        const float to_fixed = pow2i(sum_exp(w1max) - 2 * sq_e);
        unsigned long long* dst = sc->sum(__float_as_uint(ldsf(s_red + 48)), 32 * q + 8 * (part >> 1) + 2 * t + (part & 1));
        named_bar(11, CONS_THREADS);
        const unsigned in_piece = 32 * q + 8 * (part >> 1) + 2 * t + (part & 1) - (blockIdx.x - lenders) % 8 * 48;
        const float helped = in_piece < 48 ? ldsf(sb + SM_BIASH + in_piece * 4) * pow2i(2 * sq_e) : 0.f;
        float f[8] = {};
#pragma unroll 1
        for (int i = 0; i < NCONS; i++) {
            const int src_wg = (last_wg + 1 + i) % NCONS;
            if (i == NCONS - 1) {
                named_bar(13, CONS_THREADS);
                if (leader) {
                    fence_async();
#pragma unroll
                    for (int k = 1; k < NCONS; k++) {
                        const int o = (last_wg + k) % NCONS * SQ_WG;
                        bulk_load(sb + SM_W2 + o, reinterpret_cast<const char*>(sc->w2h) + o, SQ_WG, sb + BAR_W);
                    }
                }
                __syncwarp();
                named_bar(14, NTHREADS);
            }
            const uint32_t upper = sq_e ? SM_SQ + (NCONS + src_wg) * SQ_WG : SM_RING + (wk.rows + i) % NSLOT * SLOT_BYTES;
            const uint32_t src = sb + lane * 16 + (q < 6 ? SM_SQ + src_wg * SQ_WG + q * SQ_ROW : upper + (q - 6) * SQ_ROW);
#pragma unroll
            for (int r = 0; r < 4; r++) {
                uint32_t u[4];
                lds128(u[0], u[1], u[2], u[3], src + r * 512);
#pragma unroll
                for (int k = 0; k < 4; k++) { f[2 * k] += h_lo(u[k]); f[2 * k + 1] += h_hi(u[k]); }
            }
        }
        const bool b2 = part & 4, b1 = part & 2, b0 = part & 1;
        float r4[4], r2[2];
#pragma unroll
        for (int k = 0; k < 4; k++) r4[k] = (b2 ? f[k + 4] : f[k]) + __shfl_xor_sync(~0u, b2 ? f[k] : f[k + 4], 16);
#pragma unroll
        for (int k = 0; k < 2; k++) r2[k] = (b1 ? r4[k + 2] : r4[k]) + __shfl_xor_sync(~0u, b1 ? r4[k] : r4[k + 2], 8);
        const float tot = (b0 ? r2[1] : r2[0]) + __shfl_xor_sync(~0u, b0 ? r2[0] : r2[1], 4);
        atomicAdd(dst, __float2ull_rn(fminf((tot + helped) * to_fixed, 0x1p47f)) << 8 | 1);
    };
    const uint32_t s_fac = sb + SM_RING + (wk.rows + 1) % NSLOT * SLOT_BYTES + SQ_WG;
    if (warp_id < 4) {
        conv_producer(wk, &tmap, dw, sc, sb, warp_id);
        const int lane = opaque(tid & 31), g = lane >> 2, t = lane & 3;
        const unsigned epoch = __float_as_uint(ldsf(s_red + 48));
        set_lane(lane);
#pragma unroll 1
        for (int q = gridDim.x - 1 - blockIdx.x; q < W2_GROUPS; q += gridDim.x) {
            uint32_t u[3], rmax = 0;
#pragma unroll
            for (int m = 0; m < 3; m++) {
                const uint4 w = ldg128_ordered(w2 + (8 * q + g) * CH + 32 * m + 8 * t);
                rmax = bf_absmax(bf_absmax(rmax, bf_absmax(w.x, w.y)), bf_absmax(w.z, w.w));
                u[m] = w4 & 2 ? (w4 & 1 ? w.w : w.z) : (w4 & 1 ? w.y : w.x);
            }
            const float bt = __bfloat162float(beta[8 * q + g]);
            rmax = bf_absmax(rmax, __shfl_xor_sync(~0u, rmax, 1));
            rmax = bf_absmax(rmax, __shfl_xor_sync(~0u, rmax, 2));
            const float mx = fmaxf(fabsf(bf_lo(rmax)), fabsf(bf_hi(rmax))), rs = row_scale(mx);
            if (t == 0 && w4 == 0) sc->w2max[8 * q + g] = mx;
#pragma unroll
            for (int m = 0; m < 3; m++) {
                float lo = bf_lo(u[m]), hi = bf_hi(u[m]);
                sc->w2h[(4 * m + w4) * 1536 + q * 32 + lane] = transpose8x8(pack_h2(lo * rs, hi * rs));
                lo *= bt; hi *= bt;
#pragma unroll
                for (int o = 4; o <= 16; o <<= 1) { lo += __shfl_xor_sync(~0u, lo, o); hi += __shfl_xor_sync(~0u, hi, o); }
                if (g == 0) {
                    float* dst = &sc->bias[epoch & 1][32 * m + 8 * t + 2 * w4];
                    asm volatile("red.global.add.v2.f32 [%0], {%1, %2};" ::"l"(dst), "f"(lo), "f"(hi) : "memory");
                }
            }
            asm volatile("fence.proxy.async.global;" ::: "memory");
            signal(&sc->prep);
        }
        const unsigned piece = blockIdx.x - lenders;
        if (piece < 8 * LENT * lenders) {
            spin_until(&sc->lent_in, (epoch + 1) * 4 * lenders);
            next_off = tile_offset(piece / (8 * LENT) * (per_cta + 1) + piece / 8 % LENT);
            load_first();
            uint32_t d[12], gl[12];
            wg_fence();
#pragma unroll
            for (int s = 0; s < 6; s++) wgmma(d, a[s][0], a[s][1], a[s][2], a[s][3], ds.w1[0][s] + piece % 8 * (6 * 1536 / 16), s ? 1 : 0);
            wg_commit();
            wg_wait<0>();
            gelu_to(gl, d);
#pragma unroll
            for (int s = 0; s < 3; s++) sc->lent[((piece * 4 + w4) * 3 + s) * 32 + lane] = make_uint4(gl[4 * s], gl[4 * s + 1], gl[4 * s + 2], gl[4 * s + 3]);
            float f[6], r[3];
#pragma unroll
            for (int j = 0; j < 6; j++) {
                const float lo = fmaf(h_lo(gl[2 * j]), h_lo(gl[2 * j]), h_lo(gl[2 * j + 1]) * h_lo(gl[2 * j + 1]));
                const float hi = fmaf(h_hi(gl[2 * j]), h_hi(gl[2 * j]), h_hi(gl[2 * j + 1]) * h_hi(gl[2 * j + 1]));
                f[j] = (g & 1 ? hi : lo) + __shfl_xor_sync(~0u, g & 1 ? lo : hi, 4);
            }
#pragma unroll
            for (int j = 0; j < 3; j++) {
                r[j] = (g & 2 ? f[j + 3] : f[j]) + __shfl_xor_sync(~0u, g & 2 ? f[j] : f[j + 3], 8);
                asm volatile("red.shared.add.f32 [%0], %1;" ::"r"(sb + SM_BIASH + (8 * j + 12 * (g & 2) + 2 * t + (g & 1)) * 4), "f"(r[j]) : "memory");
            }
        }
        if (piece < 8 * LENT * lenders) signal(&sc->lent_out);
        const bool leader = warp_id == 0 && lane == 0;
        const float w1max = max_w1();
        const bool plain = square_exp(w1max) == 0;
        auto load_upper = [&]() {
            bulk_load(sb + SM_W2 + NCONS * SQ_WG, reinterpret_cast<const char*>(sc->w2h) + NCONS * SQ_WG, EX * CH * 2 - NCONS * SQ_WG, sb + BAR_W);
        };
        if (leader) {
            spin_until(&sc->prep, (epoch + 1) * 4 * W2_GROUPS);
            asm volatile("fence.proxy.async.global;" ::: "memory");
            fence_async();
            mbar_expect_tx(sb + BAR_W, EX * CH * 2);
            if (plain) load_upper();
        }
        __syncwarp();
        named_bar(1, 128);
        const int i0 = w4 * 32 + lane;
        float gam[3], rmax[3];
#pragma unroll
        for (int m = 0; m < 3; m++) { gam[m] = __bfloat162float(gamma[i0 + 128 * m]); rmax[m] = __ldcg(&sc->w2max[i0 + 128 * m]); }
        float2 bpair = make_float2(0.f, 0.f);
        if (i0 < 96) bpair = __ldcg(reinterpret_cast<const float2*>(&sc->bias[epoch & 1][32 * (i0 % 24 >> 3) + 8 * (i0 / 24) + (i0 % 24 & 6)]));
        const float gbound = fmaxf(2.f * KZ * 9.7979590f * 192.f * w1max, 1.f) * 19.5959180f * INV_2KZ;
        const unsigned fixed = __reduce_max_sync(~0u, __float_as_uint(fmaf(gbound, fmaxf(fmaxf(rmax[0], rmax[1]), rmax[2]), fmaxf(fabsf(bpair.x), fabsf(bpair.y)))));
        if (lane == 0) sts32(s_red + 96 + w4 * 4, fixed);
        reduce(4 * last_wg + w4, lane, leader);
        PROF(2);
        named_bar(15, CONS_THREADS);
        if (leader) {
            fence_async();
            bulk_load(sb + SM_W2 + last_wg * SQ_WG, reinterpret_cast<const char*>(sc->w2h) + last_wg * SQ_WG, SQ_WG, sb + BAR_W);
            if (!plain) load_upper();
        }
        stage = sb + SM_RING + (wk.rows % NSLOT) * SLOT_BYTES + w4 * REGION_BYTES;
        auto grn = [&]() {
            auto peek = [&](int e) {
                unsigned long long v;
                asm volatile("ld.relaxed.gpu.global.u64 %0, [%1];" : "=l"(v) : "l"(sc->sum(epoch, e)) : "memory");
                return v;
            };
            unsigned n = 0;
            while (((unsigned)peek((blockIdx.x * 4 + w4) % (EX / 4) * 4) & 255u) != gridDim.x)
                if (++n > SPIN_LIMIT) __trap();
            unsigned long long sum[3];
            for (;;) {
                bool all = true;
#pragma unroll
                for (int m = 0; m < 3; m++) {
                    sum[m] = peek(i0 + 128 * m);
                    all &= ((unsigned)sum[m] & 255u) == gridDim.x;
                }
                if (__all_sync(~0u, all)) break;
                if (++n > SPIN_LIMIT) __trap();
            }
            PROF(3);
            if (blockIdx.x == 0 && leader) sc->launch = epoch + 1;
            float gx[3], tot = 0.f, vary = 0.f;
#pragma unroll
            for (int m = 0; m < 3; m++) {
                gx[m] = grn_norm(__ull2float_rn(sum[m] >> 8) * pow2i(-sum_exp(w1max)));
                tot += gx[m];
                vary = fmaxf(vary, fabsf(gam[m]) * gx[m] * rmax[m]);
            }
#pragma unroll
            for (int o = 16; o >= 1; o >>= 1) tot += __shfl_xor_sync(~0u, tot, o);
            const unsigned vwarp = __reduce_max_sync(~0u, __float_as_uint(vary));
            if (lane == 0) { sts32(s_red + 64 + w4 * 4, __float_as_uint(tot)); sts32(s_red + 80 + w4 * 4, vwarp); }
            named_bar(1, 128);
            uint32_t u[4], v[4], w[4];
            lds128(u[0], u[1], u[2], u[3], s_red + 64);
            lds128(v[0], v[1], v[2], v[3], s_red + 80);
            lds128(w[0], w[1], w[2], w[3], s_red + 96);
            tot = (__uint_as_float(u[0]) + __uint_as_float(u[1])) + (__uint_as_float(u[2]) + __uint_as_float(u[3]));
            const float vmax = __uint_as_float(max(max(v[0], v[1]), max(v[2], v[3]))), fmax2 = __uint_as_float(max(max(w[0], w[1]), max(w[2], w[3])));
            const float inv_mean = __fdividef(1.f, tot * (1.f / EX) + 1e-6f);
            const float bound = fmaf(gbound * vmax, inv_mean, 2.f * fmax2);
            const int rho_e = bound > 0.f ? 14 - ilog2f(bound) : 0;
            const float rho = pow2i(rho_e), inv_rho = pow2i(-rho_e);
            inv_rho2 = pack_bf2(inv_rho, inv_rho);
#pragma unroll
            for (int m = 0; m < 3; m++) {
                const float f = __fdividef(fmaf(gam[m], gx[m] * inv_mean, 1.f) * INV_2KZ * rho, row_scale(rmax[m]));
                asm volatile("st.shared.u16 [%0], %1;" ::"r"(s_fac + (i0 + 128 * m) * 2), "h"((unsigned short)pack_h2(f, 0.f)) : "memory");
            }
            if (i0 < 96) sts32(sb + SM_BIASH + i0 * 4, pack_h2(bpair.x * rho, bpair.y * rho));
            if (i0 == 96) sts32(s_red + 52, inv_rho2);
            named_arrive(12, NTHREADS);
        };
        uint32_t gl[4][12] = {};
        const uint4* src = &sc->lent[(blockIdx.x * LENT * 8 * 4 + w4) * 96 + lane];
        auto fetch = [&](uint32_t (&v)[12], int c, bool on) {
#pragma unroll
            for (int s = 0; s < 3; s++) ldg128_if(on, reinterpret_cast<uint32_t (&)[4]>(v[4 * s]), src + c * 384 + s * 32);
        };
        if (__builtin_expect(wk.lent, 0)) {
            first = 4;
            tile_off = tile_offset(wk.tA);
            stage_x();
            if (elect_one()) prefetch_l2(reinterpret_cast<const char*>(x) + tile_offset(wk.tA + 1) + w4 * WARP_BYTES, WARP_BYTES);
            spin_until(&sc->lent_out, (epoch + 1) * 32 * LENT * lenders);
#pragma unroll
            for (int c = 0; c < 3; c++) fetch(gl[c], c, true);
        }
        lds32(next_off, sb + SM_TILES + first * 4);
        if (!wk.lent) load_first();
        grn();
        if (__builtin_expect(wk.lent, 0)) {
            named_bar(3, NTHREADS);
#pragma unroll 1
            for (int e = 0; e < LENT; e++) {
                load_bias(acc);
#define CNX_LENT(C)                                  \
    pin(gl[C % 4]);                                  \
    wg_fence();                                      \
    gemm2_chunk<48 * C>(acc, gl[C % 4], ds);         \
    wg_commit();                                     \
    wg_wait<(C < 7 ? 1 : 0)>();                      \
    fetch(gl[(C + 3) % 4], C + 3, C < 5 || e == 0);  \
    if (lane == 0) mbar_arrive(sb + BAR_PIN);
                CNX_LENT(0) CNX_LENT(1) CNX_LENT(2) CNX_LENT(3) CNX_LENT(4) CNX_LENT(5) CNX_LENT(6) CNX_LENT(7)
#undef CNX_LENT
                src += 8 * 384;
                mbar_wait(bar_r, rpar);
                epilogue(acc);
                tile_off = tile_offset(wk.tA + 1);
                if (e == 0) stage_x();
            }
            load_first();
        }
    } else {
        {
            if (!(cw & 1) && elect_one()) {
                mbar_init(sb + BAR_W + (cw >> 1) * 8, 1);
                fence_async();
                mbar_expect_tx(sb + BAR_W + (cw >> 1) * 8, 64 * CH * 2);
                tma_2d(sb + SM_W2 + (cw >> 1) * (64 * CH * 2), &tmap_w1, sb + BAR_W + (cw >> 1) * 8, 32 * cw, 0);
            }
            __syncwarp();
            const int ct = tid - 128, lane = tid & 31;
            const unsigned epoch = *reinterpret_cast<volatile unsigned*>(&sc->launch);
            const int r = lane & 7, mi = lane >> 3;
            const uint32_t src = sb + SM_W2 + (cw >> 1) * (64 * CH * 2) + r * 128 + ((((cw & 1) * 4 + mi) ^ r) * 16);
            const uint32_t dst = sb + SM_W1 + (4 * cw + mi) * 1536 + r * 16;
            named_bar(0, NTHREADS);
            mbar_wait(sb + BAR_W + (cw >> 1) * 8, 0);
            uint32_t wmax[4] = {}, wsum[4] = {};
#pragma unroll 3
            for (int c = 0; c < 12; c++) {
                uint32_t u[4];
                ldsm4_t(u, src + c * 1024);
#pragma unroll
                for (int q = 0; q < 4; q++) {
                    wmax[q] = bf_absmax(wmax[q], u[q]);
                    wsum[q] = bf_fma(u[q], 0x3f803f80u, wsum[q]);
                    u[q] = pack_h2(bf_lo(u[q]), bf_hi(u[q]));
                }
                stsm4(dst + c * 128, u[0], u[1], u[2], u[3]);
            }
            float mean[4];
            bool center = false;
#pragma unroll
            for (int q = 0; q < 4; q++) {
                uint32_t m = wmax[q];
                float sum = bf_lo(wsum[q]) + bf_hi(wsum[q]);
#pragma unroll
                for (int o = 1; o <= 2; o <<= 1) { m = bf_absmax(m, __shfl_xor_sync(~0u, m, o)); sum += __shfl_xor_sync(~0u, sum, o); }
                mean[q] = sum * (1.f / CH);
                center |= fabsf(mean[q]) > 0.2f * fmaxf(fabsf(bf_lo(m)), fabsf(bf_hi(m)));
            }
            if (__builtin_expect(__any_sync(~0u, center), 0)) {
#pragma unroll 1
                for (int pass = 0; pass < 2; pass++) {
                    float sum[4] = {};
#pragma unroll 1
                    for (int c = 0; c < 12; c++) {
                        uint32_t u[4];
                        ldsm4_t(u, src + c * 1024);
#pragma unroll
                        for (int q = 0; q < 4; q++) {
                            sum[q] += bf_lo(u[q]) + bf_hi(u[q]);
                            u[q] = pack_h2(bf_lo(u[q]) - mean[q], bf_hi(u[q]) - mean[q]);
                        }
                        stsm4(dst + c * 128, u[0], u[1], u[2], u[3]);
                    }
#pragma unroll
                    for (int q = 0; q < 4; q++) {
                        sum[q] += __shfl_xor_sync(~0u, sum[q], 1);
                        sum[q] += __shfl_xor_sync(~0u, sum[q], 2);
                        mean[q] = sum[q] * (1.f / CH);
                    }
                }
            }
            const float w1max = warp_absmax(bf_absmax(bf_absmax(wmax[0], wmax[1]), bf_absmax(wmax[2], wmax[3])));
            if (lane == 0) sts32(s_red + cw * 4, __float_as_uint(w1max));
            if (ct < 32) sts32(sb + SM_ONES + ct * 4, 0x3f803f80u);
            if (ct < 48) sts32(sb + SM_BIASH + ct * 4, 0);
            if (blockIdx.x == 0) {
                *sc->sum(epoch + 1, ct) = 0;
                if (ct < CH) sc->bias[(epoch & 1) ^ 1][ct] = 0.f;
            }
            if (ct == 0) sts32(s_red + 48, epoch);
            fence_async();
            named_bar(2, CONS_THREADS);
#pragma unroll
            for (int q = 0; q < 12; q++) sts128(sb + SM_SQ + (wgi + q / 6 * NCONS) * SQ_WG + q % 6 * SQ_ROW + (ct & 127) * 16, 0, 0, 0, 0);
            mbar_wait(sb + BAR_A + w4 * 8 + 32, 0);
        }

        PROF(1);
        const uint32_t a_addr = opaque(sb + SM_RING + w4 * REGION_BYTES + ((tid >> 3) & 1) * A_SBO + ((tid >> 4) & 1) * A_LBO + (tid & 7) * 16);
        const uint32_t bar_a = sb + BAR_A + w4 * 8, bar_e = sb + BAR_E + w4 * 8;
        const uint32_t sq = opaque(sb + SM_SQ + wgi * SQ_WG + (tid & 127) * 16);
        const uint32_t sq_warp = sb + SM_SQ + wgi * SQ_WG + w4 * 512;
        uint32_t k1[24], k2[24], k3[24];
        constexpr int SQC = 3 * SQ_ROW;
        const int pass_to = 4 + (wgi == NCONS - 1 ? 0 : wgi + 1);
        auto store_frags = [&](const uint32_t (&a)[6][4], int j) {
            char* ap = reinterpret_cast<char*>(out) + (tile_offset(wk.tile(j)) + w4 * WARP_BYTES - sq_warp + sq);
#pragma unroll
            for (int s = 0; s < 6; s++) stg128(ap + s * 512, a[s]);
        };
        int jt = wgi < wk.lent ? wgi : wk.lent + wgi;
        Cursor cur = {2, 0};
        cur.advance(jt + (jt >= wk.nA ? 2 : 0));
        if (wgi == NCONS - 1) named_arrive(4, 256);
        for (;;) {
            const bool plain = __all_sync(~0u, square_exp(max_w1()) == 0);
            if (plain && jt >= wk.lent) {
                uint32_t hs2[12] = {}, hs3[12] = {};
#pragma unroll 1
                for (; jt + NCONS < ntiles; jt += NCONS) {
                    uint32_t a[6][4], d0[24], d1[24], unused[24];
#define AT(pos) \
    if (K_WAIT == pos) named_bar(4 + wgi, 256); \
    if (K_PASS == pos) named_arrive(pass_to, 256); \
    if (K_STG == pos) store_frags(a, jt); \
    if (K_REL == pos) { if (elect_one()) mbar_arrive(bar_e + cur.slot * 32); }
                    AT(20)
                    mbar_wait(bar_a + cur.slot * 32, cur.par);
                    load_tile(a, a_addr + cur.slot * SLOT_BYTES);
                    AT(21)
                    const uint2 st = ln_stats(a, ds.ones);
                    AT(0)
                    ln_apply(a, st);
                    AT(1)
                    wg_fence();
                    gemm1_chunk<0>(d0, a, ds, 0);
                    wg_commit();
                    gemm1_chunk<96>(d1, a, ds, 0);
                    wg_commit();
                    AT(2)
                    wg_wait<1>();
                    AT(3)
                    gelu_sq<false, 0, 1>(d0, unused, sq, 0);
                    AT(4)
                    gelu_sq<false, 1, 2>(d0, unused, sq, 0);
                    AT(5)
                    gelu_sq<false, 2, 3>(d0, unused, sq, 0);
                    AT(6)
                    wg_fence();
                    gemm1_chunk<192>(d0, a, ds, zero);
                    wg_commit();
                    AT(7)
                    wg_wait<1>();
                    gelu_sq<false, 0, 1>(d1, unused, sq + SQC, 0);
                    AT(8)
                    gelu_sq<false, 1, 3>(d1, unused, sq + SQC, 0);
                    AT(9)
                    wg_fence();
                    gemm1_chunk<288>(d1, a, ds, zero);
                    wg_commit();
                    AT(10)
                    wg_wait<1>();
                    gelu_sq_reg(d0, hs2);
                    if (K_ANCH < 3) anchor(sq, hs2[4 * (K_ANCH % 3)], hs2[4 * (K_ANCH % 3) + 1], hs2[4 * (K_ANCH % 3) + 2], hs2[4 * (K_ANCH % 3) + 3]);
                    wg_wait<0>();
                    AT(11)
                    gelu_sq_reg(d1, hs3);
#undef AT
                    cur.advance(NCONS + ((jt < wk.nA && jt + NCONS >= wk.nA) ? 2 : 0));
                }
                const uint32_t sq2 = sq - (SM_SQ + wgi * SQ_WG) + SM_RING + (cur.slot + 3) % NSLOT * SLOT_BYTES;
#pragma unroll
                for (int k = 0; k < 3; k++) {
                    sts128(sq2 + k * SQ_ROW, hs2[4 * k], hs2[4 * k + 1], hs2[4 * k + 2], hs2[4 * k + 3]);
                    sts128(sq2 + SQC + k * SQ_ROW, hs3[4 * k], hs3[4 * k + 1], hs3[4 * k + 2], hs3[4 * k + 3]);
                }
            }
            const bool last = jt + NCONS >= ntiles;
            uint32_t a[6][4], d0[24], d1[24], d3[24], k0[24];
#define AT(pos) \
    if (K_WAIT == pos && jt >= wk.lent) named_bar(4 + wgi, 256); \
    if (K_PASS == pos && jt >= wk.lent && jt + 1 < ntiles) named_arrive(pass_to, 256);
            AT(20)
            mbar_wait(bar_a + cur.slot * 32, cur.par);
            load_tile(a, a_addr + cur.slot * SLOT_BYTES);
            AT(21)
            const uint2 st = ln_stats(a, ds.ones);
            AT(0)
            ln_apply(a, st);
            AT(1)
            if (!last) {
                store_frags(a, jt);
                __syncwarp();
                if (elect_one()) mbar_arrive(bar_e + cur.slot * 32);
                if (jt < wk.lent) {
                    jt += LENT;
                    cur.advance(LENT);
                    continue;
                }
            }
            wg_fence();
            gemm1_chunk<0>(d0, a, ds, 0);
            wg_commit();
            gemm1_chunk<96>(d1, a, ds, 0);
            wg_commit();
            const int sq_e = square_exp(max_w1());
            const uint32_t scale2 = pack_h2(pow2i(sq_e), pow2i(sq_e));
            stage = sb + SM_RING + cur.slot * SLOT_BYTES + w4 * REGION_BYTES;
            AT(2)
            wg_wait<1>();
            AT(3)
            gelu_sq<true, 0, 1>(d0, k0, sq, scale2);
            AT(4)
            gelu_sq<true, 1, 2>(d0, k0, sq, scale2);
            AT(5)
            gelu_sq<true, 2, 3>(d0, k0, sq, scale2);
            AT(6)
            if (last) {
#pragma unroll
                for (int q = 0; q < 6; q++) sts128(stage - sq_warp + sq + q * 512, k0[4 * q], k0[4 * q + 1], k0[4 * q + 2], k0[4 * q + 3]);
            }
            wg_fence();
            gemm1_chunk<192>(d0, a, ds, zero);
            wg_commit();
            AT(7)
            wg_wait<1>();
            gelu_sq<true, 0, 1>(d1, k1, sq + SQC, scale2);
            AT(8)
            gelu_sq<true, 1, 3>(d1, k1, sq + SQC, scale2);
            AT(9)
#undef AT
            wg_fence();
            gemm1_chunk<288>(d3, a, ds, 0);
            wg_commit();
            wg_wait<1>();
            const uint32_t sq2 = sq + (plain ? SM_RING + (cur.slot + 3) % NSLOT * SLOT_BYTES - (SM_SQ + wgi * SQ_WG) : NCONS * SQ_WG);
            gelu_sq<true>(d0, k2, sq2, scale2);
            wg_wait<0>();
            gelu_sq<true>(d3, k3, sq2 + SQC, scale2);
            if (last) break;
            cur.advance(NCONS + ((jt < wk.nA && jt + NCONS >= wk.nA) ? 2 : 0));
            jt += NCONS;
        }
        {
            if (wgi == last_wg) {
                named_arrive(14, NTHREADS);
            } else {
                reduce(cw, (sq >> 4) & 31, false);
                named_arrive(15, CONS_THREADS);
            }
        }
        PROF(2);
        tile_off = tile_offset(wk.tile(jt));
        {
            set_lane((sq >> 4) & 31);
            if (elect_one()) prefetch_l2(reinterpret_cast<const char*>(x) + tile_off + w4 * WARP_BYTES, WARP_BYTES);
            const uint32_t row = sb + SM_W2 + cw * 512 + lane16;
            uint32_t u[W2_EARLY][4], f2[4];
            mbar_wait(sb + BAR_W, 1);
#pragma unroll
            for (int nb = 0; nb < W2_EARLY; nb++) lds128(u[nb][0], u[nb][1], u[nb][2], u[nb][3], row + nb * 6144);
            named_bar(12, NTHREADS);
            PROF(3);
            lds128(f2[0], f2[1], f2[2], f2[3], s_fac + cw * 64 + (lane16 >> 7) * 16);
            lds32(inv_rho2, s_red + 52);
#pragma unroll
            for (int nb = 0; nb < 12; nb++) {
                uint32_t v[4];
                if (nb < W2_EARLY) { v[0] = u[nb % W2_EARLY][0]; v[1] = u[nb % W2_EARLY][1]; v[2] = u[nb % W2_EARLY][2]; v[3] = u[nb % W2_EARLY][3]; }
                else lds128(v[0], v[1], v[2], v[3], row + nb * 6144);
                sts128(row + nb * 6144, h_round8(h_mul(v[0], f2[0])), h_round8(h_mul(v[1], f2[1])), h_round8(h_mul(v[2], f2[2])), h_round8(h_mul(v[3], f2[3])));
            }
            fence_async();
            named_bar(3, NTHREADS);
        }
        PROF(4);
        {
            load_bias(acc);
            lds32(next_off, sb + SM_TILES + wg * 4);
            if (wgi > 0) named_bar(8 + wgi, 256);
            pin(k1); pin(k2); pin(k3);
            wg_fence();
            gemm2_chunk<288>(acc, k3, ds);
            wg_commit();
            gemm2_chunk<96>(acc, k1, ds);
            gemm2_chunk<192>(acc, k2, ds);
            wg_commit();
            if (wgi + 1 < NCONS) named_arrive(9 + wgi, 256);
            wg_wait<1>();
            uint32_t k0[24];
#pragma unroll
            for (int q = 0; q < 6; q++) lds128(k0[4 * q], k0[4 * q + 1], k0[4 * q + 2], k0[4 * q + 3], stage + lane16 + q * 512);
            pin(k0);
            wg_fence();
            gemm2_chunk<0>(acc, k0, ds);
            wg_commit();
            stage_x();
            wg_wait<1>();
            load_first();
            if (lane16 == 0) mbar_arrive(sb + BAR_PIN);
            mbar_wait(bar_r, rpar);
            wg_wait<0>();
            first = wg - 4;
        }
    }
    {
        const int nrest = ntiles - NCONS - wk.lent / 2;
        for (int jt = first; jt < nrest; jt += 4) {
            if (jt >= 0) {
            uint32_t d0[12], d1[12], g0[12], g1[12];
            tile_off = next_off;
            lds32(next_off, sb + SM_TILES + (jt + 4) * 4);
            if (jt >= S2_FIRST) named_bar(4 + wg, 256);
            wg_fence();
            gemm1_chunk<0>(d0, a, ds, 0);
            wg_commit();
            gemm1_chunk<48>(d1, a, ds, 0);
            wg_commit();
            load_bias(acc);
            const bool more = jt + 4 < nrest;
            tile_off = __shfl_sync(~0u, tile_off, 0);
            next_off = __shfl_sync(~0u, next_off, 0);
            wg_wait<1>();
#define CNX_PASS if (jt + 1 >= S2_FIRST && jt + 1 < nrest) named_arrive(4 + ((wg + 1) & 3), 256);
#define CNX_STEP(C, D, G)                                              \
    gelu_to(G, D);                                                     \
    if (C == 0 && jt == 0) {                                           \
        named_bar(3, NTHREADS);                                        \
        load_bias(acc);                                                \
    }                                                                  \
    wg_fence();                                                        \
    if (C < 6) gemm1_chunk<48 * (C < 6 ? C + 2 : 0)>(D, a, ds, zero); \
    gemm2_chunk<48 * C>(acc, G, ds);                                  \
    wg_commit();                                                       \
    if (C == S2_PASS) { CNX_PASS }                                     \
    wg_wait<(C < 7 ? 1 : 0)>();
            CNX_STEP(0, d0, g0)
            stage_x();
            if (more && elect_one()) prefetch_l2(reinterpret_cast<const char*>(out) + next_off + w4 * WARP_BYTES, WARP_BYTES);
            CNX_STEP(1, d1, g1)
            CNX_STEP(2, d0, g0)
            CNX_STEP(3, d1, g1)
            CNX_STEP(4, d0, g0)
            CNX_STEP(5, d1, g1)
            CNX_STEP(6, d0, g0)
            load_frags(more);
            if (lane16 == 0) mbar_arrive(sb + BAR_PIN);
            mbar_wait(bar_r, rpar);
            CNX_STEP(7, d1, g1)
#undef CNX_STEP
            }
            epilogue(acc);
        }
    }
    PROF(5);
}

}

typedef CUresult (*EncodeTiledFn)(CUtensorMap*, CUtensorMapDataType, cuuint32_t, void*, const cuuint64_t*, const cuuint64_t*,
                                  const cuuint32_t*, const cuuint32_t*, CUtensorMapInterleave, CUtensorMapSwizzle,
                                  CUtensorMapL2promotion, CUtensorMapFloatOOBfill);

extern "C" void kernel_launch(void* const* d_in, const int* in_sizes, int n_in, void* d_out, int out_size) {
    using namespace cnx;
    static EncodeTiledFn encode = nullptr;
    static int num_sms = 0;
    static Scratch* scratch = nullptr;
    if (!encode) {
        void* fn = nullptr;
        cudaDriverEntryPointQueryResult qr;
        cudaGetDriverEntryPoint("cuTensorMapEncodeTiled", &fn, cudaEnableDefault, &qr);
        encode = (EncodeTiledFn)fn;
        cudaGetSymbolAddress((void**)&scratch, g_scratch);
        int dev = 0;
        cudaGetDevice(&dev);
        cudaDeviceGetAttribute(&num_sms, cudaDevAttrMultiProcessorCount, dev);
        if (num_sms > MAX_CTAS) num_sms = MAX_CTAS;
        cudaFuncSetAttribute(block_kernel, cudaFuncAttributeMaxDynamicSharedMemorySize, SM_TOTAL);
    }
    CUtensorMap tm;
    cuuint64_t dims[3] = {(cuuint64_t)CH, (cuuint64_t)IMG_W, (cuuint64_t)IMG_H};
    cuuint64_t strides[2] = {(cuuint64_t)CH * 2, (cuuint64_t)CH * 2 * IMG_W};
    cuuint32_t box[3] = {(cuuint32_t)CH, (cuuint32_t)REGION_PX, 1};
    cuuint32_t estr[3] = {1, 1, 1};
    encode(&tm, CU_TENSOR_MAP_DATA_TYPE_BFLOAT16, 3, d_in[0], dims, strides, box, estr, CU_TENSOR_MAP_INTERLEAVE_NONE,
           CU_TENSOR_MAP_SWIZZLE_NONE, CU_TENSOR_MAP_L2_PROMOTION_L2_128B, CU_TENSOR_MAP_FLOAT_OOB_FILL_NONE);
    Descs ds;
    for (int c = 0; c < 8; c++)
        for (int k = 0; k < 6; k++) ds.w1[c][k] = make_desc(SB + SM_W1 + c * 6 * 1536 + k * 256, 128, 1536);
    for (int k = 0; k < 24; k++) ds.w2[k] = make_desc(SB + SM_W2 + k * 256, 128, 6144);
    ds.ones = make_desc(SB + SM_ONES, 0, 0);
    CUtensorMap tw;
    cuuint64_t wdims[2] = {(cuuint64_t)EX, (cuuint64_t)CH};
    cuuint64_t wstrides[1] = {(cuuint64_t)EX * 2};
    cuuint32_t wbox[2] = {64, (cuuint32_t)CH};
    encode(&tw, CU_TENSOR_MAP_DATA_TYPE_BFLOAT16, 2, d_in[2], wdims, wstrides, wbox, estr, CU_TENSOR_MAP_INTERLEAVE_NONE,
           CU_TENSOR_MAP_SWIZZLE_128B, CU_TENSOR_MAP_L2_PROMOTION_L2_128B, CU_TENSOR_MAP_FLOAT_OOB_FILL_NONE);
    const int per_cta = NTILES / num_sms, extra = NTILES % num_sms;
    const int lenders = extra * (8 * LENT + 1) <= num_sms && extra * (per_cta + 1) <= IMG_H ? extra : 0;
    block_kernel<<<num_sms, NTHREADS, SM_TOTAL>>>(tm, tw, (const __nv_bfloat16*)d_in[0], (const __nv_bfloat16*)d_in[1],
                                             (const __nv_bfloat16*)d_in[3],
                                             (const __nv_bfloat16*)d_in[4], (const __nv_bfloat16*)d_in[5], (__nv_bfloat16*)d_out,
                                             scratch, ds, 0, per_cta, extra, lenders);
}
```

```cpp
#include <cuda_runtime.h>
#include <cuda_bf16.h>
#include <cuda_fp16.h>
#include <cuda.h>
#include <stdint.h>

namespace cnx {

constexpr int IMG_H = 512, IMG_W = 512, CH = 96, EX = 384;
constexpr int TILE_W = 64;
constexpr int NTILES = (IMG_W / TILE_W) * IMG_H;
constexpr int NSLOT = 6;
constexpr int REGION_PX = 18;
constexpr int REGION_BYTES = REGION_PX * CH * 2;
constexpr int SLOT_BYTES = 4 * REGION_BYTES;
constexpr int A_LBO = 144, A_SBO = 12 * A_LBO;
constexpr int PREFETCH_ROWS = 3;
constexpr int NCONS = 3;
constexpr int CONS_THREADS = 128 * NCONS;
constexpr int NTHREADS = 128 + CONS_THREADS;
constexpr int MAX_ROWS = 52;
constexpr int TILE_BYTES = TILE_W * CH * 2, WARP_BYTES = TILE_BYTES / 4;
constexpr int S1_PASS = 1, S2_PASS = 1;
#define K_PASS 4
#define K_WAIT 20
#define K_STG 6
#define K_REL 6
#define K_ANCH 2
#define K_CVT 0
#define W2_EARLY 6
#define S2_FIRST 4
#define ORDER_P 3
#define ORDER_Q 1
static_assert(MAX_ROWS <= 128, "one table entry per producer thread");
static_assert(2 * A_SBO == REGION_BYTES && REGION_BYTES % 128 == 0, "region layout");

constexpr uint32_t SB = 1024;
constexpr int SM_W1 = 0;
constexpr int SM_W2 = SM_W1 + CH * EX * 2;
constexpr int SM_RING = SM_W2 + CH * EX * 2;
constexpr int SM_BIASH = SM_RING + NSLOT * SLOT_BYTES;
constexpr int SM_RED = SM_BIASH + 384;
constexpr int SM_ROWS = SM_RED + 256;
constexpr int SM_TILES = SM_ROWS + MAX_ROWS * 4;
constexpr int SM_ONES = SM_TILES + MAX_ROWS * 4;
constexpr int SM_BAR = SM_ONES + 128;
constexpr int BAR_X = SM_BAR;
constexpr int BAR_A = BAR_X + NSLOT * 4 * 8;
constexpr int BAR_E = BAR_A + NSLOT * 4 * 8;
constexpr int BAR_PIN = BAR_E + NSLOT * 4 * 8;
constexpr int BAR_W = BAR_PIN + 8;
constexpr int BAR_F = BAR_W + 6 * 8;
constexpr int BAR_R = BAR_F + 8;
constexpr int SM_TOTAL = BAR_R + 16 * 8;
constexpr int SM_FILTER = SM_RING + (NSLOT - 1) * SLOT_BYTES + 9 * 128;
constexpr int SM_SQ = SM_W2;
constexpr int SQ_ROW = 128 * 16, SQ_WG = 6 * SQ_ROW;
static_assert(SM_ONES % 16 == 0 && SM_TOTAL <= 232448, "shared memory budget");

constexpr float KZ = 0.3292034911525734f;
constexpr uint32_t GELU_C2 = 0x40d940d9u;
constexpr float INV_2KZ = 0.5f / KZ;
constexpr unsigned SPIN_LIMIT = 1u << 19;

constexpr int MAX_CTAS = 255;
constexpr int W2_GROUPS = EX / 8;
constexpr int LENT = 2, MAX_LENDERS = MAX_CTAS / (8 * LENT + 1);
struct Scratch {
    uint32_t w2h[EX * CH / 2];
    float w2max[EX];
    float bias[2][CH];
    unsigned long long sums[2][EX / 4][32];
    __device__ __forceinline__ unsigned long long* sum(unsigned launch, int e) { return &sums[launch & 1][e >> 2][e & 3]; }
    uint4 lent[MAX_LENDERS * LENT * 8 * 4 * 3 * 32];
    unsigned launch, pad0[31], prep, pad1[31], lent_in, pad2[31], lent_out, pad3[31];
};
__device__ __align__(128) Scratch g_scratch;

#define PROF(k)

__device__ __forceinline__ uint32_t smem_u32(const void* p) { return (uint32_t)__cvta_generic_to_shared(p); }
__device__ __forceinline__ void mbar_init(uint32_t bar, uint32_t cnt) {
    asm volatile("mbarrier.init.shared::cta.b64 [%0], %1;" ::"r"(bar), "r"(cnt) : "memory");
}
__device__ __forceinline__ void mbar_arrive(uint32_t bar) {
    asm volatile("mbarrier.arrive.shared::cta.b64 _, [%0];" ::"r"(bar) : "memory");
}
__device__ __forceinline__ void mbar_expect_tx(uint32_t bar, uint32_t bytes) {
    asm volatile("mbarrier.arrive.expect_tx.shared::cta.b64 _, [%0], %1;" ::"r"(bar), "r"(bytes) : "memory");
}
__device__ __forceinline__ bool mbar_try(uint32_t bar, uint32_t par) {
    uint32_t ok;
    asm volatile("{\n.reg .pred p;\nmbarrier.try_wait.parity.shared::cta.b64 p, [%1], %2;\nselp.u32 %0, 1, 0, p;\n}\n"
                 : "=r"(ok) : "r"(bar), "r"(par) : "memory");
    return ok != 0;
}
__device__ __forceinline__ void mbar_wait(uint32_t bar, uint32_t par) {
    unsigned n = 0;
    while (!mbar_try(bar, par)) {
        if (++n > SPIN_LIMIT) __trap();
    }
}
__device__ __forceinline__ bool mbar_test(uint32_t bar, uint32_t par) {
    uint32_t ok;
    asm volatile("{\n.reg .pred p;\nmbarrier.test_wait.parity.shared::cta.b64 p, [%1], %2;\nselp.u32 %0, 1, 0, p;\n}\n"
                 : "=r"(ok) : "r"(bar), "r"(par) : "memory");
    return ok != 0;
}
__device__ __forceinline__ bool elect_one() {
    uint32_t ok;
    asm volatile("{\n.reg .pred p;\nelect.sync _|p, 0xffffffff;\nselp.u32 %0, 1, 0, p;\n}\n" : "=r"(ok));
    return ok != 0;
}
__device__ __forceinline__ uint32_t opaque(uint32_t v) { return __shfl_sync(~0u, v, threadIdx.x & 31); }
__device__ __forceinline__ void named_bar(int id, int n) { asm volatile("bar.sync %0, %1;" ::"r"(id), "r"(n) : "memory"); }
__device__ __forceinline__ void named_arrive(int id, int n) { asm volatile("bar.arrive %0, %1;" ::"r"(id), "r"(n) : "memory"); }
__device__ __forceinline__ void fence_async() { asm volatile("fence.proxy.async.shared::cta;" ::: "memory"); }
__device__ __forceinline__ uint64_t evict_first() {
    uint64_t p;
    asm("createpolicy.fractional.L2::evict_first.b64 %0, 1.0;" : "=l"(p));
    return p;
}
__device__ __forceinline__ void tma_row(uint32_t dst, const CUtensorMap* tm, uint32_t bar, int x, int y) {
    asm volatile("cp.async.bulk.tensor.3d.shared::cluster.global.mbarrier::complete_tx::bytes.L2::cache_hint [%0], [%1, {%3, %4, %5}], [%2], %6;"
                 ::"r"(dst), "l"(tm), "r"(bar), "r"(0), "r"(x), "r"(y), "l"(evict_first()) : "memory");
}
__device__ __forceinline__ void bulk_load_stream(uint32_t dst, const void* src, uint32_t bytes, uint32_t bar) {
    asm volatile("cp.async.bulk.shared::cluster.global.mbarrier::complete_tx::bytes.L2::cache_hint [%0], [%1], %2, [%3], %4;"
                 ::"r"(dst), "l"(src), "r"(bytes), "r"(bar), "l"(evict_first()) : "memory");
}
__device__ __forceinline__ void prefetch_l2(const void* src, uint32_t bytes) {
    asm volatile("cp.async.bulk.prefetch.L2.global [%0], %1;" ::"l"(src), "r"(bytes) : "memory");
}
__device__ __forceinline__ void tma_2d(uint32_t dst, const CUtensorMap* tm, uint32_t bar, int x, int y) {
    asm volatile("cp.async.bulk.tensor.2d.shared::cluster.global.mbarrier::complete_tx::bytes [%0], [%1, {%3, %4}], [%2];"
                 ::"r"(dst), "l"(tm), "r"(bar), "r"(x), "r"(y) : "memory");
}
__device__ __forceinline__ void bulk_load(uint32_t dst, const void* src, uint32_t bytes, uint32_t bar) {
    asm volatile("cp.async.bulk.shared::cluster.global.mbarrier::complete_tx::bytes [%0], [%1], %2, [%3];"
                 ::"r"(dst), "l"(src), "r"(bytes), "r"(bar) : "memory");
}
__device__ __forceinline__ void wg_fence() { asm volatile("wgmma.fence.sync.aligned;" ::: "memory"); }
__device__ __forceinline__ void wg_commit() { asm volatile("wgmma.commit_group.sync.aligned;" ::: "memory"); }
template <int N> __device__ __forceinline__ void wg_wait() { asm volatile("wgmma.wait_group.sync.aligned %0;" ::"n"(N) : "memory"); }
template <int N> __device__ __forceinline__ void pin(uint32_t (&d)[N]) {
#pragma unroll
    for (int q = 0; q < N; q++) asm volatile("" : "+r"(d[q])::"memory");
}
__device__ __forceinline__ void stg128(void* p, const uint32_t (&v)[4]) {
    asm volatile("st.global.v4.u32 [%0], {%1, %2, %3, %4};" ::"l"(p), "r"(v[0]), "r"(v[1]), "r"(v[2]), "r"(v[3]) : "memory");
}
__device__ __forceinline__ void ldg128(uint32_t (&v)[4], const void* p) {
    asm volatile("ld.global.L1::no_allocate.v4.u32 {%0, %1, %2, %3}, [%4];" : "=r"(v[0]), "=r"(v[1]), "=r"(v[2]), "=r"(v[3]) : "l"(p) : "memory");
}
__device__ __forceinline__ void ldg128_if(bool on, uint32_t (&v)[4], const void* p) {
    asm volatile("{\n.reg .pred p;\nsetp.ne.b32 p, %5, 0;\n@p ld.global.L1::no_allocate.v4.u32 {%0, %1, %2, %3}, [%4];\n}\n"
                 : "+r"(v[0]), "+r"(v[1]), "+r"(v[2]), "+r"(v[3]) : "l"(p), "r"((int)on) : "memory");
}
__device__ __forceinline__ uint4 ldg128_ordered(const void* p) {
    uint4 v;
    asm volatile("ld.global.nc.v4.u32 {%0, %1, %2, %3}, [%4];" : "=r"(v.x), "=r"(v.y), "=r"(v.z), "=r"(v.w) : "l"(p) : "memory");
    return v;
}
__host__ __device__ constexpr uint64_t make_desc(uint32_t addr, uint32_t lbo, uint32_t sbo) {
    return (uint64_t)((addr & 0x3FFFF) >> 4) | ((uint64_t)(lbo >> 4) << 16) | ((uint64_t)(sbo >> 4) << 32);
}
__device__ __forceinline__ void wgmma(uint32_t (&d)[12], uint32_t a0, uint32_t a1, uint32_t a2, uint32_t a3, uint64_t db, int acc) {
    asm volatile("{\n.reg .pred p;\nsetp.ne.b32 p, %17, 0;\n"
                 "wgmma.mma_async.sync.aligned.m64n48k16.f16.f16.f16 "
                 "{%0, %1, %2, %3, %4, %5, %6, %7, %8, %9, %10, %11}, "
                 "{%12, %13, %14, %15}, %16, p, 1, 1, 0;\n}\n"
                 : "+r"(d[0]), "+r"(d[1]), "+r"(d[2]), "+r"(d[3]), "+r"(d[4]), "+r"(d[5]), "+r"(d[6]), "+r"(d[7]), "+r"(d[8]), "+r"(d[9]), "+r"(d[10]), "+r"(d[11])
                 : "r"(a0), "r"(a1), "r"(a2), "r"(a3), "l"(db), "r"(acc));
}
__device__ __forceinline__ void wgmma(uint32_t (&d)[24], uint32_t a0, uint32_t a1, uint32_t a2, uint32_t a3, uint64_t db, int acc) {
    asm volatile("{\n.reg .pred p;\nsetp.ne.b32 p, %29, 0;\n"
                 "wgmma.mma_async.sync.aligned.m64n96k16.f16.f16.f16 "
                 "{%0, %1, %2, %3, %4, %5, %6, %7, %8, %9, %10, %11, %12, %13, %14, %15, %16, %17, %18, %19, %20, %21, %22, %23}, "
                 "{%24, %25, %26, %27}, %28, p, 1, 1, 0;\n}\n"
                 : "+r"(d[0]), "+r"(d[1]), "+r"(d[2]), "+r"(d[3]), "+r"(d[4]), "+r"(d[5]), "+r"(d[6]), "+r"(d[7]), "+r"(d[8]), "+r"(d[9]), "+r"(d[10]), "+r"(d[11]), "+r"(d[12]), "+r"(d[13]), "+r"(d[14]), "+r"(d[15]), "+r"(d[16]), "+r"(d[17]), "+r"(d[18]), "+r"(d[19]), "+r"(d[20]), "+r"(d[21]), "+r"(d[22]), "+r"(d[23])
                 : "r"(a0), "r"(a1), "r"(a2), "r"(a3), "l"(db), "r"(acc));
}
template <int ACC>
__device__ __forceinline__ void wgmma_rowsum(float (&d)[4], const uint32_t (&a)[4], uint64_t ones) {
    asm volatile("{\n.reg .pred p;\nsetp.ne.b32 p, %9, 0;\n"
                 "wgmma.mma_async.sync.aligned.m64n8k16.f32.bf16.bf16 {%0, %1, %2, %3}, {%4, %5, %6, %7}, %8, p, 1, 1, 0;\n}\n"
                 : "+f"(d[0]), "+f"(d[1]), "+f"(d[2]), "+f"(d[3])
                 : "r"(a[0]), "r"(a[1]), "r"(a[2]), "r"(a[3]), "l"(ones), "n"(ACC));
}
__device__ __forceinline__ void ldsm4(uint32_t (&r)[4], uint32_t addr) {
    asm volatile("ldmatrix.sync.aligned.m8n8.x4.shared.b16 {%0, %1, %2, %3}, [%4];"
                 : "=r"(r[0]), "=r"(r[1]), "=r"(r[2]), "=r"(r[3]) : "r"(addr) : "memory");
}
__device__ __forceinline__ void ldsm4_t(uint32_t (&r)[4], uint32_t addr) {
    asm volatile("ldmatrix.sync.aligned.m8n8.x4.trans.shared.b16 {%0, %1, %2, %3}, [%4];"
                 : "=r"(r[0]), "=r"(r[1]), "=r"(r[2]), "=r"(r[3]) : "r"(addr) : "memory");
}
__device__ __forceinline__ void stsm4(uint32_t addr, uint32_t a, uint32_t b, uint32_t c, uint32_t d) {
    asm volatile("stmatrix.sync.aligned.m8n8.x4.shared.b16 [%0], {%1, %2, %3, %4};"
                 ::"r"(addr), "r"(a), "r"(b), "r"(c), "r"(d) : "memory");
}
__device__ __forceinline__ uint32_t transpose8x8(uint32_t v) {
    uint32_t d; asm volatile("movmatrix.sync.aligned.m8n8.trans.b16 %0, %1;" : "=r"(d) : "r"(v)); return d;
}
__device__ __forceinline__ void spin_until(const unsigned* counter, unsigned target) {
    unsigned n = 0, c;
    do {
        asm volatile("ld.acquire.gpu.global.u32 %0, [%1];" : "=r"(c) : "l"(counter) : "memory");
        if (++n > SPIN_LIMIT) __trap();
    } while ((int)(c - target) < 0);
}
__device__ __forceinline__ void signal(unsigned* counter) {
    __syncwarp();
    if (elect_one()) asm volatile("red.release.gpu.global.add.u32 [%0], 1;" ::"l"(counter) : "memory");
    __syncwarp();
}
__device__ __forceinline__ void lds128(uint32_t& a, uint32_t& b, uint32_t& c, uint32_t& d, uint32_t addr) {
    asm volatile("ld.shared.v4.u32 {%0, %1, %2, %3}, [%4];" : "=r"(a), "=r"(b), "=r"(c), "=r"(d) : "r"(addr) : "memory");
}
__device__ __forceinline__ void lds64(uint32_t& a, uint32_t& b, uint32_t addr) {
    asm volatile("ld.shared.v2.u32 {%0, %1}, [%2];" : "=r"(a), "=r"(b) : "r"(addr) : "memory");
}
__device__ __forceinline__ void lds32(uint32_t& a, uint32_t addr) {
    asm volatile("ld.shared.u32 %0, [%1];" : "=r"(a) : "r"(addr) : "memory");
}
__device__ __forceinline__ float ldsf(uint32_t addr) {
    uint32_t v;
    lds32(v, addr);
    return __uint_as_float(v);
}
__device__ __forceinline__ void sts32(uint32_t addr, uint32_t a) {
    asm volatile("st.shared.u32 [%0], %1;" ::"r"(addr), "r"(a) : "memory");
}
__device__ __forceinline__ void sts128(uint32_t addr, uint32_t a, uint32_t b, uint32_t c, uint32_t d) {
    asm volatile("st.shared.v4.u32 [%0], {%1, %2, %3, %4};" ::"r"(addr), "r"(a), "r"(b), "r"(c), "r"(d) : "memory");
}
__device__ __forceinline__ void sts64(uint32_t addr, uint32_t a, uint32_t b) {
    asm volatile("st.shared.v2.u32 [%0], {%1, %2};" ::"r"(addr), "r"(a), "r"(b) : "memory");
}
__device__ __forceinline__ void anchor(uint32_t addr, uint32_t a, uint32_t b, uint32_t c, uint32_t d) {
    asm volatile("{\n.reg .pred p;\nsetp.eq.b32 p, %0, 0;\n@p st.shared.v4.u32 [%0], {%1, %2, %3, %4};\n}\n"
                 ::"r"(addr), "r"(a), "r"(b), "r"(c), "r"(d) : "memory");
}
__device__ __forceinline__ uint32_t bf_fma(uint32_t a, uint32_t b, uint32_t c) {
    uint32_t d; asm("fma.rn.bf16x2 %0, %1, %2, %3;" : "=r"(d) : "r"(a), "r"(b), "r"(c)); return d;
}
__device__ __forceinline__ uint32_t bf_mul(uint32_t a, uint32_t b) {
    uint32_t d; asm("mul.rn.bf16x2 %0, %1, %2;" : "=r"(d) : "r"(a), "r"(b)); return d;
}
__device__ __forceinline__ uint32_t bf_absmax(uint32_t a, uint32_t b) {
    uint32_t d; asm("max.xorsign.abs.bf16x2 %0, %1, %2;" : "=r"(d) : "r"(a), "r"(b)); return d;
}
__device__ __forceinline__ uint32_t h_fma(uint32_t a, uint32_t b, uint32_t c) {
    uint32_t d; asm("fma.rn.f16x2 %0, %1, %2, %3;" : "=r"(d) : "r"(a), "r"(b), "r"(c)); return d;
}
__device__ __forceinline__ uint32_t h_mul(uint32_t a, uint32_t b) {
    uint32_t d; asm("mul.rn.f16x2 %0, %1, %2;" : "=r"(d) : "r"(a), "r"(b)); return d;
}
__device__ __forceinline__ uint32_t h_round8(uint32_t v) { return (v + 0x00040004u) & 0xfff8fff8u; }
__device__ __forceinline__ uint32_t h_tanh(uint32_t a) {
    uint32_t d; asm("tanh.approx.f16x2 %0, %1;" : "=r"(d) : "r"(a)); return d;
}
__device__ __forceinline__ uint32_t pack_h2(float lo, float hi) {
    uint32_t d; asm("cvt.rn.f16x2.f32 %0, %1, %2;" : "=r"(d) : "f"(hi), "f"(lo)); return d;
}
__device__ __forceinline__ uint32_t pack_bf2(float lo, float hi) {
    uint32_t d; asm("cvt.rn.bf16x2.f32 %0, %1, %2;" : "=r"(d) : "f"(hi), "f"(lo)); return d;
}
__device__ __forceinline__ float bf_lo(uint32_t v) { return __uint_as_float(v << 16); }
__device__ __forceinline__ float bf_hi(uint32_t v) { return __uint_as_float(v & 0xffff0000u); }
__device__ __forceinline__ float h_lo(uint32_t v) { return __low2float(*reinterpret_cast<__half2*>(&v)); }
__device__ __forceinline__ float h_hi(uint32_t v) { return __high2float(*reinterpret_cast<__half2*>(&v)); }
__device__ __forceinline__ float warp_absmax(uint32_t v) {
    return __uint_as_float(__reduce_max_sync(~0u, max((v & 0x7fffu) << 16, v & 0x7fff0000u)));
}
__device__ __forceinline__ uint32_t gelu2(uint32_t z) {
    uint32_t p = h_fma(z, z, GELU_C2);
    uint32_t t = h_tanh(h_mul(z, p));
    return h_fma(z, t, z);
}
__device__ __forceinline__ float grn_norm(float ss) {
    float r;
    asm("sqrt.approx.f32 %0, %1;" : "=f"(r) : "f"(fmaf(ss, INV_2KZ * INV_2KZ, 1e-6f)));
    return r;
}
__device__ __forceinline__ float pow2i(int e) { return __uint_as_float((uint32_t)(e + 127) << 23); }
__device__ __forceinline__ int ilog2f(float v) {
    int e = (int)((__float_as_uint(v) >> 23) & 0xff) - 127;
    return max(-100, min(100, e));
}

__device__ __forceinline__ int sum_exp(float w1max) {
    return w1max > 0.f ? max(-90, min(90, 33 - 2 * ilog2f(2.f * KZ * 96.f * w1max))) : 0;
}
__device__ __forceinline__ float row_scale(float m) { return m > 0.f ? pow2i(2 - ilog2f(m)) : 1.f; }

struct Work {
    int tA, tB, nA, nB, dir, rows, lent;
    __device__ __forceinline__ int tile(int j) const { return j < nA ? tA + dir * j : tB + dir * (j - nA); }
};
__device__ __forceinline__ Work get_work(int cta, int per_cta, int extra, int lenders) {
    Work w;
    w.lent = cta < lenders ? LENT : 0;
    const int t0 = cta * per_cta + min(cta, extra);
    const int t1 = t0 + per_cta + (cta < extra);
    const int tm = min(t1, (t0 | 511) + 1);
    const bool swap = t1 > tm && t1 - tm < tm - t0, down = cta & 1;
    w.nA = swap ? t1 - tm : tm - t0;
    w.nB = t1 - t0 - w.nA;
    w.tA = down ? (swap ? tm : t0) : (swap ? t1 : tm) - 1;
    w.tB = down ? (swap ? t0 : tm) : (swap ? tm : t1) - 1;
    w.dir = down ? 1 : -1;
    w.rows = w.nA + 2 + (w.nB ? w.nB + 2 : 0);
    return w;
}
__device__ __forceinline__ int row_code(const Work& w, int i) {
    const bool in_a = i < w.nA + 2;
    const int t = in_a ? w.tA : w.tB;
    return ((t & 511) + w.dir * ((in_a ? i : i - (w.nA + 2)) - 1)) << 16 | (t >> 9) * TILE_W;
}
__device__ __forceinline__ uint32_t tile_offset(int tile) { return ((tile & 511) * IMG_W + (tile >> 9) * TILE_W) * (CH * 2); }
__device__ __forceinline__ int tile_order(int j, int n) {
    const int olds = (j / ORDER_P) * ORDER_Q + max(0, j % ORDER_P - (ORDER_P - ORDER_Q));
    return (j % ORDER_P >= ORDER_P - ORDER_Q) ? olds : n - 1 - (j - olds);
}
__device__ __forceinline__ void issue_region(const CUtensorMap* tm, uint32_t dst, uint32_t bar, int warp, int code) {
    mbar_expect_tx(bar, REGION_BYTES);
    tma_row(dst, tm, bar, (code & 0xffff) + (16 * warp - 1), code >> 16);
}

__device__ __forceinline__ void conv_producer(const Work& wk, const CUtensorMap* tm, Scratch* sc, uint32_t sb, int warp) {
    const int lane = threadIdx.x & 31;
    const int j = lane & 15, grp = lane >> 4;
    const uint32_t reg0 = sb + SM_RING + warp * REGION_BYTES;
    const uint32_t bars = sb + SM_BAR + warp * 8;
    if (lane >= PREFETCH_ROWS && lane < 3 * NSLOT) mbar_init(bars + lane * 32, 1);
    if (lane >= 28) mbar_init(sb + BAR_R + ((lane - 28) * 4 + warp) * 8, 1);
    if (lane == 0 && warp == 0) mbar_init(sb + BAR_PIN, 1);
    if (warp * 32 + lane < MAX_ROWS) {
        sts32(sb + SM_ROWS + (warp * 32 + lane) * 4, row_code(wk, warp * 32 + lane));
        sts32(sb + SM_TILES + (warp * 32 + lane) * 4, tile_offset(wk.tile(wk.lent + tile_order(max(warp * 32 + lane - wk.lent / 2, 0), wk.nA + wk.nB - NCONS - wk.lent))));
    }
    const uint32_t ld64 = opaque(reg0 + grp * 8 * 192 + j * 8), ld32 = opaque(reg0 + grp * 8 * 192 + 128 + j * 4);
    const uint32_t st64 = opaque(reg0 + grp * A_SBO + (j >> 1) * A_LBO + (j & 1) * 8);
    const uint32_t st32 = opaque(reg0 + grp * A_SBO + (8 + (j >> 2)) * A_LBO + (j & 3) * 4);
    fence_async();
    named_bar(0, NTHREADS);
    uint32_t w[3][3][3];
    mbar_wait(sb + BAR_F, 0);
#pragma unroll
    for (int tap = 0; tap < 9; tap++) {
        const uint32_t p = sb + SM_FILTER + (3 + wk.dir * 3 * (tap / 3 - 1) + tap % 3) * (CH * 2);
        lds64(w[tap / 3][tap % 3][0], w[tap / 3][tap % 3][1], p + 8 * j);
        lds32(w[tap / 3][tap % 3][2], p + 128 + 4 * j);
    }
#pragma unroll
    for (int tap = 0; tap < 9; tap++) sts64(reg0 + (NSLOT - 1) * SLOT_BYTES + tap * 128 + j * 8, w[tap / 3][tap % 3][1], w[tap / 3][tap % 3][0]);
#pragma unroll
    for (int tap = 0; tap < 9; tap++) lds64(w[tap / 3][tap % 3][1], w[tap / 3][tap % 3][0], reg0 + (NSLOT - 1) * SLOT_BYTES + tap * 128 + j * 8);
    fence_async();
    named_bar(1, 128);
    static_assert(2 * PREFETCH_ROWS == NSLOT, "prefetch slot arithmetic");
    uint32_t so = 0, bo = 0, par = 0, tbl = sb + SM_ROWS + PREFETCH_ROWS * 4;
    const uint32_t tbl_end = sb + SM_ROWS + wk.rows * 4, publish = wk.lent ? tbl + 12 * 4 : 0;
    auto next_row = [&](int code, bool e_ready) {
        const bool wrap = bo == (NSLOT - 1) * 32, low = bo < PREFETCH_ROWS * 32;
        if (tbl < tbl_end) {
            const uint32_t pbo = low ? bo + PREFETCH_ROWS * 32 : bo - PREFETCH_ROWS * 32;
            if (!e_ready) mbar_wait(bars + (BAR_E - SM_BAR) + pbo, par ^ low);
            code = __shfl_sync(~0u, code, 0);
            if (elect_one()) issue_region(tm, reg0 + (low ? so + PREFETCH_ROWS * SLOT_BYTES : so - PREFETCH_ROWS * SLOT_BYTES), bars + pbo, warp, code);
        }
        tbl += 4;
        so = wrap ? 0 : so + SLOT_BYTES;
        bo = wrap ? 0 : bo + 32;
        par ^= wrap;
    };
    int n = wk.nA;
#pragma unroll 1
    for (int seg = 0; seg < 2 && n > 0; seg++, n = wk.nB) {
        uint32_t accB[8][3], accC[8][3];
        {
            const uint32_t so0 = so, bo0 = bo;
            uint32_t so1, bo1;
#pragma unroll 1
            for (int r = 0; r < 2; r++) {
                uint32_t code;
                lds32(code, tbl);
                mbar_wait(bars + bo, par);
                so1 = so;
                bo1 = bo;
                next_row(code, false);
            }
#pragma unroll
            for (int p = 0; p < 10; p++) {
                uint32_t u[3], v[3];
                lds64(u[0], u[1], so0 + ld64 + p * 192);
                lds32(u[2], so0 + ld32 + p * 192);
                lds64(v[0], v[1], so1 + ld64 + p * 192);
                lds32(v[2], so1 + ld32 + p * 192);
#pragma unroll
                for (int dx = 0; dx < 3; dx++) {
                    const int o = p - dx;
                    if (o < 0 || o > 7) continue;
#pragma unroll
                    for (int q = 0; q < 3; q++) {
                        accB[o][q] = bf_fma(v[q], w[1][dx][q], dx == 0 ? bf_mul(u[q], w[0][dx][q]) : bf_fma(u[q], w[0][dx][q], accB[o][q]));
                        accC[o][q] = dx == 0 ? bf_mul(v[q], w[0][dx][q]) : bf_fma(v[q], w[0][dx][q], accC[o][q]);
                    }
                }
            }
            anchor(ld64, accB[7][0], accB[7][1], accB[7][2], 0);
            __syncwarp();
            if (elect_one()) {
                mbar_arrive(bars + (BAR_A - SM_BAR) + bo0);
                mbar_arrive(bars + (BAR_E - SM_BAR) + bo0);
                mbar_arrive(bars + (BAR_A - SM_BAR) + bo1);
                mbar_arrive(bars + (BAR_E - SM_BAR) + bo1);
            }
        }
        bool x_ready = false;
#pragma unroll 1
        for (int k = 0; k < n; k++) {
            if (!x_ready) mbar_wait(bars + bo, par);
            uint32_t out[8][3];
            int code;
            bool e_ready;
#pragma unroll
            for (int p = 0; p < 10; p++) {
                uint32_t xv[3];
                lds64(xv[0], xv[1], so + ld64 + p * 192);
                lds32(xv[2], so + ld32 + p * 192);
                if (p == 9) {
                    const bool wrap = bo == (NSLOT - 1) * 32, low = bo < PREFETCH_ROWS * 32;
                    asm volatile("ld.shared.u32 %0, [%1];" : "=r"(code) : "r"(tbl));
                    e_ready = mbar_test(bars + (BAR_E - SM_BAR) + (low ? bo + PREFETCH_ROWS * 32 : bo - PREFETCH_ROWS * 32), par ^ low);
                    x_ready = mbar_test(bars + (wrap ? 0 : bo + 32), par ^ wrap);
                }
#pragma unroll
                for (int dx = 0; dx < 3; dx++) {
                    const int o = p - dx;
                    if (o < 0 || o > 7) continue;
#pragma unroll
                    for (int q = 0; q < 3; q++) {
                        out[o][q] = bf_fma(xv[q], w[2][dx][q], dx == 0 ? accB[o][q] : out[o][q]);
                        accB[o][q] = bf_fma(xv[q], w[1][dx][q], dx == 0 ? accC[o][q] : accB[o][q]);
                        accC[o][q] = dx == 0 ? bf_mul(xv[q], w[0][dx][q]) : bf_fma(xv[q], w[0][dx][q], accC[o][q]);
                    }
                }
            }
            __syncwarp();
#pragma unroll
            for (int o = 0; o < 8; o++) {
                sts64(so + st64 + o * 16, out[o][0], out[o][1]);
                sts32(so + st32 + o * 16, out[o][2]);
            }
            __syncwarp();
            if (elect_one()) mbar_arrive(bars + (BAR_A - SM_BAR) + bo);
            if (tbl == publish) signal(&sc->lent_in);
            next_row(code, e_ready);
        }
    }
}

template <bool SCALED, int K0 = 0, int K1 = 3>
__device__ __forceinline__ void gelu_sq(uint32_t (&d)[24], uint32_t (&keep)[24], uint32_t sq_addr, uint32_t scale2) {
    pin(d);
#pragma unroll
    for (int k = K0; k < K1; k++) {
        uint32_t hs[4];
        lds128(hs[0], hs[1], hs[2], hs[3], sq_addr + k * SQ_ROW);
#pragma unroll
        for (int q = 0; q < 4; q++) {
            uint32_t g0 = gelu2(d[8 * k + 2 * q]), g1 = gelu2(d[8 * k + 2 * q + 1]);
            keep[8 * k + 2 * q] = g0;
            keep[8 * k + 2 * q + 1] = g1;
            if (SCALED) { g0 = h_mul(g0, scale2); g1 = h_mul(g1, scale2); }
            hs[q] = h_fma(g1, g1, h_fma(g0, g0, hs[q]));
        }
        sts128(sq_addr + k * SQ_ROW, hs[0], hs[1], hs[2], hs[3]);
    }
}
__device__ __forceinline__ void gelu_sq_reg(uint32_t (&d)[24], uint32_t (&hs)[12]) {
    pin(d);
#pragma unroll
    for (int q = 0; q < 12; q++) {
        const uint32_t g0 = gelu2(d[2 * q]), g1 = gelu2(d[2 * q + 1]);
        hs[q] = h_fma(g1, g1, h_fma(g0, g0, hs[q]));
    }
}
__device__ __forceinline__ void gelu_to(uint32_t (&g)[12], uint32_t (&d)[12]) {
    pin(d);
#pragma unroll
    for (int q = 0; q < 12; q++) g[q] = gelu2(d[q]);
    pin(g);
}
__device__ __forceinline__ void load_tile(uint32_t (&raw)[6][4], uint32_t addr) {
#pragma unroll
    for (int s = 0; s < 6; s++) ldsm4(raw[s], addr + s * 2 * A_LBO);
}
__device__ __forceinline__ uint2 ln_stats(const uint32_t (&raw)[6][4], uint64_t ones) {
    uint32_t sq[6][4];
#pragma unroll
    for (int s = 0; s < 6; s++)
#pragma unroll
        for (int q = 0; q < 4; q++) sq[s][q] = bf_mul(raw[s][q], raw[s][q]);
    float sum[4], ssq[4];
    wg_fence();
    wgmma_rowsum<0>(sum, raw[0], ones);
#pragma unroll
    for (int s = 1; s < 6; s++) wgmma_rowsum<1>(sum, raw[s], ones);
    wgmma_rowsum<0>(ssq, sq[0], ones);
#pragma unroll
    for (int s = 1; s < 6; s++) wgmma_rowsum<1>(ssq, sq[s], ones);
    wg_commit();
    wg_wait<0>();
    uint32_t st[2];
#pragma unroll
    for (int h = 0; h < 2; h++) {
        asm volatile("" : "+f"(sum[2 * h]), "+f"(ssq[2 * h])::"memory");
        const float mean = sum[2 * h] * (1.f / CH);
        const float var = fmaxf(fmaf(ssq[2 * h], 1.f / CH, -mean * mean), 0.f);
        float rstd;
        asm("rsqrt.approx.ftz.f32 %0, %1;" : "=f"(rstd) : "f"(var + 1e-5f));
        rstd = bf_lo(pack_bf2(rstd * (K_CVT == 0 ? KZ : KZ * 0x1p-112f), 0.f));
        st[h] = pack_bf2(rstd, -mean * rstd);
    }
    return make_uint2(st[0], st[1]);
}
__device__ __forceinline__ void ln_apply(uint32_t (&a)[6][4], const uint2& st) {
    const uint32_t sc[2] = {__byte_perm(st.x, 0, 0x1010), __byte_perm(st.y, 0, 0x1010)};
    const uint32_t sh[2] = {__byte_perm(st.x, 0, 0x3232), __byte_perm(st.y, 0, 0x3232)};
#pragma unroll
    for (int s = 0; s < 6; s++)
#pragma unroll
        for (int q = 0; q < 4; q++) {
            const uint32_t v = bf_fma(a[s][q], sc[q & 1], sh[q & 1]);
            a[s][q] = K_CVT == 0 ? pack_h2(bf_lo(v), bf_hi(v)) : (v & 0x7fff7fffu) * 7u + v;
        }
}
struct Cursor {
    int slot;
    uint32_t par;
    __device__ __forceinline__ void advance(int n) {
        slot += n;
        if (slot >= NSLOT) { slot -= NSLOT; par ^= 1; }
    }
};
struct Descs {
    uint64_t w1[8][6];
    uint64_t w2[24];
    uint64_t ones;
};
template <int E0, int N>
__device__ __forceinline__ void gemm1_chunk(uint32_t (&d)[N], const uint32_t (&a)[6][4], const Descs& ds, int zero) {
#pragma unroll
    for (int s = 0; s < 6; s++) wgmma(d, a[s][0], a[s][1], a[s][2], a[s][3], ds.w1[E0 / 48][s], s ? 1 : zero);
}
template <int E0, int N>
__device__ __forceinline__ void gemm2_chunk(uint32_t (&acc)[24], const uint32_t (&g)[N], const Descs& ds) {
#pragma unroll
    for (int s = 0; s < N / 4; s++) wgmma(acc, g[4 * s], g[4 * s + 1], g[4 * s + 2], g[4 * s + 3], ds.w2[E0 / 16 + s], 1);
}

__global__ void __launch_bounds__(NTHREADS, 1)
block_kernel(const __grid_constant__ CUtensorMap tmap, const __grid_constant__ CUtensorMap tmap_w1,
             const __nv_bfloat16* __restrict__ x, const __nv_bfloat16* __restrict__ dw, const __nv_bfloat16* __restrict__ w2,
             const __nv_bfloat16* __restrict__ gamma, const __nv_bfloat16* __restrict__ beta, __nv_bfloat16* __restrict__ out,
             Scratch* __restrict__ sc, const __grid_constant__ Descs ds,
             const int zero, const int per_cta, const int extra, const int lenders) {
    extern __shared__ __align__(1024) uint8_t smem[];
    constexpr uint32_t sb = SB;
    const int tid = threadIdx.x;
    const Work wk = get_work(blockIdx.x, per_cta, extra, lenders);
    constexpr uint32_t s_red = sb + SM_RED;
    if (smem_u32(smem) != SB) __trap();

    PROF(0);
    const int warp_id = __shfl_sync(~0u, tid >> 5, 0);
    const int cw = warp_id - 4, wgi = cw >> 2, w4 = warp_id & 3;
    if (elect_one()) {
        if (warp_id < 8) {
            mbar_init(sb + BAR_X + warp_id * 8, 1);
            if (warp_id < 4) mbar_init(sb + BAR_X + (warp_id + 8) * 8, 1);
            fence_async();
#pragma unroll 1
            for (int r = warp_id >> 2; r < PREFETCH_ROWS; r += 2)
                issue_region(&tmap, sb + SM_RING + r * SLOT_BYTES + w4 * REGION_BYTES, sb + BAR_X + (r * 4 + w4) * 8, w4,
                             ((wk.tA & 511) + wk.dir * (r - 1)) << 16 | (wk.tA >> 9) * TILE_W);
        } else if (warp_id < 15) {
            const int b = warp_id - 8;
            mbar_init(sb + BAR_W + b * 8, 1);
            fence_async();
            mbar_expect_tx(sb + BAR_W + b * 8, b < 6 ? 64 * CH * 2 : 9 * CH * 2);
            if (b < 6) tma_2d(sb + SM_W2 + b * (64 * CH * 2), &tmap_w1, sb + BAR_W + b * 8, 64 * b, 0);
            else bulk_load(sb + SM_FILTER, dw, 9 * CH * 2, sb + BAR_F);
        }
    }
    __syncwarp();
    const int ntiles = wk.nA + wk.nB;
    const int wg = warp_id >> 2;
    int first = wg;
    uint32_t a[6][4], acc[24], tile_off, next_off, stage, inv_rho2 = 0, rpar = 0, bias_addr, lane16, lane_off;
    auto set_lane = [&](uint32_t lane) {
        bias_addr = sb + SM_BIASH + (lane & 3) * 96;
        lane16 = lane * 16;
        lane_off = ((lane >> 2) * CH + 8 * (lane & 3)) * 2;
    };
    const uint32_t bar_r = sb + BAR_R + warp_id * 8;
    auto load_bias = [&](uint32_t (&acc)[24]) {
#pragma unroll
        for (int q = 0; q < 6; q++) lds128(acc[4 * q], acc[4 * q + 1], acc[4 * q + 2], acc[4 * q + 3], bias_addr + q * 16);
    };
    auto load_frags = [&](bool on) {
#pragma unroll
        for (int s = 0; s < 6; s++) ldg128_if(on, a[s], reinterpret_cast<const char*>(out) + next_off + w4 * WARP_BYTES + lane16 + s * 512);
    };
    auto load_first = [&]() {
#pragma unroll
        for (int s = 0; s < 6; s++) ldg128(a[s], reinterpret_cast<const char*>(out) + next_off + w4 * WARP_BYTES + lane16 + s * 512);
    };
    auto stage_x = [&]() {
        if (elect_one()) {
            mbar_expect_tx(bar_r, WARP_BYTES);
            bulk_load_stream(stage, reinterpret_cast<const char*>(x) + tile_off + w4 * WARP_BYTES, WARP_BYTES, bar_r);
        }
    };
    auto epilogue = [&](uint32_t (&acc)[24]) {
        pin(acc);
        rpar ^= 1;
        uint4* op = reinterpret_cast<uint4*>(reinterpret_cast<char*>(out) + tile_off + w4 * WARP_BYTES + lane_off);
#pragma unroll
        for (int h = 0; h < 2; h++)
#pragma unroll
            for (int m = 0; m < 3; m++) {
                uint32_t xin[4], o[4];
                lds128(xin[0], xin[1], xin[2], xin[3], stage + lane_off + h * 1536 + m * 64);
#pragma unroll
                for (int q = 0; q < 4; q++) {
                    const uint32_t v = acc[2 * (4 * m + q) + h];
                    o[q] = bf_fma(pack_bf2(h_lo(v), h_hi(v)), inv_rho2, xin[q]);
                }
                __stcs(op + h * 96 + m * 4, make_uint4(o[0], o[1], o[2], o[3]));
            }
        __syncwarp();
    };
    auto max_w1 = [&]() {
        float m = 0.f;
#pragma unroll
        for (int q = 0; q < 3; q++) {
            uint32_t u[4];
            lds128(u[0], u[1], u[2], u[3], s_red + q * 16);
#pragma unroll
            for (int k = 0; k < 4; k++) m = fmaxf(m, __uint_as_float(u[k]));
        }
        return m;
    };
    auto square_exp = [&](float w1max) {
        const int e = w1max > 0.f ? 4 - ilog2f(2.f * KZ * 96.f * w1max) : 0;
        return (e >= 0 && e <= 6) ? 0 : max(-14, min(e, 14));
    };
    const int last_wg = (ntiles - 1 - wk.lent) % NCONS;
    auto reduce = [&](int q, uint32_t lane, bool leader) {
        const int t = lane & 3, part = lane >> 2;
        const float w1max = max_w1();
        const int sq_e = square_exp(w1max);
        const float to_fixed = pow2i(sum_exp(w1max) - 2 * sq_e);
        unsigned long long* dst = sc->sum(__float_as_uint(ldsf(s_red + 48)), 32 * q + 8 * (part >> 1) + 2 * t + (part & 1));
        named_bar(11, CONS_THREADS);
        const unsigned in_piece = 32 * q + 8 * (part >> 1) + 2 * t + (part & 1) - (blockIdx.x - lenders) % 8 * 48;
        const float helped = in_piece < 48 ? ldsf(sb + SM_BIASH + in_piece * 4) * pow2i(2 * sq_e) : 0.f;
        float f[8] = {};
#pragma unroll 1
        for (int i = 0; i < NCONS; i++) {
            const int src_wg = (last_wg + 1 + i) % NCONS;
            if (i == NCONS - 1) {
                named_bar(13, CONS_THREADS);
                if (leader) {
                    fence_async();
#pragma unroll
                    for (int k = 1; k < NCONS; k++) {
                        const int o = (last_wg + k) % NCONS * SQ_WG;
                        bulk_load(sb + SM_W2 + o, reinterpret_cast<const char*>(sc->w2h) + o, SQ_WG, sb + BAR_W);
                    }
                }
                __syncwarp();
                named_bar(14, NTHREADS);
            }
            const uint32_t upper = sq_e ? SM_SQ + (NCONS + src_wg) * SQ_WG : SM_RING + (wk.rows + i) % NSLOT * SLOT_BYTES;
            const uint32_t src = sb + lane * 16 + (q < 6 ? SM_SQ + src_wg * SQ_WG + q * SQ_ROW : upper + (q - 6) * SQ_ROW);
#pragma unroll
            for (int r = 0; r < 4; r++) {
                uint32_t u[4];
                lds128(u[0], u[1], u[2], u[3], src + r * 512);
#pragma unroll
                for (int k = 0; k < 4; k++) { f[2 * k] += h_lo(u[k]); f[2 * k + 1] += h_hi(u[k]); }
            }
        }
        const bool b2 = part & 4, b1 = part & 2, b0 = part & 1;
        float r4[4], r2[2];
#pragma unroll
        for (int k = 0; k < 4; k++) r4[k] = (b2 ? f[k + 4] : f[k]) + __shfl_xor_sync(~0u, b2 ? f[k] : f[k + 4], 16);
#pragma unroll
        for (int k = 0; k < 2; k++) r2[k] = (b1 ? r4[k + 2] : r4[k]) + __shfl_xor_sync(~0u, b1 ? r4[k] : r4[k + 2], 8);
        const float tot = (b0 ? r2[1] : r2[0]) + __shfl_xor_sync(~0u, b0 ? r2[0] : r2[1], 4);
        atomicAdd(dst, __float2ull_rn(fminf((tot + helped) * to_fixed, 0x1p47f)) << 8 | 1);
    };
    const uint32_t s_fac = sb + SM_RING + (wk.rows + 1) % NSLOT * SLOT_BYTES + SQ_WG;
    if (warp_id < 4) {
        conv_producer(wk, &tmap, sc, sb, warp_id);
        const int lane = opaque(tid & 31), g = lane >> 2, t = lane & 3;
        const unsigned epoch = __float_as_uint(ldsf(s_red + 48));
        set_lane(lane);
#pragma unroll 1
        for (int q = gridDim.x - 1 - blockIdx.x; q < W2_GROUPS; q += gridDim.x) {
            uint32_t u[3], rmax = 0;
#pragma unroll
            for (int m = 0; m < 3; m++) {
                const uint4 w = ldg128_ordered(w2 + (8 * q + g) * CH + 32 * m + 8 * t);
                rmax = bf_absmax(bf_absmax(rmax, bf_absmax(w.x, w.y)), bf_absmax(w.z, w.w));
                u[m] = w4 & 2 ? (w4 & 1 ? w.w : w.z) : (w4 & 1 ? w.y : w.x);
            }
            const float bt = __bfloat162float(beta[8 * q + g]);
            rmax = bf_absmax(rmax, __shfl_xor_sync(~0u, rmax, 1));
            rmax = bf_absmax(rmax, __shfl_xor_sync(~0u, rmax, 2));
            const float mx = fmaxf(fabsf(bf_lo(rmax)), fabsf(bf_hi(rmax))), rs = row_scale(mx);
            if (t == 0 && w4 == 0) sc->w2max[8 * q + g] = mx;
#pragma unroll
            for (int m = 0; m < 3; m++) {
                float lo = bf_lo(u[m]), hi = bf_hi(u[m]);
                sc->w2h[(4 * m + w4) * 1536 + q * 32 + lane] = transpose8x8(pack_h2(lo * rs, hi * rs));
                lo *= bt; hi *= bt;
#pragma unroll
                for (int o = 4; o <= 16; o <<= 1) { lo += __shfl_xor_sync(~0u, lo, o); hi += __shfl_xor_sync(~0u, hi, o); }
                if (g == 0) {
                    float* dst = &sc->bias[epoch & 1][32 * m + 8 * t + 2 * w4];
                    asm volatile("red.global.add.v2.f32 [%0], {%1, %2};" ::"l"(dst), "f"(lo), "f"(hi) : "memory");
                }
            }
            asm volatile("fence.proxy.async.global;" ::: "memory");
            signal(&sc->prep);
        }
        const unsigned piece = blockIdx.x - lenders;
        if (piece < 8 * LENT * lenders) {
            spin_until(&sc->lent_in, (epoch + 1) * 4 * lenders);
            next_off = tile_offset(get_work(piece / (8 * LENT), per_cta, extra, lenders).tile(piece / 8 % LENT));
            load_first();
            uint32_t d[12], gl[12];
            wg_fence();
#pragma unroll
            for (int s = 0; s < 6; s++) wgmma(d, a[s][0], a[s][1], a[s][2], a[s][3], ds.w1[0][s] + piece % 8 * (6 * 1536 / 16), s ? 1 : 0);
            wg_commit();
            wg_wait<0>();
            gelu_to(gl, d);
#pragma unroll
            for (int s = 0; s < 3; s++) sc->lent[((piece * 4 + w4) * 3 + s) * 32 + lane] = make_uint4(gl[4 * s], gl[4 * s + 1], gl[4 * s + 2], gl[4 * s + 3]);
            float f[6], r[3];
#pragma unroll
            for (int j = 0; j < 6; j++) {
                const float lo = fmaf(h_lo(gl[2 * j]), h_lo(gl[2 * j]), h_lo(gl[2 * j + 1]) * h_lo(gl[2 * j + 1]));
                const float hi = fmaf(h_hi(gl[2 * j]), h_hi(gl[2 * j]), h_hi(gl[2 * j + 1]) * h_hi(gl[2 * j + 1]));
                f[j] = (g & 1 ? hi : lo) + __shfl_xor_sync(~0u, g & 1 ? lo : hi, 4);
            }
#pragma unroll
            for (int j = 0; j < 3; j++) {
                r[j] = (g & 2 ? f[j + 3] : f[j]) + __shfl_xor_sync(~0u, g & 2 ? f[j] : f[j + 3], 8);
                asm volatile("red.shared.add.f32 [%0], %1;" ::"r"(sb + SM_BIASH + (8 * j + 12 * (g & 2) + 2 * t + (g & 1)) * 4), "f"(r[j]) : "memory");
            }
        }
        if (piece < 8 * LENT * lenders) signal(&sc->lent_out);
        const bool leader = warp_id == 0 && lane == 0;
        const float w1max = max_w1();
        const bool plain = square_exp(w1max) == 0;
        auto load_upper = [&]() {
            bulk_load(sb + SM_W2 + NCONS * SQ_WG, reinterpret_cast<const char*>(sc->w2h) + NCONS * SQ_WG, EX * CH * 2 - NCONS * SQ_WG, sb + BAR_W);
        };
        if (leader) {
            spin_until(&sc->prep, (epoch + 1) * 4 * W2_GROUPS);
            asm volatile("fence.proxy.async.global;" ::: "memory");
            fence_async();
            mbar_expect_tx(sb + BAR_W, EX * CH * 2);
            if (plain) load_upper();
        }
        __syncwarp();
        named_bar(1, 128);
        const int i0 = w4 * 32 + lane;
        float gam[3], rmax[3];
#pragma unroll
        for (int m = 0; m < 3; m++) { gam[m] = __bfloat162float(gamma[i0 + 128 * m]); rmax[m] = __ldcg(&sc->w2max[i0 + 128 * m]); }
        float2 bpair = make_float2(0.f, 0.f);
        if (i0 < 96) bpair = __ldcg(reinterpret_cast<const float2*>(&sc->bias[epoch & 1][32 * (i0 % 24 >> 3) + 8 * (i0 / 24) + (i0 % 24 & 6)]));
        const float gbound = fmaxf(2.f * KZ * 9.7979590f * 192.f * w1max, 1.f) * 19.5959180f * INV_2KZ;
        const unsigned fixed = __reduce_max_sync(~0u, __float_as_uint(fmaf(gbound, fmaxf(fmaxf(rmax[0], rmax[1]), rmax[2]), fmaxf(fabsf(bpair.x), fabsf(bpair.y)))));
        if (lane == 0) sts32(s_red + 96 + w4 * 4, fixed);
        reduce(4 * last_wg + w4, lane, leader);
        PROF(2);
        named_bar(15, CONS_THREADS);
        if (leader) {
            fence_async();
            bulk_load(sb + SM_W2 + last_wg * SQ_WG, reinterpret_cast<const char*>(sc->w2h) + last_wg * SQ_WG, SQ_WG, sb + BAR_W);
            if (!plain) load_upper();
        }
        stage = sb + SM_RING + (wk.rows % NSLOT) * SLOT_BYTES + w4 * REGION_BYTES;
        auto grn = [&]() {
            auto peek = [&](int e) {
                unsigned long long v;
                asm volatile("ld.relaxed.gpu.global.u64 %0, [%1];" : "=l"(v) : "l"(sc->sum(epoch, e)) : "memory");
                return v;
            };
            unsigned n = 0;
            while (((unsigned)peek((blockIdx.x * 4 + w4) % (EX / 4) * 4) & 255u) != gridDim.x)
                if (++n > SPIN_LIMIT) __trap();
            unsigned long long sum[3];
            for (;;) {
                bool all = true;
#pragma unroll
                for (int m = 0; m < 3; m++) {
                    sum[m] = peek(i0 + 128 * m);
                    all &= ((unsigned)sum[m] & 255u) == gridDim.x;
                }
                if (__all_sync(~0u, all)) break;
                if (++n > SPIN_LIMIT) __trap();
            }
            PROF(3);
            if (blockIdx.x == 0 && leader) sc->launch = epoch + 1;
            float gx[3], tot = 0.f, vary = 0.f;
#pragma unroll
            for (int m = 0; m < 3; m++) {
                gx[m] = grn_norm(__ull2float_rn(sum[m] >> 8) * pow2i(-sum_exp(w1max)));
                tot += gx[m];
                vary = fmaxf(vary, fabsf(gam[m]) * gx[m] * rmax[m]);
            }
#pragma unroll
            for (int o = 16; o >= 1; o >>= 1) tot += __shfl_xor_sync(~0u, tot, o);
            const unsigned vwarp = __reduce_max_sync(~0u, __float_as_uint(vary));
            if (lane == 0) { sts32(s_red + 64 + w4 * 4, __float_as_uint(tot)); sts32(s_red + 80 + w4 * 4, vwarp); }
            named_bar(1, 128);
            uint32_t u[4], v[4], w[4];
            lds128(u[0], u[1], u[2], u[3], s_red + 64);
            lds128(v[0], v[1], v[2], v[3], s_red + 80);
            lds128(w[0], w[1], w[2], w[3], s_red + 96);
            tot = (__uint_as_float(u[0]) + __uint_as_float(u[1])) + (__uint_as_float(u[2]) + __uint_as_float(u[3]));
            const float vmax = __uint_as_float(max(max(v[0], v[1]), max(v[2], v[3]))), fmax2 = __uint_as_float(max(max(w[0], w[1]), max(w[2], w[3])));
            const float inv_mean = __fdividef(1.f, tot * (1.f / EX) + 1e-6f);
            const float bound = fmaf(gbound * vmax, inv_mean, 2.f * fmax2);
            const int rho_e = bound > 0.f ? 14 - ilog2f(bound) : 0;
            const float rho = pow2i(rho_e), inv_rho = pow2i(-rho_e);
            inv_rho2 = pack_bf2(inv_rho, inv_rho);
#pragma unroll
            for (int m = 0; m < 3; m++) {
                const float f = __fdividef(fmaf(gam[m], gx[m] * inv_mean, 1.f) * INV_2KZ * rho, row_scale(rmax[m]));
                asm volatile("st.shared.u16 [%0], %1;" ::"r"(s_fac + (i0 + 128 * m) * 2), "h"((unsigned short)pack_h2(f, 0.f)) : "memory");
            }
            if (i0 < 96) sts32(sb + SM_BIASH + i0 * 4, pack_h2(bpair.x * rho, bpair.y * rho));
            if (i0 == 96) sts32(s_red + 52, inv_rho2);
            named_arrive(12, NTHREADS);
        };
        uint32_t gl[4][12] = {};
        const uint4* src = &sc->lent[(blockIdx.x * LENT * 8 * 4 + w4) * 96 + lane];
        auto fetch = [&](uint32_t (&v)[12], int c, bool on) {
#pragma unroll
            for (int s = 0; s < 3; s++) ldg128_if(on, reinterpret_cast<uint32_t (&)[4]>(v[4 * s]), src + c * 384 + s * 32);
        };
        if (__builtin_expect(wk.lent, 0)) {
            first = 4;
            tile_off = tile_offset(wk.tA);
            stage_x();
            if (elect_one()) prefetch_l2(reinterpret_cast<const char*>(x) + tile_offset(wk.tA + wk.dir) + w4 * WARP_BYTES, WARP_BYTES);
            spin_until(&sc->lent_out, (epoch + 1) * 32 * LENT * lenders);
#pragma unroll
            for (int c = 0; c < 3; c++) fetch(gl[c], c, true);
        }
        lds32(next_off, sb + SM_TILES + first * 4);
        if (!wk.lent) load_first();
        grn();
        if (__builtin_expect(wk.lent, 0)) {
            named_bar(3, NTHREADS);
#pragma unroll 1
            for (int e = 0; e < LENT; e++) {
                load_bias(acc);
#define CNX_LENT(C)                                  \
    pin(gl[C % 4]);                                  \
    wg_fence();                                      \
    gemm2_chunk<48 * C>(acc, gl[C % 4], ds);         \
    wg_commit();                                     \
    wg_wait<(C < 7 ? 1 : 0)>();                      \
    fetch(gl[(C + 3) % 4], C + 3, C < 5 || e == 0);  \
    if (lane == 0) mbar_arrive(sb + BAR_PIN);
                CNX_LENT(0) CNX_LENT(1) CNX_LENT(2) CNX_LENT(3) CNX_LENT(4) CNX_LENT(5) CNX_LENT(6) CNX_LENT(7)
#undef CNX_LENT
                src += 8 * 384;
                mbar_wait(bar_r, rpar);
                epilogue(acc);
                tile_off = tile_offset(wk.tA + wk.dir);
                if (e == 0) stage_x();
            }
            load_first();
        }
    } else {
        {
            const int ct = tid - 128, lane = tid & 31;
            const unsigned epoch = *reinterpret_cast<volatile unsigned*>(&sc->launch);
            const int r = lane & 7, mi = lane >> 3;
            const uint32_t src = sb + SM_W2 + (cw >> 1) * (64 * CH * 2) + r * 128 + ((((cw & 1) * 4 + mi) ^ r) * 16);
            const uint32_t dst = sb + SM_W1 + (4 * cw + mi) * 1536 + r * 16;
            named_bar(0, NTHREADS);
            mbar_wait(sb + BAR_W + (cw >> 1) * 8, 0);
            uint32_t wmax[4] = {}, wsum[4] = {};
#pragma unroll 3
            for (int c = 0; c < 12; c++) {
                uint32_t u[4];
                ldsm4_t(u, src + c * 1024);
#pragma unroll
                for (int q = 0; q < 4; q++) {
                    wmax[q] = bf_absmax(wmax[q], u[q]);
                    wsum[q] = bf_fma(u[q], 0x3f803f80u, wsum[q]);
                    u[q] = pack_h2(bf_lo(u[q]), bf_hi(u[q]));
                }
                stsm4(dst + c * 128, u[0], u[1], u[2], u[3]);
            }
            float mean[4];
            bool center = false;
#pragma unroll
            for (int q = 0; q < 4; q++) {
                uint32_t m = wmax[q];
                float sum = bf_lo(wsum[q]) + bf_hi(wsum[q]);
#pragma unroll
                for (int o = 1; o <= 2; o <<= 1) { m = bf_absmax(m, __shfl_xor_sync(~0u, m, o)); sum += __shfl_xor_sync(~0u, sum, o); }
                mean[q] = sum * (1.f / CH);
                center |= fabsf(mean[q]) > 0.2f * fmaxf(fabsf(bf_lo(m)), fabsf(bf_hi(m)));
            }
            if (__builtin_expect(__any_sync(~0u, center), 0)) {
#pragma unroll 1
                for (int pass = 0; pass < 2; pass++) {
                    float sum[4] = {};
#pragma unroll 1
                    for (int c = 0; c < 12; c++) {
                        uint32_t u[4];
                        ldsm4_t(u, src + c * 1024);
#pragma unroll
                        for (int q = 0; q < 4; q++) {
                            sum[q] += bf_lo(u[q]) + bf_hi(u[q]);
                            u[q] = pack_h2(bf_lo(u[q]) - mean[q], bf_hi(u[q]) - mean[q]);
                        }
                        stsm4(dst + c * 128, u[0], u[1], u[2], u[3]);
                    }
#pragma unroll
                    for (int q = 0; q < 4; q++) {
                        sum[q] += __shfl_xor_sync(~0u, sum[q], 1);
                        sum[q] += __shfl_xor_sync(~0u, sum[q], 2);
                        mean[q] = sum[q] * (1.f / CH);
                    }
                }
            }
            if (cw < 2 * NCONS) {
#pragma unroll
                for (int c = 0; c < 12; c++) sts128(src + c * 1024, 0, 0, 0, 0);
            }
            const float w1max = warp_absmax(bf_absmax(bf_absmax(wmax[0], wmax[1]), bf_absmax(wmax[2], wmax[3])));
            if (lane == 0) sts32(s_red + cw * 4, __float_as_uint(w1max));
            if (ct < 32) sts32(sb + SM_ONES + ct * 4, 0x3f803f80u);
            if (ct < 48) sts32(sb + SM_BIASH + ct * 4, 0);
            if (blockIdx.x == 0) {
                *sc->sum(epoch + 1, ct) = 0;
                if (ct < CH) sc->bias[(epoch & 1) ^ 1][ct] = 0.f;
            }
            if (ct == 0) sts32(s_red + 48, epoch);
            fence_async();
            named_bar(2, CONS_THREADS);
            if (square_exp(max_w1())) {
#pragma unroll 1
                for (int q = 0; q < 6; q++) sts128(sb + SM_SQ + (wgi + NCONS) * SQ_WG + q * SQ_ROW + (ct & 127) * 16, 0, 0, 0, 0);
            }
            mbar_wait(sb + BAR_A + w4 * 8 + 32, 0);
        }

        PROF(1);
        const uint32_t a_addr = opaque(sb + SM_RING + w4 * REGION_BYTES + ((tid >> 3) & 1) * A_SBO + ((tid >> 4) & 1) * A_LBO + (tid & 7) * 16);
        const uint32_t bar_a = sb + BAR_A + w4 * 8, bar_e = sb + BAR_E + w4 * 8;
        const uint32_t sq = opaque(sb + SM_SQ + wgi * SQ_WG + (tid & 127) * 16);
        const uint32_t sq_warp = sb + SM_SQ + wgi * SQ_WG + w4 * 512;
        uint32_t k1[24], k2[24], k3[24];
        constexpr int SQC = 3 * SQ_ROW;
        const int pass_to = 4 + (wgi == NCONS - 1 ? 0 : wgi + 1);
        auto store_frags = [&](const uint32_t (&a)[6][4], int j) {
            char* ap = reinterpret_cast<char*>(out) + (tile_offset(wk.tile(j)) + w4 * WARP_BYTES - sq_warp + sq);
#pragma unroll
            for (int s = 0; s < 6; s++) stg128(ap + s * 512, a[s]);
        };
        int jt = wgi < wk.lent ? wgi : wk.lent + wgi;
        Cursor cur = {2, 0};
        cur.advance(jt + (jt >= wk.nA ? 2 : 0));
        if (wgi == NCONS - 1) named_arrive(4, 256);
        for (;;) {
            const bool plain = __all_sync(~0u, square_exp(max_w1()) == 0);
            if (plain && jt >= wk.lent) {
                uint32_t hs2[12] = {}, hs3[12] = {};
#pragma unroll 1
                for (; jt + NCONS < ntiles; jt += NCONS) {
                    uint32_t a[6][4], d0[24], d1[24], unused[24];
#define AT(pos) \
    if (K_WAIT == pos) named_bar(4 + wgi, 256); \
    if (K_PASS == pos) named_arrive(pass_to, 256); \
    if (K_STG == pos) store_frags(a, jt); \
    if (K_REL == pos) { if (elect_one()) mbar_arrive(bar_e + cur.slot * 32); }
                    AT(20)
                    mbar_wait(bar_a + cur.slot * 32, cur.par);
                    load_tile(a, a_addr + cur.slot * SLOT_BYTES);
                    AT(21)
                    const uint2 st = ln_stats(a, ds.ones);
                    AT(0)
                    ln_apply(a, st);
                    AT(1)
                    wg_fence();
                    gemm1_chunk<0>(d0, a, ds, 0);
                    wg_commit();
                    gemm1_chunk<96>(d1, a, ds, 0);
                    wg_commit();
                    AT(2)
                    wg_wait<1>();
                    AT(3)
                    gelu_sq<false, 0, 1>(d0, unused, sq, 0);
                    AT(4)
                    gelu_sq<false, 1, 2>(d0, unused, sq, 0);
                    AT(5)
                    gelu_sq<false, 2, 3>(d0, unused, sq, 0);
                    AT(6)
                    wg_fence();
                    gemm1_chunk<192>(d0, a, ds, zero);
                    wg_commit();
                    AT(7)
                    wg_wait<1>();
                    gelu_sq<false, 0, 1>(d1, unused, sq + SQC, 0);
                    AT(8)
                    gelu_sq<false, 1, 3>(d1, unused, sq + SQC, 0);
                    AT(9)
                    wg_fence();
                    gemm1_chunk<288>(d1, a, ds, zero);
                    wg_commit();
                    AT(10)
                    wg_wait<1>();
                    gelu_sq_reg(d0, hs2);
                    if (K_ANCH < 3) anchor(sq, hs2[4 * (K_ANCH % 3)], hs2[4 * (K_ANCH % 3) + 1], hs2[4 * (K_ANCH % 3) + 2], hs2[4 * (K_ANCH % 3) + 3]);
                    wg_wait<0>();
                    AT(11)
                    gelu_sq_reg(d1, hs3);
#undef AT
                    cur.advance(NCONS + ((jt < wk.nA && jt + NCONS >= wk.nA) ? 2 : 0));
                }
                const uint32_t sq2 = sq - (SM_SQ + wgi * SQ_WG) + SM_RING + (cur.slot + 3) % NSLOT * SLOT_BYTES;
#pragma unroll
                for (int k = 0; k < 3; k++) {
                    sts128(sq2 + k * SQ_ROW, hs2[4 * k], hs2[4 * k + 1], hs2[4 * k + 2], hs2[4 * k + 3]);
                    sts128(sq2 + SQC + k * SQ_ROW, hs3[4 * k], hs3[4 * k + 1], hs3[4 * k + 2], hs3[4 * k + 3]);
                }
            }
            const bool last = jt + NCONS >= ntiles;
            uint32_t a[6][4], d0[24], d1[24], d3[24], k0[24];
#define AT(pos) \
    if (K_WAIT == pos && jt >= wk.lent) named_bar(4 + wgi, 256); \
    if (K_PASS == pos && jt >= wk.lent && jt + 1 < ntiles) named_arrive(pass_to, 256);
            AT(20)
            mbar_wait(bar_a + cur.slot * 32, cur.par);
            load_tile(a, a_addr + cur.slot * SLOT_BYTES);
            AT(21)
            const uint2 st = ln_stats(a, ds.ones);
            AT(0)
            ln_apply(a, st);
            AT(1)
            if (!last) {
                store_frags(a, jt);
                __syncwarp();
                if (elect_one()) mbar_arrive(bar_e + cur.slot * 32);
                if (jt < wk.lent) {
                    jt += LENT;
                    cur.advance(LENT);
                    continue;
                }
            }
            wg_fence();
            gemm1_chunk<0>(d0, a, ds, 0);
            wg_commit();
            gemm1_chunk<96>(d1, a, ds, 0);
            wg_commit();
            const int sq_e = square_exp(max_w1());
            const uint32_t scale2 = pack_h2(pow2i(sq_e), pow2i(sq_e));
            stage = sb + SM_RING + cur.slot * SLOT_BYTES + w4 * REGION_BYTES;
            AT(2)
            wg_wait<1>();
            AT(3)
            gelu_sq<true, 0, 1>(d0, k0, sq, scale2);
            AT(4)
            gelu_sq<true, 1, 2>(d0, k0, sq, scale2);
            AT(5)
            gelu_sq<true, 2, 3>(d0, k0, sq, scale2);
            AT(6)
            if (last) {
#pragma unroll
                for (int q = 0; q < 6; q++) sts128(stage - sq_warp + sq + q * 512, k0[4 * q], k0[4 * q + 1], k0[4 * q + 2], k0[4 * q + 3]);
            }
            wg_fence();
            gemm1_chunk<192>(d0, a, ds, zero);
            wg_commit();
            AT(7)
            wg_wait<1>();
            gelu_sq<true, 0, 1>(d1, k1, sq + SQC, scale2);
            AT(8)
            gelu_sq<true, 1, 3>(d1, k1, sq + SQC, scale2);
            AT(9)
#undef AT
            wg_fence();
            gemm1_chunk<288>(d3, a, ds, 0);
            wg_commit();
            wg_wait<1>();
            const uint32_t sq2 = sq + (plain ? SM_RING + (cur.slot + 3) % NSLOT * SLOT_BYTES - (SM_SQ + wgi * SQ_WG) : NCONS * SQ_WG);
            gelu_sq<true>(d0, k2, sq2, scale2);
            wg_wait<0>();
            gelu_sq<true>(d3, k3, sq2 + SQC, scale2);
            if (last) break;
            cur.advance(NCONS + ((jt < wk.nA && jt + NCONS >= wk.nA) ? 2 : 0));
            jt += NCONS;
        }
        {
            if (wgi == last_wg) {
                named_arrive(14, NTHREADS);
            } else {
                reduce(cw, (sq >> 4) & 31, false);
                named_arrive(15, CONS_THREADS);
            }
        }
        PROF(2);
        tile_off = tile_offset(wk.tile(jt));
        {
            set_lane((sq >> 4) & 31);
            if (elect_one()) prefetch_l2(reinterpret_cast<const char*>(x) + tile_off + w4 * WARP_BYTES, WARP_BYTES);
            const uint32_t row = sb + SM_W2 + cw * 512 + lane16;
            uint32_t u[W2_EARLY][4], f2[4];
            mbar_wait(sb + BAR_W, 1);
#pragma unroll
            for (int nb = 0; nb < W2_EARLY; nb++) lds128(u[nb][0], u[nb][1], u[nb][2], u[nb][3], row + nb * 6144);
            named_bar(12, NTHREADS);
            PROF(3);
            lds128(f2[0], f2[1], f2[2], f2[3], s_fac + cw * 64 + (lane16 >> 7) * 16);
            lds32(inv_rho2, s_red + 52);
#pragma unroll
            for (int nb = 0; nb < 12; nb++) {
                uint32_t v[4];
                if (nb < W2_EARLY) { v[0] = u[nb % W2_EARLY][0]; v[1] = u[nb % W2_EARLY][1]; v[2] = u[nb % W2_EARLY][2]; v[3] = u[nb % W2_EARLY][3]; }
                else lds128(v[0], v[1], v[2], v[3], row + nb * 6144);
                sts128(row + nb * 6144, h_round8(h_mul(v[0], f2[0])), h_round8(h_mul(v[1], f2[1])), h_round8(h_mul(v[2], f2[2])), h_round8(h_mul(v[3], f2[3])));
            }
            fence_async();
            named_bar(3, NTHREADS);
        }
        PROF(4);
        {
            load_bias(acc);
            lds32(next_off, sb + SM_TILES + wg * 4);
            if (wgi > 0) named_bar(8 + wgi, 256);
            pin(k1); pin(k2); pin(k3);
            wg_fence();
            gemm2_chunk<288>(acc, k3, ds);
            wg_commit();
            gemm2_chunk<96>(acc, k1, ds);
            gemm2_chunk<192>(acc, k2, ds);
            wg_commit();
            if (wgi + 1 < NCONS) named_arrive(9 + wgi, 256);
            wg_wait<1>();
            uint32_t k0[24];
#pragma unroll
            for (int q = 0; q < 6; q++) lds128(k0[4 * q], k0[4 * q + 1], k0[4 * q + 2], k0[4 * q + 3], stage + lane16 + q * 512);
            pin(k0);
            wg_fence();
            gemm2_chunk<0>(acc, k0, ds);
            wg_commit();
            stage_x();
            wg_wait<1>();
            load_first();
            if (lane16 == 0) mbar_arrive(sb + BAR_PIN);
            mbar_wait(bar_r, rpar);
            wg_wait<0>();
            first = wg - 4;
        }
    }
    {
        const int nrest = ntiles - NCONS - wk.lent / 2;
        for (int jt = first; jt < nrest; jt += 4) {
            if (jt >= 0) {
            uint32_t d0[12], d1[12], g0[12], g1[12];
            tile_off = next_off;
            lds32(next_off, sb + SM_TILES + (jt + 4) * 4);
            if (jt >= S2_FIRST) named_bar(4 + wg, 256);
            wg_fence();
            gemm1_chunk<0>(d0, a, ds, 0);
            wg_commit();
            gemm1_chunk<48>(d1, a, ds, 0);
            wg_commit();
            load_bias(acc);
            const bool more = jt + 4 < nrest;
            tile_off = __shfl_sync(~0u, tile_off, 0);
            next_off = __shfl_sync(~0u, next_off, 0);
            wg_wait<1>();
#define CNX_PASS if (jt + 1 >= S2_FIRST && jt + 1 < nrest) named_arrive(4 + ((wg + 1) & 3), 256);
#define CNX_STEP(C, D, G)                                              \
    gelu_to(G, D);                                                     \
    if (C == 0 && jt == 0) {                                           \
        named_bar(3, NTHREADS);                                        \
        load_bias(acc);                                                \
    }                                                                  \
    wg_fence();                                                        \
    if (C < 6) gemm1_chunk<48 * (C < 6 ? C + 2 : 0)>(D, a, ds, zero); \
    gemm2_chunk<48 * C>(acc, G, ds);                                  \
    wg_commit();                                                       \
    if (C == S2_PASS) { CNX_PASS }                                     \
    wg_wait<(C < 7 ? 1 : 0)>();
            CNX_STEP(0, d0, g0)
            stage_x();
            if (more && elect_one()) prefetch_l2(reinterpret_cast<const char*>(out) + next_off + w4 * WARP_BYTES, WARP_BYTES);
            CNX_STEP(1, d1, g1)
            CNX_STEP(2, d0, g0)
            CNX_STEP(3, d1, g1)
            CNX_STEP(4, d0, g0)
            CNX_STEP(5, d1, g1)
            CNX_STEP(6, d0, g0)
            load_frags(more);
            if (lane16 == 0) mbar_arrive(sb + BAR_PIN);
            mbar_wait(bar_r, rpar);
            CNX_STEP(7, d1, g1)
#undef CNX_STEP
            }
            epilogue(acc);
        }
    }
    PROF(5);
}

}

typedef CUresult (*EncodeTiledFn)(CUtensorMap*, CUtensorMapDataType, cuuint32_t, void*, const cuuint64_t*, const cuuint64_t*,
                                  const cuuint32_t*, const cuuint32_t*, CUtensorMapInterleave, CUtensorMapSwizzle,
                                  CUtensorMapL2promotion, CUtensorMapFloatOOBfill);

extern "C" void kernel_launch(void* const* d_in, const int* in_sizes, int n_in, void* d_out, int out_size) {
    using namespace cnx;
    static EncodeTiledFn encode = nullptr;
    static int num_sms = 0;
    static Scratch* scratch = nullptr;
    if (!encode) {
        void* fn = nullptr;
        cudaDriverEntryPointQueryResult qr;
        cudaGetDriverEntryPoint("cuTensorMapEncodeTiled", &fn, cudaEnableDefault, &qr);
        encode = (EncodeTiledFn)fn;
        cudaGetSymbolAddress((void**)&scratch, g_scratch);
        int dev = 0;
        cudaGetDevice(&dev);
        cudaDeviceGetAttribute(&num_sms, cudaDevAttrMultiProcessorCount, dev);
        if (num_sms > MAX_CTAS) num_sms = MAX_CTAS;
        cudaFuncSetAttribute(block_kernel, cudaFuncAttributeMaxDynamicSharedMemorySize, SM_TOTAL);
    }
    CUtensorMap tm;
    cuuint64_t dims[3] = {(cuuint64_t)CH, (cuuint64_t)IMG_W, (cuuint64_t)IMG_H};
    cuuint64_t strides[2] = {(cuuint64_t)CH * 2, (cuuint64_t)CH * 2 * IMG_W};
    cuuint32_t box[3] = {(cuuint32_t)CH, (cuuint32_t)REGION_PX, 1};
    cuuint32_t estr[3] = {1, 1, 1};
    encode(&tm, CU_TENSOR_MAP_DATA_TYPE_BFLOAT16, 3, d_in[0], dims, strides, box, estr, CU_TENSOR_MAP_INTERLEAVE_NONE,
           CU_TENSOR_MAP_SWIZZLE_NONE, CU_TENSOR_MAP_L2_PROMOTION_L2_128B, CU_TENSOR_MAP_FLOAT_OOB_FILL_NONE);
    Descs ds;
    for (int c = 0; c < 8; c++)
        for (int k = 0; k < 6; k++) ds.w1[c][k] = make_desc(SB + SM_W1 + c * 6 * 1536 + k * 256, 128, 1536);
    for (int k = 0; k < 24; k++) ds.w2[k] = make_desc(SB + SM_W2 + k * 256, 128, 6144);
    ds.ones = make_desc(SB + SM_ONES, 0, 0);
    CUtensorMap tw;
    cuuint64_t wdims[2] = {(cuuint64_t)EX, (cuuint64_t)CH};
    cuuint64_t wstrides[1] = {(cuuint64_t)EX * 2};
    cuuint32_t wbox[2] = {64, (cuuint32_t)CH};
    encode(&tw, CU_TENSOR_MAP_DATA_TYPE_BFLOAT16, 2, d_in[2], wdims, wstrides, wbox, estr, CU_TENSOR_MAP_INTERLEAVE_NONE,
           CU_TENSOR_MAP_SWIZZLE_128B, CU_TENSOR_MAP_L2_PROMOTION_L2_128B, CU_TENSOR_MAP_FLOAT_OOB_FILL_NONE);
    const int per_cta = NTILES / num_sms, extra = NTILES % num_sms;
    if (per_cta + 9 > MAX_ROWS) return;
    const int lenders = extra * (8 * LENT + 1) <= num_sms && extra * (per_cta + 1) <= IMG_H ? extra : 0;
    block_kernel<<<num_sms, NTHREADS, SM_TOTAL>>>(tm, tw, (const __nv_bfloat16*)d_in[0], (const __nv_bfloat16*)d_in[1],
                                             (const __nv_bfloat16*)d_in[3],
                                             (const __nv_bfloat16*)d_in[4], (const __nv_bfloat16*)d_in[5], (__nv_bfloat16*)d_out,
                                             scratch, ds, 0, per_cta, extra, lenders);
}
```

```cpp
#include <cuda_runtime.h>
#include <cuda_bf16.h>
#include <cuda_fp16.h>
#include <cuda.h>
#include <stdint.h>

namespace cnx {

constexpr int IMG_H = 512, IMG_W = 512, CH = 96, EX = 384;
constexpr int TILE_W = 64;
constexpr int NTILES = (IMG_W / TILE_W) * IMG_H;
constexpr int NSLOT = 6;
constexpr int REGION_PX = 18;
constexpr int REGION_BYTES = REGION_PX * CH * 2;
constexpr int SLOT_BYTES = 4 * REGION_BYTES;
constexpr int A_LBO = 144, A_SBO = 12 * A_LBO;
constexpr int PREFETCH_ROWS = 3;
constexpr int NCONS = 3;
constexpr int CONS_THREADS = 128 * NCONS;
constexpr int NTHREADS = 128 + CONS_THREADS;
constexpr int MAX_ROWS = 52;
constexpr int TILE_BYTES = TILE_W * CH * 2, WARP_BYTES = TILE_BYTES / 4;
constexpr int S1_PASS = 1, S2_PASS = 1;
#define K_PASS 4
#define K_WAIT 20
#define K_STG 6
#define K_REL 6
#define K_ANCH 2
#define K_CVT 0
#define W2_EARLY 6
#define S2_FIRST 4
#define ORDER_P 3
#define ORDER_Q 1
static_assert(MAX_ROWS <= 128, "one table entry per producer thread");
static_assert(2 * A_SBO == REGION_BYTES && REGION_BYTES % 128 == 0, "region layout");

constexpr uint32_t SB = 1024;
constexpr int SM_W1 = 0;
constexpr int SM_W2 = SM_W1 + CH * EX * 2;
constexpr int SM_RING = SM_W2 + CH * EX * 2;
constexpr int SM_BIASH = SM_RING + NSLOT * SLOT_BYTES;
constexpr int SM_RED = SM_BIASH + 384;
constexpr int RED_MAX = 0, RED_LAUNCH = 4, RED_SQ_EXP = 8, RED_SUM_EXP = 12, RED_INV_RHO = 16;
constexpr int SM_ROWS = SM_RED + 256;
constexpr int SM_TILES = SM_ROWS + MAX_ROWS * 4;
constexpr int SM_ONES = SM_TILES + MAX_ROWS * 4;
constexpr int SM_BAR = SM_ONES + 128;
constexpr int BAR_X = SM_BAR;
constexpr int BAR_A = BAR_X + NSLOT * 4 * 8;
constexpr int BAR_E = BAR_A + NSLOT * 4 * 8;
constexpr int BAR_PIN = BAR_E + NSLOT * 4 * 8;
constexpr int BAR_W = BAR_PIN + 8;
constexpr int BAR_F = BAR_W + 6 * 8;
constexpr int BAR_R = BAR_F + 8;
constexpr int SM_TOTAL = BAR_R + 16 * 8;
constexpr int SM_FILTER = SM_RING + (NSLOT - 1) * SLOT_BYTES + 9 * 128;
constexpr int SM_SQ = SM_W2;
constexpr int SQ_ROW = 128 * 16, SQ_WG = 6 * SQ_ROW;
static_assert(SM_ONES % 16 == 0 && SM_TOTAL <= 232448, "shared memory budget");

constexpr float KZ = 0.3292034911525734f;
constexpr uint32_t GELU_C2 = 0x40d940d9u;
constexpr float INV_2KZ = 0.5f / KZ;
constexpr unsigned SPIN_LIMIT = 1u << 19;

constexpr int MAX_CTAS = 255;
constexpr int W2_GROUPS = EX / 8;
constexpr int LENT = 2, MAX_LENDERS = MAX_CTAS / (8 * LENT + 1);
struct Scratch {
    uint32_t w2h[EX * CH / 2];
    float w2max[EX];
    float bias[2][CH];
    unsigned long long sums[EX / 4][32];
    __device__ __forceinline__ unsigned long long* sum(int e) { return &sums[e >> 2][e & 3]; }
    uint4 lent[MAX_LENDERS * LENT * 8 * 4 * 3 * 32];
    unsigned launch, pad0[31], prep, pad1[31], lent_in, pad2[31], lent_out, pad3[31];
};
__device__ __align__(128) Scratch g_scratch;

#define PROF(k)

__device__ __forceinline__ uint32_t smem_u32(const void* p) { return (uint32_t)__cvta_generic_to_shared(p); }
__device__ __forceinline__ void mbar_init(uint32_t bar, uint32_t cnt) {
    asm volatile("mbarrier.init.shared::cta.b64 [%0], %1;" ::"r"(bar), "r"(cnt) : "memory");
}
__device__ __forceinline__ void mbar_arrive(uint32_t bar) {
    asm volatile("mbarrier.arrive.shared::cta.b64 _, [%0];" ::"r"(bar) : "memory");
}
__device__ __forceinline__ void mbar_expect_tx(uint32_t bar, uint32_t bytes) {
    asm volatile("mbarrier.arrive.expect_tx.shared::cta.b64 _, [%0], %1;" ::"r"(bar), "r"(bytes) : "memory");
}
__device__ __forceinline__ bool mbar_try(uint32_t bar, uint32_t par) {
    uint32_t ok;
    asm volatile("{\n.reg .pred p;\nmbarrier.try_wait.parity.shared::cta.b64 p, [%1], %2;\nselp.u32 %0, 1, 0, p;\n}\n"
                 : "=r"(ok) : "r"(bar), "r"(par) : "memory");
    return ok != 0;
}
__device__ __forceinline__ void mbar_wait(uint32_t bar, uint32_t par) {
    unsigned n = 0;
    while (!mbar_try(bar, par)) {
        if (++n > SPIN_LIMIT) __trap();
    }
}
__device__ __forceinline__ bool mbar_test(uint32_t bar, uint32_t par) {
    uint32_t ok;
    asm volatile("{\n.reg .pred p;\nmbarrier.test_wait.parity.shared::cta.b64 p, [%1], %2;\nselp.u32 %0, 1, 0, p;\n}\n"
                 : "=r"(ok) : "r"(bar), "r"(par) : "memory");
    return ok != 0;
}
__device__ __forceinline__ bool elect_one() {
    uint32_t ok;
    asm volatile("{\n.reg .pred p;\nelect.sync _|p, 0xffffffff;\nselp.u32 %0, 1, 0, p;\n}\n" : "=r"(ok));
    return ok != 0;
}
__device__ __forceinline__ uint32_t opaque(uint32_t v) { return __shfl_sync(~0u, v, threadIdx.x & 31); }
__device__ __forceinline__ void named_bar(int id, int n) { asm volatile("bar.sync %0, %1;" ::"r"(id), "r"(n) : "memory"); }
__device__ __forceinline__ void named_arrive(int id, int n) { asm volatile("bar.arrive %0, %1;" ::"r"(id), "r"(n) : "memory"); }
__device__ __forceinline__ void fence_async() { asm volatile("fence.proxy.async.shared::cta;" ::: "memory"); }
__device__ __forceinline__ uint64_t evict_first() {
    uint64_t p;
    asm("createpolicy.fractional.L2::evict_first.b64 %0, 1.0;" : "=l"(p));
    return p;
}
__device__ __forceinline__ void tma_row(uint32_t dst, const CUtensorMap* tm, uint32_t bar, int x, int y) {
    asm volatile("cp.async.bulk.tensor.3d.shared::cluster.global.mbarrier::complete_tx::bytes.L2::cache_hint [%0], [%1, {%3, %4, %5}], [%2], %6;"
                 ::"r"(dst), "l"(tm), "r"(bar), "r"(0), "r"(x), "r"(y), "l"(evict_first()) : "memory");
}
__device__ __forceinline__ void bulk_load_stream(uint32_t dst, const void* src, uint32_t bytes, uint32_t bar) {
    asm volatile("cp.async.bulk.shared::cluster.global.mbarrier::complete_tx::bytes.L2::cache_hint [%0], [%1], %2, [%3], %4;"
                 ::"r"(dst), "l"(src), "r"(bytes), "r"(bar), "l"(evict_first()) : "memory");
}
__device__ __forceinline__ void prefetch_l2(const void* src, uint32_t bytes) {
    asm volatile("cp.async.bulk.prefetch.L2.global [%0], %1;" ::"l"(src), "r"(bytes) : "memory");
}
__device__ __forceinline__ void tma_2d(uint32_t dst, const CUtensorMap* tm, uint32_t bar, int x, int y) {
    asm volatile("cp.async.bulk.tensor.2d.shared::cluster.global.mbarrier::complete_tx::bytes [%0], [%1, {%3, %4}], [%2];"
                 ::"r"(dst), "l"(tm), "r"(bar), "r"(x), "r"(y) : "memory");
}
__device__ __forceinline__ void bulk_load(uint32_t dst, const void* src, uint32_t bytes, uint32_t bar) {
    asm volatile("cp.async.bulk.shared::cluster.global.mbarrier::complete_tx::bytes [%0], [%1], %2, [%3];"
                 ::"r"(dst), "l"(src), "r"(bytes), "r"(bar) : "memory");
}
__device__ __forceinline__ void wg_fence() { asm volatile("wgmma.fence.sync.aligned;" ::: "memory"); }
__device__ __forceinline__ void wg_commit() { asm volatile("wgmma.commit_group.sync.aligned;" ::: "memory"); }
template <int N> __device__ __forceinline__ void wg_wait() { asm volatile("wgmma.wait_group.sync.aligned %0;" ::"n"(N) : "memory"); }
template <int N> __device__ __forceinline__ void pin(uint32_t (&d)[N]) {
#pragma unroll
    for (int q = 0; q < N; q++) asm volatile("" : "+r"(d[q])::"memory");
}
__device__ __forceinline__ void stg128(void* p, const uint32_t (&v)[4]) {
    asm volatile("st.global.v4.u32 [%0], {%1, %2, %3, %4};" ::"l"(p), "r"(v[0]), "r"(v[1]), "r"(v[2]), "r"(v[3]) : "memory");
}
__device__ __forceinline__ void ldg128(uint32_t (&v)[4], const void* p) {
    asm volatile("ld.global.L1::no_allocate.v4.u32 {%0, %1, %2, %3}, [%4];" : "=r"(v[0]), "=r"(v[1]), "=r"(v[2]), "=r"(v[3]) : "l"(p) : "memory");
}
__device__ __forceinline__ void ldg128_if(bool on, uint32_t (&v)[4], const void* p) {
    asm volatile("{\n.reg .pred p;\nsetp.ne.b32 p, %5, 0;\n@p ld.global.L1::no_allocate.v4.u32 {%0, %1, %2, %3}, [%4];\n}\n"
                 : "+r"(v[0]), "+r"(v[1]), "+r"(v[2]), "+r"(v[3]) : "l"(p), "r"((int)on) : "memory");
}
__device__ __forceinline__ uint4 ldg128_ordered(const void* p) {
    uint4 v;
    asm volatile("ld.global.nc.v4.u32 {%0, %1, %2, %3}, [%4];" : "=r"(v.x), "=r"(v.y), "=r"(v.z), "=r"(v.w) : "l"(p) : "memory");
    return v;
}
__host__ __device__ constexpr uint64_t make_desc(uint32_t addr, uint32_t lbo, uint32_t sbo) {
    return (uint64_t)((addr & 0x3FFFF) >> 4) | ((uint64_t)(lbo >> 4) << 16) | ((uint64_t)(sbo >> 4) << 32);
}
__device__ __forceinline__ void wgmma(uint32_t (&d)[12], uint32_t a0, uint32_t a1, uint32_t a2, uint32_t a3, uint64_t db, int acc) {
    asm volatile("{\n.reg .pred p;\nsetp.ne.b32 p, %17, 0;\n"
                 "wgmma.mma_async.sync.aligned.m64n48k16.f16.f16.f16 "
                 "{%0, %1, %2, %3, %4, %5, %6, %7, %8, %9, %10, %11}, "
                 "{%12, %13, %14, %15}, %16, p, 1, 1, 0;\n}\n"
                 : "+r"(d[0]), "+r"(d[1]), "+r"(d[2]), "+r"(d[3]), "+r"(d[4]), "+r"(d[5]), "+r"(d[6]), "+r"(d[7]), "+r"(d[8]), "+r"(d[9]), "+r"(d[10]), "+r"(d[11])
                 : "r"(a0), "r"(a1), "r"(a2), "r"(a3), "l"(db), "r"(acc));
}
__device__ __forceinline__ void wgmma(uint32_t (&d)[24], uint32_t a0, uint32_t a1, uint32_t a2, uint32_t a3, uint64_t db, int acc) {
    asm volatile("{\n.reg .pred p;\nsetp.ne.b32 p, %29, 0;\n"
                 "wgmma.mma_async.sync.aligned.m64n96k16.f16.f16.f16 "
                 "{%0, %1, %2, %3, %4, %5, %6, %7, %8, %9, %10, %11, %12, %13, %14, %15, %16, %17, %18, %19, %20, %21, %22, %23}, "
                 "{%24, %25, %26, %27}, %28, p, 1, 1, 0;\n}\n"
                 : "+r"(d[0]), "+r"(d[1]), "+r"(d[2]), "+r"(d[3]), "+r"(d[4]), "+r"(d[5]), "+r"(d[6]), "+r"(d[7]), "+r"(d[8]), "+r"(d[9]), "+r"(d[10]), "+r"(d[11]), "+r"(d[12]), "+r"(d[13]), "+r"(d[14]), "+r"(d[15]), "+r"(d[16]), "+r"(d[17]), "+r"(d[18]), "+r"(d[19]), "+r"(d[20]), "+r"(d[21]), "+r"(d[22]), "+r"(d[23])
                 : "r"(a0), "r"(a1), "r"(a2), "r"(a3), "l"(db), "r"(acc));
}
template <int ACC>
__device__ __forceinline__ void wgmma_rowsum(float (&d)[4], const uint32_t (&a)[4], uint64_t ones) {
    asm volatile("{\n.reg .pred p;\nsetp.ne.b32 p, %9, 0;\n"
                 "wgmma.mma_async.sync.aligned.m64n8k16.f32.bf16.bf16 {%0, %1, %2, %3}, {%4, %5, %6, %7}, %8, p, 1, 1, 0;\n}\n"
                 : "+f"(d[0]), "+f"(d[1]), "+f"(d[2]), "+f"(d[3])
                 : "r"(a[0]), "r"(a[1]), "r"(a[2]), "r"(a[3]), "l"(ones), "n"(ACC));
}
__device__ __forceinline__ void ldsm4(uint32_t (&r)[4], uint32_t addr) {
    asm volatile("ldmatrix.sync.aligned.m8n8.x4.shared.b16 {%0, %1, %2, %3}, [%4];"
                 : "=r"(r[0]), "=r"(r[1]), "=r"(r[2]), "=r"(r[3]) : "r"(addr) : "memory");
}
__device__ __forceinline__ void ldsm4_t(uint32_t (&r)[4], uint32_t addr) {
    asm volatile("ldmatrix.sync.aligned.m8n8.x4.trans.shared.b16 {%0, %1, %2, %3}, [%4];"
                 : "=r"(r[0]), "=r"(r[1]), "=r"(r[2]), "=r"(r[3]) : "r"(addr) : "memory");
}
__device__ __forceinline__ void stsm4(uint32_t addr, uint32_t a, uint32_t b, uint32_t c, uint32_t d) {
    asm volatile("stmatrix.sync.aligned.m8n8.x4.shared.b16 [%0], {%1, %2, %3, %4};"
                 ::"r"(addr), "r"(a), "r"(b), "r"(c), "r"(d) : "memory");
}
__device__ __forceinline__ uint32_t transpose8x8(uint32_t v) {
    uint32_t d; asm volatile("movmatrix.sync.aligned.m8n8.trans.b16 %0, %1;" : "=r"(d) : "r"(v)); return d;
}
__device__ __forceinline__ void spin_until(const unsigned* counter, unsigned target) {
    unsigned n = 0, c;
    do {
        asm volatile("ld.acquire.gpu.global.u32 %0, [%1];" : "=r"(c) : "l"(counter) : "memory");
        if (++n > SPIN_LIMIT) __trap();
    } while ((int)(c - target) < 0);
}
__device__ __forceinline__ void signal(unsigned* counter) {
    __syncwarp();
    if (elect_one()) asm volatile("red.release.gpu.global.add.u32 [%0], 1;" ::"l"(counter) : "memory");
    __syncwarp();
}
__device__ __forceinline__ void lds128(uint32_t& a, uint32_t& b, uint32_t& c, uint32_t& d, uint32_t addr) {
    asm volatile("ld.shared.v4.u32 {%0, %1, %2, %3}, [%4];" : "=r"(a), "=r"(b), "=r"(c), "=r"(d) : "r"(addr) : "memory");
}
__device__ __forceinline__ void lds64(uint32_t& a, uint32_t& b, uint32_t addr) {
    asm volatile("ld.shared.v2.u32 {%0, %1}, [%2];" : "=r"(a), "=r"(b) : "r"(addr) : "memory");
}
__device__ __forceinline__ void lds32(uint32_t& a, uint32_t addr) {
    asm volatile("ld.shared.u32 %0, [%1];" : "=r"(a) : "r"(addr) : "memory");
}
__device__ __forceinline__ int ldsi(uint32_t addr) {
    uint32_t v;
    lds32(v, addr);
    return (int)v;
}
__device__ __forceinline__ float ldsf(uint32_t addr) {
    uint32_t v;
    lds32(v, addr);
    return __uint_as_float(v);
}
__device__ __forceinline__ void sts32(uint32_t addr, uint32_t a) {
    asm volatile("st.shared.u32 [%0], %1;" ::"r"(addr), "r"(a) : "memory");
}
__device__ __forceinline__ void sts128(uint32_t addr, uint32_t a, uint32_t b, uint32_t c, uint32_t d) {
    asm volatile("st.shared.v4.u32 [%0], {%1, %2, %3, %4};" ::"r"(addr), "r"(a), "r"(b), "r"(c), "r"(d) : "memory");
}
__device__ __forceinline__ void sts64(uint32_t addr, uint32_t a, uint32_t b) {
    asm volatile("st.shared.v2.u32 [%0], {%1, %2};" ::"r"(addr), "r"(a), "r"(b) : "memory");
}
__device__ __forceinline__ void anchor(uint32_t addr, uint32_t a, uint32_t b, uint32_t c, uint32_t d) {
    asm volatile("{\n.reg .pred p;\nsetp.eq.b32 p, %0, 0;\n@p st.shared.v4.u32 [%0], {%1, %2, %3, %4};\n}\n"
                 ::"r"(addr), "r"(a), "r"(b), "r"(c), "r"(d) : "memory");
}
__device__ __forceinline__ uint32_t bf_fma(uint32_t a, uint32_t b, uint32_t c) {
    uint32_t d; asm("fma.rn.bf16x2 %0, %1, %2, %3;" : "=r"(d) : "r"(a), "r"(b), "r"(c)); return d;
}
__device__ __forceinline__ uint32_t bf_mul(uint32_t a, uint32_t b) {
    uint32_t d; asm("mul.rn.bf16x2 %0, %1, %2;" : "=r"(d) : "r"(a), "r"(b)); return d;
}
__device__ __forceinline__ uint32_t bf_absmax(uint32_t a, uint32_t b) {
    uint32_t d; asm("max.xorsign.abs.bf16x2 %0, %1, %2;" : "=r"(d) : "r"(a), "r"(b)); return d;
}
__device__ __forceinline__ uint32_t h_fma(uint32_t a, uint32_t b, uint32_t c) {
    uint32_t d; asm("fma.rn.f16x2 %0, %1, %2, %3;" : "=r"(d) : "r"(a), "r"(b), "r"(c)); return d;
}
__device__ __forceinline__ uint32_t h_mul(uint32_t a, uint32_t b) {
    uint32_t d; asm("mul.rn.f16x2 %0, %1, %2;" : "=r"(d) : "r"(a), "r"(b)); return d;
}
__device__ __forceinline__ uint32_t h_round8(uint32_t v) { return (v + 0x00040004u) & 0xfff8fff8u; }
__device__ __forceinline__ uint32_t h_tanh(uint32_t a) {
    uint32_t d; asm("tanh.approx.f16x2 %0, %1;" : "=r"(d) : "r"(a)); return d;
}
__device__ __forceinline__ uint32_t pack_h2(float lo, float hi) {
    uint32_t d; asm("cvt.rn.f16x2.f32 %0, %1, %2;" : "=r"(d) : "f"(hi), "f"(lo)); return d;
}
__device__ __forceinline__ uint32_t pack_bf2(float lo, float hi) {
    uint32_t d; asm("cvt.rn.bf16x2.f32 %0, %1, %2;" : "=r"(d) : "f"(hi), "f"(lo)); return d;
}
__device__ __forceinline__ float bf_lo(uint32_t v) { return __uint_as_float(v << 16); }
__device__ __forceinline__ float bf_hi(uint32_t v) { return __uint_as_float(v & 0xffff0000u); }
__device__ __forceinline__ float h_lo(uint32_t v) { return __low2float(*reinterpret_cast<__half2*>(&v)); }
__device__ __forceinline__ float h_hi(uint32_t v) { return __high2float(*reinterpret_cast<__half2*>(&v)); }
__device__ __forceinline__ float warp_absmax(uint32_t v) {
    return __uint_as_float(__reduce_max_sync(~0u, max((v & 0x7fffu) << 16, v & 0x7fff0000u)));
}
__device__ __forceinline__ uint32_t gelu2(uint32_t z) {
    uint32_t p = h_fma(z, z, GELU_C2);
    uint32_t t = h_tanh(h_mul(z, p));
    return h_fma(z, t, z);
}
__device__ __forceinline__ float grn_norm(float ss) {
    float r;
    asm("sqrt.approx.f32 %0, %1;" : "=f"(r) : "f"(fmaf(ss, INV_2KZ * INV_2KZ, 1e-6f)));
    return r;
}
__device__ __forceinline__ float pow2i(int e) { return __uint_as_float((uint32_t)(e + 127) << 23); }
__device__ __forceinline__ int ilog2f(float v) {
    int e = (int)((__float_as_uint(v) >> 23) & 0xff) - 127;
    return max(-100, min(100, e));
}

__device__ __forceinline__ int square_exp(float w1max) {
    const int e = w1max > 0.f ? 4 - ilog2f(2.f * KZ * 96.f * w1max) : 0;
    return (e >= 0 && e <= 6) ? 0 : max(-14, min(e, 14));
}
__device__ __forceinline__ int sum_exp(float w1max) {
    return w1max > 0.f ? max(-90, min(90, 33 - 2 * ilog2f(2.f * KZ * 96.f * w1max))) : 0;
}
__device__ __forceinline__ float row_scale(float m) { return m > 0.f ? pow2i(2 - ilog2f(m)) : 1.f; }

struct Work {
    int tA, tB, nA, nB, dir, rows, lent;
    __device__ __forceinline__ int tile(int j) const { return j < nA ? tA + dir * j : tB + dir * (j - nA); }
};
__device__ __forceinline__ Work get_work(int cta, int per_cta, int extra, int lenders) {
    Work w;
    w.lent = cta < lenders ? LENT : 0;
    const int t0 = cta * per_cta + min(cta, extra);
    const int t1 = t0 + per_cta + (cta < extra);
    const int tm = min(t1, (t0 | 511) + 1);
    const bool swap = t1 > tm && t1 - tm < tm - t0, down = cta & 1;
    w.nA = swap ? t1 - tm : tm - t0;
    w.nB = t1 - t0 - w.nA;
    w.tA = down ? (swap ? tm : t0) : (swap ? t1 : tm) - 1;
    w.tB = down ? (swap ? t0 : tm) : (swap ? tm : t1) - 1;
    w.dir = down ? 1 : -1;
    w.rows = w.nA + 2 + (w.nB ? w.nB + 2 : 0);
    return w;
}
__device__ __forceinline__ int row_code(const Work& w, int i) {
    const bool in_a = i < w.nA + 2;
    const int t = in_a ? w.tA : w.tB;
    return ((t & 511) + w.dir * ((in_a ? i : i - (w.nA + 2)) - 1)) << 16 | (t >> 9) * TILE_W;
}
__device__ __forceinline__ uint32_t tile_offset(int tile) { return ((tile & 511) * IMG_W + (tile >> 9) * TILE_W) * (CH * 2); }
__device__ __forceinline__ int tile_order(int j, int n) {
    const int olds = (j / ORDER_P) * ORDER_Q + max(0, j % ORDER_P - (ORDER_P - ORDER_Q));
    return (j % ORDER_P >= ORDER_P - ORDER_Q) ? olds : n - 1 - (j - olds);
}
__device__ __forceinline__ void issue_region(const CUtensorMap* tm, uint32_t dst, uint32_t bar, int warp, int code) {
    mbar_expect_tx(bar, REGION_BYTES);
    tma_row(dst, tm, bar, (code & 0xffff) + (16 * warp - 1), code >> 16);
}

__device__ __forceinline__ void conv_producer(const Work& wk, const CUtensorMap* tm, Scratch* sc, uint32_t sb, int warp) {
    const int lane = threadIdx.x & 31;
    const int j = lane & 15, grp = lane >> 4;
    const uint32_t reg0 = sb + SM_RING + warp * REGION_BYTES;
    const uint32_t bars = sb + SM_BAR + warp * 8;
    if (lane >= PREFETCH_ROWS && lane < 3 * NSLOT) mbar_init(bars + lane * 32, 1);
    if (lane >= 28) mbar_init(sb + BAR_R + ((lane - 28) * 4 + warp) * 8, 1);
    if (lane == 0 && warp == 0) mbar_init(sb + BAR_PIN, 1);
    if (warp * 32 + lane < MAX_ROWS) {
        sts32(sb + SM_ROWS + (warp * 32 + lane) * 4, row_code(wk, warp * 32 + lane));
        sts32(sb + SM_TILES + (warp * 32 + lane) * 4, tile_offset(wk.tile(wk.lent + tile_order(max(warp * 32 + lane - wk.lent / 2, 0), wk.nA + wk.nB - NCONS - wk.lent))));
    }
    const uint32_t ld64 = opaque(reg0 + grp * 8 * 192 + j * 8), ld32 = opaque(reg0 + grp * 8 * 192 + 128 + j * 4);
    const uint32_t st64 = opaque(reg0 + grp * A_SBO + (j >> 1) * A_LBO + (j & 1) * 8);
    const uint32_t st32 = opaque(reg0 + grp * A_SBO + (8 + (j >> 2)) * A_LBO + (j & 3) * 4);
    fence_async();
    named_bar(0, NTHREADS);
    uint32_t w[3][3][3];
    mbar_wait(sb + BAR_F, 0);
#pragma unroll
    for (int tap = 0; tap < 9; tap++) {
        const uint32_t p = sb + SM_FILTER + (3 + wk.dir * 3 * (tap / 3 - 1) + tap % 3) * (CH * 2);
        lds64(w[tap / 3][tap % 3][0], w[tap / 3][tap % 3][1], p + 8 * j);
        lds32(w[tap / 3][tap % 3][2], p + 128 + 4 * j);
    }
#pragma unroll
    for (int tap = 0; tap < 9; tap++) sts64(reg0 + (NSLOT - 1) * SLOT_BYTES + tap * 128 + j * 8, w[tap / 3][tap % 3][1], w[tap / 3][tap % 3][0]);
#pragma unroll
    for (int tap = 0; tap < 9; tap++) lds64(w[tap / 3][tap % 3][1], w[tap / 3][tap % 3][0], reg0 + (NSLOT - 1) * SLOT_BYTES + tap * 128 + j * 8);
    fence_async();
    named_bar(1, 128);
    static_assert(2 * PREFETCH_ROWS == NSLOT, "prefetch slot arithmetic");
    uint32_t so = 0, bo = 0, par = 0, tbl = sb + SM_ROWS + PREFETCH_ROWS * 4;
    const uint32_t tbl_end = sb + SM_ROWS + wk.rows * 4, publish = wk.lent ? tbl + 12 * 4 : 0;
    auto next_row = [&](int code, bool e_ready) {
        const bool wrap = bo == (NSLOT - 1) * 32, low = bo < PREFETCH_ROWS * 32;
        if (tbl < tbl_end) {
            const uint32_t pbo = low ? bo + PREFETCH_ROWS * 32 : bo - PREFETCH_ROWS * 32;
            if (!e_ready) mbar_wait(bars + (BAR_E - SM_BAR) + pbo, par ^ low);
            code = __shfl_sync(~0u, code, 0);
            if (elect_one()) issue_region(tm, reg0 + (low ? so + PREFETCH_ROWS * SLOT_BYTES : so - PREFETCH_ROWS * SLOT_BYTES), bars + pbo, warp, code);
        }
        tbl += 4;
        so = wrap ? 0 : so + SLOT_BYTES;
        bo = wrap ? 0 : bo + 32;
        par ^= wrap;
    };
    int n = wk.nA;
#pragma unroll 1
    for (int seg = 0; seg < 2 && n > 0; seg++, n = wk.nB) {
        uint32_t accB[8][3], accC[8][3];
        {
            const uint32_t so0 = so, bo0 = bo;
            uint32_t so1, bo1;
#pragma unroll 1
            for (int r = 0; r < 2; r++) {
                uint32_t code;
                lds32(code, tbl);
                mbar_wait(bars + bo, par);
                so1 = so;
                bo1 = bo;
                next_row(code, false);
            }
#pragma unroll
            for (int p = 0; p < 10; p++) {
                uint32_t u[3], v[3];
                lds64(u[0], u[1], so0 + ld64 + p * 192);
                lds32(u[2], so0 + ld32 + p * 192);
                lds64(v[0], v[1], so1 + ld64 + p * 192);
                lds32(v[2], so1 + ld32 + p * 192);
#pragma unroll
                for (int dx = 0; dx < 3; dx++) {
                    const int o = p - dx;
                    if (o < 0 || o > 7) continue;
#pragma unroll
                    for (int q = 0; q < 3; q++) {
                        accB[o][q] = bf_fma(v[q], w[1][dx][q], dx == 0 ? bf_mul(u[q], w[0][dx][q]) : bf_fma(u[q], w[0][dx][q], accB[o][q]));
                        accC[o][q] = dx == 0 ? bf_mul(v[q], w[0][dx][q]) : bf_fma(v[q], w[0][dx][q], accC[o][q]);
                    }
                }
            }
            anchor(ld64, accB[7][0], accB[7][1], accB[7][2], 0);
            __syncwarp();
            if (elect_one()) {
                mbar_arrive(bars + (BAR_A - SM_BAR) + bo0);
                mbar_arrive(bars + (BAR_E - SM_BAR) + bo0);
                mbar_arrive(bars + (BAR_A - SM_BAR) + bo1);
                mbar_arrive(bars + (BAR_E - SM_BAR) + bo1);
            }
        }
        bool x_ready = false;
#pragma unroll 1
        for (int k = 0; k < n; k++) {
            if (!x_ready) mbar_wait(bars + bo, par);
            uint32_t out[8][3];
            int code;
            bool e_ready;
#pragma unroll
            for (int p = 0; p < 10; p++) {
                uint32_t xv[3];
                lds64(xv[0], xv[1], so + ld64 + p * 192);
                lds32(xv[2], so + ld32 + p * 192);
                if (p == 9) {
                    const bool wrap = bo == (NSLOT - 1) * 32, low = bo < PREFETCH_ROWS * 32;
                    asm volatile("ld.shared.u32 %0, [%1];" : "=r"(code) : "r"(tbl));
                    e_ready = mbar_test(bars + (BAR_E - SM_BAR) + (low ? bo + PREFETCH_ROWS * 32 : bo - PREFETCH_ROWS * 32), par ^ low);
                    x_ready = mbar_test(bars + (wrap ? 0 : bo + 32), par ^ wrap);
                }
#pragma unroll
                for (int dx = 0; dx < 3; dx++) {
                    const int o = p - dx;
                    if (o < 0 || o > 7) continue;
#pragma unroll
                    for (int q = 0; q < 3; q++) {
                        out[o][q] = bf_fma(xv[q], w[2][dx][q], dx == 0 ? accB[o][q] : out[o][q]);
                        accB[o][q] = bf_fma(xv[q], w[1][dx][q], dx == 0 ? accC[o][q] : accB[o][q]);
                        accC[o][q] = dx == 0 ? bf_mul(xv[q], w[0][dx][q]) : bf_fma(xv[q], w[0][dx][q], accC[o][q]);
                    }
                }
            }
            __syncwarp();
#pragma unroll
            for (int o = 0; o < 8; o++) {
                sts64(so + st64 + o * 16, out[o][0], out[o][1]);
                sts32(so + st32 + o * 16, out[o][2]);
            }
            __syncwarp();
            if (elect_one()) mbar_arrive(bars + (BAR_A - SM_BAR) + bo);
            if (tbl == publish) signal(&sc->lent_in);
            next_row(code, e_ready);
        }
    }
}

template <bool SCALED, int K0 = 0, int K1 = 3>
__device__ __forceinline__ void gelu_sq(uint32_t (&d)[24], uint32_t (&keep)[24], uint32_t sq_addr, uint32_t scale2) {
    pin(d);
#pragma unroll
    for (int k = K0; k < K1; k++) {
        uint32_t hs[4];
        lds128(hs[0], hs[1], hs[2], hs[3], sq_addr + k * SQ_ROW);
#pragma unroll
        for (int q = 0; q < 4; q++) {
            uint32_t g0 = gelu2(d[8 * k + 2 * q]), g1 = gelu2(d[8 * k + 2 * q + 1]);
            keep[8 * k + 2 * q] = g0;
            keep[8 * k + 2 * q + 1] = g1;
            if (SCALED) { g0 = h_mul(g0, scale2); g1 = h_mul(g1, scale2); }
            hs[q] = h_fma(g1, g1, h_fma(g0, g0, hs[q]));
        }
        sts128(sq_addr + k * SQ_ROW, hs[0], hs[1], hs[2], hs[3]);
    }
}
__device__ __forceinline__ void gelu_sq_reg(uint32_t (&d)[24], uint32_t (&hs)[12]) {
    pin(d);
#pragma unroll
    for (int q = 0; q < 12; q++) {
        const uint32_t g0 = gelu2(d[2 * q]), g1 = gelu2(d[2 * q + 1]);
        hs[q] = h_fma(g1, g1, h_fma(g0, g0, hs[q]));
    }
}
__device__ __forceinline__ void gelu_to(uint32_t (&g)[12], uint32_t (&d)[12]) {
    pin(d);
#pragma unroll
    for (int q = 0; q < 12; q++) g[q] = gelu2(d[q]);
    pin(g);
}
__device__ __forceinline__ void load_tile(uint32_t (&raw)[6][4], uint32_t addr) {
#pragma unroll
    for (int s = 0; s < 6; s++) ldsm4(raw[s], addr + s * 2 * A_LBO);
}
__device__ __forceinline__ uint2 ln_stats(const uint32_t (&raw)[6][4], uint64_t ones) {
    uint32_t sq[6][4];
#pragma unroll
    for (int s = 0; s < 6; s++)
#pragma unroll
        for (int q = 0; q < 4; q++) sq[s][q] = bf_mul(raw[s][q], raw[s][q]);
    float sum[4], ssq[4];
    wg_fence();
    wgmma_rowsum<0>(sum, raw[0], ones);
#pragma unroll
    for (int s = 1; s < 6; s++) wgmma_rowsum<1>(sum, raw[s], ones);
    wgmma_rowsum<0>(ssq, sq[0], ones);
#pragma unroll
    for (int s = 1; s < 6; s++) wgmma_rowsum<1>(ssq, sq[s], ones);
    wg_commit();
    wg_wait<0>();
    uint32_t st[2];
#pragma unroll
    for (int h = 0; h < 2; h++) {
        asm volatile("" : "+f"(sum[2 * h]), "+f"(ssq[2 * h])::"memory");
        const float mean = sum[2 * h] * (1.f / CH);
        const float var = fmaxf(fmaf(ssq[2 * h], 1.f / CH, -mean * mean), 0.f);
        float rstd;
        asm("rsqrt.approx.ftz.f32 %0, %1;" : "=f"(rstd) : "f"(var + 1e-5f));
        rstd = bf_lo(pack_bf2(rstd * (K_CVT == 0 ? KZ : KZ * 0x1p-112f), 0.f));
        st[h] = pack_bf2(rstd, -mean * rstd);
    }
    return make_uint2(st[0], st[1]);
}
__device__ __forceinline__ void ln_apply(uint32_t (&a)[6][4], const uint2& st) {
    const uint32_t sc[2] = {__byte_perm(st.x, 0, 0x1010), __byte_perm(st.y, 0, 0x1010)};
    const uint32_t sh[2] = {__byte_perm(st.x, 0, 0x3232), __byte_perm(st.y, 0, 0x3232)};
#pragma unroll
    for (int s = 0; s < 6; s++)
#pragma unroll
        for (int q = 0; q < 4; q++) {
            const uint32_t v = bf_fma(a[s][q], sc[q & 1], sh[q & 1]);
            a[s][q] = K_CVT == 0 ? pack_h2(bf_lo(v), bf_hi(v)) : (v & 0x7fff7fffu) * 7u + v;
        }
}
struct Cursor {
    int slot;
    uint32_t par;
    __device__ __forceinline__ void advance(int n) {
        slot += n;
        if (slot >= NSLOT) { slot -= NSLOT; par ^= 1; }
    }
};
struct Descs {
    uint64_t w1[8][6];
    uint64_t w2[24];
    uint64_t ones;
};
template <int E0, int N>
__device__ __forceinline__ void gemm1_chunk(uint32_t (&d)[N], const uint32_t (&a)[6][4], const Descs& ds, int zero) {
#pragma unroll
    for (int s = 0; s < 6; s++) wgmma(d, a[s][0], a[s][1], a[s][2], a[s][3], ds.w1[E0 / 48][s], s ? 1 : zero);
}
template <int E0, int N>
__device__ __forceinline__ void gemm2_chunk(uint32_t (&acc)[24], const uint32_t (&g)[N], const Descs& ds) {
#pragma unroll
    for (int s = 0; s < N / 4; s++) wgmma(acc, g[4 * s], g[4 * s + 1], g[4 * s + 2], g[4 * s + 3], ds.w2[E0 / 16 + s], 1);
}

__global__ void __launch_bounds__(NTHREADS, 1)
block_kernel(const __grid_constant__ CUtensorMap tmap, const __grid_constant__ CUtensorMap tmap_w1,
             const __nv_bfloat16* __restrict__ x, const __nv_bfloat16* __restrict__ dw, const __nv_bfloat16* __restrict__ w2,
             const __nv_bfloat16* __restrict__ gamma, const __nv_bfloat16* __restrict__ beta, __nv_bfloat16* __restrict__ out,
             Scratch* __restrict__ sc, const __grid_constant__ Descs ds,
             const int zero, const int per_cta, const int extra, const int lenders) {
    extern __shared__ __align__(1024) uint8_t smem[];
    constexpr uint32_t sb = SB;
    const int tid = threadIdx.x;
    const Work wk = get_work(blockIdx.x, per_cta, extra, lenders);
    constexpr uint32_t s_red = sb + SM_RED;
    if (smem_u32(smem) != SB) __trap();

    PROF(0);
    const int warp_id = __shfl_sync(~0u, tid >> 5, 0);
    const int cw = warp_id - 4, wgi = cw >> 2, w4 = warp_id & 3;
    if (elect_one()) {
        if (warp_id < 8) {
            mbar_init(sb + BAR_X + warp_id * 8, 1);
            if (warp_id < 4) mbar_init(sb + BAR_X + (warp_id + 8) * 8, 1);
            fence_async();
#pragma unroll 1
            for (int r = warp_id >> 2; r < PREFETCH_ROWS; r += 2)
                issue_region(&tmap, sb + SM_RING + r * SLOT_BYTES + w4 * REGION_BYTES, sb + BAR_X + (r * 4 + w4) * 8, w4,
                             ((wk.tA & 511) + wk.dir * (r - 1)) << 16 | (wk.tA >> 9) * TILE_W);
        } else if (warp_id < 15) {
            const int b = warp_id - 8;
            mbar_init(sb + BAR_W + b * 8, 1);
            fence_async();
            mbar_expect_tx(sb + BAR_W + b * 8, b < 6 ? 64 * CH * 2 : 9 * CH * 2);
            if (b < 6) tma_2d(sb + SM_W2 + b * (64 * CH * 2), &tmap_w1, sb + BAR_W + b * 8, 64 * b, 0);
            else bulk_load(sb + SM_FILTER, dw, 9 * CH * 2, sb + BAR_F);
        }
    }
    __syncwarp();
    const int ntiles = wk.nA + wk.nB;
    const int wg = warp_id >> 2;
    int first = wg;
    uint32_t a[6][4], acc[24], tile_off, next_off, stage, inv_rho2 = 0, rpar = 0, bias_addr, lane16, lane_off;
    auto set_lane = [&](uint32_t lane) {
        bias_addr = sb + SM_BIASH + (lane & 3) * 96;
        lane16 = lane * 16;
        lane_off = ((lane >> 2) * CH + 8 * (lane & 3)) * 2;
    };
    const uint32_t bar_r = sb + BAR_R + warp_id * 8;
    auto load_bias = [&](uint32_t (&acc)[24]) {
#pragma unroll
        for (int q = 0; q < 6; q++) lds128(acc[4 * q], acc[4 * q + 1], acc[4 * q + 2], acc[4 * q + 3], bias_addr + q * 16);
    };
    auto load_frags = [&](bool on) {
#pragma unroll
        for (int s = 0; s < 6; s++) ldg128_if(on, a[s], reinterpret_cast<const char*>(out) + next_off + w4 * WARP_BYTES + lane16 + s * 512);
    };
    auto load_first = [&]() {
#pragma unroll
        for (int s = 0; s < 6; s++) ldg128(a[s], reinterpret_cast<const char*>(out) + next_off + w4 * WARP_BYTES + lane16 + s * 512);
    };
    auto stage_x = [&]() {
        if (elect_one()) {
            mbar_expect_tx(bar_r, WARP_BYTES);
            bulk_load_stream(stage, reinterpret_cast<const char*>(x) + tile_off + w4 * WARP_BYTES, WARP_BYTES, bar_r);
        }
    };
    auto epilogue = [&](uint32_t (&acc)[24]) {
        pin(acc);
        rpar ^= 1;
        uint4* op = reinterpret_cast<uint4*>(reinterpret_cast<char*>(out) + tile_off + w4 * WARP_BYTES + lane_off);
#pragma unroll
        for (int h = 0; h < 2; h++)
#pragma unroll
            for (int m = 0; m < 3; m++) {
                uint32_t xin[4], o[4];
                lds128(xin[0], xin[1], xin[2], xin[3], stage + lane_off + h * 1536 + m * 64);
#pragma unroll
                for (int q = 0; q < 4; q++) {
                    const uint32_t v = acc[2 * (4 * m + q) + h];
                    o[q] = bf_fma(pack_bf2(h_lo(v), h_hi(v)), inv_rho2, xin[q]);
                }
                __stcs(op + h * 96 + m * 4, make_uint4(o[0], o[1], o[2], o[3]));
            }
        __syncwarp();
    };
    auto reduce = [&](int q, uint32_t lane, bool leader) {
        const int part = lane >> 2, ch = 32 * q + 8 * (part >> 1) + 2 * (lane & 3) + (part & 1);
        uint32_t sq_e, sum_e;
        lds64(sq_e, sum_e, s_red + RED_SQ_EXP);
        const float to_fixed = pow2i(sum_e - 2 * sq_e);
        unsigned long long* dst = sc->sum(ch);
        named_bar(11, CONS_THREADS);
        const unsigned in_piece = ch - (blockIdx.x - lenders) % 8 * 48;
        const float helped = in_piece < 48 ? ldsf(sb + SM_BIASH + in_piece * 4) * pow2i(2 * sq_e) : 0.f;
        float f[8] = {};
        int slot = wk.rows % NSLOT;
#pragma unroll 1
        for (int i = 0; i < NCONS; i++) {
            if (i == NCONS - 1) {
                named_bar(13, CONS_THREADS);
                if (leader) {
                    fence_async();
                    bulk_load(sb + SM_W2, sc->w2h, (NCONS - 1) * SQ_WG, sb + BAR_W);
                }
                __syncwarp();
                named_bar(14, NTHREADS);
            }
            const uint32_t src = sb + lane * 16 + q * SQ_ROW + (q < 6 ? SM_SQ + i * SQ_WG : sq_e ? SM_SQ + (NCONS - 1 + i) * SQ_WG : SM_RING + slot * SLOT_BYTES - SQ_WG);
            slot = slot == NSLOT - 1 ? 0 : slot + 1;
#pragma unroll
            for (int r = 0; r < 4; r++) {
                uint32_t u[4];
                lds128(u[0], u[1], u[2], u[3], src + r * 512);
#pragma unroll
                for (int k = 0; k < 4; k++) { f[2 * k] += h_lo(u[k]); f[2 * k + 1] += h_hi(u[k]); }
            }
        }
        const bool b2 = part & 4, b1 = part & 2, b0 = part & 1;
        float r4[4], r2[2];
#pragma unroll
        for (int k = 0; k < 4; k++) r4[k] = (b2 ? f[k + 4] : f[k]) + __shfl_xor_sync(~0u, b2 ? f[k] : f[k + 4], 16);
#pragma unroll
        for (int k = 0; k < 2; k++) r2[k] = (b1 ? r4[k + 2] : r4[k]) + __shfl_xor_sync(~0u, b1 ? r4[k] : r4[k + 2], 8);
        const float tot = (b0 ? r2[1] : r2[0]) + __shfl_xor_sync(~0u, b0 ? r2[0] : r2[1], 4);
        atomicAdd(dst, __float2ull_rn(fminf((tot + helped) * to_fixed, 0x1p47f)) << 8 | 1);
    };
    const uint32_t s_fac = sb + SM_RING + (wk.rows + 1) % NSLOT * SLOT_BYTES + SQ_WG;
    if (warp_id < 4) {
        conv_producer(wk, &tmap, sc, sb, warp_id);
        const int lane = opaque(tid & 31), g = lane >> 2, t = lane & 3;
        const unsigned epoch = ldsi(s_red + RED_LAUNCH);
        set_lane(lane);
#pragma unroll 1
        for (int q = gridDim.x - 1 - blockIdx.x; q < W2_GROUPS; q += gridDim.x) {
            uint32_t u[3], rmax = 0;
#pragma unroll
            for (int m = 0; m < 3; m++) {
                const uint4 w = ldg128_ordered(w2 + (8 * q + g) * CH + 32 * m + 8 * t);
                rmax = bf_absmax(bf_absmax(rmax, bf_absmax(w.x, w.y)), bf_absmax(w.z, w.w));
                u[m] = w4 & 2 ? (w4 & 1 ? w.w : w.z) : (w4 & 1 ? w.y : w.x);
            }
            const float bt = __bfloat162float(beta[8 * q + g]);
            rmax = bf_absmax(rmax, __shfl_xor_sync(~0u, rmax, 1));
            rmax = bf_absmax(rmax, __shfl_xor_sync(~0u, rmax, 2));
            const float mx = fmaxf(fabsf(bf_lo(rmax)), fabsf(bf_hi(rmax))), rs = row_scale(mx);
            if (t == 0 && w4 == 0) { sc->w2max[8 * q + g] = mx; *sc->sum(8 * q + g) = 0; }
#pragma unroll
            for (int m = 0; m < 3; m++) {
                float lo = bf_lo(u[m]), hi = bf_hi(u[m]);
                sc->w2h[(4 * m + w4) * 1536 + q * 32 + lane] = transpose8x8(pack_h2(lo * rs, hi * rs));
                lo *= bt; hi *= bt;
#pragma unroll
                for (int o = 4; o <= 16; o <<= 1) { lo += __shfl_xor_sync(~0u, lo, o); hi += __shfl_xor_sync(~0u, hi, o); }
                if (g == 0) {
                    float* dst = &sc->bias[epoch & 1][32 * m + 8 * t + 2 * w4];
                    asm volatile("red.global.add.v2.f32 [%0], {%1, %2};" ::"l"(dst), "f"(lo), "f"(hi) : "memory");
                }
            }
            asm volatile("fence.proxy.async.global;" ::: "memory");
            signal(&sc->prep);
        }
        const unsigned piece = blockIdx.x - lenders;
        if (piece < 8 * LENT * lenders) {
            spin_until(&sc->lent_in, (epoch + 1) * 4 * lenders);
            next_off = tile_offset(get_work(piece / (8 * LENT), per_cta, extra, lenders).tile(piece / 8 % LENT));
            load_first();
            uint32_t d[12], gl[12];
            wg_fence();
#pragma unroll
            for (int s = 0; s < 6; s++) wgmma(d, a[s][0], a[s][1], a[s][2], a[s][3], ds.w1[0][s] + piece % 8 * (6 * 1536 / 16), s ? 1 : 0);
            wg_commit();
            wg_wait<0>();
            gelu_to(gl, d);
#pragma unroll
            for (int s = 0; s < 3; s++) sc->lent[((piece * 4 + w4) * 3 + s) * 32 + lane] = make_uint4(gl[4 * s], gl[4 * s + 1], gl[4 * s + 2], gl[4 * s + 3]);
            float f[6], r[3];
#pragma unroll
            for (int j = 0; j < 6; j++) {
                const float lo = fmaf(h_lo(gl[2 * j]), h_lo(gl[2 * j]), h_lo(gl[2 * j + 1]) * h_lo(gl[2 * j + 1]));
                const float hi = fmaf(h_hi(gl[2 * j]), h_hi(gl[2 * j]), h_hi(gl[2 * j + 1]) * h_hi(gl[2 * j + 1]));
                f[j] = (g & 1 ? hi : lo) + __shfl_xor_sync(~0u, g & 1 ? lo : hi, 4);
            }
#pragma unroll
            for (int j = 0; j < 3; j++) {
                r[j] = (g & 2 ? f[j + 3] : f[j]) + __shfl_xor_sync(~0u, g & 2 ? f[j] : f[j + 3], 8);
                asm volatile("red.shared.add.f32 [%0], %1;" ::"r"(sb + SM_BIASH + (8 * j + 12 * (g & 2) + 2 * t + (g & 1)) * 4), "f"(r[j]) : "memory");
            }
        }
        if (piece < 8 * LENT * lenders) signal(&sc->lent_out);
        const bool leader = warp_id == 0 && lane == 0;
        const float w1max = ldsf(s_red + RED_MAX), from_fixed = pow2i(-ldsi(s_red + RED_SUM_EXP));
        const bool plain = ldsi(s_red + RED_SQ_EXP) == 0;
        auto load_upper = [&]() {
            bulk_load(sb + SM_W2 + NCONS * SQ_WG, reinterpret_cast<const char*>(sc->w2h) + NCONS * SQ_WG, EX * CH * 2 - NCONS * SQ_WG, sb + BAR_W);
        };
        if (leader) {
            spin_until(&sc->prep, (epoch + 1) * 4 * W2_GROUPS);
            asm volatile("fence.proxy.async.global;" ::: "memory");
            fence_async();
            mbar_expect_tx(sb + BAR_W, EX * CH * 2);
            if (plain) load_upper();
        }
        __syncwarp();
        named_bar(1, 128);
        const int i0 = w4 * 32 + lane;
        float gam[3], rmax[3];
#pragma unroll
        for (int m = 0; m < 3; m++) { gam[m] = __bfloat162float(gamma[i0 + 128 * m]); rmax[m] = __ldcg(&sc->w2max[i0 + 128 * m]); }
        float2 bpair = make_float2(0.f, 0.f);
        if (i0 < 96) bpair = __ldcg(reinterpret_cast<const float2*>(&sc->bias[epoch & 1][32 * (i0 % 24 >> 3) + 8 * (i0 / 24) + (i0 % 24 & 6)]));
        const float gbound = fmaxf(2.f * KZ * 9.7979590f * 192.f * w1max, 1.f) * 19.5959180f * INV_2KZ;
        const unsigned fixed = __reduce_max_sync(~0u, __float_as_uint(fmaf(gbound, fmaxf(fmaxf(rmax[0], rmax[1]), rmax[2]), fmaxf(fabsf(bpair.x), fabsf(bpair.y)))));
        if (lane == 0) sts32(s_red + 96 + w4 * 4, fixed);
        reduce(4 * (NCONS - 1) + w4, lane, leader);
        PROF(2);
        named_bar(15, CONS_THREADS);
        if (leader) {
            fence_async();
            bulk_load(sb + SM_W2 + (NCONS - 1) * SQ_WG, reinterpret_cast<const char*>(sc->w2h) + (NCONS - 1) * SQ_WG, SQ_WG, sb + BAR_W);
            if (!plain) load_upper();
        }
        stage = sb + SM_RING + (wk.rows % NSLOT) * SLOT_BYTES + w4 * REGION_BYTES;
        auto grn = [&]() {
            auto peek = [&](int e) {
                unsigned long long v;
                asm volatile("ld.relaxed.gpu.global.u64 %0, [%1];" : "=l"(v) : "l"(sc->sum(e)) : "memory");
                return v;
            };
            unsigned n = 0;
            while (((unsigned)peek((blockIdx.x * 4 + w4) % (EX / 4) * 4) & 255u) != gridDim.x)
                if (++n > SPIN_LIMIT) __trap();
            unsigned long long sum[3];
            for (;;) {
                bool all = true;
#pragma unroll
                for (int m = 0; m < 3; m++) {
                    sum[m] = peek(i0 + 128 * m);
                    all &= ((unsigned)sum[m] & 255u) == gridDim.x;
                }
                if (__all_sync(~0u, all)) break;
                if (++n > SPIN_LIMIT) __trap();
            }
            PROF(3);
            if (blockIdx.x == 0 && leader) sc->launch = epoch + 1;
            float gx[3], tot = 0.f, vary = 0.f;
#pragma unroll
            for (int m = 0; m < 3; m++) {
                gx[m] = grn_norm(__ull2float_rn(sum[m] >> 8) * from_fixed);
                tot += gx[m];
                vary = fmaxf(vary, fabsf(gam[m]) * gx[m] * rmax[m]);
            }
#pragma unroll
            for (int o = 16; o >= 1; o >>= 1) tot += __shfl_xor_sync(~0u, tot, o);
            const unsigned vwarp = __reduce_max_sync(~0u, __float_as_uint(vary));
            if (lane == 0) { sts32(s_red + 64 + w4 * 4, __float_as_uint(tot)); sts32(s_red + 80 + w4 * 4, vwarp); }
            named_bar(1, 128);
            uint32_t u[4], v[4], w[4];
            lds128(u[0], u[1], u[2], u[3], s_red + 64);
            lds128(v[0], v[1], v[2], v[3], s_red + 80);
            lds128(w[0], w[1], w[2], w[3], s_red + 96);
            tot = (__uint_as_float(u[0]) + __uint_as_float(u[1])) + (__uint_as_float(u[2]) + __uint_as_float(u[3]));
            const float vmax = __uint_as_float(max(max(v[0], v[1]), max(v[2], v[3]))), fmax2 = __uint_as_float(max(max(w[0], w[1]), max(w[2], w[3])));
            const float inv_mean = __fdividef(1.f, tot * (1.f / EX) + 1e-6f);
            const float bound = fmaf(gbound * vmax, inv_mean, 2.f * fmax2);
            const int rho_e = bound > 0.f ? 14 - ilog2f(bound) : 0;
            const float rho = pow2i(rho_e), inv_rho = pow2i(-rho_e);
            inv_rho2 = pack_bf2(inv_rho, inv_rho);
#pragma unroll
            for (int m = 0; m < 3; m++) {
                const float f = __fdividef(fmaf(gam[m], gx[m] * inv_mean, 1.f) * INV_2KZ * rho, row_scale(rmax[m]));
                asm volatile("st.shared.u16 [%0], %1;" ::"r"(s_fac + (i0 + 128 * m) * 2), "h"((unsigned short)pack_h2(f, 0.f)) : "memory");
            }
            if (i0 < 96) sts32(sb + SM_BIASH + i0 * 4, pack_h2(bpair.x * rho, bpair.y * rho));
            if (i0 == 96) sts32(s_red + RED_INV_RHO, inv_rho2);
            named_arrive(12, NTHREADS);
        };
        uint32_t gl[4][12] = {};
        const uint4* src = &sc->lent[(blockIdx.x * LENT * 8 * 4 + w4) * 96 + lane];
        auto fetch = [&](uint32_t (&v)[12], int c, bool on) {
#pragma unroll
            for (int s = 0; s < 3; s++) ldg128_if(on, reinterpret_cast<uint32_t (&)[4]>(v[4 * s]), src + c * 384 + s * 32);
        };
        if (__builtin_expect(wk.lent, 0)) {
            first = 4;
            tile_off = tile_offset(wk.tA);
            stage_x();
            if (elect_one()) prefetch_l2(reinterpret_cast<const char*>(x) + tile_offset(wk.tA + wk.dir) + w4 * WARP_BYTES, WARP_BYTES);
            spin_until(&sc->lent_out, (epoch + 1) * 32 * LENT * lenders);
#pragma unroll
            for (int c = 0; c < 3; c++) fetch(gl[c], c, true);
        }
        lds32(next_off, sb + SM_TILES + first * 4);
        if (!wk.lent) load_first();
        grn();
        if (__builtin_expect(wk.lent, 0)) {
            named_bar(3, NTHREADS);
#pragma unroll 1
            for (int e = 0; e < LENT; e++) {
                load_bias(acc);
#define CNX_LENT(C)                                  \
    pin(gl[C % 4]);                                  \
    wg_fence();                                      \
    gemm2_chunk<48 * C>(acc, gl[C % 4], ds);         \
    wg_commit();                                     \
    wg_wait<(C < 7 ? 1 : 0)>();                      \
    fetch(gl[(C + 3) % 4], C + 3, C < 5 || e == 0);  \
    if (lane == 0) mbar_arrive(sb + BAR_PIN);
                CNX_LENT(0) CNX_LENT(1) CNX_LENT(2) CNX_LENT(3) CNX_LENT(4) CNX_LENT(5) CNX_LENT(6) CNX_LENT(7)
#undef CNX_LENT
                src += 8 * 384;
                mbar_wait(bar_r, rpar);
                epilogue(acc);
                tile_off = tile_offset(wk.tA + wk.dir);
                if (e == 0) stage_x();
            }
            load_first();
        }
    } else {
        const int rank = (wgi + wk.lent + 2 * ntiles) % NCONS;
        {
            const int ct = tid - 128, lane = tid & 31;
            const unsigned epoch = *reinterpret_cast<volatile unsigned*>(&sc->launch);
            const int r = lane & 7, mi = lane >> 3;
            const uint32_t src = sb + SM_W2 + (cw >> 1) * (64 * CH * 2) + r * 128 + ((((cw & 1) * 4 + mi) ^ r) * 16);
            const uint32_t dst = sb + SM_W1 + (4 * cw + mi) * 1536 + r * 16;
            if (ct == 0) sts32(s_red + RED_MAX, 0);
            named_bar(0, NTHREADS);
            mbar_wait(sb + BAR_W + (cw >> 1) * 8, 0);
            uint32_t wmax[4] = {}, wsum[4] = {};
#pragma unroll 3
            for (int c = 0; c < 12; c++) {
                uint32_t u[4];
                ldsm4_t(u, src + c * 1024);
#pragma unroll
                for (int q = 0; q < 4; q++) {
                    wmax[q] = bf_absmax(wmax[q], u[q]);
                    wsum[q] = bf_fma(u[q], 0x3f803f80u, wsum[q]);
                    u[q] = pack_h2(bf_lo(u[q]), bf_hi(u[q]));
                }
                stsm4(dst + c * 128, u[0], u[1], u[2], u[3]);
            }
            float mean[4];
            bool center = false;
#pragma unroll
            for (int q = 0; q < 4; q++) {
                uint32_t m = wmax[q];
                float sum = bf_lo(wsum[q]) + bf_hi(wsum[q]);
#pragma unroll
                for (int o = 1; o <= 2; o <<= 1) { m = bf_absmax(m, __shfl_xor_sync(~0u, m, o)); sum += __shfl_xor_sync(~0u, sum, o); }
                mean[q] = sum * (1.f / CH);
                center |= fabsf(mean[q]) > 0.2f * fmaxf(fabsf(bf_lo(m)), fabsf(bf_hi(m)));
            }
            if (__builtin_expect(__any_sync(~0u, center), 0)) {
#pragma unroll 1
                for (int pass = 0; pass < 2; pass++) {
                    float sum[4] = {};
#pragma unroll 1
                    for (int c = 0; c < 12; c++) {
                        uint32_t u[4];
                        ldsm4_t(u, src + c * 1024);
#pragma unroll
                        for (int q = 0; q < 4; q++) {
                            sum[q] += bf_lo(u[q]) + bf_hi(u[q]);
                            u[q] = pack_h2(bf_lo(u[q]) - mean[q], bf_hi(u[q]) - mean[q]);
                        }
                        stsm4(dst + c * 128, u[0], u[1], u[2], u[3]);
                    }
#pragma unroll
                    for (int q = 0; q < 4; q++) {
                        sum[q] += __shfl_xor_sync(~0u, sum[q], 1);
                        sum[q] += __shfl_xor_sync(~0u, sum[q], 2);
                        mean[q] = sum[q] * (1.f / CH);
                    }
                }
            }
            if (cw < 2 * NCONS) {
#pragma unroll
                for (int c = 0; c < 12; c++) sts128(src + c * 1024, 0, 0, 0, 0);
            }
            const float w1max = warp_absmax(bf_absmax(bf_absmax(wmax[0], wmax[1]), bf_absmax(wmax[2], wmax[3])));
            if (lane == 0) asm volatile("red.shared.max.u32 [%0], %1;" ::"r"(s_red + RED_MAX), "r"(__float_as_uint(w1max)) : "memory");
            if (ct < 32) sts32(sb + SM_ONES + ct * 4, 0x3f803f80u);
            if (ct < 48) sts32(sb + SM_BIASH + ct * 4, 0);
            if (blockIdx.x == 0 && ct < CH) sc->bias[(epoch & 1) ^ 1][ct] = 0.f;
            if (ct == 0) sts32(s_red + RED_LAUNCH, epoch);
            fence_async();
            named_bar(2, CONS_THREADS);
            const float all_max = ldsf(s_red + RED_MAX);
            const int sq_e = square_exp(all_max);
            sts64(s_red + RED_SQ_EXP, sq_e, sum_exp(all_max));
            if (sq_e) {
#pragma unroll 1
                for (int q = 0; q < 6; q++) sts128(sb + SM_SQ + (rank + NCONS) * SQ_WG + q * SQ_ROW + (ct & 127) * 16, 0, 0, 0, 0);
            }
            mbar_wait(sb + BAR_A + w4 * 8 + 32, 0);
        }

        PROF(1);
        const uint32_t a_addr = opaque(sb + SM_RING + w4 * REGION_BYTES + ((tid >> 3) & 1) * A_SBO + ((tid >> 4) & 1) * A_LBO + (tid & 7) * 16);
        const uint32_t bar_a = sb + BAR_A + w4 * 8, bar_e = sb + BAR_E + w4 * 8;
        const uint32_t sq = opaque(sb + SM_SQ + rank * SQ_WG + (tid & 127) * 16);
        const uint32_t sq_warp = sb + SM_SQ + rank * SQ_WG + w4 * 512;
        uint32_t k1[24], k2[24], k3[24];
        constexpr int SQC = 3 * SQ_ROW;
        const int pass_to = 4 + (wgi == NCONS - 1 ? 0 : wgi + 1);
        auto store_frags = [&](const uint32_t (&a)[6][4], int j) {
            char* ap = reinterpret_cast<char*>(out) + (tile_offset(wk.tile(j)) + w4 * WARP_BYTES - sq_warp + sq);
#pragma unroll
            for (int s = 0; s < 6; s++) stg128(ap + s * 512, a[s]);
        };
        int jt = wgi < wk.lent ? wgi : wk.lent + wgi;
        Cursor cur = {2, 0};
        cur.advance(jt + (jt >= wk.nA ? 2 : 0));
        if (wgi == NCONS - 1) named_arrive(4, 256);
        for (;;) {
            const bool plain = __all_sync(~0u, ldsi(s_red + RED_SQ_EXP) == 0);
            if (plain && jt >= wk.lent) {
                uint32_t hs2[12] = {}, hs3[12] = {};
#pragma unroll 1
                for (; jt + NCONS < ntiles; jt += NCONS) {
                    uint32_t a[6][4], d0[24], d1[24], unused[24];
#define AT(pos) \
    if (K_WAIT == pos) named_bar(4 + wgi, 256); \
    if (K_PASS == pos) named_arrive(pass_to, 256); \
    if (K_STG == pos) store_frags(a, jt); \
    if (K_REL == pos) { if (elect_one()) mbar_arrive(bar_e + cur.slot * 32); }
                    AT(20)
                    mbar_wait(bar_a + cur.slot * 32, cur.par);
                    load_tile(a, a_addr + cur.slot * SLOT_BYTES);
                    AT(21)
                    const uint2 st = ln_stats(a, ds.ones);
                    AT(0)
                    ln_apply(a, st);
                    AT(1)
                    wg_fence();
                    gemm1_chunk<0>(d0, a, ds, 0);
                    wg_commit();
                    gemm1_chunk<96>(d1, a, ds, 0);
                    wg_commit();
                    AT(2)
                    wg_wait<1>();
                    AT(3)
                    gelu_sq<false, 0, 1>(d0, unused, sq, 0);
                    AT(4)
                    gelu_sq<false, 1, 2>(d0, unused, sq, 0);
                    AT(5)
                    gelu_sq<false, 2, 3>(d0, unused, sq, 0);
                    AT(6)
                    wg_fence();
                    gemm1_chunk<192>(d0, a, ds, zero);
                    wg_commit();
                    AT(7)
                    wg_wait<1>();
                    gelu_sq<false, 0, 1>(d1, unused, sq + SQC, 0);
                    AT(8)
                    gelu_sq<false, 1, 3>(d1, unused, sq + SQC, 0);
                    AT(9)
                    wg_fence();
                    gemm1_chunk<288>(d1, a, ds, zero);
                    wg_commit();
                    AT(10)
                    wg_wait<1>();
                    gelu_sq_reg(d0, hs2);
                    if (K_ANCH < 3) anchor(sq, hs2[4 * (K_ANCH % 3)], hs2[4 * (K_ANCH % 3) + 1], hs2[4 * (K_ANCH % 3) + 2], hs2[4 * (K_ANCH % 3) + 3]);
                    wg_wait<0>();
                    AT(11)
                    gelu_sq_reg(d1, hs3);
#undef AT
                    cur.advance(NCONS + ((jt < wk.nA && jt + NCONS >= wk.nA) ? 2 : 0));
                }
                const uint32_t sq2 = sq - (SM_SQ + rank * SQ_WG) + SM_RING + (cur.slot + 3) % NSLOT * SLOT_BYTES;
#pragma unroll
                for (int k = 0; k < 3; k++) {
                    sts128(sq2 + k * SQ_ROW, hs2[4 * k], hs2[4 * k + 1], hs2[4 * k + 2], hs2[4 * k + 3]);
                    sts128(sq2 + SQC + k * SQ_ROW, hs3[4 * k], hs3[4 * k + 1], hs3[4 * k + 2], hs3[4 * k + 3]);
                }
            }
            const bool last = jt + NCONS >= ntiles;
            if (last) {
                tile_off = tile_offset(wk.tile(jt));
                lds32(next_off, sb + SM_TILES + wg * 4);
                next_off = __shfl_sync(~0u, next_off, 0);
                if (elect_one()) {
                    prefetch_l2(reinterpret_cast<const char*>(x) + tile_off + w4 * WARP_BYTES, WARP_BYTES);
                    if ((wg - wk.lent / 2) % ORDER_P >= ORDER_P - ORDER_Q) prefetch_l2(reinterpret_cast<const char*>(out) + next_off + w4 * WARP_BYTES, WARP_BYTES);
                }
            }
            uint32_t a[6][4], d0[24], d1[24], d3[24], k0[24];
#define AT(pos) \
    if (K_WAIT == pos && jt >= wk.lent) named_bar(4 + wgi, 256); \
    if (K_PASS == pos && jt >= wk.lent && jt + 1 < ntiles) named_arrive(pass_to, 256);
            AT(20)
            mbar_wait(bar_a + cur.slot * 32, cur.par);
            load_tile(a, a_addr + cur.slot * SLOT_BYTES);
            AT(21)
            const uint2 st = ln_stats(a, ds.ones);
            AT(0)
            ln_apply(a, st);
            AT(1)
            if (!last) {
                store_frags(a, jt);
                __syncwarp();
                if (elect_one()) mbar_arrive(bar_e + cur.slot * 32);
                if (jt < wk.lent) {
                    jt += LENT;
                    cur.advance(LENT);
                    continue;
                }
            }
            wg_fence();
            gemm1_chunk<0>(d0, a, ds, 0);
            wg_commit();
            gemm1_chunk<96>(d1, a, ds, 0);
            wg_commit();
            const int sq_e = ldsi(s_red + RED_SQ_EXP);
            const uint32_t scale2 = pack_h2(pow2i(sq_e), pow2i(sq_e));
            stage = sb + SM_RING + cur.slot * SLOT_BYTES + w4 * REGION_BYTES;
            AT(2)
            wg_wait<1>();
            AT(3)
            gelu_sq<true, 0, 1>(d0, k0, sq, scale2);
            AT(4)
            gelu_sq<true, 1, 2>(d0, k0, sq, scale2);
            AT(5)
            gelu_sq<true, 2, 3>(d0, k0, sq, scale2);
            AT(6)
            if (last) {
#pragma unroll
                for (int q = 0; q < 6; q++) sts128(stage - sq_warp + sq + q * 512, k0[4 * q], k0[4 * q + 1], k0[4 * q + 2], k0[4 * q + 3]);
            }
            wg_fence();
            gemm1_chunk<192>(d0, a, ds, zero);
            wg_commit();
            AT(7)
            wg_wait<1>();
            gelu_sq<true, 0, 1>(d1, k1, sq + SQC, scale2);
            AT(8)
            gelu_sq<true, 1, 3>(d1, k1, sq + SQC, scale2);
            AT(9)
#undef AT
            wg_fence();
            gemm1_chunk<288>(d3, a, ds, 0);
            wg_commit();
            wg_wait<1>();
            const uint32_t sq2 = sq + (plain ? SM_RING + (cur.slot + 3) % NSLOT * SLOT_BYTES - (SM_SQ + rank * SQ_WG) : NCONS * SQ_WG);
            gelu_sq<true>(d0, k2, sq2, scale2);
            wg_wait<0>();
            gelu_sq<true>(d3, k3, sq2 + SQC, scale2);
            if (last) break;
            cur.advance(NCONS + ((jt < wk.nA && jt + NCONS >= wk.nA) ? 2 : 0));
            jt += NCONS;
        }
        {
            if (rank == NCONS - 1) {
                named_arrive(14, NTHREADS);
            } else {
                reduce(4 * rank + w4, (sq >> 4) & 31, false);
                named_arrive(15, CONS_THREADS);
            }
        }
        PROF(2);
        {
            set_lane((sq >> 4) & 31);
            const uint32_t row = sb + SM_W2 + cw * 512 + lane16;
            uint32_t u[W2_EARLY][4], f2[4];
            mbar_wait(sb + BAR_W, 1);
#pragma unroll
            for (int nb = 0; nb < W2_EARLY; nb++) lds128(u[nb][0], u[nb][1], u[nb][2], u[nb][3], row + nb * 6144);
            named_bar(12, NTHREADS);
            PROF(3);
            lds128(f2[0], f2[1], f2[2], f2[3], s_fac + cw * 64 + (lane16 >> 7) * 16);
            lds32(inv_rho2, s_red + RED_INV_RHO);
#pragma unroll
            for (int nb = 0; nb < 12; nb++) {
                uint32_t v[4];
                if (nb < W2_EARLY) { v[0] = u[nb % W2_EARLY][0]; v[1] = u[nb % W2_EARLY][1]; v[2] = u[nb % W2_EARLY][2]; v[3] = u[nb % W2_EARLY][3]; }
                else lds128(v[0], v[1], v[2], v[3], row + nb * 6144);
                sts128(row + nb * 6144, h_round8(h_mul(v[0], f2[0])), h_round8(h_mul(v[1], f2[1])), h_round8(h_mul(v[2], f2[2])), h_round8(h_mul(v[3], f2[3])));
            }
            fence_async();
            named_bar(3, NTHREADS);
        }
        PROF(4);
        {
            load_bias(acc);
            if (wgi > 0) named_bar(8 + wgi, 256);
            pin(k1); pin(k2); pin(k3);
            wg_fence();
            gemm2_chunk<288>(acc, k3, ds);
            wg_commit();
            gemm2_chunk<96>(acc, k1, ds);
            gemm2_chunk<192>(acc, k2, ds);
            wg_commit();
            if (wgi + 1 < NCONS) named_arrive(9 + wgi, 256);
            wg_wait<1>();
            uint32_t k0[24];
#pragma unroll
            for (int q = 0; q < 6; q++) lds128(k0[4 * q], k0[4 * q + 1], k0[4 * q + 2], k0[4 * q + 3], stage + lane16 + q * 512);
            pin(k0);
            wg_fence();
            gemm2_chunk<0>(acc, k0, ds);
            wg_commit();
            stage_x();
            wg_wait<1>();
            load_first();
            if (lane16 == 0) mbar_arrive(sb + BAR_PIN);
            mbar_wait(bar_r, rpar);
            wg_wait<0>();
            first = wg - 4;
        }
    }
    {
        const int nrest = ntiles - NCONS - wk.lent / 2;
        for (int jt = first; jt < nrest; jt += 4) {
            if (jt >= 0) {
            uint32_t d0[12], d1[12], g0[12], g1[12];
            tile_off = next_off;
            lds32(next_off, sb + SM_TILES + (jt + 4) * 4);
            if (jt >= S2_FIRST) named_bar(4 + wg, 256);
            wg_fence();
            gemm1_chunk<0>(d0, a, ds, 0);
            wg_commit();
            gemm1_chunk<48>(d1, a, ds, 0);
            wg_commit();
            load_bias(acc);
            const bool more = jt + 4 < nrest;
            tile_off = __shfl_sync(~0u, tile_off, 0);
            next_off = __shfl_sync(~0u, next_off, 0);
            wg_wait<1>();
#define CNX_PASS if (jt + 1 >= S2_FIRST && jt + 1 < nrest) named_arrive(4 + ((wg + 1) & 3), 256);
#define CNX_STEP(C, D, G)                                              \
    gelu_to(G, D);                                                     \
    if (C == 0 && jt == 0) {                                           \
        named_bar(3, NTHREADS);                                        \
        load_bias(acc);                                                \
    }                                                                  \
    wg_fence();                                                        \
    if (C < 6) gemm1_chunk<48 * (C < 6 ? C + 2 : 0)>(D, a, ds, zero); \
    gemm2_chunk<48 * C>(acc, G, ds);                                  \
    wg_commit();                                                       \
    if (C == S2_PASS) { CNX_PASS }                                     \
    wg_wait<(C < 7 ? 1 : 0)>();
            CNX_STEP(0, d0, g0)
            stage_x();
            if (more && elect_one()) prefetch_l2(reinterpret_cast<const char*>(out) + next_off + w4 * WARP_BYTES, WARP_BYTES);
            CNX_STEP(1, d1, g1)
            CNX_STEP(2, d0, g0)
            CNX_STEP(3, d1, g1)
            CNX_STEP(4, d0, g0)
            CNX_STEP(5, d1, g1)
            CNX_STEP(6, d0, g0)
            load_frags(more);
            if (lane16 == 0) mbar_arrive(sb + BAR_PIN);
            mbar_wait(bar_r, rpar);
            CNX_STEP(7, d1, g1)
#undef CNX_STEP
            }
            epilogue(acc);
        }
    }
    PROF(5);
}

}

typedef CUresult (*EncodeTiledFn)(CUtensorMap*, CUtensorMapDataType, cuuint32_t, void*, const cuuint64_t*, const cuuint64_t*,
                                  const cuuint32_t*, const cuuint32_t*, CUtensorMapInterleave, CUtensorMapSwizzle,
                                  CUtensorMapL2promotion, CUtensorMapFloatOOBfill);

extern "C" void kernel_launch(void* const* d_in, const int* in_sizes, int n_in, void* d_out, int out_size) {
    using namespace cnx;
    static EncodeTiledFn encode = nullptr;
    static int num_sms = 0;
    static Scratch* scratch = nullptr;
    if (!encode) {
        void* fn = nullptr;
        cudaDriverEntryPointQueryResult qr;
        cudaGetDriverEntryPoint("cuTensorMapEncodeTiled", &fn, cudaEnableDefault, &qr);
        encode = (EncodeTiledFn)fn;
        cudaGetSymbolAddress((void**)&scratch, g_scratch);
        int dev = 0;
        cudaGetDevice(&dev);
        cudaDeviceGetAttribute(&num_sms, cudaDevAttrMultiProcessorCount, dev);
        if (num_sms > MAX_CTAS) num_sms = MAX_CTAS;
        cudaFuncSetAttribute(block_kernel, cudaFuncAttributeMaxDynamicSharedMemorySize, SM_TOTAL);
    }
    CUtensorMap tm;
    cuuint64_t dims[3] = {(cuuint64_t)CH, (cuuint64_t)IMG_W, (cuuint64_t)IMG_H};
    cuuint64_t strides[2] = {(cuuint64_t)CH * 2, (cuuint64_t)CH * 2 * IMG_W};
    cuuint32_t box[3] = {(cuuint32_t)CH, (cuuint32_t)REGION_PX, 1};
    cuuint32_t estr[3] = {1, 1, 1};
    encode(&tm, CU_TENSOR_MAP_DATA_TYPE_BFLOAT16, 3, d_in[0], dims, strides, box, estr, CU_TENSOR_MAP_INTERLEAVE_NONE,
           CU_TENSOR_MAP_SWIZZLE_NONE, CU_TENSOR_MAP_L2_PROMOTION_L2_128B, CU_TENSOR_MAP_FLOAT_OOB_FILL_NONE);
    Descs ds;
    for (int c = 0; c < 8; c++)
        for (int k = 0; k < 6; k++) ds.w1[c][k] = make_desc(SB + SM_W1 + c * 6 * 1536 + k * 256, 128, 1536);
    for (int k = 0; k < 24; k++) ds.w2[k] = make_desc(SB + SM_W2 + k * 256, 128, 6144);
    ds.ones = make_desc(SB + SM_ONES, 0, 0);
    CUtensorMap tw;
    cuuint64_t wdims[2] = {(cuuint64_t)EX, (cuuint64_t)CH};
    cuuint64_t wstrides[1] = {(cuuint64_t)EX * 2};
    cuuint32_t wbox[2] = {64, (cuuint32_t)CH};
    encode(&tw, CU_TENSOR_MAP_DATA_TYPE_BFLOAT16, 2, d_in[2], wdims, wstrides, wbox, estr, CU_TENSOR_MAP_INTERLEAVE_NONE,
           CU_TENSOR_MAP_SWIZZLE_128B, CU_TENSOR_MAP_L2_PROMOTION_L2_128B, CU_TENSOR_MAP_FLOAT_OOB_FILL_NONE);
    const int per_cta = NTILES / num_sms, extra = NTILES % num_sms;
    if (per_cta + 9 > MAX_ROWS) return;
    const int lenders = extra * (8 * LENT + 1) <= num_sms && extra * (per_cta + 1) <= IMG_H ? extra : 0;
    block_kernel<<<num_sms, NTHREADS, SM_TOTAL>>>(tm, tw, (const __nv_bfloat16*)d_in[0], (const __nv_bfloat16*)d_in[1],
                                             (const __nv_bfloat16*)d_in[3],
                                             (const __nv_bfloat16*)d_in[4], (const __nv_bfloat16*)d_in[5], (__nv_bfloat16*)d_out,
                                             scratch, ds, 0, per_cta, extra, lenders);
}
```

```cpp
#include <cuda_runtime.h>
#include <cuda_bf16.h>
#include <cuda_fp16.h>
#include <cuda.h>
#include <stdint.h>

namespace cnx {

constexpr int IMG_H = 512, IMG_W = 512, CH = 96, EX = 384;
constexpr int TILE_W = 64;
constexpr int NTILES = (IMG_W / TILE_W) * IMG_H;
constexpr int NSLOT = 6;
constexpr int REGION_PX = 18;
constexpr int REGION_BYTES = REGION_PX * CH * 2;
constexpr int SLOT_BYTES = 4 * REGION_BYTES;
constexpr int A_LBO = 144, A_SBO = 12 * A_LBO;
constexpr int PREFETCH_ROWS = 3;
constexpr int NCONS = 3;
constexpr int CONS_THREADS = 128 * NCONS;
constexpr int NTHREADS = 128 + CONS_THREADS;
constexpr int MAX_ROWS = 52;
constexpr int TILE_BYTES = TILE_W * CH * 2, WARP_BYTES = TILE_BYTES / 4;
constexpr int S1_PASS = 1, S2_PASS = 1;
#define K_PASS 4
#define K_WAIT 20
#define K_STG 6
#define K_REL 6
#define K_ANCH 2
#define K_CVT 0
#define K_LATE 1
#define K_FINE 1
#define K_SWAP 0
#define K_TAIL 0
#define W2_EARLY 6
#define S2_FIRST 2
#define ORDER_P 3
#define ORDER_Q 1
static_assert(MAX_ROWS <= 128, "one table entry per producer thread");
static_assert(2 * A_SBO == REGION_BYTES && REGION_BYTES % 128 == 0, "region layout");

constexpr uint32_t SB = 1024;
constexpr int SM_W1 = 0;
constexpr int SM_W2 = SM_W1 + CH * EX * 2;
constexpr int SM_RING = SM_W2 + CH * EX * 2;
constexpr int SM_BIASH = SM_RING + NSLOT * SLOT_BYTES;
constexpr int SM_RED = SM_BIASH + 384;
constexpr int RED_MAX = 0, RED_LAUNCH = 4, RED_SQ_EXP = 8, RED_SUM_EXP = 12, RED_INV_RHO = 16;
constexpr int SM_ROWS = SM_RED + 256;
constexpr int SM_TILES = SM_ROWS + MAX_ROWS * 4;
constexpr int SM_ONES = SM_TILES + MAX_ROWS * 4;
constexpr int SM_BAR = SM_ONES + 128;
constexpr int BAR_X = SM_BAR;
constexpr int BAR_A = BAR_X + NSLOT * 4 * 8;
constexpr int BAR_E = BAR_A + NSLOT * 4 * 8;
constexpr int BAR_PIN = BAR_E + NSLOT * 4 * 8;
constexpr int BAR_W = BAR_PIN + 8;
constexpr int BAR_F = BAR_W + 6 * 8;
constexpr int BAR_R = BAR_F + 8;
constexpr int SM_TOTAL = BAR_R + 16 * 8;
constexpr int SM_FILTER = SM_RING + (NSLOT - 1) * SLOT_BYTES + 9 * 128;
constexpr int SM_SQ = SM_W2;
constexpr int SQ_ROW = 128 * 16, SQ_WG = 6 * SQ_ROW;
static_assert(SM_ONES % 16 == 0 && SM_TOTAL <= 232448, "shared memory budget");

constexpr float KZ = 0.3292034911525734f;
constexpr uint32_t GELU_C2 = 0x40d940d9u;
constexpr float INV_2KZ = 0.5f / KZ;
constexpr unsigned SPIN_LIMIT = 1u << 19;

constexpr int MAX_CTAS = 255;
constexpr int W2_GROUPS = EX / 8;
#define K_LENT 3
constexpr int LENT = K_LENT, MAX_LENDERS = MAX_CTAS / (8 * LENT + 1);
struct Scratch {
    uint32_t w2h[EX * CH / 2];
    float w2max[EX];
    float bias[2][CH];
    unsigned long long sums[EX / 4][32];
    __device__ __forceinline__ unsigned long long* sum(int e) { return &sums[e >> 2][e & 3]; }
    uint4 lent[MAX_LENDERS * LENT * 8 * 4 * 3 * 32];
    unsigned launch, pad0[31], prep, pad1[31], lent_in, pad2[31], lent_out, pad3[31];
};
__device__ __align__(128) Scratch g_scratch;

#define PROF(k)

__device__ __forceinline__ uint32_t smem_u32(const void* p) { return (uint32_t)__cvta_generic_to_shared(p); }
__device__ __forceinline__ void mbar_init(uint32_t bar, uint32_t cnt) {
    asm volatile("mbarrier.init.shared::cta.b64 [%0], %1;" ::"r"(bar), "r"(cnt) : "memory");
}
__device__ __forceinline__ void mbar_arrive(uint32_t bar) {
    asm volatile("mbarrier.arrive.shared::cta.b64 _, [%0];" ::"r"(bar) : "memory");
}
__device__ __forceinline__ void mbar_expect_tx(uint32_t bar, uint32_t bytes) {
    asm volatile("mbarrier.arrive.expect_tx.shared::cta.b64 _, [%0], %1;" ::"r"(bar), "r"(bytes) : "memory");
}
__device__ __forceinline__ bool mbar_try(uint32_t bar, uint32_t par) {
    uint32_t ok;
    asm volatile("{\n.reg .pred p;\nmbarrier.try_wait.parity.shared::cta.b64 p, [%1], %2;\nselp.u32 %0, 1, 0, p;\n}\n"
                 : "=r"(ok) : "r"(bar), "r"(par) : "memory");
    return ok != 0;
}
__device__ __forceinline__ void mbar_wait(uint32_t bar, uint32_t par) {
    unsigned n = 0;
    while (!mbar_try(bar, par)) {
        if (++n > SPIN_LIMIT) __trap();
    }
}
__device__ __forceinline__ bool mbar_test(uint32_t bar, uint32_t par) {
    uint32_t ok;
    asm volatile("{\n.reg .pred p;\nmbarrier.test_wait.parity.shared::cta.b64 p, [%1], %2;\nselp.u32 %0, 1, 0, p;\n}\n"
                 : "=r"(ok) : "r"(bar), "r"(par) : "memory");
    return ok != 0;
}
__device__ __forceinline__ bool elect_one() {
    uint32_t ok;
    asm volatile("{\n.reg .pred p;\nelect.sync _|p, 0xffffffff;\nselp.u32 %0, 1, 0, p;\n}\n" : "=r"(ok));
    return ok != 0;
}
__device__ __forceinline__ uint32_t opaque(uint32_t v) { return __shfl_sync(~0u, v, threadIdx.x & 31); }
__device__ __forceinline__ void named_bar(int id, int n) { asm volatile("bar.sync %0, %1;" ::"r"(id), "r"(n) : "memory"); }
__device__ __forceinline__ void named_arrive(int id, int n) { asm volatile("bar.arrive %0, %1;" ::"r"(id), "r"(n) : "memory"); }
__device__ __forceinline__ void fence_async() { asm volatile("fence.proxy.async.shared::cta;" ::: "memory"); }
__device__ __forceinline__ uint64_t evict_first() {
    uint64_t p;
    asm("createpolicy.fractional.L2::evict_first.b64 %0, 1.0;" : "=l"(p));
    return p;
}
__device__ __forceinline__ void tma_row(uint32_t dst, const CUtensorMap* tm, uint32_t bar, int x, int y) {
    asm volatile("cp.async.bulk.tensor.3d.shared::cluster.global.mbarrier::complete_tx::bytes.L2::cache_hint [%0], [%1, {%3, %4, %5}], [%2], %6;"
                 ::"r"(dst), "l"(tm), "r"(bar), "r"(0), "r"(x), "r"(y), "l"(evict_first()) : "memory");
}
__device__ __forceinline__ void bulk_load_stream(uint32_t dst, const void* src, uint32_t bytes, uint32_t bar) {
    asm volatile("cp.async.bulk.shared::cluster.global.mbarrier::complete_tx::bytes.L2::cache_hint [%0], [%1], %2, [%3], %4;"
                 ::"r"(dst), "l"(src), "r"(bytes), "r"(bar), "l"(evict_first()) : "memory");
}
__device__ __forceinline__ void prefetch_l2(const void* src, uint32_t bytes) {
    asm volatile("cp.async.bulk.prefetch.L2.global [%0], %1;" ::"l"(src), "r"(bytes) : "memory");
}
__device__ __forceinline__ void tma_2d(uint32_t dst, const CUtensorMap* tm, uint32_t bar, int x, int y) {
    asm volatile("cp.async.bulk.tensor.2d.shared::cluster.global.mbarrier::complete_tx::bytes [%0], [%1, {%3, %4}], [%2];"
                 ::"r"(dst), "l"(tm), "r"(bar), "r"(x), "r"(y) : "memory");
}
__device__ __forceinline__ void bulk_load(uint32_t dst, const void* src, uint32_t bytes, uint32_t bar) {
    asm volatile("cp.async.bulk.shared::cluster.global.mbarrier::complete_tx::bytes [%0], [%1], %2, [%3];"
                 ::"r"(dst), "l"(src), "r"(bytes), "r"(bar) : "memory");
}
__device__ __forceinline__ void wg_fence() { asm volatile("wgmma.fence.sync.aligned;" ::: "memory"); }
__device__ __forceinline__ void wg_commit() { asm volatile("wgmma.commit_group.sync.aligned;" ::: "memory"); }
template <int N> __device__ __forceinline__ void wg_wait() { asm volatile("wgmma.wait_group.sync.aligned %0;" ::"n"(N) : "memory"); }
template <int N> __device__ __forceinline__ void pin(uint32_t (&d)[N]) {
#pragma unroll
    for (int q = 0; q < N; q++) asm volatile("" : "+r"(d[q])::"memory");
}
__device__ __forceinline__ void stg128(void* p, const uint32_t (&v)[4]) {
    asm volatile("st.global.v4.u32 [%0], {%1, %2, %3, %4};" ::"l"(p), "r"(v[0]), "r"(v[1]), "r"(v[2]), "r"(v[3]) : "memory");
}
__device__ __forceinline__ void ldg128(uint32_t (&v)[4], const void* p) {
    asm volatile("ld.global.L1::no_allocate.v4.u32 {%0, %1, %2, %3}, [%4];" : "=r"(v[0]), "=r"(v[1]), "=r"(v[2]), "=r"(v[3]) : "l"(p) : "memory");
}
__device__ __forceinline__ void ldg128_if(bool on, uint32_t (&v)[4], const void* p) {
    asm volatile("{\n.reg .pred p;\nsetp.ne.b32 p, %5, 0;\n@p ld.global.L1::no_allocate.v4.u32 {%0, %1, %2, %3}, [%4];\n}\n"
                 : "+r"(v[0]), "+r"(v[1]), "+r"(v[2]), "+r"(v[3]) : "l"(p), "r"((int)on) : "memory");
}
__device__ __forceinline__ uint4 ldg128_ordered(const void* p) {
    uint4 v;
    asm volatile("ld.global.nc.v4.u32 {%0, %1, %2, %3}, [%4];" : "=r"(v.x), "=r"(v.y), "=r"(v.z), "=r"(v.w) : "l"(p) : "memory");
    return v;
}
__host__ __device__ constexpr uint64_t make_desc(uint32_t addr, uint32_t lbo, uint32_t sbo) {
    return (uint64_t)((addr & 0x3FFFF) >> 4) | ((uint64_t)(lbo >> 4) << 16) | ((uint64_t)(sbo >> 4) << 32);
}
__device__ __forceinline__ void wgmma(uint32_t (&d)[12], uint32_t a0, uint32_t a1, uint32_t a2, uint32_t a3, uint64_t db, int acc) {
    asm volatile("{\n.reg .pred p;\nsetp.ne.b32 p, %17, 0;\n"
                 "wgmma.mma_async.sync.aligned.m64n48k16.f16.f16.f16 "
                 "{%0, %1, %2, %3, %4, %5, %6, %7, %8, %9, %10, %11}, "
                 "{%12, %13, %14, %15}, %16, p, 1, 1, 0;\n}\n"
                 : "+r"(d[0]), "+r"(d[1]), "+r"(d[2]), "+r"(d[3]), "+r"(d[4]), "+r"(d[5]), "+r"(d[6]), "+r"(d[7]), "+r"(d[8]), "+r"(d[9]), "+r"(d[10]), "+r"(d[11])
                 : "r"(a0), "r"(a1), "r"(a2), "r"(a3), "l"(db), "r"(acc));
}
__device__ __forceinline__ void wgmma(uint32_t (&d)[24], uint32_t a0, uint32_t a1, uint32_t a2, uint32_t a3, uint64_t db, int acc) {
    asm volatile("{\n.reg .pred p;\nsetp.ne.b32 p, %29, 0;\n"
                 "wgmma.mma_async.sync.aligned.m64n96k16.f16.f16.f16 "
                 "{%0, %1, %2, %3, %4, %5, %6, %7, %8, %9, %10, %11, %12, %13, %14, %15, %16, %17, %18, %19, %20, %21, %22, %23}, "
                 "{%24, %25, %26, %27}, %28, p, 1, 1, 0;\n}\n"
                 : "+r"(d[0]), "+r"(d[1]), "+r"(d[2]), "+r"(d[3]), "+r"(d[4]), "+r"(d[5]), "+r"(d[6]), "+r"(d[7]), "+r"(d[8]), "+r"(d[9]), "+r"(d[10]), "+r"(d[11]), "+r"(d[12]), "+r"(d[13]), "+r"(d[14]), "+r"(d[15]), "+r"(d[16]), "+r"(d[17]), "+r"(d[18]), "+r"(d[19]), "+r"(d[20]), "+r"(d[21]), "+r"(d[22]), "+r"(d[23])
                 : "r"(a0), "r"(a1), "r"(a2), "r"(a3), "l"(db), "r"(acc));
}
template <int ACC>
__device__ __forceinline__ void wgmma_rowsum(float (&d)[4], const uint32_t (&a)[4], uint64_t ones) {
    asm volatile("{\n.reg .pred p;\nsetp.ne.b32 p, %9, 0;\n"
                 "wgmma.mma_async.sync.aligned.m64n8k16.f32.bf16.bf16 {%0, %1, %2, %3}, {%4, %5, %6, %7}, %8, p, 1, 1, 0;\n}\n"
                 : "+f"(d[0]), "+f"(d[1]), "+f"(d[2]), "+f"(d[3])
                 : "r"(a[0]), "r"(a[1]), "r"(a[2]), "r"(a[3]), "l"(ones), "n"(ACC));
}
__device__ __forceinline__ void ldsm4(uint32_t (&r)[4], uint32_t addr) {
    asm volatile("ldmatrix.sync.aligned.m8n8.x4.shared.b16 {%0, %1, %2, %3}, [%4];"
                 : "=r"(r[0]), "=r"(r[1]), "=r"(r[2]), "=r"(r[3]) : "r"(addr) : "memory");
}
__device__ __forceinline__ void ldsm4_t(uint32_t (&r)[4], uint32_t addr) {
    asm volatile("ldmatrix.sync.aligned.m8n8.x4.trans.shared.b16 {%0, %1, %2, %3}, [%4];"
                 : "=r"(r[0]), "=r"(r[1]), "=r"(r[2]), "=r"(r[3]) : "r"(addr) : "memory");
}
__device__ __forceinline__ void stsm4(uint32_t addr, uint32_t a, uint32_t b, uint32_t c, uint32_t d) {
    asm volatile("stmatrix.sync.aligned.m8n8.x4.shared.b16 [%0], {%1, %2, %3, %4};"
                 ::"r"(addr), "r"(a), "r"(b), "r"(c), "r"(d) : "memory");
}
__device__ __forceinline__ uint32_t transpose8x8(uint32_t v) {
    uint32_t d; asm volatile("movmatrix.sync.aligned.m8n8.trans.b16 %0, %1;" : "=r"(d) : "r"(v)); return d;
}
__device__ __forceinline__ void spin_until(const unsigned* counter, unsigned target) {
    unsigned n = 0, c;
    do {
        asm volatile("ld.acquire.gpu.global.u32 %0, [%1];" : "=r"(c) : "l"(counter) : "memory");
        if (++n > SPIN_LIMIT) __trap();
    } while ((int)(c - target) < 0);
}
__device__ __forceinline__ void signal(unsigned* counter) {
    __syncwarp();
    if (elect_one()) asm volatile("red.release.gpu.global.add.u32 [%0], 1;" ::"l"(counter) : "memory");
    __syncwarp();
}
__device__ __forceinline__ void lds128(uint32_t& a, uint32_t& b, uint32_t& c, uint32_t& d, uint32_t addr) {
    asm volatile("ld.shared.v4.u32 {%0, %1, %2, %3}, [%4];" : "=r"(a), "=r"(b), "=r"(c), "=r"(d) : "r"(addr) : "memory");
}
__device__ __forceinline__ void lds64(uint32_t& a, uint32_t& b, uint32_t addr) {
    asm volatile("ld.shared.v2.u32 {%0, %1}, [%2];" : "=r"(a), "=r"(b) : "r"(addr) : "memory");
}
__device__ __forceinline__ void lds32(uint32_t& a, uint32_t addr) {
    asm volatile("ld.shared.u32 %0, [%1];" : "=r"(a) : "r"(addr) : "memory");
}
__device__ __forceinline__ int ldsi(uint32_t addr) {
    uint32_t v;
    lds32(v, addr);
    return (int)v;
}
__device__ __forceinline__ float ldsf(uint32_t addr) {
    uint32_t v;
    lds32(v, addr);
    return __uint_as_float(v);
}
__device__ __forceinline__ void sts32(uint32_t addr, uint32_t a) {
    asm volatile("st.shared.u32 [%0], %1;" ::"r"(addr), "r"(a) : "memory");
}
__device__ __forceinline__ void sts128(uint32_t addr, uint32_t a, uint32_t b, uint32_t c, uint32_t d) {
    asm volatile("st.shared.v4.u32 [%0], {%1, %2, %3, %4};" ::"r"(addr), "r"(a), "r"(b), "r"(c), "r"(d) : "memory");
}
__device__ __forceinline__ void sts64(uint32_t addr, uint32_t a, uint32_t b) {
    asm volatile("st.shared.v2.u32 [%0], {%1, %2};" ::"r"(addr), "r"(a), "r"(b) : "memory");
}
__device__ __forceinline__ void anchor(uint32_t addr, uint32_t a, uint32_t b, uint32_t c, uint32_t d) {
    asm volatile("{\n.reg .pred p;\nsetp.eq.b32 p, %0, 0;\n@p st.shared.v4.u32 [%0], {%1, %2, %3, %4};\n}\n"
                 ::"r"(addr), "r"(a), "r"(b), "r"(c), "r"(d) : "memory");
}
__device__ __forceinline__ uint32_t bf_fma(uint32_t a, uint32_t b, uint32_t c) {
    uint32_t d; asm("fma.rn.bf16x2 %0, %1, %2, %3;" : "=r"(d) : "r"(a), "r"(b), "r"(c)); return d;
}
__device__ __forceinline__ uint32_t bf_mul(uint32_t a, uint32_t b) {
    uint32_t d; asm("mul.rn.bf16x2 %0, %1, %2;" : "=r"(d) : "r"(a), "r"(b)); return d;
}
__device__ __forceinline__ uint32_t bf_absmax(uint32_t a, uint32_t b) {
    uint32_t d; asm("max.xorsign.abs.bf16x2 %0, %1, %2;" : "=r"(d) : "r"(a), "r"(b)); return d;
}
__device__ __forceinline__ uint32_t h_fma(uint32_t a, uint32_t b, uint32_t c) {
    uint32_t d; asm("fma.rn.f16x2 %0, %1, %2, %3;" : "=r"(d) : "r"(a), "r"(b), "r"(c)); return d;
}
__device__ __forceinline__ uint32_t h_mul(uint32_t a, uint32_t b) {
    uint32_t d; asm("mul.rn.f16x2 %0, %1, %2;" : "=r"(d) : "r"(a), "r"(b)); return d;
}
__device__ __forceinline__ uint32_t h_round8(uint32_t v) { return (v + 0x00040004u) & 0xfff8fff8u; }
__device__ __forceinline__ uint32_t h_tanh(uint32_t a) {
    uint32_t d; asm("tanh.approx.f16x2 %0, %1;" : "=r"(d) : "r"(a)); return d;
}
__device__ __forceinline__ uint32_t pack_h2(float lo, float hi) {
    uint32_t d; asm("cvt.rn.f16x2.f32 %0, %1, %2;" : "=r"(d) : "f"(hi), "f"(lo)); return d;
}
__device__ __forceinline__ uint32_t pack_bf2(float lo, float hi) {
    uint32_t d; asm("cvt.rn.bf16x2.f32 %0, %1, %2;" : "=r"(d) : "f"(hi), "f"(lo)); return d;
}
__device__ __forceinline__ float bf_lo(uint32_t v) { return __uint_as_float(v << 16); }
__device__ __forceinline__ float bf_hi(uint32_t v) { return __uint_as_float(v & 0xffff0000u); }
__device__ __forceinline__ float h_lo(uint32_t v) { return __low2float(*reinterpret_cast<__half2*>(&v)); }
__device__ __forceinline__ float h_hi(uint32_t v) { return __high2float(*reinterpret_cast<__half2*>(&v)); }
__device__ __forceinline__ float warp_absmax(uint32_t v) {
    return __uint_as_float(__reduce_max_sync(~0u, max((v & 0x7fffu) << 16, v & 0x7fff0000u)));
}
__device__ __forceinline__ uint32_t gelu2(uint32_t z) {
    uint32_t p = h_fma(z, z, GELU_C2);
    uint32_t t = h_tanh(h_mul(z, p));
    return h_fma(z, t, z);
}
__device__ __forceinline__ float grn_norm(float ss) {
    float r;
    asm("sqrt.approx.f32 %0, %1;" : "=f"(r) : "f"(fmaf(ss, INV_2KZ * INV_2KZ, 1e-6f)));
    return r;
}
__device__ __forceinline__ float pow2i(int e) { return __uint_as_float((uint32_t)(e + 127) << 23); }
__device__ __forceinline__ int ilog2f(float v) {
    int e = (int)((__float_as_uint(v) >> 23) & 0xff) - 127;
    return max(-100, min(100, e));
}

__device__ __forceinline__ int square_exp(float w1max) {
    const int e = w1max > 0.f ? 4 - ilog2f(2.f * KZ * 96.f * w1max) : 0;
    return (e >= 0 && e <= 6) ? 0 : max(-14, min(e, 14));
}
__device__ __forceinline__ int sum_exp(float w1max) {
    return w1max > 0.f ? max(-90, min(90, 33 - 2 * ilog2f(2.f * KZ * 96.f * w1max))) : 0;
}
__device__ __forceinline__ float row_scale(float m) { return m > 0.f ? pow2i(2 - ilog2f(m)) : 1.f; }

struct Split {
    int per_cta, extra, period, inv_period, lenders;
    __host__ __device__ __forceinline__ int longer_before(int cta) const {
        const int n = (cta + period / 2) * inv_period >> 16;
        return n < extra ? n : extra;
    }
};
struct Work {
    int tA, tB, nA, nB, dir, rows, lent, index;
    __device__ __forceinline__ int tile(int j) const { return j < nA ? tA + dir * j : tB + dir * (j - nA); }
};
__host__ __device__ __forceinline__ Work get_work(int cta, const Split& sp) {
    Work w;
    const int before = sp.longer_before(cta), longer = sp.longer_before(cta + 1) - before;
    w.lent = longer && sp.lenders ? LENT : 0;
    w.index = longer ? before : cta - before;
    const int t0 = cta * sp.per_cta + before, t1 = t0 + sp.per_cta + longer;
    const int tm = t1 < (t0 | 511) + 1 ? t1 : (t0 | 511) + 1;
    const bool swap = t1 > tm && t1 - tm < tm - t0, down = cta & 1;
    w.nA = swap ? t1 - tm : tm - t0;
    w.nB = t1 - t0 - w.nA;
    w.tA = down ? (swap ? tm : t0) : (swap ? t1 : tm) - 1;
    w.tB = down ? (swap ? t0 : tm) : (swap ? tm : t1) - 1;
    w.dir = down ? 1 : -1;
    w.rows = w.nA + 2 + (w.nB ? w.nB + 2 : 0);
    return w;
}
__device__ __forceinline__ int row_code(const Work& w, int i) {
    const bool in_a = i < w.nA + 2;
    const int t = in_a ? w.tA : w.tB;
    return ((t & 511) + w.dir * ((in_a ? i : i - (w.nA + 2)) - 1)) << 16 | (t >> 9) * TILE_W;
}
__device__ __forceinline__ uint32_t tile_offset(int tile) { return ((tile & 511) * IMG_W + (tile >> 9) * TILE_W) * (CH * 2); }
__device__ __forceinline__ int tile_order(int j, int n) {
    const int olds = (j / ORDER_P) * ORDER_Q + max(0, j % ORDER_P - (ORDER_P - ORDER_Q));
    return (j % ORDER_P >= ORDER_P - ORDER_Q) ? olds : n - 1 - (j - olds);
}
__device__ __forceinline__ void issue_region(const CUtensorMap* tm, uint32_t dst, uint32_t bar, int warp, int code) {
    mbar_expect_tx(bar, REGION_BYTES);
    tma_row(dst, tm, bar, (code & 0xffff) + (16 * warp - 1), code >> 16);
}

__device__ __forceinline__ void conv_producer(const Work& wk, const CUtensorMap* tm, Scratch* sc, uint32_t sb, int warp) {
    const int lane = threadIdx.x & 31;
    const int j = lane & 15, grp = lane >> 4;
    const uint32_t reg0 = sb + SM_RING + warp * REGION_BYTES;
    const uint32_t bars = sb + SM_BAR + warp * 8;
    if (lane >= PREFETCH_ROWS && lane < 3 * NSLOT) mbar_init(bars + lane * 32, 1);
    if (lane >= 28) mbar_init(sb + BAR_R + ((lane - 28) * 4 + warp) * 8, 1);
    if (lane == 0 && warp == 0) mbar_init(sb + BAR_PIN, 1);
    if (warp * 32 + lane < MAX_ROWS) {
        sts32(sb + SM_ROWS + (warp * 32 + lane) * 4, row_code(wk, warp * 32 + lane));
        const int i = warp * 32 + lane, before = min(i / 5, wk.lent);
        const bool back = i % 5 == 0 && i > 0 && i / 5 <= wk.lent;
        sts32(sb + SM_TILES + i * 4, back ? tile_offset(wk.tile(before - 1)) | before
                                          : tile_offset(wk.tile(wk.lent + tile_order(i - before, wk.nA + wk.nB - NCONS - wk.lent))));
    }
    const uint32_t ld64 = opaque(reg0 + grp * 8 * 192 + j * 8), ld32 = opaque(reg0 + grp * 8 * 192 + 128 + j * 4);
    const uint32_t st64 = opaque(reg0 + grp * A_SBO + (j >> 1) * A_LBO + (j & 1) * 8);
    const uint32_t st32 = opaque(reg0 + grp * A_SBO + (8 + (j >> 2)) * A_LBO + (j & 3) * 4);
    fence_async();
    named_bar(0, NTHREADS);
    uint32_t w[3][3][3];
    mbar_wait(sb + BAR_F, 0);
#pragma unroll
    for (int tap = 0; tap < 9; tap++) {
        const uint32_t p = sb + SM_FILTER + (3 + wk.dir * 3 * (tap / 3 - 1) + tap % 3) * (CH * 2);
        lds64(w[tap / 3][tap % 3][0], w[tap / 3][tap % 3][1], p + 8 * j);
        lds32(w[tap / 3][tap % 3][2], p + 128 + 4 * j);
    }
#pragma unroll
    for (int tap = 0; tap < 9; tap++) sts64(reg0 + (NSLOT - 1) * SLOT_BYTES + tap * 128 + j * 8, w[tap / 3][tap % 3][1], w[tap / 3][tap % 3][0]);
#pragma unroll
    for (int tap = 0; tap < 9; tap++) lds64(w[tap / 3][tap % 3][1], w[tap / 3][tap % 3][0], reg0 + (NSLOT - 1) * SLOT_BYTES + tap * 128 + j * 8);
    fence_async();
    named_bar(1, 128);
    static_assert(2 * PREFETCH_ROWS == NSLOT, "prefetch slot arithmetic");
    uint32_t so = 0, bo = 0, par = 0, tbl = sb + SM_ROWS + PREFETCH_ROWS * 4;
    const uint32_t tbl_end = sb + SM_ROWS + wk.rows * 4, publish = wk.lent ? tbl + 12 * 4 : 0;
    auto next_row = [&](int code, bool e_ready) {
        const bool wrap = bo == (NSLOT - 1) * 32, low = bo < PREFETCH_ROWS * 32;
        if (tbl < tbl_end) {
            const uint32_t pbo = low ? bo + PREFETCH_ROWS * 32 : bo - PREFETCH_ROWS * 32;
            if (!e_ready) mbar_wait(bars + (BAR_E - SM_BAR) + pbo, par ^ low);
            code = __shfl_sync(~0u, code, 0);
            if (elect_one()) issue_region(tm, reg0 + (low ? so + PREFETCH_ROWS * SLOT_BYTES : so - PREFETCH_ROWS * SLOT_BYTES), bars + pbo, warp, code);
        }
        tbl += 4;
        so = wrap ? 0 : so + SLOT_BYTES;
        bo = wrap ? 0 : bo + 32;
        par ^= wrap;
    };
    int n = wk.nA;
#pragma unroll 1
    for (int seg = 0; seg < 2 && n > 0; seg++, n = wk.nB) {
        uint32_t accB[8][3], accC[8][3];
        {
            const uint32_t so0 = so, bo0 = bo;
            uint32_t so1, bo1;
#pragma unroll 1
            for (int r = 0; r < 2; r++) {
                uint32_t code;
                lds32(code, tbl);
                mbar_wait(bars + bo, par);
                so1 = so;
                bo1 = bo;
                next_row(code, false);
            }
#pragma unroll
            for (int p = 0; p < 10; p++) {
                uint32_t u[3], v[3];
                lds64(u[0], u[1], so0 + ld64 + p * 192);
                lds32(u[2], so0 + ld32 + p * 192);
                lds64(v[0], v[1], so1 + ld64 + p * 192);
                lds32(v[2], so1 + ld32 + p * 192);
#pragma unroll
                for (int dx = 0; dx < 3; dx++) {
                    const int o = p - dx;
                    if (o < 0 || o > 7) continue;
#pragma unroll
                    for (int q = 0; q < 3; q++) {
                        accB[o][q] = bf_fma(v[q], w[1][dx][q], dx == 0 ? bf_mul(u[q], w[0][dx][q]) : bf_fma(u[q], w[0][dx][q], accB[o][q]));
                        accC[o][q] = dx == 0 ? bf_mul(v[q], w[0][dx][q]) : bf_fma(v[q], w[0][dx][q], accC[o][q]);
                    }
                }
            }
            anchor(ld64, accB[7][0], accB[7][1], accB[7][2], 0);
            __syncwarp();
            if (elect_one()) {
                mbar_arrive(bars + (BAR_A - SM_BAR) + bo0);
                mbar_arrive(bars + (BAR_E - SM_BAR) + bo0);
                mbar_arrive(bars + (BAR_A - SM_BAR) + bo1);
                mbar_arrive(bars + (BAR_E - SM_BAR) + bo1);
            }
        }
        bool x_ready = false;
#pragma unroll 1
        for (int k = 0; k < n; k++) {
            if (!x_ready) mbar_wait(bars + bo, par);
            uint32_t out[8][3];
            int code;
            bool e_ready;
#pragma unroll
            for (int p = 0; p < 10; p++) {
                uint32_t xv[3];
                lds64(xv[0], xv[1], so + ld64 + p * 192);
                lds32(xv[2], so + ld32 + p * 192);
                if (p == 9) {
                    const bool wrap = bo == (NSLOT - 1) * 32, low = bo < PREFETCH_ROWS * 32;
                    asm volatile("ld.shared.u32 %0, [%1];" : "=r"(code) : "r"(tbl));
                    e_ready = mbar_test(bars + (BAR_E - SM_BAR) + (low ? bo + PREFETCH_ROWS * 32 : bo - PREFETCH_ROWS * 32), par ^ low);
                    x_ready = mbar_test(bars + (wrap ? 0 : bo + 32), par ^ wrap);
                }
#pragma unroll
                for (int dx = 0; dx < 3; dx++) {
                    const int o = p - dx;
                    if (o < 0 || o > 7) continue;
#pragma unroll
                    for (int q = 0; q < 3; q++) {
                        out[o][q] = bf_fma(xv[q], w[2][dx][q], dx == 0 ? accB[o][q] : out[o][q]);
                        accB[o][q] = bf_fma(xv[q], w[1][dx][q], dx == 0 ? accC[o][q] : accB[o][q]);
                        accC[o][q] = dx == 0 ? bf_mul(xv[q], w[0][dx][q]) : bf_fma(xv[q], w[0][dx][q], accC[o][q]);
                    }
                }
            }
            __syncwarp();
#pragma unroll
            for (int o = 0; o < 8; o++) {
                sts64(so + st64 + o * 16, out[o][0], out[o][1]);
                sts32(so + st32 + o * 16, out[o][2]);
            }
            __syncwarp();
            if (elect_one()) mbar_arrive(bars + (BAR_A - SM_BAR) + bo);
            if (tbl == publish) signal(&sc->lent_in);
            next_row(code, e_ready);
        }
    }
}

template <bool SCALED, int K0 = 0, int K1 = 3>
__device__ __forceinline__ void gelu_sq(uint32_t (&d)[24], uint32_t (&keep)[24], uint32_t sq_addr, uint32_t scale2) {
    pin(d);
#pragma unroll
    for (int k = K0; k < K1; k++) {
        uint32_t hs[4];
        lds128(hs[0], hs[1], hs[2], hs[3], sq_addr + k * SQ_ROW);
#pragma unroll
        for (int q = 0; q < 4; q++) {
            uint32_t g0 = gelu2(d[8 * k + 2 * q]), g1 = gelu2(d[8 * k + 2 * q + 1]);
            keep[8 * k + 2 * q] = g0;
            keep[8 * k + 2 * q + 1] = g1;
            if (SCALED) { g0 = h_mul(g0, scale2); g1 = h_mul(g1, scale2); }
            hs[q] = h_fma(g1, g1, h_fma(g0, g0, hs[q]));
        }
        sts128(sq_addr + k * SQ_ROW, hs[0], hs[1], hs[2], hs[3]);
    }
}
__device__ __forceinline__ void gelu_sq_reg(uint32_t (&d)[24], uint32_t (&hs)[12]) {
    pin(d);
#pragma unroll
    for (int q = 0; q < 12; q++) {
        const uint32_t g0 = gelu2(d[2 * q]), g1 = gelu2(d[2 * q + 1]);
        hs[q] = h_fma(g1, g1, h_fma(g0, g0, hs[q]));
    }
}
__device__ __forceinline__ void gelu_to(uint32_t (&g)[12], uint32_t (&d)[12]) {
    pin(d);
#pragma unroll
    for (int q = 0; q < 12; q++) g[q] = gelu2(d[q]);
    pin(g);
}
__device__ __forceinline__ void load_tile(uint32_t (&raw)[6][4], uint32_t addr) {
#pragma unroll
    for (int s = 0; s < 6; s++) ldsm4(raw[s], addr + s * 2 * A_LBO);
}
__device__ __forceinline__ uint2 ln_stats(const uint32_t (&raw)[6][4], uint64_t ones) {
    uint32_t sq[6][4];
#pragma unroll
    for (int s = 0; s < 6; s++)
#pragma unroll
        for (int q = 0; q < 4; q++) sq[s][q] = bf_mul(raw[s][q], raw[s][q]);
    float sum[4], ssq[4];
    wg_fence();
    wgmma_rowsum<0>(sum, raw[0], ones);
#pragma unroll
    for (int s = 1; s < 6; s++) wgmma_rowsum<1>(sum, raw[s], ones);
    wgmma_rowsum<0>(ssq, sq[0], ones);
#pragma unroll
    for (int s = 1; s < 6; s++) wgmma_rowsum<1>(ssq, sq[s], ones);
    wg_commit();
    wg_wait<0>();
    uint32_t st[2];
#pragma unroll
    for (int h = 0; h < 2; h++) {
        asm volatile("" : "+f"(sum[2 * h]), "+f"(ssq[2 * h])::"memory");
        const float mean = sum[2 * h] * (1.f / CH);
        const float var = fmaxf(fmaf(ssq[2 * h], 1.f / CH, -mean * mean), 0.f);
        float rstd;
        asm("rsqrt.approx.ftz.f32 %0, %1;" : "=f"(rstd) : "f"(var + 1e-5f));
        rstd = bf_lo(pack_bf2(rstd * (K_CVT == 0 ? KZ : KZ * 0x1p-112f), 0.f));
        st[h] = pack_bf2(rstd, -mean * rstd);
    }
    return make_uint2(st[0], st[1]);
}
__device__ __forceinline__ void ln_apply(uint32_t (&a)[6][4], const uint2& st) {
    const uint32_t sc[2] = {__byte_perm(st.x, 0, 0x1010), __byte_perm(st.y, 0, 0x1010)};
    const uint32_t sh[2] = {__byte_perm(st.x, 0, 0x3232), __byte_perm(st.y, 0, 0x3232)};
#pragma unroll
    for (int s = 0; s < 6; s++)
#pragma unroll
        for (int q = 0; q < 4; q++) {
            const uint32_t v = bf_fma(a[s][q], sc[q & 1], sh[q & 1]);
            a[s][q] = K_CVT == 0 ? pack_h2(bf_lo(v), bf_hi(v)) : (v & 0x7fff7fffu) * 7u + v;
        }
}
struct Cursor {
    int slot;
    uint32_t par;
    __device__ __forceinline__ void advance(int n) {
        slot += n;
        if (slot >= NSLOT) { slot -= NSLOT; par ^= 1; }
    }
};
struct Descs {
    uint64_t w1[8][6];
    uint64_t w2[24];
    uint64_t ones;
};
template <int E0, int N>
__device__ __forceinline__ void gemm1_chunk(uint32_t (&d)[N], const uint32_t (&a)[6][4], const Descs& ds, int zero) {
#pragma unroll
    for (int s = 0; s < 6; s++) wgmma(d, a[s][0], a[s][1], a[s][2], a[s][3], ds.w1[E0 / 48][s], s ? 1 : zero);
}
template <int E0, int N>
__device__ __forceinline__ void gemm2_chunk(uint32_t (&acc)[24], const uint32_t (&g)[N], const Descs& ds) {
#pragma unroll
    for (int s = 0; s < N / 4; s++) wgmma(acc, g[4 * s], g[4 * s + 1], g[4 * s + 2], g[4 * s + 3], ds.w2[E0 / 16 + s], 1);
}

__global__ void __launch_bounds__(NTHREADS, 1)
block_kernel(const __grid_constant__ CUtensorMap tmap, const __grid_constant__ CUtensorMap tmap_w1,
             const __nv_bfloat16* __restrict__ x, const __nv_bfloat16* __restrict__ dw, const __nv_bfloat16* __restrict__ w2,
             const __nv_bfloat16* __restrict__ gamma, const __nv_bfloat16* __restrict__ beta, __nv_bfloat16* __restrict__ out,
             Scratch* __restrict__ sc, const __grid_constant__ Descs ds,
             const int zero, const __grid_constant__ Split sp) {
    extern __shared__ __align__(1024) uint8_t smem[];
    constexpr uint32_t sb = SB;
    const int tid = threadIdx.x;
    const Work wk = get_work(blockIdx.x, sp);
    constexpr uint32_t s_red = sb + SM_RED;
    if (smem_u32(smem) != SB) __trap();

    PROF(0);
    const int warp_id = __shfl_sync(~0u, tid >> 5, 0);
    const int cw = warp_id - 4, wgi = cw >> 2, w4 = warp_id & 3;
    if (elect_one()) {
        if (warp_id < 8) {
            mbar_init(sb + BAR_X + warp_id * 8, 1);
            if (warp_id < 4) mbar_init(sb + BAR_X + (warp_id + 8) * 8, 1);
            fence_async();
#pragma unroll 1
            for (int r = warp_id >> 2; r < PREFETCH_ROWS; r += 2)
                issue_region(&tmap, sb + SM_RING + r * SLOT_BYTES + w4 * REGION_BYTES, sb + BAR_X + (r * 4 + w4) * 8, w4,
                             ((wk.tA & 511) + wk.dir * (r - 1)) << 16 | (wk.tA >> 9) * TILE_W);
        } else if (warp_id < 15) {
            const int b = warp_id - 8;
            mbar_init(sb + BAR_W + b * 8, 1);
            fence_async();
            mbar_expect_tx(sb + BAR_W + b * 8, b < 6 ? 64 * CH * 2 : 9 * CH * 2);
            if (b < 6) tma_2d(sb + SM_W2 + b * (64 * CH * 2), &tmap_w1, sb + BAR_W + b * 8, 64 * b, 0);
            else bulk_load(sb + SM_FILTER, dw, 9 * CH * 2, sb + BAR_F);
        }
    }
    __syncwarp();
    const int ntiles = wk.nA + wk.nB;
    const int wg = warp_id >> 2;
    int first = wg;
    uint32_t a[6][4], acc[24], tile_off, next_off, stage, inv_rho2 = 0, rpar = 0, bias_addr, lane16, lane_off;
    auto set_lane = [&](uint32_t lane) {
        bias_addr = sb + SM_BIASH + (lane & 3) * 96;
        lane16 = lane * 16;
        lane_off = ((lane >> 2) * CH + 8 * (lane & 3)) * 2;
    };
    const uint32_t bar_r = sb + BAR_R + warp_id * 8;
    auto load_bias = [&](uint32_t (&acc)[24]) {
#pragma unroll
        for (int q = 0; q < 6; q++) lds128(acc[4 * q], acc[4 * q + 1], acc[4 * q + 2], acc[4 * q + 3], bias_addr + q * 16);
    };
    auto load_frags = [&](bool on) {
#pragma unroll
        for (int s = 0; s < 6; s++) ldg128_if(on, a[s], reinterpret_cast<const char*>(out) + next_off + w4 * WARP_BYTES + lane16 + s * 512);
    };
    auto load_first = [&]() {
#pragma unroll
        for (int s = 0; s < 6; s++) ldg128(a[s], reinterpret_cast<const char*>(out) + next_off + w4 * WARP_BYTES + lane16 + s * 512);
    };
    auto stage_x = [&]() {
        if (elect_one()) {
            mbar_expect_tx(bar_r, WARP_BYTES);
            bulk_load_stream(stage, reinterpret_cast<const char*>(x) + tile_off + w4 * WARP_BYTES, WARP_BYTES, bar_r);
        }
    };
    auto epilogue = [&](uint32_t (&acc)[24]) {
        pin(acc);
        rpar ^= 1;
        uint4* op = reinterpret_cast<uint4*>(reinterpret_cast<char*>(out) + tile_off + w4 * WARP_BYTES + lane_off);
#pragma unroll
        for (int h = 0; h < 2; h++)
#pragma unroll
            for (int m = 0; m < 3; m++) {
                uint32_t xin[4], o[4];
                lds128(xin[0], xin[1], xin[2], xin[3], stage + lane_off + h * 1536 + m * 64);
#pragma unroll
                for (int q = 0; q < 4; q++) {
                    const uint32_t v = acc[2 * (4 * m + q) + h];
                    o[q] = bf_fma(pack_bf2(h_lo(v), h_hi(v)), inv_rho2, xin[q]);
                }
                __stcs(op + h * 96 + m * 4, make_uint4(o[0], o[1], o[2], o[3]));
            }
        __syncwarp();
    };
    auto reduce = [&](int q, uint32_t lane, bool leader) {
        const int part = lane >> 2, ch = 32 * q + 8 * (part >> 1) + 2 * (lane & 3) + (part & 1);
        uint32_t sq_e, sum_e;
        lds64(sq_e, sum_e, s_red + RED_SQ_EXP);
        const float to_fixed = pow2i(sum_e - 2 * sq_e);
        unsigned long long* dst = sc->sum(ch);
        named_bar(11, CONS_THREADS);
        const unsigned in_piece = ch - wk.index % 8 * 48;
        const float helped = in_piece < 48 ? ldsf(sb + SM_BIASH + in_piece * 4) * pow2i(2 * sq_e) : 0.f;
        float f[8] = {};
        int slot = wk.rows % NSLOT;
#pragma unroll 1
        for (int i = 0; i < NCONS; i++) {
            if (i == NCONS - 1) {
                named_bar(13, CONS_THREADS);
                if (leader) {
                    fence_async();
                    bulk_load(sb + SM_W2, sc->w2h, (NCONS - 1) * SQ_WG, sb + BAR_W);
                }
                __syncwarp();
                named_bar(14, NTHREADS);
            }
            const uint32_t src = sb + lane * 16 + q * SQ_ROW + (q < 6 ? SM_SQ + i * SQ_WG : sq_e ? SM_SQ + (NCONS - 1 + i) * SQ_WG : SM_RING + slot * SLOT_BYTES - SQ_WG);
            slot = slot == NSLOT - 1 ? 0 : slot + 1;
#pragma unroll
            for (int r = 0; r < 4; r++) {
                uint32_t u[4];
                lds128(u[0], u[1], u[2], u[3], src + r * 512);
#pragma unroll
                for (int k = 0; k < 4; k++) { f[2 * k] += h_lo(u[k]); f[2 * k + 1] += h_hi(u[k]); }
            }
        }
        const bool b2 = part & 4, b1 = part & 2, b0 = part & 1;
        float r4[4], r2[2];
#pragma unroll
        for (int k = 0; k < 4; k++) r4[k] = (b2 ? f[k + 4] : f[k]) + __shfl_xor_sync(~0u, b2 ? f[k] : f[k + 4], 16);
#pragma unroll
        for (int k = 0; k < 2; k++) r2[k] = (b1 ? r4[k + 2] : r4[k]) + __shfl_xor_sync(~0u, b1 ? r4[k] : r4[k + 2], 8);
        const float tot = (b0 ? r2[1] : r2[0]) + __shfl_xor_sync(~0u, b0 ? r2[0] : r2[1], 4);
        atomicAdd(dst, __float2ull_rn(fminf((tot + helped) * to_fixed, 0x1p47f)) << 8 | 1);
    };
    const uint32_t s_fac = sb + SM_RING + (wk.rows + 1) % NSLOT * SLOT_BYTES + SQ_WG;
    if (warp_id < 4) {
        conv_producer(wk, &tmap, sc, sb, warp_id);
        const int lane = opaque(tid & 31), g = lane >> 2, t = lane & 3;
        const unsigned epoch = ldsi(s_red + RED_LAUNCH);
        set_lane(lane);
        if (gridDim.x - blockIdx.x <= W2_GROUPS / 2) {
            const int q = (gridDim.x - 1 - blockIdx.x) * 2 + (w4 >> 1), half = w4 & 1;
            uint32_t u[3][2], rmax = 0;
#pragma unroll
            for (int m = 0; m < 3; m++) {
                const uint4 w = ldg128_ordered(w2 + (8 * q + g) * CH + 32 * m + 8 * t);
                rmax = bf_absmax(bf_absmax(rmax, bf_absmax(w.x, w.y)), bf_absmax(w.z, w.w));
                u[m][0] = half ? w.z : w.x;
                u[m][1] = half ? w.w : w.y;
            }
            const float bt = __bfloat162float(beta[8 * q + g]);
            rmax = bf_absmax(rmax, __shfl_xor_sync(~0u, rmax, 1));
            rmax = bf_absmax(rmax, __shfl_xor_sync(~0u, rmax, 2));
            const float mx = fmaxf(fabsf(bf_lo(rmax)), fabsf(bf_hi(rmax))), rs = row_scale(mx);
            if (t == 0 && !half) { sc->w2max[8 * q + g] = mx; *sc->sum(8 * q + g) = 0; }
#pragma unroll
            for (int m = 0; m < 3; m++) {
                float f[4];
#pragma unroll
                for (int k = 0; k < 2; k++) {
                    const float lo = bf_lo(u[m][k]), hi = bf_hi(u[m][k]);
                    sc->w2h[(4 * m + 2 * half + k) * 1536 + q * 32 + lane] = transpose8x8(pack_h2(lo * rs, hi * rs));
                    f[2 * k] = lo * bt;
                    f[2 * k + 1] = hi * bt;
                }
                const float r0 = (g & 2 ? f[2] : f[0]) + __shfl_xor_sync(~0u, g & 2 ? f[0] : f[2], 8);
                const float r1 = (g & 2 ? f[3] : f[1]) + __shfl_xor_sync(~0u, g & 2 ? f[1] : f[3], 8);
                float r = (g & 1 ? r1 : r0) + __shfl_xor_sync(~0u, g & 1 ? r0 : r1, 4);
                r += __shfl_xor_sync(~0u, r, 16);
                if (g < 4) atomicAdd(&sc->bias[epoch & 1][32 * m + 8 * t + 4 * half + g], r);
            }
            asm volatile("fence.proxy.async.global;" ::: "memory");
            signal(&sc->prep);
        }
        const int piece = wk.index, lenders = sp.lenders;
        const bool helps = !wk.lent && piece < 8 * LENT * lenders;
        if (helps) {
            spin_until(&sc->lent_in, (epoch + 1) * 4 * lenders);
            next_off = tile_offset(get_work((piece / (8 * LENT) + 1) * sp.period - sp.period / 2 - 1, sp).tile(piece / 8 % LENT));
            load_first();
            uint32_t d[12], gl[12];
            wg_fence();
#pragma unroll
            for (int s = 0; s < 6; s++) wgmma(d, a[s][0], a[s][1], a[s][2], a[s][3], ds.w1[0][s] + piece % 8 * (6 * 1536 / 16), s ? 1 : 0);
            wg_commit();
            wg_wait<0>();
            gelu_to(gl, d);
#pragma unroll
            for (int s = 0; s < 3; s++) sc->lent[(((piece / (8 * LENT) * 4 + w4) * (8 * LENT) + piece % (8 * LENT)) * 3 + s) * 32 + lane] = make_uint4(gl[4 * s], gl[4 * s + 1], gl[4 * s + 2], gl[4 * s + 3]);
            float f[6], r[3];
#pragma unroll
            for (int j = 0; j < 6; j++) {
                const float lo = fmaf(h_lo(gl[2 * j]), h_lo(gl[2 * j]), h_lo(gl[2 * j + 1]) * h_lo(gl[2 * j + 1]));
                const float hi = fmaf(h_hi(gl[2 * j]), h_hi(gl[2 * j]), h_hi(gl[2 * j + 1]) * h_hi(gl[2 * j + 1]));
                f[j] = (g & 1 ? hi : lo) + __shfl_xor_sync(~0u, g & 1 ? lo : hi, 4);
            }
#pragma unroll
            for (int j = 0; j < 3; j++) {
                r[j] = (g & 2 ? f[j + 3] : f[j]) + __shfl_xor_sync(~0u, g & 2 ? f[j] : f[j + 3], 8);
                asm volatile("red.shared.add.f32 [%0], %1;" ::"r"(sb + SM_BIASH + (8 * j + 12 * (g & 2) + 2 * t + (g & 1)) * 4), "f"(r[j]) : "memory");
            }
        }
        if (helps) signal(&sc->lent_out);
        const bool leader = warp_id == 0 && lane == 0;
        const float w1max = ldsf(s_red + RED_MAX), from_fixed = pow2i(-ldsi(s_red + RED_SUM_EXP));
        const bool plain = ldsi(s_red + RED_SQ_EXP) == 0;
        auto load_upper = [&]() {
            bulk_load(sb + SM_W2 + NCONS * SQ_WG, reinterpret_cast<const char*>(sc->w2h) + NCONS * SQ_WG, EX * CH * 2 - NCONS * SQ_WG, sb + BAR_W);
        };
        if (leader) {
            spin_until(&sc->prep, (epoch + 1) * 2 * W2_GROUPS);
            asm volatile("fence.proxy.async.global;" ::: "memory");
            fence_async();
            mbar_expect_tx(sb + BAR_W, EX * CH * 2);
            if (plain) load_upper();
        }
        __syncwarp();
        named_bar(1, 128);
        const int i0 = w4 * 32 + lane;
        float gam[3], rmax[3];
#pragma unroll
        for (int m = 0; m < 3; m++) { gam[m] = __bfloat162float(gamma[i0 + 128 * m]); rmax[m] = __ldcg(&sc->w2max[i0 + 128 * m]); }
        float2 bpair = make_float2(0.f, 0.f);
        if (i0 < 96) bpair = __ldcg(reinterpret_cast<const float2*>(&sc->bias[epoch & 1][32 * (i0 % 24 >> 3) + 8 * (i0 / 24) + (i0 % 24 & 6)]));
        const float gbound = fmaxf(2.f * KZ * 9.7979590f * 192.f * w1max, 1.f) * 19.5959180f * INV_2KZ;
        const unsigned fixed = __reduce_max_sync(~0u, __float_as_uint(fmaf(gbound, fmaxf(fmaxf(rmax[0], rmax[1]), rmax[2]), fmaxf(fabsf(bpair.x), fabsf(bpair.y)))));
        if (lane == 0) sts32(s_red + 96 + w4 * 4, fixed);
        reduce(4 * (NCONS - 1) + w4, lane, leader);
        PROF(2);
        named_bar(15, CONS_THREADS);
        if (leader) {
            fence_async();
            bulk_load(sb + SM_W2 + (NCONS - 1) * SQ_WG, reinterpret_cast<const char*>(sc->w2h) + (NCONS - 1) * SQ_WG, SQ_WG, sb + BAR_W);
            if (!plain) load_upper();
        }
        stage = sb + SM_RING + (wk.rows + 3 + (wk.lent + 2 * ntiles) % NCONS) % NSLOT * SLOT_BYTES + w4 * REGION_BYTES;
        auto grn = [&]() {
            auto peek = [&](int e) {
                unsigned long long v;
                asm volatile("ld.relaxed.gpu.global.u64 %0, [%1];" : "=l"(v) : "l"(sc->sum(e)) : "memory");
                return v;
            };
            unsigned n = 0;
            while (((unsigned)peek((blockIdx.x * 4 + w4) % (EX / 4) * 4) & 255u) != gridDim.x)
                if (++n > SPIN_LIMIT) __trap();
            unsigned long long sum[3];
            for (;;) {
                bool all = true;
#pragma unroll
                for (int m = 0; m < 3; m++) {
                    sum[m] = peek(i0 + 128 * m);
                    all &= ((unsigned)sum[m] & 255u) == gridDim.x;
                }
                if (__all_sync(~0u, all)) break;
                if (++n > SPIN_LIMIT) __trap();
            }
            PROF(3);
            if (blockIdx.x == 0 && leader) sc->launch = epoch + 1;
            float gx[3], tot = 0.f, vary = 0.f;
#pragma unroll
            for (int m = 0; m < 3; m++) {
                gx[m] = grn_norm(__ull2float_rn(sum[m] >> 8) * from_fixed);
                tot += gx[m];
                vary = fmaxf(vary, fabsf(gam[m]) * gx[m] * rmax[m]);
            }
#pragma unroll
            for (int o = 16; o >= 1; o >>= 1) tot += __shfl_xor_sync(~0u, tot, o);
            const unsigned vwarp = __reduce_max_sync(~0u, __float_as_uint(vary));
            if (lane == 0) { sts32(s_red + 64 + w4 * 4, __float_as_uint(tot)); sts32(s_red + 80 + w4 * 4, vwarp); }
            named_bar(1, 128);
            uint32_t u[4], v[4], w[4];
            lds128(u[0], u[1], u[2], u[3], s_red + 64);
            lds128(v[0], v[1], v[2], v[3], s_red + 80);
            lds128(w[0], w[1], w[2], w[3], s_red + 96);
            tot = (__uint_as_float(u[0]) + __uint_as_float(u[1])) + (__uint_as_float(u[2]) + __uint_as_float(u[3]));
            const float vmax = __uint_as_float(max(max(v[0], v[1]), max(v[2], v[3]))), fmax2 = __uint_as_float(max(max(w[0], w[1]), max(w[2], w[3])));
            const float inv_mean = __fdividef(1.f, tot * (1.f / EX) + 1e-6f);
            const float bound = fmaf(gbound * vmax, inv_mean, 2.f * fmax2);
            const int rho_e = bound > 0.f ? 14 - ilog2f(bound) : 0;
            const float rho = pow2i(rho_e), inv_rho = pow2i(-rho_e);
            inv_rho2 = pack_bf2(inv_rho, inv_rho);
#pragma unroll
            for (int m = 0; m < 3; m++) {
                const float f = __fdividef(fmaf(gam[m], gx[m] * inv_mean, 1.f) * INV_2KZ * rho, row_scale(rmax[m]));
                asm volatile("st.shared.u16 [%0], %1;" ::"r"(s_fac + (i0 + 128 * m) * 2), "h"((unsigned short)pack_h2(f, 0.f)) : "memory");
            }
            if (i0 < 96) sts32(sb + SM_BIASH + i0 * 4, pack_h2(bpair.x * rho, bpair.y * rho));
            if (i0 == 96) sts32(s_red + RED_INV_RHO, inv_rho2);
            named_arrive(12, NTHREADS);
        };
        if (wk.lent) spin_until(&sc->lent_out, (epoch + 1) * 32 * LENT * lenders);
        lds32(next_off, sb + SM_TILES);
        next_off = __shfl_sync(~0u, next_off, 0);
        load_first();
        grn();
    } else {
        const int rank = (wgi + wk.lent + 2 * ntiles) % NCONS;
        {
            const int ct = tid - 128, lane = tid & 31;
            const unsigned epoch = *reinterpret_cast<volatile unsigned*>(&sc->launch);
            const int r = lane & 7, mi = lane >> 3;
            const uint32_t src = sb + SM_W2 + (cw >> 1) * (64 * CH * 2) + r * 128 + ((((cw & 1) * 4 + mi) ^ r) * 16);
            const uint32_t dst = sb + SM_W1 + (4 * cw + mi) * 1536 + r * 16;
            if (ct == 0) sts32(s_red + RED_MAX, 0);
            named_bar(0, NTHREADS);
            mbar_wait(sb + BAR_W + (cw >> 1) * 8, 0);
            uint32_t wmax[4] = {}, wsum[4] = {};
#pragma unroll 3
            for (int c = 0; c < 12; c++) {
                uint32_t u[4];
                ldsm4_t(u, src + c * 1024);
#pragma unroll
                for (int q = 0; q < 4; q++) {
                    wmax[q] = bf_absmax(wmax[q], u[q]);
                    wsum[q] = bf_fma(u[q], 0x3f803f80u, wsum[q]);
                    u[q] = pack_h2(bf_lo(u[q]), bf_hi(u[q]));
                }
                stsm4(dst + c * 128, u[0], u[1], u[2], u[3]);
            }
            float mean[4];
            bool center = false;
#pragma unroll
            for (int q = 0; q < 4; q++) {
                uint32_t m = wmax[q];
                float sum = bf_lo(wsum[q]) + bf_hi(wsum[q]);
#pragma unroll
                for (int o = 1; o <= 2; o <<= 1) { m = bf_absmax(m, __shfl_xor_sync(~0u, m, o)); sum += __shfl_xor_sync(~0u, sum, o); }
                mean[q] = sum * (1.f / CH);
                center |= fabsf(mean[q]) > 0.2f * fmaxf(fabsf(bf_lo(m)), fabsf(bf_hi(m)));
            }
            if (__builtin_expect(__any_sync(~0u, center), 0)) {
#pragma unroll 1
                for (int pass = 0; pass < 2; pass++) {
                    float sum[4] = {};
#pragma unroll 1
                    for (int c = 0; c < 12; c++) {
                        uint32_t u[4];
                        ldsm4_t(u, src + c * 1024);
#pragma unroll
                        for (int q = 0; q < 4; q++) {
                            sum[q] += bf_lo(u[q]) + bf_hi(u[q]);
                            u[q] = pack_h2(bf_lo(u[q]) - mean[q], bf_hi(u[q]) - mean[q]);
                        }
                        stsm4(dst + c * 128, u[0], u[1], u[2], u[3]);
                    }
#pragma unroll
                    for (int q = 0; q < 4; q++) {
                        sum[q] += __shfl_xor_sync(~0u, sum[q], 1);
                        sum[q] += __shfl_xor_sync(~0u, sum[q], 2);
                        mean[q] = sum[q] * (1.f / CH);
                    }
                }
            }
            if (cw < 2 * NCONS) {
#pragma unroll
                for (int c = 0; c < 12; c++) sts128(src + c * 1024, 0, 0, 0, 0);
            }
            const float w1max = warp_absmax(bf_absmax(bf_absmax(wmax[0], wmax[1]), bf_absmax(wmax[2], wmax[3])));
            if (lane == 0) asm volatile("red.shared.max.u32 [%0], %1;" ::"r"(s_red + RED_MAX), "r"(__float_as_uint(w1max)) : "memory");
            if (ct < 32) sts32(sb + SM_ONES + ct * 4, 0x3f803f80u);
            if (ct < 48) sts32(sb + SM_BIASH + ct * 4, 0);
            if (blockIdx.x == 0 && ct < CH) sc->bias[(epoch & 1) ^ 1][ct] = 0.f;
            if (ct == 0) sts32(s_red + RED_LAUNCH, epoch);
            fence_async();
            named_bar(2, CONS_THREADS);
            const float all_max = ldsf(s_red + RED_MAX);
            const int sq_e = square_exp(all_max);
            sts64(s_red + RED_SQ_EXP, sq_e, sum_exp(all_max));
            if (sq_e) {
#pragma unroll 1
                for (int q = 0; q < 6; q++) sts128(sb + SM_SQ + (rank + NCONS) * SQ_WG + q * SQ_ROW + (ct & 127) * 16, 0, 0, 0, 0);
            }
            mbar_wait(sb + BAR_A + w4 * 8 + 32, 0);
        }

        PROF(1);
        const uint32_t a_addr = opaque(sb + SM_RING + w4 * REGION_BYTES + ((tid >> 3) & 1) * A_SBO + ((tid >> 4) & 1) * A_LBO + (tid & 7) * 16);
        const uint32_t bar_a = sb + BAR_A + w4 * 8, bar_e = sb + BAR_E + w4 * 8;
        const uint32_t sq = opaque(sb + SM_SQ + rank * SQ_WG + (tid & 127) * 16);
        const uint32_t sq_warp = sb + SM_SQ + rank * SQ_WG + w4 * 512;
        uint32_t k1[24], k2[24], k3[24];
        constexpr int SQC = 3 * SQ_ROW;
        const int pass_to = 4 + (wgi == NCONS - 1 ? 0 : wgi + 1);
        auto store_frags = [&](const uint32_t (&a)[6][4], int j) {
            char* ap = reinterpret_cast<char*>(out) + (tile_offset(wk.tile(j)) + w4 * WARP_BYTES - sq_warp + sq);
#pragma unroll
            for (int s = 0; s < 6; s++) stg128(ap + s * 512, a[s]);
        };
        int jt = wgi < wk.lent ? wgi : wk.lent + wgi;
        Cursor cur = {2, 0};
        cur.advance(jt + (jt >= wk.nA ? 2 : 0));
        if (wgi == NCONS - 1) named_arrive(4, 256);
        for (;;) {
            const bool plain = __all_sync(~0u, ldsi(s_red + RED_SQ_EXP) == 0);
            if (plain && jt >= wk.lent) {
                uint32_t hs2[12] = {}, hs3[12] = {};
#pragma unroll 1
                for (; jt + NCONS < ntiles; jt += NCONS) {
                    uint32_t a[6][4], d0[24], d1[24], unused[24];
#define AT(pos) \
    if (K_WAIT == pos) named_bar(4 + wgi, 256); \
    if (K_PASS == pos) named_arrive(pass_to, 256); \
    if (K_STG == pos) store_frags(a, jt); \
    if (K_REL == pos) { if (elect_one()) mbar_arrive(bar_e + cur.slot * 32); }
                    AT(20)
                    mbar_wait(bar_a + cur.slot * 32, cur.par);
                    load_tile(a, a_addr + cur.slot * SLOT_BYTES);
                    AT(21)
                    const uint2 st = ln_stats(a, ds.ones);
                    AT(0)
                    ln_apply(a, st);
                    AT(1)
                    wg_fence();
                    gemm1_chunk<0>(d0, a, ds, 0);
                    wg_commit();
                    gemm1_chunk<96>(d1, a, ds, 0);
                    wg_commit();
                    AT(2)
                    wg_wait<1>();
                    AT(3)
                    gelu_sq<false, 0, 1>(d0, unused, sq, 0);
                    AT(4)
                    gelu_sq<false, 1, 2>(d0, unused, sq, 0);
                    AT(5)
                    gelu_sq<false, 2, 3>(d0, unused, sq, 0);
                    AT(6)
                    wg_fence();
                    gemm1_chunk<192>(d0, a, ds, zero);
                    wg_commit();
                    AT(7)
                    wg_wait<1>();
                    gelu_sq<false, 0, 1>(d1, unused, sq + SQC, 0);
                    AT(8)
                    gelu_sq<false, 1, 3>(d1, unused, sq + SQC, 0);
                    AT(9)
                    wg_fence();
                    gemm1_chunk<288>(d1, a, ds, zero);
                    wg_commit();
                    AT(10)
                    wg_wait<1>();
                    gelu_sq_reg(d0, hs2);
                    if (K_ANCH < 3) anchor(sq, hs2[4 * (K_ANCH % 3)], hs2[4 * (K_ANCH % 3) + 1], hs2[4 * (K_ANCH % 3) + 2], hs2[4 * (K_ANCH % 3) + 3]);
                    wg_wait<0>();
                    AT(11)
                    gelu_sq_reg(d1, hs3);
#undef AT
                    cur.advance(NCONS + ((jt < wk.nA && jt + NCONS >= wk.nA) ? 2 : 0));
                }
                const uint32_t sq2 = sq - (SM_SQ + rank * SQ_WG) + SM_RING + (cur.slot + 3) % NSLOT * SLOT_BYTES;
#pragma unroll
                for (int k = 0; k < 3; k++) {
                    sts128(sq2 + k * SQ_ROW, hs2[4 * k], hs2[4 * k + 1], hs2[4 * k + 2], hs2[4 * k + 3]);
                    sts128(sq2 + SQC + k * SQ_ROW, hs3[4 * k], hs3[4 * k + 1], hs3[4 * k + 2], hs3[4 * k + 3]);
                }
            }
            const bool last = jt + NCONS >= ntiles;
            if (last) {
                tile_off = tile_offset(wk.tile(jt));
                lds32(next_off, sb + SM_TILES + wg * 4);
                next_off = __shfl_sync(~0u, next_off, 0);
                if (elect_one()) {
                    prefetch_l2(reinterpret_cast<const char*>(x) + tile_off + w4 * WARP_BYTES, WARP_BYTES);
                    if (wg % ORDER_P >= ORDER_P - ORDER_Q) prefetch_l2(reinterpret_cast<const char*>(out) + next_off + w4 * WARP_BYTES, WARP_BYTES);
                }
            }
            uint32_t a[6][4], d0[24], d1[24], d3[24], k0[24];
#define AT(pos) \
    if (K_WAIT == pos && jt >= wk.lent) named_bar(4 + wgi, 256); \
    if (K_PASS == pos && jt >= wk.lent && jt + 1 < ntiles) named_arrive(pass_to, 256);
            AT(20)
            mbar_wait(bar_a + cur.slot * 32, cur.par);
            load_tile(a, a_addr + cur.slot * SLOT_BYTES);
            AT(21)
            const uint2 st = ln_stats(a, ds.ones);
            AT(0)
            ln_apply(a, st);
            AT(1)
            if (!last) {
                store_frags(a, jt);
                __syncwarp();
                if (elect_one()) mbar_arrive(bar_e + cur.slot * 32);
                if (jt < wk.lent) {
                    jt += LENT;
                    cur.advance(LENT);
                    continue;
                }
            }
            wg_fence();
            gemm1_chunk<0>(d0, a, ds, 0);
            wg_commit();
            gemm1_chunk<96>(d1, a, ds, 0);
            wg_commit();
            const int sq_e = ldsi(s_red + RED_SQ_EXP);
            const uint32_t scale2 = pack_h2(pow2i(sq_e), pow2i(sq_e));
            AT(2)
            wg_wait<1>();
            AT(3)
            gelu_sq<true, 0, 1>(d0, k0, sq, scale2);
            AT(4)
            gelu_sq<true, 1, 2>(d0, k0, sq, scale2);
            AT(5)
            gelu_sq<true, 2, 3>(d0, k0, sq, scale2);
            AT(6)
            if (last) {
#pragma unroll
                for (int q = 0; q < 6; q++) sts128(sb + SM_RING + cur.slot * SLOT_BYTES + w4 * REGION_BYTES - sq_warp + sq + q * 512, k0[4 * q], k0[4 * q + 1], k0[4 * q + 2], k0[4 * q + 3]);
            }
            wg_fence();
            gemm1_chunk<192>(d0, a, ds, zero);
            wg_commit();
            AT(7)
            wg_wait<1>();
            gelu_sq<true, 0, 1>(d1, k1, sq + SQC, scale2);
            AT(8)
            gelu_sq<true, 1, 3>(d1, k1, sq + SQC, scale2);
            AT(9)
#undef AT
            wg_fence();
            gemm1_chunk<288>(d3, a, ds, 0);
            wg_commit();
            wg_wait<1>();
            const uint32_t sq2 = sq + (plain ? SM_RING + (cur.slot + 3) % NSLOT * SLOT_BYTES - (SM_SQ + rank * SQ_WG) : NCONS * SQ_WG);
            gelu_sq<true>(d0, k2, sq2, scale2);
            wg_wait<0>();
            gelu_sq<true>(d3, k3, sq2 + SQC, scale2);
            if (last) break;
            cur.advance(NCONS + ((jt < wk.nA && jt + NCONS >= wk.nA) ? 2 : 0));
            jt += NCONS;
        }
        {
            if (rank == NCONS - 1) {
                named_arrive(14, NTHREADS);
            } else {
                reduce(4 * rank + w4, (sq >> 4) & 31, false);
                named_arrive(15, CONS_THREADS);
            }
        }
        PROF(2);
        {
            set_lane((sq >> 4) & 31);
            const uint32_t row = sb + SM_W2 + cw * 512 + lane16;
            uint32_t u[W2_EARLY][4], f2[4];
            mbar_wait(sb + BAR_W, 1);
#pragma unroll
            for (int nb = 0; nb < W2_EARLY; nb++) lds128(u[nb][0], u[nb][1], u[nb][2], u[nb][3], row + nb * 6144);
            named_bar(12, NTHREADS);
            PROF(3);
            stage = sb + SM_RING + (cur.slot + 3) % NSLOT * SLOT_BYTES + w4 * WARP_BYTES;
            stage_x();
            lds128(f2[0], f2[1], f2[2], f2[3], s_fac + cw * 64 + (lane16 >> 7) * 16);
            lds32(inv_rho2, s_red + RED_INV_RHO);
#pragma unroll
            for (int nb = 0; nb < 12; nb++) {
                uint32_t v[4];
                if (nb < W2_EARLY) { v[0] = u[nb % W2_EARLY][0]; v[1] = u[nb % W2_EARLY][1]; v[2] = u[nb % W2_EARLY][2]; v[3] = u[nb % W2_EARLY][3]; }
                else lds128(v[0], v[1], v[2], v[3], row + nb * 6144);
                sts128(row + nb * 6144, h_round8(h_mul(v[0], f2[0])), h_round8(h_mul(v[1], f2[1])), h_round8(h_mul(v[2], f2[2])), h_round8(h_mul(v[3], f2[3])));
            }
            fence_async();
            named_bar(3, NTHREADS);
        }
        PROF(4);
        {
            load_bias(acc);
            if (wgi > 0) named_bar(8 + wgi, 256);
            pin(k1); pin(k2); pin(k3);
            wg_fence();
            gemm2_chunk<288>(acc, k3, ds);
            wg_commit();
            gemm2_chunk<(K_SWAP ? 192 : 96)>(acc, K_SWAP ? k2 : k1, ds);
            if (K_FINE) wg_commit();
            gemm2_chunk<(K_SWAP ? 96 : 192)>(acc, K_SWAP ? k1 : k2, ds);
            wg_commit();
            if (!K_LATE && wgi + 1 < NCONS) named_arrive(9 + wgi, 256);
            wg_wait<1 + K_FINE>();
            uint32_t k0[24];
#pragma unroll
            for (int q = 0; q < 6; q++)
                lds128(k0[4 * q], k0[4 * q + 1], k0[4 * q + 2], k0[4 * q + 3], sb + SM_RING + cur.slot * SLOT_BYTES + w4 * REGION_BYTES + lane16 + q * 512);
            pin(k0);
            wg_fence();
            gemm2_chunk<0>(acc, k0, ds);
            wg_commit();
            if (K_LATE && wgi + 1 < NCONS) named_arrive(9 + wgi, 256);
            if (wgi == 0) named_arrive(8, 256);
            wg_wait<1 + K_FINE>();
            load_first();
            if (lane16 == 0) mbar_arrive(sb + BAR_PIN);
            mbar_wait(bar_r, rpar);
            wg_wait<0>();
            first = wg - 4;
        }
    }
    {
        const int nrest = ntiles - NCONS;
        auto lent = [&](uint32_t entry) { return &sc->lent[((wk.index * 4 + w4) * LENT + (entry & 3) - 1) * (8 * 96)]; };
        for (int jt = first; jt < nrest; jt += 4) {
            if (jt >= 0) {
            tile_off = next_off;
            lds32(next_off, sb + SM_TILES + (jt + 4) * 4);
            if (tile_off & 3) {
                uint32_t gl[2][24];
                const uint4* src = lent(tile_off) + (lane16 >> 4);
                auto fetch = [&](uint32_t (&v)[24], int c) {
#pragma unroll
                    for (int s = 0; s < 6; s++) ldg128(reinterpret_cast<uint32_t (&)[4]>(v[4 * s]), src + (6 * c + s) * 32);
                };
                tile_off &= ~3u;
                next_off = __shfl_sync(~0u, next_off, 0);
                stage_x();
                if (elect_one()) prefetch_l2(reinterpret_cast<const char*>(out) + next_off + w4 * WARP_BYTES, WARP_BYTES);
                load_bias(acc);
#pragma unroll
                for (int half = 0; half < 2; half++) {
                    fetch(gl[0], 2 * half);
                    fetch(gl[1], 2 * half + 1);
                    if (!half) {
                        named_bar(4 + wg, 256);
                        named_arrive(4 + ((wg + 1) & 3), 256);
                    }
                    pin(gl[0]); pin(gl[1]);
                    wg_fence();
                    if (half) gemm2_chunk<192>(acc, gl[0], ds); else gemm2_chunk<0>(acc, gl[0], ds);
                    if (half) gemm2_chunk<288>(acc, gl[1], ds); else gemm2_chunk<96>(acc, gl[1], ds);
                    wg_commit();
                    wg_wait<0>();
                }
                load_first();
                mbar_wait(bar_r, rpar);
            } else {
            uint32_t d0[12], d1[12], g0[12], g1[12];
            if (jt >= S2_FIRST && jt < nrest - K_TAIL) named_bar(4 + wg, 256);
            wg_fence();
            gemm1_chunk<0>(d0, a, ds, 0);
            wg_commit();
            gemm1_chunk<48>(d1, a, ds, 0);
            wg_commit();
            load_bias(acc);
            next_off = __shfl_sync(~0u, next_off, 0);
            const bool more = jt + 4 < nrest && !(next_off & 3);
            wg_wait<1>();
#define CNX_PASS if (jt + 1 >= S2_FIRST && jt + 1 < nrest - K_TAIL) named_arrive(4 + ((wg + 1) & 3), 256);
#define CNX_STEP(C, D, G)                                              \
    gelu_to(G, D);                                                     \
    if (C == 0 && jt == 0) {                                           \
        named_bar(3, NTHREADS);                                        \
        load_bias(acc);                                                \
    }                                                                  \
    wg_fence();                                                        \
    if (C < 6) gemm1_chunk<48 * (C < 6 ? C + 2 : 0)>(D, a, ds, zero); \
    gemm2_chunk<48 * C>(acc, G, ds);                                  \
    wg_commit();                                                       \
    if (C == S2_PASS) { CNX_PASS }                                     \
    wg_wait<(C < 7 ? 1 : 0)>();
            CNX_STEP(0, d0, g0)
            CNX_STEP(1, d1, g1)
            if (jt == 0) named_bar(8, 256);
            stage_x();
            if (elect_one()) {
                if (more) prefetch_l2(reinterpret_cast<const char*>(out) + next_off + w4 * WARP_BYTES, WARP_BYTES);
                else if (next_off & 3) prefetch_l2(lent(next_off), 8 * 96 * 16);
            }
            CNX_STEP(2, d0, g0)
            CNX_STEP(3, d1, g1)
            CNX_STEP(4, d0, g0)
            CNX_STEP(5, d1, g1)
            CNX_STEP(6, d0, g0)
            load_frags(more);
            if (lane16 == 0) mbar_arrive(sb + BAR_PIN);
            mbar_wait(bar_r, rpar);
            CNX_STEP(7, d1, g1)
#undef CNX_STEP
            }
            }
            epilogue(acc);
        }
    }
    PROF(5);
}

}

typedef CUresult (*EncodeTiledFn)(CUtensorMap*, CUtensorMapDataType, cuuint32_t, void*, const cuuint64_t*, const cuuint64_t*,
                                  const cuuint32_t*, const cuuint32_t*, CUtensorMapInterleave, CUtensorMapSwizzle,
                                  CUtensorMapL2promotion, CUtensorMapFloatOOBfill);

extern "C" void kernel_launch(void* const* d_in, const int* in_sizes, int n_in, void* d_out, int out_size) {
    using namespace cnx;
    static EncodeTiledFn encode = nullptr;
    static int num_sms = 0;
    static Scratch* scratch = nullptr;
    if (!encode) {
        void* fn = nullptr;
        cudaDriverEntryPointQueryResult qr;
        cudaGetDriverEntryPoint("cuTensorMapEncodeTiled", &fn, cudaEnableDefault, &qr);
        encode = (EncodeTiledFn)fn;
        cudaGetSymbolAddress((void**)&scratch, g_scratch);
        int dev = 0;
        cudaGetDevice(&dev);
        cudaDeviceGetAttribute(&num_sms, cudaDevAttrMultiProcessorCount, dev);
        if (num_sms > MAX_CTAS) num_sms = MAX_CTAS;
        cudaFuncSetAttribute(block_kernel, cudaFuncAttributeMaxDynamicSharedMemorySize, SM_TOTAL);
    }
    CUtensorMap tm;
    cuuint64_t dims[3] = {(cuuint64_t)CH, (cuuint64_t)IMG_W, (cuuint64_t)IMG_H};
    cuuint64_t strides[2] = {(cuuint64_t)CH * 2, (cuuint64_t)CH * 2 * IMG_W};
    cuuint32_t box[3] = {(cuuint32_t)CH, (cuuint32_t)REGION_PX, 1};
    cuuint32_t estr[3] = {1, 1, 1};
    encode(&tm, CU_TENSOR_MAP_DATA_TYPE_BFLOAT16, 3, d_in[0], dims, strides, box, estr, CU_TENSOR_MAP_INTERLEAVE_NONE,
           CU_TENSOR_MAP_SWIZZLE_NONE, CU_TENSOR_MAP_L2_PROMOTION_L2_128B, CU_TENSOR_MAP_FLOAT_OOB_FILL_NONE);
    Descs ds;
    for (int c = 0; c < 8; c++)
        for (int k = 0; k < 6; k++) ds.w1[c][k] = make_desc(SB + SM_W1 + c * 6 * 1536 + k * 256, 128, 1536);
    for (int k = 0; k < 24; k++) ds.w2[k] = make_desc(SB + SM_W2 + k * 256, 128, 6144);
    ds.ones = make_desc(SB + SM_ONES, 0, 0);
    CUtensorMap tw;
    cuuint64_t wdims[2] = {(cuuint64_t)EX, (cuuint64_t)CH};
    cuuint64_t wstrides[1] = {(cuuint64_t)EX * 2};
    cuuint32_t wbox[2] = {64, (cuuint32_t)CH};
    encode(&tw, CU_TENSOR_MAP_DATA_TYPE_BFLOAT16, 2, d_in[2], wdims, wstrides, wbox, estr, CU_TENSOR_MAP_INTERLEAVE_NONE,
           CU_TENSOR_MAP_SWIZZLE_128B, CU_TENSOR_MAP_L2_PROMOTION_L2_128B, CU_TENSOR_MAP_FLOAT_OOB_FILL_NONE);
    Split sp = {NTILES / num_sms, NTILES % num_sms, 1, 1 << 16, 0};
    if (sp.per_cta + 9 > MAX_ROWS) return;
    if (sp.extra && sp.extra * (8 * LENT + 1) <= num_sms && sp.per_cta >= 5 * LENT + 7) {
        sp.period = num_sms / sp.extra;
        sp.inv_period = 65535 / sp.period + 1;
        sp.lenders = sp.extra;
        for (int l = 0; l < sp.extra; l++)
            if (get_work((l + 1) * sp.period - sp.period / 2 - 1, sp).nA < 2 * LENT) sp.lenders = 0;
    }
    block_kernel<<<num_sms, NTHREADS, SM_TOTAL>>>(tm, tw, (const __nv_bfloat16*)d_in[0], (const __nv_bfloat16*)d_in[1],
                                             (const __nv_bfloat16*)d_in[3],
                                             (const __nv_bfloat16*)d_in[4], (const __nv_bfloat16*)d_in[5], (__nv_bfloat16*)d_out,
                                             scratch, ds, 0, sp);
}
```

```cpp
#include <cuda_runtime.h>
#include <cuda_bf16.h>
#include <cuda_fp16.h>
#include <cuda.h>
#include <stdint.h>

namespace cnx {

constexpr int IMG_H = 512, IMG_W = 512, CH = 96, EX = 384;
constexpr int TILE_W = 64;
constexpr int NTILES = (IMG_W / TILE_W) * IMG_H;
constexpr int NSLOT = 6;
constexpr int REGION_PX = 18;
constexpr int REGION_BYTES = REGION_PX * CH * 2;
constexpr int SLOT_BYTES = 4 * REGION_BYTES;
constexpr int A_LBO = 144, A_SBO = 12 * A_LBO;
constexpr int PREFETCH_ROWS = 3;
constexpr int NCONS = 3;
constexpr int CONS_THREADS = 128 * NCONS;
constexpr int NTHREADS = 128 + CONS_THREADS;
constexpr int MAX_ROWS = 52;
constexpr int TILE_BYTES = TILE_W * CH * 2, WARP_BYTES = TILE_BYTES / 4;
constexpr int S1_PASS = 1, S2_PASS = 1;
#define K_PASS 4
#define K_WAIT 20
#define K_STG 6
#define K_REL 6
#define K_ANCH 2
#define K_CVT 0
#define K_XPOS 1
#define K_CHAIN 3
#define K_LATE 1
#define K_FINE 1
#define K_SWAP 0
#define K_TAIL 0
#define W2_EARLY 6
#define S2_FIRST 2
#define ORDER_P 3
#define ORDER_Q 1
static_assert(MAX_ROWS <= 128, "one table entry per producer thread");
static_assert(2 * A_SBO == REGION_BYTES && REGION_BYTES % 128 == 0, "region layout");

constexpr uint32_t SB = 1024;
constexpr int SM_W1 = 0;
constexpr int SM_W2 = SM_W1 + CH * EX * 2;
constexpr int SM_RING = SM_W2 + CH * EX * 2;
constexpr int SM_BIASH = SM_RING + NSLOT * SLOT_BYTES;
constexpr int SM_RED = SM_BIASH + 384;
constexpr int RED_MAX = 0, RED_LAUNCH = 4, RED_SQ_EXP = 8, RED_SUM_EXP = 12, RED_INV_RHO = 16;
constexpr int SM_ROWS = SM_RED + 256;
constexpr int SM_TILES = SM_ROWS + MAX_ROWS * 4;
constexpr int SM_ONES = SM_TILES + MAX_ROWS * 4;
constexpr int SM_BAR = SM_ONES + 128;
constexpr int BAR_X = SM_BAR;
constexpr int BAR_A = BAR_X + NSLOT * 4 * 8;
constexpr int BAR_E = BAR_A + NSLOT * 4 * 8;
constexpr int BAR_PIN = BAR_E + NSLOT * 4 * 8;
constexpr int BAR_W = BAR_PIN + 8;
constexpr int BAR_F = BAR_W + 6 * 8;
constexpr int BAR_R = BAR_F + 8;
constexpr int SM_TOTAL = BAR_R + 16 * 8;
constexpr int SM_FILTER = SM_RING + (NSLOT - 1) * SLOT_BYTES + 9 * 128;
constexpr int SM_SQ = SM_W2;
constexpr int SQ_ROW = 128 * 16, SQ_WG = 6 * SQ_ROW;
static_assert(SM_ONES % 16 == 0 && SM_TOTAL <= 232448, "shared memory budget");

constexpr float KZ = 0.3292034911525734f;
constexpr uint32_t GELU_C2 = 0x40d940d9u;
constexpr float INV_2KZ = 0.5f / KZ;
constexpr unsigned SPIN_LIMIT = 1u << 19;

constexpr int MAX_CTAS = 255;
constexpr int W2_GROUPS = EX / 8;
#define K_LENT 3
constexpr int LENT = K_LENT, MAX_LENDERS = MAX_CTAS / (8 * LENT + 1);
struct Scratch {
    uint32_t w2h[EX * CH / 2];
    float w2max[EX];
    float bias[CH + 32];
    unsigned long long sums[EX / 4][32];
    __device__ __forceinline__ unsigned long long* sum(int e) { return &sums[e >> 2][e & 3]; }
    uint4 lent[MAX_LENDERS * LENT * 8 * 4 * 3 * 32];
    unsigned launch, pad0[31], early, pad1[31], prep, pad2[31], lent_out, pad3[31];
};
__device__ __align__(128) Scratch g_scratch;

#define PROF(k)

__device__ __forceinline__ uint32_t smem_u32(const void* p) { return (uint32_t)__cvta_generic_to_shared(p); }
__device__ __forceinline__ void mbar_init(uint32_t bar, uint32_t cnt) {
    asm volatile("mbarrier.init.shared::cta.b64 [%0], %1;" ::"r"(bar), "r"(cnt) : "memory");
}
__device__ __forceinline__ void mbar_arrive(uint32_t bar) {
    asm volatile("mbarrier.arrive.shared::cta.b64 _, [%0];" ::"r"(bar) : "memory");
}
__device__ __forceinline__ void mbar_expect_tx(uint32_t bar, uint32_t bytes) {
    asm volatile("mbarrier.arrive.expect_tx.shared::cta.b64 _, [%0], %1;" ::"r"(bar), "r"(bytes) : "memory");
}
__device__ __forceinline__ bool mbar_try(uint32_t bar, uint32_t par) {
    uint32_t ok;
    asm volatile("{\n.reg .pred p;\nmbarrier.try_wait.parity.shared::cta.b64 p, [%1], %2;\nselp.u32 %0, 1, 0, p;\n}\n"
                 : "=r"(ok) : "r"(bar), "r"(par) : "memory");
    return ok != 0;
}
__device__ __forceinline__ void mbar_wait(uint32_t bar, uint32_t par) {
    unsigned n = 0;
    while (!mbar_try(bar, par)) {
        if (++n > SPIN_LIMIT) __trap();
    }
}
__device__ __forceinline__ bool mbar_test(uint32_t bar, uint32_t par) {
    uint32_t ok;
    asm volatile("{\n.reg .pred p;\nmbarrier.test_wait.parity.shared::cta.b64 p, [%1], %2;\nselp.u32 %0, 1, 0, p;\n}\n"
                 : "=r"(ok) : "r"(bar), "r"(par) : "memory");
    return ok != 0;
}
__device__ __forceinline__ bool elect_one() {
    uint32_t ok;
    asm volatile("{\n.reg .pred p;\nelect.sync _|p, 0xffffffff;\nselp.u32 %0, 1, 0, p;\n}\n" : "=r"(ok));
    return ok != 0;
}
__device__ __forceinline__ uint32_t opaque(uint32_t v) { return __shfl_sync(~0u, v, threadIdx.x & 31); }
__device__ __forceinline__ void named_bar(int id, int n) { asm volatile("bar.sync %0, %1;" ::"r"(id), "r"(n) : "memory"); }
__device__ __forceinline__ void named_arrive(int id, int n) { asm volatile("bar.arrive %0, %1;" ::"r"(id), "r"(n) : "memory"); }
__device__ __forceinline__ void fence_async() { asm volatile("fence.proxy.async.shared::cta;" ::: "memory"); }
__device__ __forceinline__ uint64_t evict_first() {
    uint64_t p;
    asm("createpolicy.fractional.L2::evict_first.b64 %0, 1.0;" : "=l"(p));
    return p;
}
__device__ __forceinline__ void tma_row(uint32_t dst, const CUtensorMap* tm, uint32_t bar, int x, int y) {
    asm volatile("cp.async.bulk.tensor.3d.shared::cluster.global.mbarrier::complete_tx::bytes.L2::cache_hint [%0], [%1, {%3, %4, %5}], [%2], %6;"
                 ::"r"(dst), "l"(tm), "r"(bar), "r"(0), "r"(x), "r"(y), "l"(evict_first()) : "memory");
}
__device__ __forceinline__ void bulk_load_stream(uint32_t dst, const void* src, uint32_t bytes, uint32_t bar) {
    asm volatile("cp.async.bulk.shared::cluster.global.mbarrier::complete_tx::bytes.L2::cache_hint [%0], [%1], %2, [%3], %4;"
                 ::"r"(dst), "l"(src), "r"(bytes), "r"(bar), "l"(evict_first()) : "memory");
}
__device__ __forceinline__ void prefetch_l2(const void* src, uint32_t bytes) {
    asm volatile("cp.async.bulk.prefetch.L2.global [%0], %1;" ::"l"(src), "r"(bytes) : "memory");
}
__device__ __forceinline__ void tma_2d(uint32_t dst, const CUtensorMap* tm, uint32_t bar, int x, int y) {
    asm volatile("cp.async.bulk.tensor.2d.shared::cluster.global.mbarrier::complete_tx::bytes [%0], [%1, {%3, %4}], [%2];"
                 ::"r"(dst), "l"(tm), "r"(bar), "r"(x), "r"(y) : "memory");
}
__device__ __forceinline__ void bulk_load(uint32_t dst, const void* src, uint32_t bytes, uint32_t bar) {
    asm volatile("cp.async.bulk.shared::cluster.global.mbarrier::complete_tx::bytes [%0], [%1], %2, [%3];"
                 ::"r"(dst), "l"(src), "r"(bytes), "r"(bar) : "memory");
}
__device__ __forceinline__ void wg_fence() { asm volatile("wgmma.fence.sync.aligned;" ::: "memory"); }
__device__ __forceinline__ void wg_commit() { asm volatile("wgmma.commit_group.sync.aligned;" ::: "memory"); }
template <int N> __device__ __forceinline__ void wg_wait() { asm volatile("wgmma.wait_group.sync.aligned %0;" ::"n"(N) : "memory"); }
template <int N> __device__ __forceinline__ void pin(uint32_t (&d)[N]) {
#pragma unroll
    for (int q = 0; q < N; q++) asm volatile("" : "+r"(d[q])::"memory");
}
__device__ __forceinline__ void stg128(void* p, const uint32_t (&v)[4]) {
    asm volatile("st.global.v4.u32 [%0], {%1, %2, %3, %4};" ::"l"(p), "r"(v[0]), "r"(v[1]), "r"(v[2]), "r"(v[3]) : "memory");
}
__device__ __forceinline__ void ldg128(uint32_t (&v)[4], const void* p) {
    asm volatile("ld.global.L1::no_allocate.v4.u32 {%0, %1, %2, %3}, [%4];" : "=r"(v[0]), "=r"(v[1]), "=r"(v[2]), "=r"(v[3]) : "l"(p) : "memory");
}
__device__ __forceinline__ void ldg128_if(bool on, uint32_t (&v)[4], const void* p) {
    asm volatile("{\n.reg .pred p;\nsetp.ne.b32 p, %5, 0;\n@p ld.global.L1::no_allocate.v4.u32 {%0, %1, %2, %3}, [%4];\n}\n"
                 : "+r"(v[0]), "+r"(v[1]), "+r"(v[2]), "+r"(v[3]) : "l"(p), "r"((int)on) : "memory");
}
__device__ __forceinline__ uint4 ldg128_ordered(const void* p) {
    uint4 v;
    asm volatile("ld.global.nc.v4.u32 {%0, %1, %2, %3}, [%4];" : "=r"(v.x), "=r"(v.y), "=r"(v.z), "=r"(v.w) : "l"(p) : "memory");
    return v;
}
__host__ __device__ constexpr uint64_t make_desc(uint32_t addr, uint32_t lbo, uint32_t sbo) {
    return (uint64_t)((addr & 0x3FFFF) >> 4) | ((uint64_t)(lbo >> 4) << 16) | ((uint64_t)(sbo >> 4) << 32);
}
__device__ __forceinline__ void wgmma(uint32_t (&d)[12], uint32_t a0, uint32_t a1, uint32_t a2, uint32_t a3, uint64_t db, int acc) {
    asm volatile("{\n.reg .pred p;\nsetp.ne.b32 p, %17, 0;\n"
                 "wgmma.mma_async.sync.aligned.m64n48k16.f16.f16.f16 "
                 "{%0, %1, %2, %3, %4, %5, %6, %7, %8, %9, %10, %11}, "
                 "{%12, %13, %14, %15}, %16, p, 1, 1, 0;\n}\n"
                 : "+r"(d[0]), "+r"(d[1]), "+r"(d[2]), "+r"(d[3]), "+r"(d[4]), "+r"(d[5]), "+r"(d[6]), "+r"(d[7]), "+r"(d[8]), "+r"(d[9]), "+r"(d[10]), "+r"(d[11])
                 : "r"(a0), "r"(a1), "r"(a2), "r"(a3), "l"(db), "r"(acc));
}
__device__ __forceinline__ void wgmma(uint32_t (&d)[24], uint32_t a0, uint32_t a1, uint32_t a2, uint32_t a3, uint64_t db, int acc) {
    asm volatile("{\n.reg .pred p;\nsetp.ne.b32 p, %29, 0;\n"
                 "wgmma.mma_async.sync.aligned.m64n96k16.f16.f16.f16 "
                 "{%0, %1, %2, %3, %4, %5, %6, %7, %8, %9, %10, %11, %12, %13, %14, %15, %16, %17, %18, %19, %20, %21, %22, %23}, "
                 "{%24, %25, %26, %27}, %28, p, 1, 1, 0;\n}\n"
                 : "+r"(d[0]), "+r"(d[1]), "+r"(d[2]), "+r"(d[3]), "+r"(d[4]), "+r"(d[5]), "+r"(d[6]), "+r"(d[7]), "+r"(d[8]), "+r"(d[9]), "+r"(d[10]), "+r"(d[11]), "+r"(d[12]), "+r"(d[13]), "+r"(d[14]), "+r"(d[15]), "+r"(d[16]), "+r"(d[17]), "+r"(d[18]), "+r"(d[19]), "+r"(d[20]), "+r"(d[21]), "+r"(d[22]), "+r"(d[23])
                 : "r"(a0), "r"(a1), "r"(a2), "r"(a3), "l"(db), "r"(acc));
}
template <int ACC>
__device__ __forceinline__ void wgmma_rowsum(float (&d)[4], const uint32_t (&a)[4], uint64_t ones) {
    asm volatile("{\n.reg .pred p;\nsetp.ne.b32 p, %9, 0;\n"
                 "wgmma.mma_async.sync.aligned.m64n8k16.f32.bf16.bf16 {%0, %1, %2, %3}, {%4, %5, %6, %7}, %8, p, 1, 1, 0;\n}\n"
                 : "+f"(d[0]), "+f"(d[1]), "+f"(d[2]), "+f"(d[3])
                 : "r"(a[0]), "r"(a[1]), "r"(a[2]), "r"(a[3]), "l"(ones), "n"(ACC));
}
__device__ __forceinline__ void ldsm4(uint32_t (&r)[4], uint32_t addr) {
    asm volatile("ldmatrix.sync.aligned.m8n8.x4.shared.b16 {%0, %1, %2, %3}, [%4];"
                 : "=r"(r[0]), "=r"(r[1]), "=r"(r[2]), "=r"(r[3]) : "r"(addr) : "memory");
}
__device__ __forceinline__ void ldsm4_t(uint32_t (&r)[4], uint32_t addr) {
    asm volatile("ldmatrix.sync.aligned.m8n8.x4.trans.shared.b16 {%0, %1, %2, %3}, [%4];"
                 : "=r"(r[0]), "=r"(r[1]), "=r"(r[2]), "=r"(r[3]) : "r"(addr) : "memory");
}
__device__ __forceinline__ void stsm4(uint32_t addr, uint32_t a, uint32_t b, uint32_t c, uint32_t d) {
    asm volatile("stmatrix.sync.aligned.m8n8.x4.shared.b16 [%0], {%1, %2, %3, %4};"
                 ::"r"(addr), "r"(a), "r"(b), "r"(c), "r"(d) : "memory");
}
__device__ __forceinline__ uint32_t transpose8x8(uint32_t v) {
    uint32_t d; asm volatile("movmatrix.sync.aligned.m8n8.trans.b16 %0, %1;" : "=r"(d) : "r"(v)); return d;
}
__device__ __forceinline__ void spin_until(const unsigned* counter, unsigned target) {
    unsigned n = 0, c;
    do {
        asm volatile("ld.acquire.gpu.global.u32 %0, [%1];" : "=r"(c) : "l"(counter) : "memory");
        if (++n > SPIN_LIMIT) __trap();
    } while ((int)(c - target) < 0);
}
__device__ __forceinline__ void signal(unsigned* counter) {
    __syncwarp();
    if (elect_one()) asm volatile("red.release.gpu.global.add.u32 [%0], 1;" ::"l"(counter) : "memory");
    __syncwarp();
}
__device__ __forceinline__ void lds128(uint32_t& a, uint32_t& b, uint32_t& c, uint32_t& d, uint32_t addr) {
    asm volatile("ld.shared.v4.u32 {%0, %1, %2, %3}, [%4];" : "=r"(a), "=r"(b), "=r"(c), "=r"(d) : "r"(addr) : "memory");
}
__device__ __forceinline__ void lds64(uint32_t& a, uint32_t& b, uint32_t addr) {
    asm volatile("ld.shared.v2.u32 {%0, %1}, [%2];" : "=r"(a), "=r"(b) : "r"(addr) : "memory");
}
__device__ __forceinline__ void lds32(uint32_t& a, uint32_t addr) {
    asm volatile("ld.shared.u32 %0, [%1];" : "=r"(a) : "r"(addr) : "memory");
}
__device__ __forceinline__ int ldsi(uint32_t addr) {
    uint32_t v;
    lds32(v, addr);
    return (int)v;
}
__device__ __forceinline__ float ldsf(uint32_t addr) {
    uint32_t v;
    lds32(v, addr);
    return __uint_as_float(v);
}
__device__ __forceinline__ void sts32(uint32_t addr, uint32_t a) {
    asm volatile("st.shared.u32 [%0], %1;" ::"r"(addr), "r"(a) : "memory");
}
__device__ __forceinline__ void sts128(uint32_t addr, uint32_t a, uint32_t b, uint32_t c, uint32_t d) {
    asm volatile("st.shared.v4.u32 [%0], {%1, %2, %3, %4};" ::"r"(addr), "r"(a), "r"(b), "r"(c), "r"(d) : "memory");
}
__device__ __forceinline__ void sts64(uint32_t addr, uint32_t a, uint32_t b) {
    asm volatile("st.shared.v2.u32 [%0], {%1, %2};" ::"r"(addr), "r"(a), "r"(b) : "memory");
}
__device__ __forceinline__ void anchor(uint32_t addr, uint32_t a, uint32_t b, uint32_t c, uint32_t d) {
    asm volatile("{\n.reg .pred p;\nsetp.eq.b32 p, %0, 0;\n@p st.shared.v4.u32 [%0], {%1, %2, %3, %4};\n}\n"
                 ::"r"(addr), "r"(a), "r"(b), "r"(c), "r"(d) : "memory");
}
__device__ __forceinline__ uint32_t bf_fma(uint32_t a, uint32_t b, uint32_t c) {
    uint32_t d; asm("fma.rn.bf16x2 %0, %1, %2, %3;" : "=r"(d) : "r"(a), "r"(b), "r"(c)); return d;
}
__device__ __forceinline__ uint32_t bf_mul(uint32_t a, uint32_t b) {
    uint32_t d; asm("mul.rn.bf16x2 %0, %1, %2;" : "=r"(d) : "r"(a), "r"(b)); return d;
}
__device__ __forceinline__ uint32_t bf_absmax(uint32_t a, uint32_t b) {
    uint32_t d; asm("max.xorsign.abs.bf16x2 %0, %1, %2;" : "=r"(d) : "r"(a), "r"(b)); return d;
}
__device__ __forceinline__ uint32_t h_fma(uint32_t a, uint32_t b, uint32_t c) {
    uint32_t d; asm("fma.rn.f16x2 %0, %1, %2, %3;" : "=r"(d) : "r"(a), "r"(b), "r"(c)); return d;
}
__device__ __forceinline__ uint32_t h_mul(uint32_t a, uint32_t b) {
    uint32_t d; asm("mul.rn.f16x2 %0, %1, %2;" : "=r"(d) : "r"(a), "r"(b)); return d;
}
__device__ __forceinline__ uint32_t h_round8(uint32_t v) { return (v + 0x00040004u) & 0xfff8fff8u; }
__device__ __forceinline__ uint32_t h_tanh(uint32_t a) {
    uint32_t d; asm("tanh.approx.f16x2 %0, %1;" : "=r"(d) : "r"(a)); return d;
}
__device__ __forceinline__ uint32_t pack_h2(float lo, float hi) {
    uint32_t d; asm("cvt.rn.f16x2.f32 %0, %1, %2;" : "=r"(d) : "f"(hi), "f"(lo)); return d;
}
__device__ __forceinline__ uint32_t pack_bf2(float lo, float hi) {
    uint32_t d; asm("cvt.rn.bf16x2.f32 %0, %1, %2;" : "=r"(d) : "f"(hi), "f"(lo)); return d;
}
__device__ __forceinline__ float bf_lo(uint32_t v) { return __uint_as_float(v << 16); }
__device__ __forceinline__ float bf_hi(uint32_t v) { return __uint_as_float(v & 0xffff0000u); }
__device__ __forceinline__ float h_lo(uint32_t v) { return __low2float(*reinterpret_cast<__half2*>(&v)); }
__device__ __forceinline__ float h_hi(uint32_t v) { return __high2float(*reinterpret_cast<__half2*>(&v)); }
__device__ __forceinline__ float warp_absmax(uint32_t v) {
    return __uint_as_float(__reduce_max_sync(~0u, max((v & 0x7fffu) << 16, v & 0x7fff0000u)));
}
__device__ __forceinline__ uint32_t gelu2(uint32_t z) {
    uint32_t p = h_fma(z, z, GELU_C2);
    uint32_t t = h_tanh(h_mul(z, p));
    return h_fma(z, t, z);
}
__device__ __forceinline__ float grn_norm(float ss) {
    float r;
    asm("sqrt.approx.f32 %0, %1;" : "=f"(r) : "f"(fmaf(ss, INV_2KZ * INV_2KZ, 1e-6f)));
    return r;
}
__device__ __forceinline__ float pow2i(int e) { return __uint_as_float((uint32_t)(e + 127) << 23); }
__device__ __forceinline__ int ilog2f(float v) {
    int e = (int)((__float_as_uint(v) >> 23) & 0xff) - 127;
    return max(-100, min(100, e));
}

__device__ __forceinline__ int square_exp(float w1max) {
    const int e = w1max > 0.f ? 4 - ilog2f(2.f * KZ * 96.f * w1max) : 0;
    return (e >= 0 && e <= 6) ? 0 : max(-14, min(e, 14));
}
__device__ __forceinline__ int sum_exp(float w1max) {
    return w1max > 0.f ? max(-90, min(90, 33 - 2 * ilog2f(2.f * KZ * 96.f * w1max))) : 0;
}
__device__ __forceinline__ float row_scale(float m) { return m > 0.f ? pow2i(2 - ilog2f(m)) : 1.f; }

struct Split {
    int per_cta, extra, period, inv_period, lenders;
    __host__ __device__ __forceinline__ int longer_before(int cta) const {
        const int n = (cta + period / 2) * inv_period >> 16;
        return n < extra ? n : extra;
    }
};
struct Work {
    int tA, tB, nA, nB, dir, rows, lent, index;
    __device__ __forceinline__ int tile(int j) const { return j < nA ? tA + dir * j : tB + dir * (j - nA); }
};
__host__ __device__ __forceinline__ Work get_work(int cta, const Split& sp) {
    Work w;
    const int before = sp.longer_before(cta), longer = sp.longer_before(cta + 1) - before;
    w.lent = longer && sp.lenders ? LENT : 0;
    w.index = longer ? before : cta - before;
    const int t0 = cta * sp.per_cta + before, t1 = t0 + sp.per_cta + longer;
    const int tm = t1 < (t0 | 511) + 1 ? t1 : (t0 | 511) + 1;
    const bool swap = t1 > tm && t1 - tm < tm - t0, down = cta & 1;
    w.nA = swap ? t1 - tm : tm - t0;
    w.nB = t1 - t0 - w.nA;
    w.tA = down ? (swap ? tm : t0) : (swap ? t1 : tm) - 1;
    w.tB = down ? (swap ? t0 : tm) : (swap ? tm : t1) - 1;
    w.dir = down ? 1 : -1;
    w.rows = w.nA + 2 + (w.nB ? w.nB + 2 : 0);
    return w;
}
__device__ __forceinline__ int row_code(const Work& w, int i) {
    const bool in_a = i < w.nA + 2;
    const int t = in_a ? w.tA : w.tB;
    return ((t & 511) + w.dir * ((in_a ? i : i - (w.nA + 2)) - 1)) << 16 | (t >> 9) * TILE_W;
}
__device__ __forceinline__ uint32_t tile_offset(int tile) { return ((tile & 511) * IMG_W + (tile >> 9) * TILE_W) * (CH * 2); }
__device__ __forceinline__ int tile_order(int j, int n) {
    const int olds = (j / ORDER_P) * ORDER_Q + max(0, j % ORDER_P - (ORDER_P - ORDER_Q));
    return (j % ORDER_P >= ORDER_P - ORDER_Q) ? olds : n - 1 - (j - olds);
}
__device__ __forceinline__ void issue_region(const CUtensorMap* tm, uint32_t dst, uint32_t bar, int warp, int code) {
    mbar_expect_tx(bar, REGION_BYTES);
    tma_row(dst, tm, bar, (code & 0xffff) + (16 * warp - 1), code >> 16);
}

template <class Event>
__device__ __forceinline__ void conv_producer(const Work& wk, const CUtensorMap* tm, uint32_t sb, int warp, Event event) {
    const int lane = threadIdx.x & 31;
    const int j = lane & 15, grp = lane >> 4;
    const uint32_t reg0 = sb + SM_RING + warp * REGION_BYTES;
    const uint32_t bars = sb + SM_BAR + warp * 8;
    if (lane >= PREFETCH_ROWS && lane < 3 * NSLOT) mbar_init(bars + lane * 32, 1);
    if (lane >= 28) mbar_init(sb + BAR_R + ((lane - 28) * 4 + warp) * 8, 1);
    if (lane == 0 && warp == 0) mbar_init(sb + BAR_PIN, 1);
    if (warp * 32 + lane < MAX_ROWS) {
        sts32(sb + SM_ROWS + (warp * 32 + lane) * 4, row_code(wk, warp * 32 + lane));
        const int i = warp * 32 + lane, before = min(i / 5, wk.lent);
        const bool back = i % 5 == 0 && i > 0 && i / 5 <= wk.lent;
        sts32(sb + SM_TILES + i * 4, back ? tile_offset(wk.tile(before - 1)) | before
                                          : tile_offset(wk.tile(wk.lent + tile_order(i - before, wk.nA + wk.nB - NCONS - wk.lent))));
    }
    const uint32_t ld64 = opaque(reg0 + grp * 8 * 192 + j * 8), ld32 = opaque(reg0 + grp * 8 * 192 + 128 + j * 4);
    const uint32_t st64 = opaque(reg0 + grp * A_SBO + (j >> 1) * A_LBO + (j & 1) * 8);
    const uint32_t st32 = opaque(reg0 + grp * A_SBO + (8 + (j >> 2)) * A_LBO + (j & 3) * 4);
    fence_async();
    named_bar(0, NTHREADS);
    uint32_t w[3][3][3];
    mbar_wait(sb + BAR_F, 0);
#pragma unroll
    for (int tap = 0; tap < 9; tap++) {
        const uint32_t p = sb + SM_FILTER + (3 + wk.dir * 3 * (tap / 3 - 1) + tap % 3) * (CH * 2);
        lds64(w[tap / 3][tap % 3][0], w[tap / 3][tap % 3][1], p + 8 * j);
        lds32(w[tap / 3][tap % 3][2], p + 128 + 4 * j);
    }
#pragma unroll
    for (int tap = 0; tap < 9; tap++) sts64(reg0 + (NSLOT - 1) * SLOT_BYTES + tap * 128 + j * 8, w[tap / 3][tap % 3][1], w[tap / 3][tap % 3][0]);
#pragma unroll
    for (int tap = 0; tap < 9; tap++) lds64(w[tap / 3][tap % 3][1], w[tap / 3][tap % 3][0], reg0 + (NSLOT - 1) * SLOT_BYTES + tap * 128 + j * 8);
    fence_async();
    named_bar(1, 128);
    static_assert(2 * PREFETCH_ROWS == NSLOT, "prefetch slot arithmetic");
    uint32_t so = 0, bo = 0, par = 0, tbl = sb + SM_ROWS + PREFETCH_ROWS * 4;
    const uint32_t tbl_end = sb + SM_ROWS + wk.rows * 4;
    auto next_row = [&](int code, bool e_ready) {
        const bool wrap = bo == (NSLOT - 1) * 32, low = bo < PREFETCH_ROWS * 32;
        if (tbl < tbl_end) {
            const uint32_t pbo = low ? bo + PREFETCH_ROWS * 32 : bo - PREFETCH_ROWS * 32;
            if (!e_ready) mbar_wait(bars + (BAR_E - SM_BAR) + pbo, par ^ low);
            code = __shfl_sync(~0u, code, 0);
            if (elect_one()) issue_region(tm, reg0 + (low ? so + PREFETCH_ROWS * SLOT_BYTES : so - PREFETCH_ROWS * SLOT_BYTES), bars + pbo, warp, code);
        }
        tbl += 4;
        so = wrap ? 0 : so + SLOT_BYTES;
        bo = wrap ? 0 : bo + 32;
        par ^= wrap;
    };
    int n = wk.nA;
#pragma unroll 1
    for (int seg = 0; seg < 2 && n > 0; seg++, n = wk.nB) {
        uint32_t accB[8][3], accC[8][3];
        {
            const uint32_t so0 = so, bo0 = bo;
            uint32_t so1, bo1;
#pragma unroll 1
            for (int r = 0; r < 2; r++) {
                uint32_t code;
                lds32(code, tbl);
                mbar_wait(bars + bo, par);
                so1 = so;
                bo1 = bo;
                next_row(code, false);
            }
#pragma unroll
            for (int p = 0; p < 10; p++) {
                uint32_t u[3], v[3];
                lds64(u[0], u[1], so0 + ld64 + p * 192);
                lds32(u[2], so0 + ld32 + p * 192);
                lds64(v[0], v[1], so1 + ld64 + p * 192);
                lds32(v[2], so1 + ld32 + p * 192);
#pragma unroll
                for (int dx = 0; dx < 3; dx++) {
                    const int o = p - dx;
                    if (o < 0 || o > 7) continue;
#pragma unroll
                    for (int q = 0; q < 3; q++) {
                        accB[o][q] = bf_fma(v[q], w[1][dx][q], dx == 0 ? bf_mul(u[q], w[0][dx][q]) : bf_fma(u[q], w[0][dx][q], accB[o][q]));
                        accC[o][q] = dx == 0 ? bf_mul(v[q], w[0][dx][q]) : bf_fma(v[q], w[0][dx][q], accC[o][q]);
                    }
                }
            }
            anchor(ld64, accB[7][0], accB[7][1], accB[7][2], 0);
            __syncwarp();
            if (elect_one()) {
                mbar_arrive(bars + (BAR_A - SM_BAR) + bo0);
                mbar_arrive(bars + (BAR_E - SM_BAR) + bo0);
                mbar_arrive(bars + (BAR_A - SM_BAR) + bo1);
                mbar_arrive(bars + (BAR_E - SM_BAR) + bo1);
            }
        }
        bool x_ready = false;
#pragma unroll 1
        for (int k = 0; k < n; k++) {
            if (!x_ready) mbar_wait(bars + bo, par);
            uint32_t out[8][3];
            int code;
            bool e_ready;
#pragma unroll
            for (int p = 0; p < 10; p++) {
                uint32_t xv[3];
                lds64(xv[0], xv[1], so + ld64 + p * 192);
                lds32(xv[2], so + ld32 + p * 192);
                if (p == 9) {
                    const bool wrap = bo == (NSLOT - 1) * 32, low = bo < PREFETCH_ROWS * 32;
                    asm volatile("ld.shared.u32 %0, [%1];" : "=r"(code) : "r"(tbl));
                    e_ready = mbar_test(bars + (BAR_E - SM_BAR) + (low ? bo + PREFETCH_ROWS * 32 : bo - PREFETCH_ROWS * 32), par ^ low);
                    x_ready = mbar_test(bars + (wrap ? 0 : bo + 32), par ^ wrap);
                }
#pragma unroll
                for (int dx = 0; dx < 3; dx++) {
                    const int o = p - dx;
                    if (o < 0 || o > 7) continue;
#pragma unroll
                    for (int q = 0; q < 3; q++) {
                        out[o][q] = bf_fma(xv[q], w[2][dx][q], dx == 0 ? accB[o][q] : out[o][q]);
                        accB[o][q] = bf_fma(xv[q], w[1][dx][q], dx == 0 ? accC[o][q] : accB[o][q]);
                        accC[o][q] = dx == 0 ? bf_mul(xv[q], w[0][dx][q]) : bf_fma(xv[q], w[0][dx][q], accC[o][q]);
                    }
                }
            }
            __syncwarp();
#pragma unroll
            for (int o = 0; o < 8; o++) {
                sts64(so + st64 + o * 16, out[o][0], out[o][1]);
                sts32(so + st32 + o * 16, out[o][2]);
            }
            __syncwarp();
            if (elect_one()) mbar_arrive(bars + (BAR_A - SM_BAR) + bo);
            if (((tbl_end - tbl) & ~32u) == 4) event(tbl_end - tbl == 4);
            next_row(code, e_ready);
        }
    }
}

template <bool SCALED, int K0 = 0, int K1 = 3>
__device__ __forceinline__ void gelu_sq(uint32_t (&d)[24], uint32_t (&keep)[24], uint32_t sq_addr, uint32_t scale2) {
    pin(d);
#pragma unroll
    for (int k = K0; k < K1; k++) {
        uint32_t hs[4];
        lds128(hs[0], hs[1], hs[2], hs[3], sq_addr + k * SQ_ROW);
#pragma unroll
        for (int q = 0; q < 4; q++) {
            uint32_t g0 = gelu2(d[8 * k + 2 * q]), g1 = gelu2(d[8 * k + 2 * q + 1]);
            keep[8 * k + 2 * q] = g0;
            keep[8 * k + 2 * q + 1] = g1;
            if (SCALED) { g0 = h_mul(g0, scale2); g1 = h_mul(g1, scale2); }
            hs[q] = h_fma(g1, g1, h_fma(g0, g0, hs[q]));
        }
        sts128(sq_addr + k * SQ_ROW, hs[0], hs[1], hs[2], hs[3]);
    }
}
__device__ __forceinline__ void gelu_sq_reg(uint32_t (&d)[24], uint32_t (&hs)[12]) {
    pin(d);
#pragma unroll
    for (int q = 0; q < 12; q++) {
        const uint32_t g0 = gelu2(d[2 * q]), g1 = gelu2(d[2 * q + 1]);
        hs[q] = h_fma(g1, g1, h_fma(g0, g0, hs[q]));
    }
}
__device__ __forceinline__ void gelu_to(uint32_t (&g)[12], uint32_t (&d)[12]) {
    pin(d);
#pragma unroll
    for (int q = 0; q < 12; q++) g[q] = gelu2(d[q]);
    pin(g);
}
__device__ __forceinline__ void load_tile(uint32_t (&raw)[6][4], uint32_t addr) {
#pragma unroll
    for (int s = 0; s < 6; s++) ldsm4(raw[s], addr + s * 2 * A_LBO);
}
__device__ __forceinline__ uint2 ln_stats(const uint32_t (&raw)[6][4], uint64_t ones) {
    constexpr int NS = 6 / K_CHAIN;
    uint32_t sq[NS][4];
#pragma unroll
    for (int s = 0; s < 6; s++)
#pragma unroll
        for (int q = 0; q < 4; q++) sq[s % NS][q] = s < NS ? bf_mul(raw[s][q], raw[s][q]) : bf_fma(raw[s][q], raw[s][q], sq[s % NS][q]);
    float sum[4], ssq[4];
    wg_fence();
    wgmma_rowsum<0>(sum, raw[0], ones);
#pragma unroll
    for (int s = 1; s < 6; s++) wgmma_rowsum<1>(sum, raw[s], ones);
    wgmma_rowsum<0>(ssq, sq[0], ones);
#pragma unroll
    for (int s = 1; s < NS; s++) wgmma_rowsum<1>(ssq, sq[s], ones);
    wg_commit();
    wg_wait<0>();
    uint32_t st[2];
#pragma unroll
    for (int h = 0; h < 2; h++) {
        asm volatile("" : "+f"(sum[2 * h]), "+f"(ssq[2 * h])::"memory");
        const float mean = sum[2 * h] * (1.f / CH);
        const float var = fmaxf(fmaf(ssq[2 * h], 1.f / CH, -mean * mean), 0.f);
        float rstd;
        asm("rsqrt.approx.ftz.f32 %0, %1;" : "=f"(rstd) : "f"(var + 1e-5f));
        rstd = bf_lo(pack_bf2(rstd * (K_CVT == 0 ? KZ : KZ * 0x1p-112f), 0.f));
        st[h] = pack_bf2(rstd, -mean * rstd);
    }
    return make_uint2(st[0], st[1]);
}
__device__ __forceinline__ void ln_apply(uint32_t (&a)[6][4], const uint2& st) {
    const uint32_t sc[2] = {__byte_perm(st.x, 0, 0x1010), __byte_perm(st.y, 0, 0x1010)};
    const uint32_t sh[2] = {__byte_perm(st.x, 0, 0x3232), __byte_perm(st.y, 0, 0x3232)};
#pragma unroll
    for (int s = 0; s < 6; s++)
#pragma unroll
        for (int q = 0; q < 4; q++) {
            const uint32_t v = bf_fma(a[s][q], sc[q & 1], sh[q & 1]);
            a[s][q] = K_CVT == 0 ? pack_h2(bf_lo(v), bf_hi(v)) : (v & 0x7fff7fffu) * 7u + v;
        }
}
struct Cursor {
    int slot;
    uint32_t par;
    __device__ __forceinline__ void advance(int n) {
        slot += n;
        if (slot >= NSLOT) { slot -= NSLOT; par ^= 1; }
    }
};
struct Descs {
    uint64_t w1[8][6];
    uint64_t w2[24];
    uint64_t ones;
};
template <int E0, int N>
__device__ __forceinline__ void gemm1_chunk(uint32_t (&d)[N], const uint32_t (&a)[6][4], const Descs& ds, int zero) {
#pragma unroll
    for (int s = 0; s < 6; s++) wgmma(d, a[s][0], a[s][1], a[s][2], a[s][3], ds.w1[E0 / 48][s], s ? 1 : zero);
}
template <int E0, int N>
__device__ __forceinline__ void gemm2_chunk(uint32_t (&acc)[24], const uint32_t (&g)[N], const Descs& ds) {
#pragma unroll
    for (int s = 0; s < N / 4; s++) wgmma(acc, g[4 * s], g[4 * s + 1], g[4 * s + 2], g[4 * s + 3], ds.w2[E0 / 16 + s], 1);
}

__global__ void __launch_bounds__(NTHREADS, 1)
block_kernel(const __grid_constant__ CUtensorMap tmap, const __grid_constant__ CUtensorMap tmap_w1,
             const __nv_bfloat16* __restrict__ x, const __nv_bfloat16* __restrict__ dw, const __nv_bfloat16* __restrict__ w2,
             const __nv_bfloat16* __restrict__ gamma, const __nv_bfloat16* __restrict__ beta, __nv_bfloat16* __restrict__ out,
             Scratch* __restrict__ sc, const __grid_constant__ Descs ds,
             const int zero, const __grid_constant__ Split sp) {
    extern __shared__ __align__(1024) uint8_t smem[];
    constexpr uint32_t sb = SB;
    const int tid = threadIdx.x;
    const Work wk = get_work(blockIdx.x, sp);
    constexpr uint32_t s_red = sb + SM_RED;
    if (smem_u32(smem) != SB) __trap();

    PROF(0);
    const int warp_id = __shfl_sync(~0u, tid >> 5, 0);
    const int cw = warp_id - 4, wgi = cw >> 2, w4 = warp_id & 3;
    if (elect_one()) {
        if (warp_id < 8) {
            mbar_init(sb + BAR_X + warp_id * 8, 1);
            if (warp_id < 4) mbar_init(sb + BAR_X + (warp_id + 8) * 8, 1);
            fence_async();
#pragma unroll 1
            for (int r = warp_id >> 2; r < PREFETCH_ROWS; r += 2)
                issue_region(&tmap, sb + SM_RING + r * SLOT_BYTES + w4 * REGION_BYTES, sb + BAR_X + (r * 4 + w4) * 8, w4,
                             ((wk.tA & 511) + wk.dir * (r - 1)) << 16 | (wk.tA >> 9) * TILE_W);
        } else if (warp_id < 15) {
            const int b = warp_id - 8;
            mbar_init(sb + BAR_W + b * 8, 1);
            fence_async();
            mbar_expect_tx(sb + BAR_W + b * 8, b < 6 ? 64 * CH * 2 : 9 * CH * 2);
            if (b < 6) tma_2d(sb + SM_W2 + b * (64 * CH * 2), &tmap_w1, sb + BAR_W + b * 8, 64 * b, 0);
            else bulk_load(sb + SM_FILTER, dw, 9 * CH * 2, sb + BAR_F);
        }
    }
    __syncwarp();
    const int ntiles = wk.nA + wk.nB;
    const int wg = warp_id >> 2;
    int first = wg;
    uint32_t a[6][4], acc[24], tile_off, next_off, stage, inv_rho2 = 0, rpar = 0, bias_addr, lane16, lane_off;
    auto set_lane = [&](uint32_t lane) {
        bias_addr = sb + SM_BIASH + (lane & 3) * 96;
        lane16 = lane * 16;
        lane_off = ((lane >> 2) * CH + 8 * (lane & 3)) * 2;
    };
    const uint32_t bar_r = sb + BAR_R + warp_id * 8;
    auto load_bias = [&](uint32_t (&acc)[24]) {
#pragma unroll
        for (int q = 0; q < 6; q++) lds128(acc[4 * q], acc[4 * q + 1], acc[4 * q + 2], acc[4 * q + 3], bias_addr + q * 16);
    };
    auto load_frags = [&](bool on) {
#pragma unroll
        for (int s = 0; s < 6; s++) ldg128_if(on, a[s], reinterpret_cast<const char*>(out) + next_off + w4 * WARP_BYTES + lane16 + s * 512);
    };
    auto load_first = [&]() {
#pragma unroll
        for (int s = 0; s < 6; s++) ldg128(a[s], reinterpret_cast<const char*>(out) + next_off + w4 * WARP_BYTES + lane16 + s * 512);
    };
    auto stage_x = [&]() {
        if (elect_one()) {
            mbar_expect_tx(bar_r, WARP_BYTES);
            bulk_load_stream(stage, reinterpret_cast<const char*>(x) + tile_off + w4 * WARP_BYTES, WARP_BYTES, bar_r);
        }
    };
    auto epilogue = [&](uint32_t (&acc)[24]) {
        pin(acc);
        rpar ^= 1;
        uint4* op = reinterpret_cast<uint4*>(reinterpret_cast<char*>(out) + tile_off + w4 * WARP_BYTES + lane_off);
#pragma unroll
        for (int h = 0; h < 2; h++)
#pragma unroll
            for (int m = 0; m < 3; m++) {
                uint32_t xin[4], o[4];
                lds128(xin[0], xin[1], xin[2], xin[3], stage + lane_off + h * 1536 + m * 64);
#pragma unroll
                for (int q = 0; q < 4; q++) {
                    const uint32_t v = acc[2 * (4 * m + q) + h];
                    o[q] = bf_fma(pack_bf2(h_lo(v), h_hi(v)), inv_rho2, xin[q]);
                }
                __stcs(op + h * 96 + m * 4, make_uint4(o[0], o[1], o[2], o[3]));
            }
        __syncwarp();
    };
    const bool helps = !wk.lent && wk.index < 8 * LENT * sp.lenders;
    const int help_slot = (wk.rows + 2) % NSLOT;
    const uint32_t s_help = sb + SM_RING + help_slot * SLOT_BYTES + SQ_WG;
    auto reduce = [&](int q, uint32_t lane, bool leader) {
        const int part = lane >> 2, ch = 32 * q + 8 * (part >> 1) + 2 * (lane & 3) + (part & 1);
        uint32_t sq_e, sum_e;
        lds64(sq_e, sum_e, s_red + RED_SQ_EXP);
        const float to_fixed = pow2i(sum_e - 2 * sq_e);
        unsigned long long* dst = sc->sum(ch);
        named_bar(11, CONS_THREADS);
        const unsigned in_piece = ch - wk.index % 8 * 48;
        float helped = 0.f;
        if (helps && in_piece < 48) {
            uint32_t u[4];
            lds128(u[0], u[1], u[2], u[3], s_help + in_piece * 16);
            helped = ((__uint_as_float(u[0]) + __uint_as_float(u[1])) + (__uint_as_float(u[2]) + __uint_as_float(u[3]))) * pow2i(2 * sq_e);
        }
        float f[8] = {};
        int slot = wk.rows % NSLOT;
#pragma unroll 1
        for (int i = 0; i < NCONS; i++) {
            if (i == NCONS - 1) {
                named_bar(13, CONS_THREADS);
                if (leader) {
                    fence_async();
                    bulk_load(sb + SM_W2, sc->w2h, (NCONS - 1) * SQ_WG, sb + BAR_W);
                }
                __syncwarp();
                named_bar(14, NTHREADS);
            }
            const uint32_t src = sb + lane * 16 + q * SQ_ROW + (q < 6 ? SM_SQ + i * SQ_WG : sq_e ? SM_SQ + (NCONS - 1 + i) * SQ_WG : SM_RING + slot * SLOT_BYTES - SQ_WG);
            slot = slot == NSLOT - 1 ? 0 : slot + 1;
#pragma unroll
            for (int r = 0; r < 4; r++) {
                uint32_t u[4];
                lds128(u[0], u[1], u[2], u[3], src + r * 512);
#pragma unroll
                for (int k = 0; k < 4; k++) { f[2 * k] += h_lo(u[k]); f[2 * k + 1] += h_hi(u[k]); }
            }
        }
        const bool b2 = part & 4, b1 = part & 2, b0 = part & 1;
        float r4[4], r2[2];
#pragma unroll
        for (int k = 0; k < 4; k++) r4[k] = (b2 ? f[k + 4] : f[k]) + __shfl_xor_sync(~0u, b2 ? f[k] : f[k + 4], 16);
#pragma unroll
        for (int k = 0; k < 2; k++) r2[k] = (b1 ? r4[k + 2] : r4[k]) + __shfl_xor_sync(~0u, b1 ? r4[k] : r4[k + 2], 8);
        const float tot = (b0 ? r2[1] : r2[0]) + __shfl_xor_sync(~0u, b0 ? r2[0] : r2[1], 4);
        atomicAdd(dst, __float2ull_rn(fminf((tot + helped) * to_fixed, 0x1p47f)) << 8 | 1);
    };
    const uint32_t s_fac = sb + SM_RING + (wk.rows + 1) % NSLOT * SLOT_BYTES + SQ_WG;
    if (warp_id < 4) {
        const bool prepares = gridDim.x - blockIdx.x <= W2_GROUPS / 2;
        const int q = (gridDim.x - 1 - blockIdx.x) * 2 + (w4 >> 1);
        auto lent_tile = [&]() {
            return tile_offset(get_work((wk.index / (8 * LENT) + 1) * sp.period - sp.period / 2 - 1, sp).tile(wk.index / 8 % LENT));
        };
        conv_producer(wk, &tmap, sb, warp_id, [&](bool second) {
            if (!second) {
                if (blockIdx.x == 0) {
#pragma unroll 1
                    for (int e = tid; e < EX; e += 128) *sc->sum(e) = 0;
                    sc->bias[tid] = 0.f;
                    signal(&sc->early);
                }
                if (wk.lent) signal(&sc->early);
            } else if (prepares || helps) {
                spin_until(&sc->early, (ldsi(s_red + RED_LAUNCH) + 1) * 4 * (sp.lenders + 1));
                if (elect_one()) {
                    if (helps) prefetch_l2(reinterpret_cast<const char*>(out) + lent_tile() + w4 * WARP_BYTES, WARP_BYTES);
                    if (prepares) { prefetch_l2(w2 + 8 * q * CH, 8 * CH * 2); prefetch_l2(beta + 8 * q, 16); }
                }
            }
        });
        const int lane = opaque(tid & 31), g = lane >> 2, t = lane & 3;
        const unsigned epoch = ldsi(s_red + RED_LAUNCH);
        set_lane(lane);
        const int i0 = w4 * 32 + lane;
        float gam[3], rmax[3];
#pragma unroll
        for (int m = 0; m < 3; m++) {
            unsigned short v;
            asm volatile("ld.global.nc.u16 %0, [%1];" : "=h"(v) : "l"(gamma + i0 + 128 * m) : "memory");
            gam[m] = bf_lo(v);
        }
        if (prepares) {
            const int half = w4 & 1;
            uint32_t u[3][2], rmax = 0;
#pragma unroll
            for (int m = 0; m < 3; m++) {
                const uint4 w = ldg128_ordered(w2 + (8 * q + g) * CH + 32 * m + 8 * t);
                rmax = bf_absmax(bf_absmax(rmax, bf_absmax(w.x, w.y)), bf_absmax(w.z, w.w));
                u[m][0] = half ? w.z : w.x;
                u[m][1] = half ? w.w : w.y;
            }
            const float bt = __bfloat162float(beta[8 * q + g]);
            rmax = bf_absmax(rmax, __shfl_xor_sync(~0u, rmax, 1));
            rmax = bf_absmax(rmax, __shfl_xor_sync(~0u, rmax, 2));
            const float mx = fmaxf(fabsf(bf_lo(rmax)), fabsf(bf_hi(rmax))), rs = row_scale(mx);
            if (t == 0 && !half) sc->w2max[8 * q + g] = mx;
#pragma unroll
            for (int m = 0; m < 3; m++) {
                float f[4];
#pragma unroll
                for (int k = 0; k < 2; k++) {
                    const float lo = bf_lo(u[m][k]), hi = bf_hi(u[m][k]);
                    sc->w2h[(4 * m + 2 * half + k) * 1536 + q * 32 + lane] = transpose8x8(pack_h2(lo * rs, hi * rs));
                    f[2 * k] = lo * bt;
                    f[2 * k + 1] = hi * bt;
                }
                const float r0 = (g & 2 ? f[2] : f[0]) + __shfl_xor_sync(~0u, g & 2 ? f[0] : f[2], 8);
                const float r1 = (g & 2 ? f[3] : f[1]) + __shfl_xor_sync(~0u, g & 2 ? f[1] : f[3], 8);
                float r = (g & 1 ? r1 : r0) + __shfl_xor_sync(~0u, g & 1 ? r0 : r1, 4);
                r += __shfl_xor_sync(~0u, r, 16);
                if (g < 4) atomicAdd(&sc->bias[32 * m + 8 * t + 4 * half + g], r);
            }
            asm volatile("fence.proxy.async.global;" ::: "memory");
            signal(&sc->prep);
        }
        const int piece = wk.index;
        if (helps) {
            next_off = lent_tile();
            load_first();
            uint32_t d[12], gl[12];
            wg_fence();
#pragma unroll
            for (int s = 0; s < 6; s++) wgmma(d, a[s][0], a[s][1], a[s][2], a[s][3], ds.w1[0][s] + piece % 8 * (6 * 1536 / 16), s ? 1 : 0);
            wg_commit();
            wg_wait<0>();
            gelu_to(gl, d);
#pragma unroll
            for (int s = 0; s < 3; s++) sc->lent[(((piece / (8 * LENT) * 4 + w4) * (8 * LENT) + piece % (8 * LENT)) * 3 + s) * 32 + lane] = make_uint4(gl[4 * s], gl[4 * s + 1], gl[4 * s + 2], gl[4 * s + 3]);
            float f[6], r[3];
#pragma unroll
            for (int j = 0; j < 6; j++) {
                const float lo = fmaf(h_lo(gl[2 * j]), h_lo(gl[2 * j]), h_lo(gl[2 * j + 1]) * h_lo(gl[2 * j + 1]));
                const float hi = fmaf(h_hi(gl[2 * j]), h_hi(gl[2 * j]), h_hi(gl[2 * j + 1]) * h_hi(gl[2 * j + 1]));
                f[j] = (g & 1 ? hi : lo) + __shfl_xor_sync(~0u, g & 1 ? lo : hi, 4);
            }
            mbar_wait(sb + BAR_E + help_slot * 32 + 24, (wk.rows - 4) / NSLOT & 1);
#pragma unroll
            for (int j = 0; j < 3; j++) {
                r[j] = (g & 2 ? f[j + 3] : f[j]) + __shfl_xor_sync(~0u, g & 2 ? f[j] : f[j + 3], 8);
                r[j] += __shfl_xor_sync(~0u, r[j], 16);
                sts32(s_help + (8 * j + 12 * (g & 2) + 2 * t + (g & 1)) * 16 + w4 * 4, __float_as_uint(r[j]));
            }
        }
        const bool leader = warp_id == 0 && lane == 0;
        const float w1max = ldsf(s_red + RED_MAX), from_fixed = pow2i(-ldsi(s_red + RED_SUM_EXP));
        const bool plain = ldsi(s_red + RED_SQ_EXP) == 0;
        auto load_upper = [&]() {
            bulk_load(sb + SM_W2 + NCONS * SQ_WG, reinterpret_cast<const char*>(sc->w2h) + NCONS * SQ_WG, EX * CH * 2 - NCONS * SQ_WG, sb + BAR_W);
        };
        if (leader) {
            spin_until(&sc->prep, (epoch + 1) * 2 * W2_GROUPS);
            asm volatile("fence.proxy.async.global;" ::: "memory");
            fence_async();
            mbar_expect_tx(sb + BAR_W, EX * CH * 2);
            if (plain) load_upper();
        }
        __syncwarp();
        named_bar(1, 128);
#pragma unroll
        for (int m = 0; m < 3; m++) rmax[m] = __ldcg(&sc->w2max[i0 + 128 * m]);
        float2 bpair = make_float2(0.f, 0.f);
        if (i0 < 96) bpair = __ldcg(reinterpret_cast<const float2*>(&sc->bias[32 * (i0 % 24 >> 3) + 8 * (i0 / 24) + (i0 % 24 & 6)]));
        const float gbound = fmaxf(2.f * KZ * 9.7979590f * 192.f * w1max, 1.f) * 19.5959180f * INV_2KZ;
        const unsigned fixed = __reduce_max_sync(~0u, __float_as_uint(fmaf(gbound, fmaxf(fmaxf(rmax[0], rmax[1]), rmax[2]), fmaxf(fabsf(bpair.x), fabsf(bpair.y)))));
        if (lane == 0) sts32(s_red + 96 + w4 * 4, fixed);
        reduce(4 * (NCONS - 1) + w4, lane, leader);
        PROF(2);
        named_bar(15, CONS_THREADS);
        if (leader) {
            fence_async();
            bulk_load(sb + SM_W2 + (NCONS - 1) * SQ_WG, reinterpret_cast<const char*>(sc->w2h) + (NCONS - 1) * SQ_WG, SQ_WG, sb + BAR_W);
            if (!plain) load_upper();
        }
        stage = sb + SM_RING + (wk.rows + 3 + (wk.lent + 2 * ntiles) % NCONS) % NSLOT * SLOT_BYTES + w4 * REGION_BYTES;
        auto grn = [&]() {
            auto peek = [&](int e) {
                unsigned long long v;
                asm volatile("ld.relaxed.gpu.global.u64 %0, [%1];" : "=l"(v) : "l"(sc->sum(e)) : "memory");
                return v;
            };
            unsigned n = 0;
            while (((unsigned)peek((blockIdx.x * 4 + w4) % (EX / 4) * 4) & 255u) != gridDim.x)
                if (++n > SPIN_LIMIT) __trap();
            unsigned long long sum[3];
            for (;;) {
                bool all = true;
#pragma unroll
                for (int m = 0; m < 3; m++) {
                    sum[m] = peek(i0 + 128 * m);
                    all &= ((unsigned)sum[m] & 255u) == gridDim.x;
                }
                if (__all_sync(~0u, all)) break;
                if (++n > SPIN_LIMIT) __trap();
            }
            PROF(3);
            if (blockIdx.x == 0 && leader) sc->launch = epoch + 1;
            float gx[3], tot = 0.f, vary = 0.f;
#pragma unroll
            for (int m = 0; m < 3; m++) {
                gx[m] = grn_norm(__ull2float_rn(sum[m] >> 8) * from_fixed);
                tot += gx[m];
                vary = fmaxf(vary, fabsf(gam[m]) * gx[m] * rmax[m]);
            }
#pragma unroll
            for (int o = 16; o >= 1; o >>= 1) tot += __shfl_xor_sync(~0u, tot, o);
            const unsigned vwarp = __reduce_max_sync(~0u, __float_as_uint(vary));
            if (lane == 0) { sts32(s_red + 64 + w4 * 4, __float_as_uint(tot)); sts32(s_red + 80 + w4 * 4, vwarp); }
            named_bar(1, 128);
            uint32_t u[4], v[4], w[4];
            lds128(u[0], u[1], u[2], u[3], s_red + 64);
            lds128(v[0], v[1], v[2], v[3], s_red + 80);
            lds128(w[0], w[1], w[2], w[3], s_red + 96);
            tot = (__uint_as_float(u[0]) + __uint_as_float(u[1])) + (__uint_as_float(u[2]) + __uint_as_float(u[3]));
            const float vmax = __uint_as_float(max(max(v[0], v[1]), max(v[2], v[3]))), fmax2 = __uint_as_float(max(max(w[0], w[1]), max(w[2], w[3])));
            const float inv_mean = __fdividef(1.f, tot * (1.f / EX) + 1e-6f);
            const float bound = fmaf(gbound * vmax, inv_mean, 2.f * fmax2);
            const int rho_e = bound > 0.f ? 14 - ilog2f(bound) : 0;
            const float rho = pow2i(rho_e), inv_rho = pow2i(-rho_e);
            inv_rho2 = pack_bf2(inv_rho, inv_rho);
#pragma unroll
            for (int m = 0; m < 3; m++) {
                const float f = __fdividef(fmaf(gam[m], gx[m] * inv_mean, 1.f) * INV_2KZ * rho, row_scale(rmax[m]));
                asm volatile("st.shared.u16 [%0], %1;" ::"r"(s_fac + (i0 + 128 * m) * 2), "h"((unsigned short)pack_h2(f, 0.f)) : "memory");
            }
            if (i0 < 96) sts32(sb + SM_BIASH + i0 * 4, pack_h2(bpair.x * rho, bpair.y * rho));
            if (i0 == 96) sts32(s_red + RED_INV_RHO, inv_rho2);
            named_arrive(12, NTHREADS);
        };
        lds32(next_off, sb + SM_TILES);
        next_off = __shfl_sync(~0u, next_off, 0);
        load_first();
        grn();
        if (wk.lent) spin_until(&sc->lent_out, (epoch + 1) * 8 * LENT * sp.lenders);
    } else {
        const int rank = (wgi + wk.lent + 2 * ntiles) % NCONS;
        {
            const int ct = tid - 128, lane = tid & 31;
            const unsigned epoch = *reinterpret_cast<volatile unsigned*>(&sc->launch);
            const int r = lane & 7, mi = lane >> 3;
            const uint32_t src = sb + SM_W2 + (cw >> 1) * (64 * CH * 2) + r * 128 + ((((cw & 1) * 4 + mi) ^ r) * 16);
            const uint32_t dst = sb + SM_W1 + (4 * cw + mi) * 1536 + r * 16;
            if (ct == 0) sts32(s_red + RED_MAX, 0);
            named_bar(0, NTHREADS);
            mbar_wait(sb + BAR_W + (cw >> 1) * 8, 0);
            uint32_t wmax[4] = {}, wsum[4] = {};
#pragma unroll 3
            for (int c = 0; c < 12; c++) {
                uint32_t u[4];
                ldsm4_t(u, src + c * 1024);
#pragma unroll
                for (int q = 0; q < 4; q++) {
                    wmax[q] = bf_absmax(wmax[q], u[q]);
                    wsum[q] = bf_fma(u[q], 0x3f803f80u, wsum[q]);
                    u[q] = pack_h2(bf_lo(u[q]), bf_hi(u[q]));
                }
                stsm4(dst + c * 128, u[0], u[1], u[2], u[3]);
            }
            float mean[4];
            bool center = false;
#pragma unroll
            for (int q = 0; q < 4; q++) {
                uint32_t m = wmax[q];
                float sum = bf_lo(wsum[q]) + bf_hi(wsum[q]);
#pragma unroll
                for (int o = 1; o <= 2; o <<= 1) { m = bf_absmax(m, __shfl_xor_sync(~0u, m, o)); sum += __shfl_xor_sync(~0u, sum, o); }
                mean[q] = sum * (1.f / CH);
                center |= fabsf(mean[q]) > 0.2f * fmaxf(fabsf(bf_lo(m)), fabsf(bf_hi(m)));
            }
            if (__builtin_expect(__any_sync(~0u, center), 0)) {
#pragma unroll 1
                for (int pass = 0; pass < 2; pass++) {
                    float sum[4] = {};
#pragma unroll 1
                    for (int c = 0; c < 12; c++) {
                        uint32_t u[4];
                        ldsm4_t(u, src + c * 1024);
#pragma unroll
                        for (int q = 0; q < 4; q++) {
                            sum[q] += bf_lo(u[q]) + bf_hi(u[q]);
                            u[q] = pack_h2(bf_lo(u[q]) - mean[q], bf_hi(u[q]) - mean[q]);
                        }
                        stsm4(dst + c * 128, u[0], u[1], u[2], u[3]);
                    }
#pragma unroll
                    for (int q = 0; q < 4; q++) {
                        sum[q] += __shfl_xor_sync(~0u, sum[q], 1);
                        sum[q] += __shfl_xor_sync(~0u, sum[q], 2);
                        mean[q] = sum[q] * (1.f / CH);
                    }
                }
            }
            if (cw < 2 * NCONS) {
#pragma unroll
                for (int c = 0; c < 12; c++) sts128(src + c * 1024, 0, 0, 0, 0);
            }
            const float w1max = warp_absmax(bf_absmax(bf_absmax(wmax[0], wmax[1]), bf_absmax(wmax[2], wmax[3])));
            if (lane == 0) asm volatile("red.shared.max.u32 [%0], %1;" ::"r"(s_red + RED_MAX), "r"(__float_as_uint(w1max)) : "memory");
            if (ct < 32) sts32(sb + SM_ONES + ct * 4, 0x3f803f80u);
            if (ct == 0) sts32(s_red + RED_LAUNCH, epoch);
            fence_async();
            named_bar(2, CONS_THREADS);
            const float all_max = ldsf(s_red + RED_MAX);
            const int sq_e = square_exp(all_max);
            sts64(s_red + RED_SQ_EXP, sq_e, sum_exp(all_max));
            if (sq_e) {
#pragma unroll 1
                for (int q = 0; q < 6; q++) sts128(sb + SM_SQ + (rank + NCONS) * SQ_WG + q * SQ_ROW + (ct & 127) * 16, 0, 0, 0, 0);
            }
            mbar_wait(sb + BAR_A + w4 * 8 + 32, 0);
        }

        PROF(1);
        const uint32_t a_addr = opaque(sb + SM_RING + w4 * REGION_BYTES + ((tid >> 3) & 1) * A_SBO + ((tid >> 4) & 1) * A_LBO + (tid & 7) * 16);
        const uint32_t bar_a = sb + BAR_A + w4 * 8, bar_e = sb + BAR_E + w4 * 8;
        const uint32_t sq = opaque(sb + SM_SQ + rank * SQ_WG + (tid & 127) * 16);
        const uint32_t sq_warp = sb + SM_SQ + rank * SQ_WG + w4 * 512;
        uint32_t k1[24], k2[24], k3[24];
        constexpr int SQC = 3 * SQ_ROW;
        const int pass_to = 4 + (wgi == NCONS - 1 ? 0 : wgi + 1);
        auto store_frags = [&](const uint32_t (&a)[6][4], int j) {
            char* ap = reinterpret_cast<char*>(out) + (tile_offset(wk.tile(j)) + w4 * WARP_BYTES - sq_warp + sq);
#pragma unroll
            for (int s = 0; s < 6; s++) stg128(ap + s * 512, a[s]);
        };
        int jt = wgi < wk.lent ? wgi : wk.lent + wgi;
        Cursor cur = {2, 0};
        cur.advance(jt + (jt >= wk.nA ? 2 : 0));
        if (wgi == NCONS - 1) named_arrive(4, 256);
        for (;;) {
            const bool plain = __all_sync(~0u, ldsi(s_red + RED_SQ_EXP) == 0);
            if (plain && jt >= wk.lent) {
                uint32_t hs2[12] = {}, hs3[12] = {};
#pragma unroll 1
                for (; jt + NCONS < ntiles; jt += NCONS) {
                    uint32_t a[6][4], d0[24], d1[24], unused[24];
#define AT(pos) \
    if (K_WAIT == pos) named_bar(4 + wgi, 256); \
    if (K_PASS == pos) named_arrive(pass_to, 256); \
    if (K_STG == pos) store_frags(a, jt); \
    if (K_REL == pos) { if (elect_one()) mbar_arrive(bar_e + cur.slot * 32); }
                    AT(20)
                    mbar_wait(bar_a + cur.slot * 32, cur.par);
                    load_tile(a, a_addr + cur.slot * SLOT_BYTES);
                    AT(21)
                    const uint2 st = ln_stats(a, ds.ones);
                    AT(0)
                    ln_apply(a, st);
                    AT(1)
                    wg_fence();
                    gemm1_chunk<0>(d0, a, ds, 0);
                    wg_commit();
                    gemm1_chunk<96>(d1, a, ds, 0);
                    wg_commit();
                    AT(2)
                    wg_wait<1>();
                    AT(3)
                    gelu_sq<false, 0, 1>(d0, unused, sq, 0);
                    AT(4)
                    gelu_sq<false, 1, 2>(d0, unused, sq, 0);
                    AT(5)
                    gelu_sq<false, 2, 3>(d0, unused, sq, 0);
                    AT(6)
                    wg_fence();
                    gemm1_chunk<192>(d0, a, ds, zero);
                    wg_commit();
                    AT(7)
                    wg_wait<1>();
                    gelu_sq<false, 0, 1>(d1, unused, sq + SQC, 0);
                    AT(8)
                    gelu_sq<false, 1, 3>(d1, unused, sq + SQC, 0);
                    AT(9)
                    wg_fence();
                    gemm1_chunk<288>(d1, a, ds, zero);
                    wg_commit();
                    AT(10)
                    wg_wait<1>();
                    gelu_sq_reg(d0, hs2);
                    if (K_ANCH < 3) anchor(sq, hs2[4 * (K_ANCH % 3)], hs2[4 * (K_ANCH % 3) + 1], hs2[4 * (K_ANCH % 3) + 2], hs2[4 * (K_ANCH % 3) + 3]);
                    wg_wait<0>();
                    AT(11)
                    gelu_sq_reg(d1, hs3);
#undef AT
                    cur.advance(NCONS + ((jt < wk.nA && jt + NCONS >= wk.nA) ? 2 : 0));
                }
                const uint32_t sq2 = sq - (SM_SQ + rank * SQ_WG) + SM_RING + (cur.slot + 3) % NSLOT * SLOT_BYTES;
#pragma unroll
                for (int k = 0; k < 3; k++) {
                    sts128(sq2 + k * SQ_ROW, hs2[4 * k], hs2[4 * k + 1], hs2[4 * k + 2], hs2[4 * k + 3]);
                    sts128(sq2 + SQC + k * SQ_ROW, hs3[4 * k], hs3[4 * k + 1], hs3[4 * k + 2], hs3[4 * k + 3]);
                }
            }
            const bool last = jt + NCONS >= ntiles;
            if (last) {
                tile_off = tile_offset(wk.tile(jt));
                lds32(next_off, sb + SM_TILES + wg * 4);
                next_off = __shfl_sync(~0u, next_off, 0);
                if (elect_one()) {
                    prefetch_l2(reinterpret_cast<const char*>(x) + tile_off + w4 * WARP_BYTES, WARP_BYTES);
                    if (wg % ORDER_P >= ORDER_P - ORDER_Q) prefetch_l2(reinterpret_cast<const char*>(out) + next_off + w4 * WARP_BYTES, WARP_BYTES);
                }
            }
            uint32_t a[6][4], d0[24], d1[24], d3[24], k0[24];
#define AT(pos) \
    if (K_WAIT == pos && jt >= wk.lent) named_bar(4 + wgi, 256); \
    if (K_PASS == pos && jt >= wk.lent && jt + 1 < ntiles) named_arrive(pass_to, 256);
            AT(20)
            mbar_wait(bar_a + cur.slot * 32, cur.par);
            load_tile(a, a_addr + cur.slot * SLOT_BYTES);
            AT(21)
            const uint2 st = ln_stats(a, ds.ones);
            AT(0)
            ln_apply(a, st);
            AT(1)
            if (!last) {
                store_frags(a, jt);
                __syncwarp();
                if (elect_one()) mbar_arrive(bar_e + cur.slot * 32);
                if (jt < wk.lent) {
                    jt += LENT;
                    cur.advance(LENT);
                    continue;
                }
            }
            wg_fence();
            gemm1_chunk<0>(d0, a, ds, 0);
            wg_commit();
            gemm1_chunk<96>(d1, a, ds, 0);
            wg_commit();
            const int sq_e = ldsi(s_red + RED_SQ_EXP);
            const uint32_t scale2 = pack_h2(pow2i(sq_e), pow2i(sq_e));
            AT(2)
            wg_wait<1>();
            AT(3)
            gelu_sq<true, 0, 1>(d0, k0, sq, scale2);
            AT(4)
            gelu_sq<true, 1, 2>(d0, k0, sq, scale2);
            AT(5)
            gelu_sq<true, 2, 3>(d0, k0, sq, scale2);
            AT(6)
            if (last) {
#pragma unroll
                for (int q = 0; q < 6; q++) sts128(sb + SM_RING + cur.slot * SLOT_BYTES + w4 * REGION_BYTES - sq_warp + sq + q * 512, k0[4 * q], k0[4 * q + 1], k0[4 * q + 2], k0[4 * q + 3]);
            }
            wg_fence();
            gemm1_chunk<192>(d0, a, ds, zero);
            wg_commit();
            AT(7)
            wg_wait<1>();
            gelu_sq<true, 0, 1>(d1, k1, sq + SQC, scale2);
            AT(8)
            gelu_sq<true, 1, 3>(d1, k1, sq + SQC, scale2);
            AT(9)
#undef AT
            wg_fence();
            gemm1_chunk<288>(d3, a, ds, 0);
            wg_commit();
            wg_wait<1>();
            const uint32_t sq2 = sq + (plain ? SM_RING + (cur.slot + 3) % NSLOT * SLOT_BYTES - (SM_SQ + rank * SQ_WG) : NCONS * SQ_WG);
            gelu_sq<true>(d0, k2, sq2, scale2);
            wg_wait<0>();
            gelu_sq<true>(d3, k3, sq2 + SQC, scale2);
            if (last) break;
            cur.advance(NCONS + ((jt < wk.nA && jt + NCONS >= wk.nA) ? 2 : 0));
            jt += NCONS;
        }
        {
            if (rank == NCONS - 1) {
                named_arrive(14, NTHREADS);
            } else {
                reduce(4 * rank + w4, (sq >> 4) & 31, false);
                named_arrive(15, CONS_THREADS);
                if (helps && rank == 0 && w4 == 0) signal(&sc->lent_out);
            }
        }
        PROF(2);
        {
            set_lane((sq >> 4) & 31);
            const uint32_t row = sb + SM_W2 + cw * 512 + lane16;
            uint32_t u[W2_EARLY][4], f2[4];
            mbar_wait(sb + BAR_W, 1);
#pragma unroll
            for (int nb = 0; nb < W2_EARLY; nb++) lds128(u[nb][0], u[nb][1], u[nb][2], u[nb][3], row + nb * 6144);
            named_bar(12, NTHREADS);
            PROF(3);
            stage = sb + SM_RING + (cur.slot + 3) % NSLOT * SLOT_BYTES + w4 * WARP_BYTES;
            if (K_XPOS == 0) stage_x();
            lds128(f2[0], f2[1], f2[2], f2[3], s_fac + cw * 64 + (lane16 >> 7) * 16);
            lds32(inv_rho2, s_red + RED_INV_RHO);
#pragma unroll
            for (int nb = 0; nb < 12; nb++) {
                uint32_t v[4];
                if (nb < W2_EARLY) { v[0] = u[nb % W2_EARLY][0]; v[1] = u[nb % W2_EARLY][1]; v[2] = u[nb % W2_EARLY][2]; v[3] = u[nb % W2_EARLY][3]; }
                else lds128(v[0], v[1], v[2], v[3], row + nb * 6144);
                sts128(row + nb * 6144, h_round8(h_mul(v[0], f2[0])), h_round8(h_mul(v[1], f2[1])), h_round8(h_mul(v[2], f2[2])), h_round8(h_mul(v[3], f2[3])));
            }
            fence_async();
            if (K_XPOS == 1) stage_x();
            named_bar(3, NTHREADS);
        }
        PROF(4);
        {
            load_bias(acc);
            if (wgi > 0) named_bar(8 + wgi, 256);
            pin(k1); pin(k2); pin(k3);
            wg_fence();
            gemm2_chunk<288>(acc, k3, ds);
            wg_commit();
            gemm2_chunk<(K_SWAP ? 192 : 96)>(acc, K_SWAP ? k2 : k1, ds);
            if (K_FINE) wg_commit();
            gemm2_chunk<(K_SWAP ? 96 : 192)>(acc, K_SWAP ? k1 : k2, ds);
            wg_commit();
            if (!K_LATE && wgi + 1 < NCONS) named_arrive(9 + wgi, 256);
            wg_wait<1 + K_FINE>();
            uint32_t k0[24];
#pragma unroll
            for (int q = 0; q < 6; q++)
                lds128(k0[4 * q], k0[4 * q + 1], k0[4 * q + 2], k0[4 * q + 3], sb + SM_RING + cur.slot * SLOT_BYTES + w4 * REGION_BYTES + lane16 + q * 512);
            pin(k0);
            wg_fence();
            gemm2_chunk<0>(acc, k0, ds);
            wg_commit();
            if (K_LATE && wgi + 1 < NCONS) named_arrive(9 + wgi, 256);
            if (wgi == 0) named_arrive(8, 256);
            wg_wait<1 + K_FINE>();
            load_first();
            if (lane16 == 0) mbar_arrive(sb + BAR_PIN);
            mbar_wait(bar_r, rpar);
            wg_wait<0>();
            first = wg - 4;
        }
    }
    {
        const int nrest = ntiles - NCONS;
        auto lent = [&](uint32_t entry) { return &sc->lent[((wk.index * 4 + w4) * LENT + (entry & 3) - 1) * (8 * 96)]; };
        for (int jt = first; jt < nrest; jt += 4) {
            if (jt >= 0) {
            tile_off = next_off;
            lds32(next_off, sb + SM_TILES + (jt + 4) * 4);
            if (tile_off & 3) {
                uint32_t gl[2][24];
                const uint4* src = lent(tile_off) + (lane16 >> 4);
                auto fetch = [&](uint32_t (&v)[24], int c) {
#pragma unroll
                    for (int s = 0; s < 6; s++) ldg128(reinterpret_cast<uint32_t (&)[4]>(v[4 * s]), src + (6 * c + s) * 32);
                };
                tile_off &= ~3u;
                next_off = __shfl_sync(~0u, next_off, 0);
                stage_x();
                if (elect_one()) prefetch_l2(reinterpret_cast<const char*>(out) + next_off + w4 * WARP_BYTES, WARP_BYTES);
                load_bias(acc);
#pragma unroll
                for (int half = 0; half < 2; half++) {
                    fetch(gl[0], 2 * half);
                    fetch(gl[1], 2 * half + 1);
                    if (!half) {
                        named_bar(4 + wg, 256);
                        named_arrive(4 + ((wg + 1) & 3), 256);
                    }
                    pin(gl[0]); pin(gl[1]);
                    wg_fence();
                    if (half) gemm2_chunk<192>(acc, gl[0], ds); else gemm2_chunk<0>(acc, gl[0], ds);
                    if (half) gemm2_chunk<288>(acc, gl[1], ds); else gemm2_chunk<96>(acc, gl[1], ds);
                    wg_commit();
                    wg_wait<0>();
                }
                load_first();
                mbar_wait(bar_r, rpar);
            } else {
            uint32_t d0[12], d1[12], g0[12], g1[12];
            if (jt >= S2_FIRST && jt < nrest - K_TAIL) named_bar(4 + wg, 256);
            wg_fence();
            gemm1_chunk<0>(d0, a, ds, 0);
            wg_commit();
            gemm1_chunk<48>(d1, a, ds, 0);
            wg_commit();
            load_bias(acc);
            next_off = __shfl_sync(~0u, next_off, 0);
            const bool more = jt + 4 < nrest && !(next_off & 3);
            wg_wait<1>();
#define CNX_PASS if (jt + 1 >= S2_FIRST && jt + 1 < nrest - K_TAIL) named_arrive(4 + ((wg + 1) & 3), 256);
#define CNX_STEP(C, D, G)                                              \
    gelu_to(G, D);                                                     \
    if (C == 0 && jt == 0) {                                           \
        named_bar(3, NTHREADS);                                        \
        load_bias(acc);                                                \
    }                                                                  \
    wg_fence();                                                        \
    if (C < 6) gemm1_chunk<48 * (C < 6 ? C + 2 : 0)>(D, a, ds, zero); \
    gemm2_chunk<48 * C>(acc, G, ds);                                  \
    wg_commit();                                                       \
    if (C == S2_PASS) { CNX_PASS }                                     \
    wg_wait<(C < 7 ? 1 : 0)>();
            CNX_STEP(0, d0, g0)
            CNX_STEP(1, d1, g1)
            if (jt == 0) named_bar(8, 256);
            stage_x();
            if (elect_one()) {
                if (more) prefetch_l2(reinterpret_cast<const char*>(out) + next_off + w4 * WARP_BYTES, WARP_BYTES);
                else if (next_off & 3) prefetch_l2(lent(next_off), 8 * 96 * 16);
            }
            CNX_STEP(2, d0, g0)
            CNX_STEP(3, d1, g1)
            CNX_STEP(4, d0, g0)
            CNX_STEP(5, d1, g1)
            CNX_STEP(6, d0, g0)
            load_frags(more);
            if (lane16 == 0) mbar_arrive(sb + BAR_PIN);
            mbar_wait(bar_r, rpar);
            CNX_STEP(7, d1, g1)
#undef CNX_STEP
            }
            }
            epilogue(acc);
        }
    }
    PROF(5);
}

}

typedef CUresult (*EncodeTiledFn)(CUtensorMap*, CUtensorMapDataType, cuuint32_t, void*, const cuuint64_t*, const cuuint64_t*,
                                  const cuuint32_t*, const cuuint32_t*, CUtensorMapInterleave, CUtensorMapSwizzle,
                                  CUtensorMapL2promotion, CUtensorMapFloatOOBfill);

extern "C" void kernel_launch(void* const* d_in, const int* in_sizes, int n_in, void* d_out, int out_size) {
    using namespace cnx;
    static EncodeTiledFn encode = nullptr;
    static int num_sms = 0;
    static Scratch* scratch = nullptr;
    if (!encode) {
        void* fn = nullptr;
        cudaDriverEntryPointQueryResult qr;
        cudaGetDriverEntryPoint("cuTensorMapEncodeTiled", &fn, cudaEnableDefault, &qr);
        encode = (EncodeTiledFn)fn;
        cudaGetSymbolAddress((void**)&scratch, g_scratch);
        int dev = 0;
        cudaGetDevice(&dev);
        cudaDeviceGetAttribute(&num_sms, cudaDevAttrMultiProcessorCount, dev);
        if (num_sms > MAX_CTAS) num_sms = MAX_CTAS;
        cudaFuncSetAttribute(block_kernel, cudaFuncAttributeMaxDynamicSharedMemorySize, SM_TOTAL);
    }
    CUtensorMap tm;
    cuuint64_t dims[3] = {(cuuint64_t)CH, (cuuint64_t)IMG_W, (cuuint64_t)IMG_H};
    cuuint64_t strides[2] = {(cuuint64_t)CH * 2, (cuuint64_t)CH * 2 * IMG_W};
    cuuint32_t box[3] = {(cuuint32_t)CH, (cuuint32_t)REGION_PX, 1};
    cuuint32_t estr[3] = {1, 1, 1};
    encode(&tm, CU_TENSOR_MAP_DATA_TYPE_BFLOAT16, 3, d_in[0], dims, strides, box, estr, CU_TENSOR_MAP_INTERLEAVE_NONE,
           CU_TENSOR_MAP_SWIZZLE_NONE, CU_TENSOR_MAP_L2_PROMOTION_L2_128B, CU_TENSOR_MAP_FLOAT_OOB_FILL_NONE);
    Descs ds;
    for (int c = 0; c < 8; c++)
        for (int k = 0; k < 6; k++) ds.w1[c][k] = make_desc(SB + SM_W1 + c * 6 * 1536 + k * 256, 128, 1536);
    for (int k = 0; k < 24; k++) ds.w2[k] = make_desc(SB + SM_W2 + k * 256, 128, 6144);
    ds.ones = make_desc(SB + SM_ONES, 0, 0);
    CUtensorMap tw;
    cuuint64_t wdims[2] = {(cuuint64_t)EX, (cuuint64_t)CH};
    cuuint64_t wstrides[1] = {(cuuint64_t)EX * 2};
    cuuint32_t wbox[2] = {64, (cuuint32_t)CH};
    encode(&tw, CU_TENSOR_MAP_DATA_TYPE_BFLOAT16, 2, d_in[2], wdims, wstrides, wbox, estr, CU_TENSOR_MAP_INTERLEAVE_NONE,
           CU_TENSOR_MAP_SWIZZLE_128B, CU_TENSOR_MAP_L2_PROMOTION_L2_128B, CU_TENSOR_MAP_FLOAT_OOB_FILL_NONE);
    Split sp = {NTILES / num_sms, NTILES % num_sms, 1, 1 << 16, 0};
    if (sp.per_cta + 9 > MAX_ROWS) return;
    if (sp.extra && sp.extra * (8 * LENT + 1) <= num_sms && sp.per_cta >= 5 * LENT + 7) {
        sp.period = num_sms / sp.extra;
        sp.inv_period = 65535 / sp.period + 1;
        sp.lenders = sp.extra;
        for (int l = 0; l < sp.extra; l++)
            if (get_work((l + 1) * sp.period - sp.period / 2 - 1, sp).nA < 2 * LENT) sp.lenders = 0;
    }
    block_kernel<<<num_sms, NTHREADS, SM_TOTAL>>>(tm, tw, (const __nv_bfloat16*)d_in[0], (const __nv_bfloat16*)d_in[1],
                                             (const __nv_bfloat16*)d_in[3],
                                             (const __nv_bfloat16*)d_in[4], (const __nv_bfloat16*)d_in[5], (__nv_bfloat16*)d_out,
                                             scratch, ds, 0, sp);
}
```

```cpp
#include <cuda_runtime.h>
#include <cuda_bf16.h>
#include <cuda_fp16.h>
#include <cuda.h>
#include <stdint.h>

namespace cnx {

constexpr int IMG_H = 512, IMG_W = 512, CH = 96, EX = 384;
constexpr int TILE_W = 64;
constexpr int NTILES = (IMG_W / TILE_W) * IMG_H;
constexpr int NSLOT = 6;
constexpr int REGION_PX = 18;
constexpr int REGION_BYTES = REGION_PX * CH * 2;
constexpr int SLOT_BYTES = 4 * REGION_BYTES;
constexpr int A_LBO = 144, A_SBO = 12 * A_LBO;
constexpr int PREFETCH_ROWS = 3;
constexpr int NCONS = 3;
constexpr int CONS_THREADS = 128 * NCONS;
constexpr int NTHREADS = 128 + CONS_THREADS;
constexpr int MAX_ROWS = 52;
constexpr int TILE_BYTES = TILE_W * CH * 2, WARP_BYTES = TILE_BYTES / 4;
constexpr int S1_PASS = 1, S2_PASS = 1;
#define K_PASS 4
#define K_WAIT 20
#define K_STG 6
#define K_REL 6
#define K_ANCH 2
#define K_CVT 0
#define K_XPOS 1
#define K_CHAIN 3
#define K_LATE 1
#define K_FINE 1
#define K_SWAP 0
#define K_TAIL 0
#define W2_EARLY 6
#define S2_FIRST 2
#define ORDER_P 3
#define ORDER_Q 1
static_assert(MAX_ROWS <= 128, "one table entry per producer thread");
static_assert(2 * A_SBO == REGION_BYTES && REGION_BYTES % 128 == 0, "region layout");

constexpr uint32_t SB = 1024;
constexpr int SM_W1 = 0;
constexpr int SM_W2 = SM_W1 + CH * EX * 2;
constexpr int SM_RING = SM_W2 + CH * EX * 2;
constexpr int SM_BIASH = SM_RING + NSLOT * SLOT_BYTES;
constexpr int SM_RED = SM_BIASH + 384;
constexpr int RED_MAX = 0, RED_LAUNCH = 4, RED_SQ_EXP = 8, RED_SUM_EXP = 12, RED_INV_RHO = 16;
constexpr int SM_TILES = SM_RED + 256;
constexpr int SM_ONES = SM_TILES + MAX_ROWS * 4;
constexpr int SM_BAR = SM_ONES + 128;
constexpr int BAR_X = SM_BAR;
constexpr int BAR_A = BAR_X + NSLOT * 4 * 8;
constexpr int BAR_E = BAR_A + NSLOT * 4 * 8;
constexpr int BAR_PIN = BAR_E + NSLOT * 4 * 8;
constexpr int BAR_W = BAR_PIN + 8;
constexpr int BAR_F = BAR_W + 6 * 8;
constexpr int BAR_R = BAR_F + 8;
constexpr int SM_TOTAL = BAR_R + 16 * 8;
constexpr int SM_FILTER = SM_RING + (NSLOT - 1) * SLOT_BYTES + 9 * 128;
constexpr int SM_SQ = SM_W2;
constexpr int SQ_ROW = 128 * 16, SQ_WG = 6 * SQ_ROW;
static_assert(SM_ONES % 16 == 0 && SM_TOTAL <= 232448, "shared memory budget");

constexpr float KZ = 0.3292034911525734f;
constexpr uint32_t GELU_C2 = 0x40d940d9u;
constexpr float INV_2KZ = 0.5f / KZ;
constexpr unsigned SPIN_LIMIT = 1u << 19;

constexpr int MAX_CTAS = 255;
constexpr int W2_GROUPS = EX / 8;
#define K_LENT 3
constexpr int LENT = K_LENT, MAX_LENDERS = MAX_CTAS / (8 * LENT + 1);
struct Scratch {
    uint32_t w2h[EX * CH / 2];
    float w2max[EX];
    float bias[CH + 32];
    unsigned long long sums[EX / 4][32];
    __device__ __forceinline__ unsigned long long* sum(int e) { return &sums[e >> 2][e & 3]; }
    uint4 lent[MAX_LENDERS * LENT * 8 * 4 * 3 * 32];
    unsigned launch, pad0[31], early, pad1[31], prep, pad2[31], lent_out, pad3[31];
};
__device__ __align__(128) Scratch g_scratch;

#define PROF(k)

__device__ __forceinline__ uint32_t smem_u32(const void* p) { return (uint32_t)__cvta_generic_to_shared(p); }
__device__ __forceinline__ void mbar_init(uint32_t bar, uint32_t cnt) {
    asm volatile("mbarrier.init.shared::cta.b64 [%0], %1;" ::"r"(bar), "r"(cnt) : "memory");
}
__device__ __forceinline__ void mbar_arrive(uint32_t bar) {
    asm volatile("mbarrier.arrive.shared::cta.b64 _, [%0];" ::"r"(bar) : "memory");
}
__device__ __forceinline__ void mbar_expect_tx(uint32_t bar, uint32_t bytes) {
    asm volatile("mbarrier.arrive.expect_tx.shared::cta.b64 _, [%0], %1;" ::"r"(bar), "r"(bytes) : "memory");
}
__device__ __forceinline__ bool mbar_try(uint32_t bar, uint32_t par) {
    uint32_t ok;
    asm volatile("{\n.reg .pred p;\nmbarrier.try_wait.parity.shared::cta.b64 p, [%1], %2;\nselp.u32 %0, 1, 0, p;\n}\n"
                 : "=r"(ok) : "r"(bar), "r"(par) : "memory");
    return ok != 0;
}
__device__ __forceinline__ void mbar_wait(uint32_t bar, uint32_t par) {
    unsigned n = 0;
    while (!mbar_try(bar, par)) {
        if (++n > SPIN_LIMIT) __trap();
    }
}
__device__ __forceinline__ bool mbar_test(uint32_t bar, uint32_t par) {
    uint32_t ok;
    asm volatile("{\n.reg .pred p;\nmbarrier.test_wait.parity.shared::cta.b64 p, [%1], %2;\nselp.u32 %0, 1, 0, p;\n}\n"
                 : "=r"(ok) : "r"(bar), "r"(par) : "memory");
    return ok != 0;
}
__device__ __forceinline__ bool elect_one() {
    uint32_t ok;
    asm volatile("{\n.reg .pred p;\nelect.sync _|p, 0xffffffff;\nselp.u32 %0, 1, 0, p;\n}\n" : "=r"(ok));
    return ok != 0;
}
__device__ __forceinline__ uint32_t opaque(uint32_t v) { return __shfl_sync(~0u, v, threadIdx.x & 31); }
__device__ __forceinline__ uint32_t opaque_uniform(uint32_t v) { return __shfl_sync(~0u, v, 0); }
__device__ __forceinline__ void named_bar(int id, int n) { asm volatile("bar.sync %0, %1;" ::"r"(id), "r"(n) : "memory"); }
__device__ __forceinline__ void named_arrive(int id, int n) { asm volatile("bar.arrive %0, %1;" ::"r"(id), "r"(n) : "memory"); }
__device__ __forceinline__ void fence_async() { asm volatile("fence.proxy.async.shared::cta;" ::: "memory"); }
__device__ __forceinline__ uint64_t evict_first() {
    uint64_t p;
    asm("createpolicy.fractional.L2::evict_first.b64 %0, 1.0;" : "=l"(p));
    return p;
}
__device__ __forceinline__ void tma_row(uint32_t dst, const CUtensorMap* tm, uint32_t bar, int x, int y) {
    asm volatile("cp.async.bulk.tensor.3d.shared::cluster.global.mbarrier::complete_tx::bytes.L2::cache_hint [%0], [%1, {%3, %4, %5}], [%2], %6;"
                 ::"r"(dst), "l"(tm), "r"(bar), "r"(0), "r"(x), "r"(y), "l"(evict_first()) : "memory");
}
__device__ __forceinline__ void bulk_load_stream(uint32_t dst, const void* src, uint32_t bytes, uint32_t bar) {
    asm volatile("cp.async.bulk.shared::cluster.global.mbarrier::complete_tx::bytes.L2::cache_hint [%0], [%1], %2, [%3], %4;"
                 ::"r"(dst), "l"(src), "r"(bytes), "r"(bar), "l"(evict_first()) : "memory");
}
__device__ __forceinline__ void prefetch_l2(const void* src, uint32_t bytes) {
    asm volatile("cp.async.bulk.prefetch.L2.global [%0], %1;" ::"l"(src), "r"(bytes) : "memory");
}
__device__ __forceinline__ void tma_2d(uint32_t dst, const CUtensorMap* tm, uint32_t bar, int x, int y) {
    asm volatile("cp.async.bulk.tensor.2d.shared::cluster.global.mbarrier::complete_tx::bytes [%0], [%1, {%3, %4}], [%2];"
                 ::"r"(dst), "l"(tm), "r"(bar), "r"(x), "r"(y) : "memory");
}
__device__ __forceinline__ void bulk_load(uint32_t dst, const void* src, uint32_t bytes, uint32_t bar) {
    asm volatile("cp.async.bulk.shared::cluster.global.mbarrier::complete_tx::bytes [%0], [%1], %2, [%3];"
                 ::"r"(dst), "l"(src), "r"(bytes), "r"(bar) : "memory");
}
__device__ __forceinline__ void wg_fence() { asm volatile("wgmma.fence.sync.aligned;" ::: "memory"); }
__device__ __forceinline__ void wg_commit() { asm volatile("wgmma.commit_group.sync.aligned;" ::: "memory"); }
template <int N> __device__ __forceinline__ void wg_wait() { asm volatile("wgmma.wait_group.sync.aligned %0;" ::"n"(N) : "memory"); }
template <int N> __device__ __forceinline__ void pin(uint32_t (&d)[N]) {
#pragma unroll
    for (int q = 0; q < N; q++) asm volatile("" : "+r"(d[q])::"memory");
}
__device__ __forceinline__ void stg128(void* p, const uint32_t (&v)[4]) {
    asm volatile("st.global.v4.u32 [%0], {%1, %2, %3, %4};" ::"l"(p), "r"(v[0]), "r"(v[1]), "r"(v[2]), "r"(v[3]) : "memory");
}
__device__ __forceinline__ void ldg128(uint32_t (&v)[4], const void* p) {
    asm volatile("ld.global.L1::no_allocate.v4.u32 {%0, %1, %2, %3}, [%4];" : "=r"(v[0]), "=r"(v[1]), "=r"(v[2]), "=r"(v[3]) : "l"(p) : "memory");
}
__device__ __forceinline__ void ldg128_if(bool on, uint32_t (&v)[4], const void* p) {
    asm volatile("{\n.reg .pred p;\nsetp.ne.b32 p, %5, 0;\n@p ld.global.L1::no_allocate.v4.u32 {%0, %1, %2, %3}, [%4];\n}\n"
                 : "+r"(v[0]), "+r"(v[1]), "+r"(v[2]), "+r"(v[3]) : "l"(p), "r"((int)on) : "memory");
}
__device__ __forceinline__ uint4 ldg128_ordered(const void* p) {
    uint4 v;
    asm volatile("ld.global.nc.v4.u32 {%0, %1, %2, %3}, [%4];" : "=r"(v.x), "=r"(v.y), "=r"(v.z), "=r"(v.w) : "l"(p) : "memory");
    return v;
}
__host__ __device__ constexpr uint64_t make_desc(uint32_t addr, uint32_t lbo, uint32_t sbo) {
    return (uint64_t)((addr & 0x3FFFF) >> 4) | ((uint64_t)(lbo >> 4) << 16) | ((uint64_t)(sbo >> 4) << 32);
}
__device__ __forceinline__ void wgmma(uint32_t (&d)[12], uint32_t a0, uint32_t a1, uint32_t a2, uint32_t a3, uint64_t db, int acc) {
    asm volatile("{\n.reg .pred p;\nsetp.ne.b32 p, %17, 0;\n"
                 "wgmma.mma_async.sync.aligned.m64n48k16.f16.f16.f16 "
                 "{%0, %1, %2, %3, %4, %5, %6, %7, %8, %9, %10, %11}, "
                 "{%12, %13, %14, %15}, %16, p, 1, 1, 0;\n}\n"
                 : "+r"(d[0]), "+r"(d[1]), "+r"(d[2]), "+r"(d[3]), "+r"(d[4]), "+r"(d[5]), "+r"(d[6]), "+r"(d[7]), "+r"(d[8]), "+r"(d[9]), "+r"(d[10]), "+r"(d[11])
                 : "r"(a0), "r"(a1), "r"(a2), "r"(a3), "l"(db), "r"(acc));
}
__device__ __forceinline__ void wgmma(uint32_t (&d)[24], uint32_t a0, uint32_t a1, uint32_t a2, uint32_t a3, uint64_t db, int acc) {
    asm volatile("{\n.reg .pred p;\nsetp.ne.b32 p, %29, 0;\n"
                 "wgmma.mma_async.sync.aligned.m64n96k16.f16.f16.f16 "
                 "{%0, %1, %2, %3, %4, %5, %6, %7, %8, %9, %10, %11, %12, %13, %14, %15, %16, %17, %18, %19, %20, %21, %22, %23}, "
                 "{%24, %25, %26, %27}, %28, p, 1, 1, 0;\n}\n"
                 : "+r"(d[0]), "+r"(d[1]), "+r"(d[2]), "+r"(d[3]), "+r"(d[4]), "+r"(d[5]), "+r"(d[6]), "+r"(d[7]), "+r"(d[8]), "+r"(d[9]), "+r"(d[10]), "+r"(d[11]), "+r"(d[12]), "+r"(d[13]), "+r"(d[14]), "+r"(d[15]), "+r"(d[16]), "+r"(d[17]), "+r"(d[18]), "+r"(d[19]), "+r"(d[20]), "+r"(d[21]), "+r"(d[22]), "+r"(d[23])
                 : "r"(a0), "r"(a1), "r"(a2), "r"(a3), "l"(db), "r"(acc));
}
template <int ACC>
__device__ __forceinline__ void wgmma_rowsum(float (&d)[4], const uint32_t (&a)[4], uint64_t ones) {
    asm volatile("{\n.reg .pred p;\nsetp.ne.b32 p, %9, 0;\n"
                 "wgmma.mma_async.sync.aligned.m64n8k16.f32.bf16.bf16 {%0, %1, %2, %3}, {%4, %5, %6, %7}, %8, p, 1, 1, 0;\n}\n"
                 : "+f"(d[0]), "+f"(d[1]), "+f"(d[2]), "+f"(d[3])
                 : "r"(a[0]), "r"(a[1]), "r"(a[2]), "r"(a[3]), "l"(ones), "n"(ACC));
}
__device__ __forceinline__ void ldsm4(uint32_t (&r)[4], uint32_t addr) {
    asm volatile("ldmatrix.sync.aligned.m8n8.x4.shared.b16 {%0, %1, %2, %3}, [%4];"
                 : "=r"(r[0]), "=r"(r[1]), "=r"(r[2]), "=r"(r[3]) : "r"(addr) : "memory");
}
__device__ __forceinline__ void ldsm4_t(uint32_t (&r)[4], uint32_t addr) {
    asm volatile("ldmatrix.sync.aligned.m8n8.x4.trans.shared.b16 {%0, %1, %2, %3}, [%4];"
                 : "=r"(r[0]), "=r"(r[1]), "=r"(r[2]), "=r"(r[3]) : "r"(addr) : "memory");
}
__device__ __forceinline__ void stsm4(uint32_t addr, uint32_t a, uint32_t b, uint32_t c, uint32_t d) {
    asm volatile("stmatrix.sync.aligned.m8n8.x4.shared.b16 [%0], {%1, %2, %3, %4};"
                 ::"r"(addr), "r"(a), "r"(b), "r"(c), "r"(d) : "memory");
}
__device__ __forceinline__ uint32_t transpose8x8(uint32_t v) {
    uint32_t d; asm volatile("movmatrix.sync.aligned.m8n8.trans.b16 %0, %1;" : "=r"(d) : "r"(v)); return d;
}
__device__ __forceinline__ void spin_until(const unsigned* counter, unsigned target) {
    unsigned n = 0, c;
    do {
        asm volatile("ld.acquire.gpu.global.u32 %0, [%1];" : "=r"(c) : "l"(counter) : "memory");
        if (++n > SPIN_LIMIT) __trap();
    } while ((int)(c - target) < 0);
}
__device__ __forceinline__ void signal(unsigned* counter) {
    __syncwarp();
    if (elect_one()) asm volatile("red.release.gpu.global.add.u32 [%0], 1;" ::"l"(counter) : "memory");
    __syncwarp();
}
__device__ __forceinline__ void lds128(uint32_t& a, uint32_t& b, uint32_t& c, uint32_t& d, uint32_t addr) {
    asm volatile("ld.shared.v4.u32 {%0, %1, %2, %3}, [%4];" : "=r"(a), "=r"(b), "=r"(c), "=r"(d) : "r"(addr) : "memory");
}
__device__ __forceinline__ void lds64(uint32_t& a, uint32_t& b, uint32_t addr) {
    asm volatile("ld.shared.v2.u32 {%0, %1}, [%2];" : "=r"(a), "=r"(b) : "r"(addr) : "memory");
}
__device__ __forceinline__ void lds32(uint32_t& a, uint32_t addr) {
    asm volatile("ld.shared.u32 %0, [%1];" : "=r"(a) : "r"(addr) : "memory");
}
__device__ __forceinline__ int ldsi(uint32_t addr) {
    uint32_t v;
    lds32(v, addr);
    return (int)v;
}
__device__ __forceinline__ float ldsf(uint32_t addr) {
    uint32_t v;
    lds32(v, addr);
    return __uint_as_float(v);
}
__device__ __forceinline__ void sts32(uint32_t addr, uint32_t a) {
    asm volatile("st.shared.u32 [%0], %1;" ::"r"(addr), "r"(a) : "memory");
}
__device__ __forceinline__ void sts128(uint32_t addr, uint32_t a, uint32_t b, uint32_t c, uint32_t d) {
    asm volatile("st.shared.v4.u32 [%0], {%1, %2, %3, %4};" ::"r"(addr), "r"(a), "r"(b), "r"(c), "r"(d) : "memory");
}
__device__ __forceinline__ void sts64(uint32_t addr, uint32_t a, uint32_t b) {
    asm volatile("st.shared.v2.u32 [%0], {%1, %2};" ::"r"(addr), "r"(a), "r"(b) : "memory");
}
__device__ __forceinline__ void anchor(uint32_t addr, uint32_t a, uint32_t b, uint32_t c, uint32_t d) {
    asm volatile("{\n.reg .pred p;\nsetp.eq.b32 p, %0, 0;\n@p st.shared.v4.u32 [%0], {%1, %2, %3, %4};\n}\n"
                 ::"r"(addr), "r"(a), "r"(b), "r"(c), "r"(d) : "memory");
}
__device__ __forceinline__ uint32_t bf_fma(uint32_t a, uint32_t b, uint32_t c) {
    uint32_t d; asm("fma.rn.bf16x2 %0, %1, %2, %3;" : "=r"(d) : "r"(a), "r"(b), "r"(c)); return d;
}
__device__ __forceinline__ uint32_t bf_mul(uint32_t a, uint32_t b) {
    uint32_t d; asm("mul.rn.bf16x2 %0, %1, %2;" : "=r"(d) : "r"(a), "r"(b)); return d;
}
__device__ __forceinline__ uint32_t bf_absmax(uint32_t a, uint32_t b) {
    uint32_t d; asm("max.xorsign.abs.bf16x2 %0, %1, %2;" : "=r"(d) : "r"(a), "r"(b)); return d;
}
__device__ __forceinline__ uint32_t h_fma(uint32_t a, uint32_t b, uint32_t c) {
    uint32_t d; asm("fma.rn.f16x2 %0, %1, %2, %3;" : "=r"(d) : "r"(a), "r"(b), "r"(c)); return d;
}
__device__ __forceinline__ uint32_t h_mul(uint32_t a, uint32_t b) {
    uint32_t d; asm("mul.rn.f16x2 %0, %1, %2;" : "=r"(d) : "r"(a), "r"(b)); return d;
}
__device__ __forceinline__ uint32_t h_round8(uint32_t v) { return (v + 0x00040004u) & 0xfff8fff8u; }
__device__ __forceinline__ uint32_t h_tanh(uint32_t a) {
    uint32_t d; asm("tanh.approx.f16x2 %0, %1;" : "=r"(d) : "r"(a)); return d;
}
__device__ __forceinline__ uint32_t pack_h2(float lo, float hi) {
    uint32_t d; asm("cvt.rn.f16x2.f32 %0, %1, %2;" : "=r"(d) : "f"(hi), "f"(lo)); return d;
}
__device__ __forceinline__ uint32_t pack_bf2(float lo, float hi) {
    uint32_t d; asm("cvt.rn.bf16x2.f32 %0, %1, %2;" : "=r"(d) : "f"(hi), "f"(lo)); return d;
}
__device__ __forceinline__ float bf_lo(uint32_t v) { return __uint_as_float(v << 16); }
__device__ __forceinline__ float bf_hi(uint32_t v) { return __uint_as_float(v & 0xffff0000u); }
__device__ __forceinline__ float h_lo(uint32_t v) { return __low2float(*reinterpret_cast<__half2*>(&v)); }
__device__ __forceinline__ float h_hi(uint32_t v) { return __high2float(*reinterpret_cast<__half2*>(&v)); }
__device__ __forceinline__ float warp_absmax(uint32_t v) {
    return __uint_as_float(__reduce_max_sync(~0u, max((v & 0x7fffu) << 16, v & 0x7fff0000u)));
}
__device__ __forceinline__ uint32_t gelu2(uint32_t z) {
    uint32_t p = h_fma(z, z, GELU_C2);
    uint32_t t = h_tanh(h_mul(z, p));
    return h_fma(z, t, z);
}
__device__ __forceinline__ float grn_norm(float ss) {
    float r;
    asm("sqrt.approx.f32 %0, %1;" : "=f"(r) : "f"(fmaf(ss, INV_2KZ * INV_2KZ, 1e-6f)));
    return r;
}
__device__ __forceinline__ float pow2i(int e) { return __uint_as_float((uint32_t)(e + 127) << 23); }
__device__ __forceinline__ int ilog2f(float v) {
    int e = (int)((__float_as_uint(v) >> 23) & 0xff) - 127;
    return max(-100, min(100, e));
}

__device__ __forceinline__ int square_exp(float w1max) {
    const int e = w1max > 0.f ? 4 - ilog2f(2.f * KZ * 96.f * w1max) : 0;
    return (e >= 0 && e <= 6) ? 0 : max(-14, min(e, 14));
}
__device__ __forceinline__ int sum_exp(float w1max) {
    return w1max > 0.f ? max(-90, min(90, 33 - 2 * ilog2f(2.f * KZ * 96.f * w1max))) : 0;
}
__device__ __forceinline__ float row_scale(float m) { return m > 0.f ? pow2i(2 - ilog2f(m)) : 1.f; }

struct Split {
    int per_cta, extra, period, inv_period, lenders;
    __host__ __device__ __forceinline__ int longer_before(int cta) const {
        const int n = (cta + period / 2) * inv_period >> 16;
        return n < extra ? n : extra;
    }
};
struct Work {
    int tA, tB, nA, nB, dir, rows, lent, index;
    __device__ __forceinline__ int tile(int j) const { return j < nA ? tA + dir * j : tB + dir * (j - nA); }
};
__host__ __device__ __forceinline__ Work get_work(int cta, const Split& sp) {
    Work w;
    const int before = sp.longer_before(cta), longer = sp.longer_before(cta + 1) - before;
    w.lent = longer && sp.lenders ? LENT : 0;
    w.index = longer ? before : cta - before;
    const int t0 = cta * sp.per_cta + before, t1 = t0 + sp.per_cta + longer;
    const int tm = t1 < (t0 | 511) + 1 ? t1 : (t0 | 511) + 1;
    const bool swap = t1 > tm && t1 - tm < tm - t0, down = cta & 1;
    w.nA = swap ? t1 - tm : tm - t0;
    w.nB = t1 - t0 - w.nA;
    w.tA = down ? (swap ? tm : t0) : (swap ? t1 : tm) - 1;
    w.tB = down ? (swap ? t0 : tm) : (swap ? tm : t1) - 1;
    w.dir = down ? 1 : -1;
    w.rows = w.nA + 2 + (w.nB ? w.nB + 2 : 0);
    return w;
}
__device__ __forceinline__ int row_code(const Work& w, int i) {
    const bool in_a = i < w.nA + 2;
    const int t = in_a ? w.tA : w.tB;
    return ((t & 511) + w.dir * ((in_a ? i : i - (w.nA + 2)) - 1)) << 16 | (t >> 9) * TILE_W;
}
__device__ __forceinline__ uint32_t tile_offset(int tile) { return ((tile & 511) * IMG_W + (tile >> 9) * TILE_W) * (CH * 2); }
__device__ __forceinline__ int tile_order(int j, int n) {
    const int olds = (j / ORDER_P) * ORDER_Q + max(0, j % ORDER_P - (ORDER_P - ORDER_Q));
    return (j % ORDER_P >= ORDER_P - ORDER_Q) ? olds : n - 1 - (j - olds);
}
__device__ __forceinline__ void issue_region(const CUtensorMap* tm, uint32_t dst, uint32_t bar, int warp, int code) {
    mbar_expect_tx(bar, REGION_BYTES);
    tma_row(dst, tm, bar, (code & 0xffff) + (16 * warp - 1), code >> 16);
}

template <class Event>
__device__ __forceinline__ void conv_producer(const Work& wk, const CUtensorMap* tm, uint32_t sb, int warp, Event event) {
    const int lane = threadIdx.x & 31;
    const int j = lane & 15, grp = lane >> 4;
    const uint32_t reg0 = sb + SM_RING + warp * REGION_BYTES;
    const uint32_t bars = sb + SM_BAR + warp * 8;
    if (lane >= PREFETCH_ROWS && lane < 3 * NSLOT) mbar_init(bars + lane * 32, 1);
    if (lane >= 28) mbar_init(sb + BAR_R + ((lane - 28) * 4 + warp) * 8, 1);
    if (lane == 0 && warp == 0) mbar_init(sb + BAR_PIN, 1);
    if (warp * 32 + lane < MAX_ROWS) {
        const int i = warp * 32 + lane, before = min(i / 5, wk.lent);
        const bool back = i % 5 == 0 && i > 0 && i / 5 <= wk.lent;
        sts32(sb + SM_TILES + i * 4, back ? tile_offset(wk.tile(before - 1)) | before
                                          : tile_offset(wk.tile(wk.lent + tile_order(i - before, wk.nA + wk.nB - NCONS - wk.lent))));
    }
    const uint32_t ld64 = opaque(reg0 + grp * 8 * 192 + j * 8), ld32 = opaque(reg0 + grp * 8 * 192 + 128 + j * 4);
    const uint32_t st64 = opaque(reg0 + grp * A_SBO + (j >> 1) * A_LBO + (j & 1) * 8);
    const uint32_t st32 = opaque(reg0 + grp * A_SBO + (8 + (j >> 2)) * A_LBO + (j & 3) * 4);
    fence_async();
    named_bar(0, NTHREADS);
    uint32_t w[3][3][3];
    mbar_wait(sb + BAR_F, 0);
#pragma unroll
    for (int tap = 0; tap < 9; tap++) {
        const uint32_t p = sb + SM_FILTER + (3 + wk.dir * 3 * (tap / 3 - 1) + tap % 3) * (CH * 2);
        lds64(w[tap / 3][tap % 3][0], w[tap / 3][tap % 3][1], p + 8 * j);
        lds32(w[tap / 3][tap % 3][2], p + 128 + 4 * j);
    }
#pragma unroll
    for (int tap = 0; tap < 9; tap++) sts64(reg0 + (NSLOT - 1) * SLOT_BYTES + tap * 128 + j * 8, w[tap / 3][tap % 3][1], w[tap / 3][tap % 3][0]);
#pragma unroll
    for (int tap = 0; tap < 9; tap++) lds64(w[tap / 3][tap % 3][1], w[tap / 3][tap % 3][0], reg0 + (NSLOT - 1) * SLOT_BYTES + tap * 128 + j * 8);
    fence_async();
    named_bar(1, 128);
    static_assert(2 * PREFETCH_ROWS == NSLOT && SLOT_BYTES % 32 == 0, "slot arithmetic");
    uint32_t bo = 0, par = 0, pbo = PREFETCH_ROWS * 32, ppar = 1;
    int px, py;
    auto request = [&]() {
        mbar_wait(bars + (BAR_E - SM_BAR) + pbo, ppar);
        if (elect_one()) {
            mbar_expect_tx(bars + pbo, REGION_BYTES);
            tma_row(reg0 + pbo * (SLOT_BYTES / 32), tm, bars + pbo, px, py);
        }
    };
    auto advance = [&]() {
        bo += 32;
        if (bo == NSLOT * 32) { bo = 0; par ^= 1; }
        pbo += 32;
        if (pbo == NSLOT * 32) { pbo = 0; ppar ^= 1; }
    };
    auto aim = [&](int row) {
        const int code = row_code(wk, row);
        px = (code & 0xffff) + (16 * warp - 1);
        py = code >> 16;
    };
    uint32_t accB[8][3], accC[8][3];
    int r = 0;
#pragma unroll 1
    while (r < wk.rows) {
        if (r == 0 || r == wk.nA + 2) {
            const uint32_t bo0 = bo;
            uint32_t bo1;
#pragma unroll 1
            for (int k = 0; k < 2; k++, r++) {
                mbar_wait(bars + bo, par);
                bo1 = bo;
                aim(r + PREFETCH_ROWS);
                request();
                advance();
            }
            const uint32_t so0 = bo0 * (SLOT_BYTES / 32), so1 = bo1 * (SLOT_BYTES / 32);
#pragma unroll
            for (int p = 0; p < 10; p++) {
                uint32_t u[3], v[3];
                lds64(u[0], u[1], so0 + ld64 + p * 192);
                lds32(u[2], so0 + ld32 + p * 192);
                lds64(v[0], v[1], so1 + ld64 + p * 192);
                lds32(v[2], so1 + ld32 + p * 192);
#pragma unroll
                for (int dx = 0; dx < 3; dx++) {
                    const int o = p - dx;
                    if (o < 0 || o > 7) continue;
#pragma unroll
                    for (int q = 0; q < 3; q++) {
                        accB[o][q] = bf_fma(v[q], w[1][dx][q], dx == 0 ? bf_mul(u[q], w[0][dx][q]) : bf_fma(u[q], w[0][dx][q], accB[o][q]));
                        accC[o][q] = dx == 0 ? bf_mul(v[q], w[0][dx][q]) : bf_fma(v[q], w[0][dx][q], accC[o][q]);
                    }
                }
            }
            anchor(ld64, accB[7][0], accB[7][1], accB[7][2], 0);
            __syncwarp();
            if (elect_one()) {
                mbar_arrive(bars + (BAR_A - SM_BAR) + bo0);
                mbar_arrive(bars + (BAR_E - SM_BAR) + bo0);
                mbar_arrive(bars + (BAR_A - SM_BAR) + bo1);
                mbar_arrive(bars + (BAR_E - SM_BAR) + bo1);
            }
        }
        int end = wk.rows;
        const int marks[4] = {wk.rows - PREFETCH_ROWS, wk.rows - 11, wk.nA + 2, wk.nA + 2 - PREFETCH_ROWS};
#pragma unroll
        for (int k = 0; k < 4; k++) end = marks[k] > r ? min(end, marks[k]) : end;
        const bool fetch = r < wk.rows - PREFETCH_ROWS;
        aim(r + PREFETCH_ROWS);
        px = opaque_uniform(px);
        const int py_end = opaque_uniform(py + wk.dir * (end - r));
        r = end;
#pragma unroll 1
        do {
            mbar_wait(bars + bo, par);
            const uint32_t so = bo * (SLOT_BYTES / 32);
            uint32_t out[8][3];
#pragma unroll
            for (int p = 0; p < 10; p++) {
                uint32_t xv[3];
                lds64(xv[0], xv[1], so + ld64 + p * 192);
                lds32(xv[2], so + ld32 + p * 192);
#pragma unroll
                for (int dx = 0; dx < 3; dx++) {
                    const int o = p - dx;
                    if (o < 0 || o > 7) continue;
#pragma unroll
                    for (int q = 0; q < 3; q++) {
                        out[o][q] = bf_fma(xv[q], w[2][dx][q], dx == 0 ? accB[o][q] : out[o][q]);
                        accB[o][q] = bf_fma(xv[q], w[1][dx][q], dx == 0 ? accC[o][q] : accB[o][q]);
                        accC[o][q] = dx == 0 ? bf_mul(xv[q], w[0][dx][q]) : bf_fma(xv[q], w[0][dx][q], accC[o][q]);
                    }
                }
            }
            __syncwarp();
#pragma unroll
            for (int o = 0; o < 8; o++) {
                sts64(so + st64 + o * 16, out[o][0], out[o][1]);
                sts32(so + st32 + o * 16, out[o][2]);
            }
            __syncwarp();
            if (elect_one()) mbar_arrive(bars + (BAR_A - SM_BAR) + bo);
            if (fetch) request();
            advance();
            py += wk.dir;
        } while (py != py_end);
        if (((wk.rows - r) & ~8) == PREFETCH_ROWS) event(wk.rows - r == PREFETCH_ROWS);
    }
}

template <bool SCALED, int K0 = 0, int K1 = 3>
__device__ __forceinline__ void gelu_sq(uint32_t (&d)[24], uint32_t (&keep)[24], uint32_t sq_addr, uint32_t scale2) {
    pin(d);
#pragma unroll
    for (int k = K0; k < K1; k++) {
        uint32_t hs[4];
        lds128(hs[0], hs[1], hs[2], hs[3], sq_addr + k * SQ_ROW);
#pragma unroll
        for (int q = 0; q < 4; q++) {
            uint32_t g0 = gelu2(d[8 * k + 2 * q]), g1 = gelu2(d[8 * k + 2 * q + 1]);
            keep[8 * k + 2 * q] = g0;
            keep[8 * k + 2 * q + 1] = g1;
            if (SCALED) { g0 = h_mul(g0, scale2); g1 = h_mul(g1, scale2); }
            hs[q] = h_fma(g1, g1, h_fma(g0, g0, hs[q]));
        }
        sts128(sq_addr + k * SQ_ROW, hs[0], hs[1], hs[2], hs[3]);
    }
}
__device__ __forceinline__ void gelu_sq_reg(uint32_t (&d)[24], uint32_t (&hs)[12]) {
    pin(d);
#pragma unroll
    for (int q = 0; q < 12; q++) {
        const uint32_t g0 = gelu2(d[2 * q]), g1 = gelu2(d[2 * q + 1]);
        hs[q] = h_fma(g1, g1, h_fma(g0, g0, hs[q]));
    }
}
__device__ __forceinline__ void gelu_to(uint32_t (&g)[12], uint32_t (&d)[12]) {
    pin(d);
#pragma unroll
    for (int q = 0; q < 12; q++) g[q] = gelu2(d[q]);
    pin(g);
}
__device__ __forceinline__ void load_tile(uint32_t (&raw)[6][4], uint32_t addr) {
#pragma unroll
    for (int s = 0; s < 6; s++) ldsm4(raw[s], addr + s * 2 * A_LBO);
}
__device__ __forceinline__ uint2 ln_stats(const uint32_t (&raw)[6][4], uint64_t ones) {
    constexpr int NS = 6 / K_CHAIN;
    uint32_t sq[NS][4];
#pragma unroll
    for (int s = 0; s < 6; s++)
#pragma unroll
        for (int q = 0; q < 4; q++) sq[s % NS][q] = s < NS ? bf_mul(raw[s][q], raw[s][q]) : bf_fma(raw[s][q], raw[s][q], sq[s % NS][q]);
    float sum[4], ssq[4];
    wg_fence();
    wgmma_rowsum<0>(sum, raw[0], ones);
#pragma unroll
    for (int s = 1; s < 6; s++) wgmma_rowsum<1>(sum, raw[s], ones);
    wgmma_rowsum<0>(ssq, sq[0], ones);
#pragma unroll
    for (int s = 1; s < NS; s++) wgmma_rowsum<1>(ssq, sq[s], ones);
    wg_commit();
    wg_wait<0>();
    uint32_t st[2];
#pragma unroll
    for (int h = 0; h < 2; h++) {
        asm volatile("" : "+f"(sum[2 * h]), "+f"(ssq[2 * h])::"memory");
        const float mean = sum[2 * h] * (1.f / CH);
        const float var = fmaxf(fmaf(ssq[2 * h], 1.f / CH, -mean * mean), 0.f);
        float rstd;
        asm("rsqrt.approx.ftz.f32 %0, %1;" : "=f"(rstd) : "f"(var + 1e-5f));
        rstd = bf_lo(pack_bf2(rstd * (K_CVT == 0 ? KZ : KZ * 0x1p-112f), 0.f));
        st[h] = pack_bf2(rstd, -mean * rstd);
    }
    return make_uint2(st[0], st[1]);
}
__device__ __forceinline__ void ln_apply(uint32_t (&a)[6][4], const uint2& st) {
    const uint32_t sc[2] = {__byte_perm(st.x, 0, 0x1010), __byte_perm(st.y, 0, 0x1010)};
    const uint32_t sh[2] = {__byte_perm(st.x, 0, 0x3232), __byte_perm(st.y, 0, 0x3232)};
#pragma unroll
    for (int s = 0; s < 6; s++)
#pragma unroll
        for (int q = 0; q < 4; q++) {
            const uint32_t v = bf_fma(a[s][q], sc[q & 1], sh[q & 1]);
            a[s][q] = K_CVT == 0 ? pack_h2(bf_lo(v), bf_hi(v)) : (v & 0x7fff7fffu) * 7u + v;
        }
}
struct Cursor {
    int slot;
    uint32_t par;
    __device__ __forceinline__ void advance(int n) {
        slot += n;
        if (slot >= NSLOT) { slot -= NSLOT; par ^= 1; }
    }
};
struct Descs {
    uint64_t w1[8][6];
    uint64_t w2[24];
    uint64_t ones;
};
template <int E0, int N>
__device__ __forceinline__ void gemm1_chunk(uint32_t (&d)[N], const uint32_t (&a)[6][4], const Descs& ds, int zero) {
#pragma unroll
    for (int s = 0; s < 6; s++) wgmma(d, a[s][0], a[s][1], a[s][2], a[s][3], ds.w1[E0 / 48][s], s ? 1 : zero);
}
template <int E0, int N>
__device__ __forceinline__ void gemm2_chunk(uint32_t (&acc)[24], const uint32_t (&g)[N], const Descs& ds) {
#pragma unroll
    for (int s = 0; s < N / 4; s++) wgmma(acc, g[4 * s], g[4 * s + 1], g[4 * s + 2], g[4 * s + 3], ds.w2[E0 / 16 + s], 1);
}

__global__ void __launch_bounds__(NTHREADS, 1)
block_kernel(const __grid_constant__ CUtensorMap tmap, const __grid_constant__ CUtensorMap tmap_w1,
             const __nv_bfloat16* __restrict__ x, const __nv_bfloat16* __restrict__ dw, const __nv_bfloat16* __restrict__ w2,
             const __nv_bfloat16* __restrict__ gamma, const __nv_bfloat16* __restrict__ beta, __nv_bfloat16* __restrict__ out,
             Scratch* __restrict__ sc, const __grid_constant__ Descs ds,
             const int zero, const __grid_constant__ Split sp) {
    extern __shared__ __align__(1024) uint8_t smem[];
    constexpr uint32_t sb = SB;
    const int tid = threadIdx.x;
    const Work wk = get_work(blockIdx.x, sp);
    constexpr uint32_t s_red = sb + SM_RED;
    if (smem_u32(smem) != SB) __trap();

    PROF(0);
    const int warp_id = __shfl_sync(~0u, tid >> 5, 0);
    const int cw = warp_id - 4, wgi = cw >> 2, w4 = warp_id & 3;
    if (elect_one()) {
        if (warp_id < 8) {
            mbar_init(sb + BAR_X + warp_id * 8, 1);
            if (warp_id < 4) mbar_init(sb + BAR_X + (warp_id + 8) * 8, 1);
            fence_async();
#pragma unroll 1
            for (int r = warp_id >> 2; r < PREFETCH_ROWS; r += 2)
                issue_region(&tmap, sb + SM_RING + r * SLOT_BYTES + w4 * REGION_BYTES, sb + BAR_X + (r * 4 + w4) * 8, w4,
                             ((wk.tA & 511) + wk.dir * (r - 1)) << 16 | (wk.tA >> 9) * TILE_W);
        } else if (warp_id < 15) {
            const int b = warp_id - 8;
            mbar_init(sb + BAR_W + b * 8, 1);
            fence_async();
            mbar_expect_tx(sb + BAR_W + b * 8, b < 6 ? 64 * CH * 2 : 9 * CH * 2);
            if (b < 6) tma_2d(sb + SM_W2 + b * (64 * CH * 2), &tmap_w1, sb + BAR_W + b * 8, 64 * b, 0);
            else bulk_load(sb + SM_FILTER, dw, 9 * CH * 2, sb + BAR_F);
        }
    }
    __syncwarp();
    const int ntiles = wk.nA + wk.nB;
    const int wg = warp_id >> 2;
    int first = wg;
    uint32_t a[6][4], acc[24], tile_off, next_off, stage, inv_rho2 = 0, rpar = 0, bias_addr, lane16, lane_off;
    auto set_lane = [&](uint32_t lane) {
        bias_addr = sb + SM_BIASH + (lane & 3) * 96;
        lane16 = lane * 16;
        lane_off = ((lane >> 2) * CH + 8 * (lane & 3)) * 2;
    };
    const uint32_t bar_r = sb + BAR_R + warp_id * 8;
    auto load_bias = [&](uint32_t (&acc)[24]) {
#pragma unroll
        for (int q = 0; q < 6; q++) lds128(acc[4 * q], acc[4 * q + 1], acc[4 * q + 2], acc[4 * q + 3], bias_addr + q * 16);
    };
    auto load_frags = [&](bool on) {
#pragma unroll
        for (int s = 0; s < 6; s++) ldg128_if(on, a[s], reinterpret_cast<const char*>(out) + next_off + w4 * WARP_BYTES + lane16 + s * 512);
    };
    auto load_first = [&]() {
#pragma unroll
        for (int s = 0; s < 6; s++) ldg128(a[s], reinterpret_cast<const char*>(out) + next_off + w4 * WARP_BYTES + lane16 + s * 512);
    };
    auto stage_x = [&]() {
        if (elect_one()) {
            mbar_expect_tx(bar_r, WARP_BYTES);
            bulk_load_stream(stage, reinterpret_cast<const char*>(x) + tile_off + w4 * WARP_BYTES, WARP_BYTES, bar_r);
        }
    };
    auto epilogue = [&](uint32_t (&acc)[24]) {
        pin(acc);
        rpar ^= 1;
        uint4* op = reinterpret_cast<uint4*>(reinterpret_cast<char*>(out) + tile_off + w4 * WARP_BYTES + lane_off);
#pragma unroll
        for (int h = 0; h < 2; h++)
#pragma unroll
            for (int m = 0; m < 3; m++) {
                uint32_t xin[4], o[4];
                lds128(xin[0], xin[1], xin[2], xin[3], stage + lane_off + h * 1536 + m * 64);
#pragma unroll
                for (int q = 0; q < 4; q++) {
                    const uint32_t v = acc[2 * (4 * m + q) + h];
                    o[q] = bf_fma(pack_bf2(h_lo(v), h_hi(v)), inv_rho2, xin[q]);
                }
                __stcs(op + h * 96 + m * 4, make_uint4(o[0], o[1], o[2], o[3]));
            }
        __syncwarp();
    };
    const bool helps = !wk.lent && wk.index < 8 * LENT * sp.lenders;
    const int help_slot = (wk.rows + 2) % NSLOT;
    const uint32_t s_help = sb + SM_RING + help_slot * SLOT_BYTES + SQ_WG;
    auto reduce = [&](int q, uint32_t lane, bool leader) {
        const int part = lane >> 2, ch = 32 * q + 8 * (part >> 1) + 2 * (lane & 3) + (part & 1);
        uint32_t sq_e, sum_e;
        lds64(sq_e, sum_e, s_red + RED_SQ_EXP);
        const float to_fixed = pow2i(sum_e - 2 * sq_e);
        unsigned long long* dst = sc->sum(ch);
        named_bar(11, CONS_THREADS);
        const unsigned in_piece = ch - wk.index % 8 * 48;
        float helped = 0.f;
        if (helps && in_piece < 48) {
            uint32_t u[4];
            lds128(u[0], u[1], u[2], u[3], s_help + in_piece * 16);
            helped = ((__uint_as_float(u[0]) + __uint_as_float(u[1])) + (__uint_as_float(u[2]) + __uint_as_float(u[3]))) * pow2i(2 * sq_e);
        }
        float f[8] = {};
        int slot = wk.rows % NSLOT;
#pragma unroll 1
        for (int i = 0; i < NCONS; i++) {
            if (i == NCONS - 1) {
                named_bar(13, CONS_THREADS);
                if (leader) {
                    fence_async();
                    bulk_load(sb + SM_W2, sc->w2h, (NCONS - 1) * SQ_WG, sb + BAR_W);
                }
                __syncwarp();
                named_bar(14, NTHREADS);
            }
            const uint32_t src = sb + lane * 16 + q * SQ_ROW + (q < 6 ? SM_SQ + i * SQ_WG : sq_e ? SM_SQ + (NCONS - 1 + i) * SQ_WG : SM_RING + slot * SLOT_BYTES - SQ_WG);
            slot = slot == NSLOT - 1 ? 0 : slot + 1;
#pragma unroll
            for (int r = 0; r < 4; r++) {
                uint32_t u[4];
                lds128(u[0], u[1], u[2], u[3], src + r * 512);
#pragma unroll
                for (int k = 0; k < 4; k++) { f[2 * k] += h_lo(u[k]); f[2 * k + 1] += h_hi(u[k]); }
            }
        }
        const bool b2 = part & 4, b1 = part & 2, b0 = part & 1;
        float r4[4], r2[2];
#pragma unroll
        for (int k = 0; k < 4; k++) r4[k] = (b2 ? f[k + 4] : f[k]) + __shfl_xor_sync(~0u, b2 ? f[k] : f[k + 4], 16);
#pragma unroll
        for (int k = 0; k < 2; k++) r2[k] = (b1 ? r4[k + 2] : r4[k]) + __shfl_xor_sync(~0u, b1 ? r4[k] : r4[k + 2], 8);
        const float tot = (b0 ? r2[1] : r2[0]) + __shfl_xor_sync(~0u, b0 ? r2[0] : r2[1], 4);
        atomicAdd(dst, __float2ull_rn(fminf((tot + helped) * to_fixed, 0x1p47f)) << 8 | 1);
    };
    const uint32_t s_fac = sb + SM_RING + (wk.rows + 1) % NSLOT * SLOT_BYTES + SQ_WG;
    if (warp_id < 4) {
        const bool prepares = gridDim.x - blockIdx.x <= W2_GROUPS / 2;
        const int q = (gridDim.x - 1 - blockIdx.x) * 2 + (w4 >> 1);
        auto lent_tile = [&]() {
            return tile_offset(get_work((wk.index / (8 * LENT) + 1) * sp.period - sp.period / 2 - 1, sp).tile(wk.index / 8 % LENT));
        };
        conv_producer(wk, &tmap, sb, warp_id, [&](bool second) {
            if (!second) {
                if (blockIdx.x == 0) {
#pragma unroll 1
                    for (int e = tid; e < EX; e += 128) *sc->sum(e) = 0;
                    sc->bias[tid] = 0.f;
                    signal(&sc->early);
                }
                if (wk.lent) signal(&sc->early);
            } else if (prepares || helps) {
                spin_until(&sc->early, (ldsi(s_red + RED_LAUNCH) + 1) * 4 * (sp.lenders + 1));
                if (elect_one()) {
                    if (helps) prefetch_l2(reinterpret_cast<const char*>(out) + lent_tile() + w4 * WARP_BYTES, WARP_BYTES);
                    if (prepares) { prefetch_l2(w2 + 8 * q * CH, 8 * CH * 2); prefetch_l2(beta + 8 * q, 16); }
                }
            }
        });
        const int lane = opaque(tid & 31), g = lane >> 2, t = lane & 3;
        const unsigned epoch = ldsi(s_red + RED_LAUNCH);
        set_lane(lane);
        const int i0 = w4 * 32 + lane;
        float gam[3], rmax[3];
#pragma unroll
        for (int m = 0; m < 3; m++) {
            unsigned short v;
            asm volatile("ld.global.nc.u16 %0, [%1];" : "=h"(v) : "l"(gamma + i0 + 128 * m) : "memory");
            gam[m] = bf_lo(v);
        }
        if (prepares) {
            const int half = w4 & 1;
            uint32_t u[3][2], rmax = 0;
#pragma unroll
            for (int m = 0; m < 3; m++) {
                const uint4 w = ldg128_ordered(w2 + (8 * q + g) * CH + 32 * m + 8 * t);
                rmax = bf_absmax(bf_absmax(rmax, bf_absmax(w.x, w.y)), bf_absmax(w.z, w.w));
                u[m][0] = half ? w.z : w.x;
                u[m][1] = half ? w.w : w.y;
            }
            const float bt = __bfloat162float(beta[8 * q + g]);
            rmax = bf_absmax(rmax, __shfl_xor_sync(~0u, rmax, 1));
            rmax = bf_absmax(rmax, __shfl_xor_sync(~0u, rmax, 2));
            const float mx = fmaxf(fabsf(bf_lo(rmax)), fabsf(bf_hi(rmax))), rs = row_scale(mx);
            if (t == 0 && !half) sc->w2max[8 * q + g] = mx;
#pragma unroll
            for (int m = 0; m < 3; m++) {
                float f[4];
#pragma unroll
                for (int k = 0; k < 2; k++) {
                    const float lo = bf_lo(u[m][k]), hi = bf_hi(u[m][k]);
                    sc->w2h[(4 * m + 2 * half + k) * 1536 + q * 32 + lane] = transpose8x8(pack_h2(lo * rs, hi * rs));
                    f[2 * k] = lo * bt;
                    f[2 * k + 1] = hi * bt;
                }
                const float r0 = (g & 2 ? f[2] : f[0]) + __shfl_xor_sync(~0u, g & 2 ? f[0] : f[2], 8);
                const float r1 = (g & 2 ? f[3] : f[1]) + __shfl_xor_sync(~0u, g & 2 ? f[1] : f[3], 8);
                float r = (g & 1 ? r1 : r0) + __shfl_xor_sync(~0u, g & 1 ? r0 : r1, 4);
                r += __shfl_xor_sync(~0u, r, 16);
                if (g < 4) atomicAdd(&sc->bias[32 * m + 8 * t + 4 * half + g], r);
            }
            asm volatile("fence.proxy.async.global;" ::: "memory");
            signal(&sc->prep);
        }
        const int piece = wk.index;
        if (helps) {
            next_off = lent_tile();
            load_first();
            uint32_t d[12], gl[12];
            wg_fence();
#pragma unroll
            for (int s = 0; s < 6; s++) wgmma(d, a[s][0], a[s][1], a[s][2], a[s][3], ds.w1[0][s] + piece % 8 * (6 * 1536 / 16), s ? 1 : 0);
            wg_commit();
            wg_wait<0>();
            gelu_to(gl, d);
#pragma unroll
            for (int s = 0; s < 3; s++) sc->lent[(((piece / (8 * LENT) * 4 + w4) * (8 * LENT) + piece % (8 * LENT)) * 3 + s) * 32 + lane] = make_uint4(gl[4 * s], gl[4 * s + 1], gl[4 * s + 2], gl[4 * s + 3]);
            float f[6], r[3];
#pragma unroll
            for (int j = 0; j < 6; j++) {
                const float lo = fmaf(h_lo(gl[2 * j]), h_lo(gl[2 * j]), h_lo(gl[2 * j + 1]) * h_lo(gl[2 * j + 1]));
                const float hi = fmaf(h_hi(gl[2 * j]), h_hi(gl[2 * j]), h_hi(gl[2 * j + 1]) * h_hi(gl[2 * j + 1]));
                f[j] = (g & 1 ? hi : lo) + __shfl_xor_sync(~0u, g & 1 ? lo : hi, 4);
            }
            mbar_wait(sb + BAR_E + help_slot * 32 + 24, (wk.rows - 4) / NSLOT & 1);
#pragma unroll
            for (int j = 0; j < 3; j++) {
                r[j] = (g & 2 ? f[j + 3] : f[j]) + __shfl_xor_sync(~0u, g & 2 ? f[j] : f[j + 3], 8);
                r[j] += __shfl_xor_sync(~0u, r[j], 16);
                sts32(s_help + (8 * j + 12 * (g & 2) + 2 * t + (g & 1)) * 16 + w4 * 4, __float_as_uint(r[j]));
            }
        }
        const bool leader = warp_id == 0 && lane == 0;
        const float w1max = ldsf(s_red + RED_MAX), from_fixed = pow2i(-ldsi(s_red + RED_SUM_EXP));
        const bool plain = ldsi(s_red + RED_SQ_EXP) == 0;
        auto load_upper = [&]() {
            bulk_load(sb + SM_W2 + NCONS * SQ_WG, reinterpret_cast<const char*>(sc->w2h) + NCONS * SQ_WG, EX * CH * 2 - NCONS * SQ_WG, sb + BAR_W);
        };
        if (leader) {
            spin_until(&sc->prep, (epoch + 1) * 2 * W2_GROUPS);
            asm volatile("fence.proxy.async.global;" ::: "memory");
            fence_async();
            mbar_expect_tx(sb + BAR_W, EX * CH * 2);
            if (plain) load_upper();
        }
        __syncwarp();
        named_bar(1, 128);
#pragma unroll
        for (int m = 0; m < 3; m++) rmax[m] = __ldcg(&sc->w2max[i0 + 128 * m]);
        float2 bpair = make_float2(0.f, 0.f);
        if (i0 < 96) bpair = __ldcg(reinterpret_cast<const float2*>(&sc->bias[32 * (i0 % 24 >> 3) + 8 * (i0 / 24) + (i0 % 24 & 6)]));
        const float gbound = fmaxf(2.f * KZ * 9.7979590f * 192.f * w1max, 1.f) * 19.5959180f * INV_2KZ;
        const unsigned fixed = __reduce_max_sync(~0u, __float_as_uint(fmaf(gbound, fmaxf(fmaxf(rmax[0], rmax[1]), rmax[2]), fmaxf(fabsf(bpair.x), fabsf(bpair.y)))));
        if (lane == 0) sts32(s_red + 96 + w4 * 4, fixed);
        reduce(4 * (NCONS - 1) + w4, lane, leader);
        PROF(2);
        named_bar(15, CONS_THREADS);
        if (leader) {
            fence_async();
            bulk_load(sb + SM_W2 + (NCONS - 1) * SQ_WG, reinterpret_cast<const char*>(sc->w2h) + (NCONS - 1) * SQ_WG, SQ_WG, sb + BAR_W);
            if (!plain) load_upper();
        }
        stage = sb + SM_RING + (wk.rows + 3 + (wk.lent + 2 * ntiles) % NCONS) % NSLOT * SLOT_BYTES + w4 * REGION_BYTES;
        auto grn = [&]() {
            auto peek = [&](int e) {
                unsigned long long v;
                asm volatile("ld.relaxed.gpu.global.u64 %0, [%1];" : "=l"(v) : "l"(sc->sum(e)) : "memory");
                return v;
            };
            unsigned n = 0;
            while (((unsigned)peek((blockIdx.x * 4 + w4) % (EX / 4) * 4) & 255u) != gridDim.x)
                if (++n > SPIN_LIMIT) __trap();
            unsigned long long sum[3];
            for (;;) {
                bool all = true;
#pragma unroll
                for (int m = 0; m < 3; m++) {
                    sum[m] = peek(i0 + 128 * m);
                    all &= ((unsigned)sum[m] & 255u) == gridDim.x;
                }
                if (__all_sync(~0u, all)) break;
                if (++n > SPIN_LIMIT) __trap();
            }
            PROF(3);
            if (blockIdx.x == 0 && leader) sc->launch = epoch + 1;
            float gx[3], tot = 0.f, vary = 0.f;
#pragma unroll
            for (int m = 0; m < 3; m++) {
                gx[m] = grn_norm(__ull2float_rn(sum[m] >> 8) * from_fixed);
                tot += gx[m];
                vary = fmaxf(vary, fabsf(gam[m]) * gx[m] * rmax[m]);
            }
#pragma unroll
            for (int o = 16; o >= 1; o >>= 1) tot += __shfl_xor_sync(~0u, tot, o);
            const unsigned vwarp = __reduce_max_sync(~0u, __float_as_uint(vary));
            if (lane == 0) { sts32(s_red + 64 + w4 * 4, __float_as_uint(tot)); sts32(s_red + 80 + w4 * 4, vwarp); }
            named_bar(1, 128);
            uint32_t u[4], v[4], w[4];
            lds128(u[0], u[1], u[2], u[3], s_red + 64);
            lds128(v[0], v[1], v[2], v[3], s_red + 80);
            lds128(w[0], w[1], w[2], w[3], s_red + 96);
            tot = (__uint_as_float(u[0]) + __uint_as_float(u[1])) + (__uint_as_float(u[2]) + __uint_as_float(u[3]));
            const float vmax = __uint_as_float(max(max(v[0], v[1]), max(v[2], v[3]))), fmax2 = __uint_as_float(max(max(w[0], w[1]), max(w[2], w[3])));
            const float inv_mean = __fdividef(1.f, tot * (1.f / EX) + 1e-6f);
            const float bound = fmaf(gbound * vmax, inv_mean, 2.f * fmax2);
            const int rho_e = bound > 0.f ? 14 - ilog2f(bound) : 0;
            const float rho = pow2i(rho_e), inv_rho = pow2i(-rho_e);
            inv_rho2 = pack_bf2(inv_rho, inv_rho);
#pragma unroll
            for (int m = 0; m < 3; m++) {
                const float f = __fdividef(fmaf(gam[m], gx[m] * inv_mean, 1.f) * INV_2KZ * rho, row_scale(rmax[m]));
                asm volatile("st.shared.u16 [%0], %1;" ::"r"(s_fac + (i0 + 128 * m) * 2), "h"((unsigned short)pack_h2(f, 0.f)) : "memory");
            }
            if (i0 < 96) sts32(sb + SM_BIASH + i0 * 4, pack_h2(bpair.x * rho, bpair.y * rho));
            if (i0 == 96) sts32(s_red + RED_INV_RHO, inv_rho2);
            named_arrive(12, NTHREADS);
        };
        lds32(next_off, sb + SM_TILES);
        next_off = __shfl_sync(~0u, next_off, 0);
        load_first();
        grn();
        if (wk.lent) spin_until(&sc->lent_out, (epoch + 1) * 8 * LENT * sp.lenders);
    } else {
        const int rank = (wgi + wk.lent + 2 * ntiles) % NCONS;
        {
            const int ct = tid - 128, lane = tid & 31;
            const unsigned epoch = *reinterpret_cast<volatile unsigned*>(&sc->launch);
            const int r = lane & 7, mi = lane >> 3;
            const uint32_t src = sb + SM_W2 + (cw >> 1) * (64 * CH * 2) + r * 128 + ((((cw & 1) * 4 + mi) ^ r) * 16);
            const uint32_t dst = sb + SM_W1 + (4 * cw + mi) * 1536 + r * 16;
            if (ct == 0) sts32(s_red + RED_MAX, 0);
            named_bar(0, NTHREADS);
            mbar_wait(sb + BAR_W + (cw >> 1) * 8, 0);
            uint32_t wmax[4] = {}, wsum[4] = {};
#pragma unroll 3
            for (int c = 0; c < 12; c++) {
                uint32_t u[4];
                ldsm4_t(u, src + c * 1024);
#pragma unroll
                for (int q = 0; q < 4; q++) {
                    wmax[q] = bf_absmax(wmax[q], u[q]);
                    wsum[q] = bf_fma(u[q], 0x3f803f80u, wsum[q]);
                    u[q] = pack_h2(bf_lo(u[q]), bf_hi(u[q]));
                }
                stsm4(dst + c * 128, u[0], u[1], u[2], u[3]);
            }
            float mean[4];
            bool center = false;
#pragma unroll
            for (int q = 0; q < 4; q++) {
                uint32_t m = wmax[q];
                float sum = bf_lo(wsum[q]) + bf_hi(wsum[q]);
#pragma unroll
                for (int o = 1; o <= 2; o <<= 1) { m = bf_absmax(m, __shfl_xor_sync(~0u, m, o)); sum += __shfl_xor_sync(~0u, sum, o); }
                mean[q] = sum * (1.f / CH);
                center |= fabsf(mean[q]) > 0.2f * fmaxf(fabsf(bf_lo(m)), fabsf(bf_hi(m)));
            }
            if (__builtin_expect(__any_sync(~0u, center), 0)) {
#pragma unroll 1
                for (int pass = 0; pass < 2; pass++) {
                    float sum[4] = {};
#pragma unroll 1
                    for (int c = 0; c < 12; c++) {
                        uint32_t u[4];
                        ldsm4_t(u, src + c * 1024);
#pragma unroll
                        for (int q = 0; q < 4; q++) {
                            sum[q] += bf_lo(u[q]) + bf_hi(u[q]);
                            u[q] = pack_h2(bf_lo(u[q]) - mean[q], bf_hi(u[q]) - mean[q]);
                        }
                        stsm4(dst + c * 128, u[0], u[1], u[2], u[3]);
                    }
#pragma unroll
                    for (int q = 0; q < 4; q++) {
                        sum[q] += __shfl_xor_sync(~0u, sum[q], 1);
                        sum[q] += __shfl_xor_sync(~0u, sum[q], 2);
                        mean[q] = sum[q] * (1.f / CH);
                    }
                }
            }
            if (cw < 2 * NCONS) {
#pragma unroll
                for (int c = 0; c < 12; c++) sts128(src + c * 1024, 0, 0, 0, 0);
            }
            const float w1max = warp_absmax(bf_absmax(bf_absmax(wmax[0], wmax[1]), bf_absmax(wmax[2], wmax[3])));
            if (lane == 0) asm volatile("red.shared.max.u32 [%0], %1;" ::"r"(s_red + RED_MAX), "r"(__float_as_uint(w1max)) : "memory");
            if (ct < 32) sts32(sb + SM_ONES + ct * 4, 0x3f803f80u);
            if (ct == 0) sts32(s_red + RED_LAUNCH, epoch);
            fence_async();
            named_bar(2, CONS_THREADS);
            const float all_max = ldsf(s_red + RED_MAX);
            const int sq_e = square_exp(all_max);
            sts64(s_red + RED_SQ_EXP, sq_e, sum_exp(all_max));
            if (sq_e) {
#pragma unroll 1
                for (int q = 0; q < 6; q++) sts128(sb + SM_SQ + (rank + NCONS) * SQ_WG + q * SQ_ROW + (ct & 127) * 16, 0, 0, 0, 0);
            }
            mbar_wait(sb + BAR_A + w4 * 8 + 32, 0);
        }

        PROF(1);
        const uint32_t a_addr = opaque(sb + SM_RING + w4 * REGION_BYTES + ((tid >> 3) & 1) * A_SBO + ((tid >> 4) & 1) * A_LBO + (tid & 7) * 16);
        const uint32_t bar_a = sb + BAR_A + w4 * 8, bar_e = sb + BAR_E + w4 * 8;
        const uint32_t sq = opaque(sb + SM_SQ + rank * SQ_WG + (tid & 127) * 16);
        const uint32_t sq_warp = sb + SM_SQ + rank * SQ_WG + w4 * 512;
        uint32_t k1[24], k2[24], k3[24];
        constexpr int SQC = 3 * SQ_ROW;
        const int pass_to = 4 + (wgi == NCONS - 1 ? 0 : wgi + 1);
        auto store_at = [&](const uint32_t (&a)[6][4], uint32_t off) {
            char* ap = reinterpret_cast<char*>(out) + (off + sq);
#pragma unroll
            for (int s = 0; s < 6; s++) stg128(ap + s * 512, a[s]);
        };
        int jt = wgi < wk.lent ? wgi : wk.lent + wgi;
        Cursor cur = {2, 0};
        cur.advance(jt + (jt >= wk.nA ? 2 : 0));
        if (wgi == NCONS - 1) named_arrive(4, 256);
        for (;;) {
            const bool plain = __all_sync(~0u, ldsi(s_red + RED_SQ_EXP) == 0);
            if (plain && jt >= wk.lent) {
                uint32_t hs2[12] = {}, hs3[12] = {};
                const uint32_t own_bar = opaque_uniform(4 + wgi), next_bar = opaque_uniform(pass_to);
                const uint32_t step = opaque_uniform(wk.dir * (NCONS * IMG_W * CH * 2));
#pragma unroll 1
                while (jt + NCONS < ntiles) {
                const int stop = jt < wk.nA ? min(wk.nA, ntiles - NCONS) : ntiles - NCONS, count = (stop - jt + NCONS - 1) / NCONS;
                const int low = cur.slot % 3;
                uint32_t turn = opaque_uniform(cur.par * 2 + cur.slot / 3);
                const uint32_t turn_end = opaque_uniform(turn + count);
                uint32_t so = opaque_uniform(cur.slot * SLOT_BYTES), bo = opaque_uniform(bar_a + cur.slot * 32);
                const uint32_t so_sum = opaque_uniform((2 * low + 3) * SLOT_BYTES), bo_sum = opaque_uniform(2 * bar_a + (2 * low + 3) * 32);
                uint32_t off = opaque_uniform(tile_offset(wk.tile(jt)) + w4 * WARP_BYTES - sq_warp);
                jt += count * NCONS;
                cur.slot = low + 3 * (turn_end & 1);
                cur.par = turn_end >> 1 & 1;
                if (jt >= wk.nA && jt - NCONS < wk.nA) cur.advance(2);
#pragma unroll 1
                do {
                    uint32_t a[6][4], d0[24], d1[24], unused[24];
#define AT(pos) \
    if (K_WAIT == pos) named_bar(own_bar, 256); \
    if (K_PASS == pos) named_arrive(next_bar, 256); \
    if (K_STG == pos) store_at(a, off); \
    if (K_REL == pos) { if (elect_one()) mbar_arrive(bo + (BAR_E - BAR_A)); }
                    AT(20)
                    mbar_wait(bo, turn >> 1 & 1);
                    load_tile(a, a_addr + so);
                    AT(21)
                    const uint2 st = ln_stats(a, ds.ones);
                    AT(0)
                    ln_apply(a, st);
                    AT(1)
                    wg_fence();
                    gemm1_chunk<0>(d0, a, ds, 0);
                    wg_commit();
                    gemm1_chunk<96>(d1, a, ds, 0);
                    wg_commit();
                    AT(2)
                    wg_wait<1>();
                    AT(3)
                    gelu_sq<false, 0, 1>(d0, unused, sq, 0);
                    AT(4)
                    gelu_sq<false, 1, 2>(d0, unused, sq, 0);
                    AT(5)
                    gelu_sq<false, 2, 3>(d0, unused, sq, 0);
                    AT(6)
                    wg_fence();
                    gemm1_chunk<192>(d0, a, ds, zero);
                    wg_commit();
                    AT(7)
                    wg_wait<1>();
                    gelu_sq<false, 0, 1>(d1, unused, sq + SQC, 0);
                    AT(8)
                    gelu_sq<false, 1, 3>(d1, unused, sq + SQC, 0);
                    AT(9)
                    wg_fence();
                    gemm1_chunk<288>(d1, a, ds, zero);
                    wg_commit();
                    AT(10)
                    wg_wait<1>();
                    gelu_sq_reg(d0, hs2);
                    if (K_ANCH < 3) anchor(sq, hs2[4 * (K_ANCH % 3)], hs2[4 * (K_ANCH % 3) + 1], hs2[4 * (K_ANCH % 3) + 2], hs2[4 * (K_ANCH % 3) + 3]);
                    wg_wait<0>();
                    AT(11)
                    gelu_sq_reg(d1, hs3);
#undef AT
                    so = so_sum - so;
                    bo = bo_sum - bo;
                    off += step;
                } while (++turn != turn_end);
                }
                const uint32_t sq2 = sq - (SM_SQ + rank * SQ_WG) + SM_RING + (cur.slot + 3) % NSLOT * SLOT_BYTES;
#pragma unroll
                for (int k = 0; k < 3; k++) {
                    sts128(sq2 + k * SQ_ROW, hs2[4 * k], hs2[4 * k + 1], hs2[4 * k + 2], hs2[4 * k + 3]);
                    sts128(sq2 + SQC + k * SQ_ROW, hs3[4 * k], hs3[4 * k + 1], hs3[4 * k + 2], hs3[4 * k + 3]);
                }
            }
            const bool last = jt + NCONS >= ntiles;
            if (last) {
                tile_off = tile_offset(wk.tile(jt));
                lds32(next_off, sb + SM_TILES + wg * 4);
                next_off = __shfl_sync(~0u, next_off, 0);
                if (elect_one()) {
                    prefetch_l2(reinterpret_cast<const char*>(x) + tile_off + w4 * WARP_BYTES, WARP_BYTES);
                    if (wg % ORDER_P >= ORDER_P - ORDER_Q) prefetch_l2(reinterpret_cast<const char*>(out) + next_off + w4 * WARP_BYTES, WARP_BYTES);
                }
            }
            uint32_t a[6][4], d0[24], d1[24], d3[24], k0[24];
#define AT(pos) \
    if (K_WAIT == pos && jt >= wk.lent) named_bar(4 + wgi, 256); \
    if (K_PASS == pos && jt >= wk.lent && jt + 1 < ntiles) named_arrive(pass_to, 256);
            AT(20)
            mbar_wait(bar_a + cur.slot * 32, cur.par);
            load_tile(a, a_addr + cur.slot * SLOT_BYTES);
            AT(21)
            const uint2 st = ln_stats(a, ds.ones);
            AT(0)
            ln_apply(a, st);
            AT(1)
            if (!last) {
                store_at(a, tile_offset(wk.tile(jt)) + w4 * WARP_BYTES - sq_warp);
                __syncwarp();
                if (elect_one()) mbar_arrive(bar_e + cur.slot * 32);
                if (jt < wk.lent) {
                    jt += LENT;
                    cur.advance(LENT);
                    continue;
                }
            }
            wg_fence();
            gemm1_chunk<0>(d0, a, ds, 0);
            wg_commit();
            gemm1_chunk<96>(d1, a, ds, 0);
            wg_commit();
            const int sq_e = ldsi(s_red + RED_SQ_EXP);
            const uint32_t scale2 = pack_h2(pow2i(sq_e), pow2i(sq_e));
            AT(2)
            wg_wait<1>();
            AT(3)
            gelu_sq<true, 0, 1>(d0, k0, sq, scale2);
            AT(4)
            gelu_sq<true, 1, 2>(d0, k0, sq, scale2);
            AT(5)
            gelu_sq<true, 2, 3>(d0, k0, sq, scale2);
            AT(6)
            if (last) {
#pragma unroll
                for (int q = 0; q < 6; q++) sts128(sb + SM_RING + cur.slot * SLOT_BYTES + w4 * REGION_BYTES - sq_warp + sq + q * 512, k0[4 * q], k0[4 * q + 1], k0[4 * q + 2], k0[4 * q + 3]);
            }
            wg_fence();
            gemm1_chunk<192>(d0, a, ds, zero);
            wg_commit();
            AT(7)
            wg_wait<1>();
            gelu_sq<true, 0, 1>(d1, k1, sq + SQC, scale2);
            AT(8)
            gelu_sq<true, 1, 3>(d1, k1, sq + SQC, scale2);
            AT(9)
#undef AT
            wg_fence();
            gemm1_chunk<288>(d3, a, ds, 0);
            wg_commit();
            wg_wait<1>();
            const uint32_t sq2 = sq + (plain ? SM_RING + (cur.slot + 3) % NSLOT * SLOT_BYTES - (SM_SQ + rank * SQ_WG) : NCONS * SQ_WG);
            gelu_sq<true>(d0, k2, sq2, scale2);
            wg_wait<0>();
            gelu_sq<true>(d3, k3, sq2 + SQC, scale2);
            if (last) break;
            cur.advance(NCONS + ((jt < wk.nA && jt + NCONS >= wk.nA) ? 2 : 0));
            jt += NCONS;
        }
        {
            if (rank == NCONS - 1) {
                named_arrive(14, NTHREADS);
            } else {
                reduce(4 * rank + w4, (sq >> 4) & 31, false);
                named_arrive(15, CONS_THREADS);
                PROF(2);
                if (helps && rank == 0 && w4 == 0) signal(&sc->lent_out);
            }
        }
        {
            set_lane((sq >> 4) & 31);
            const uint32_t row = sb + SM_W2 + cw * 512 + lane16;
            uint32_t u[W2_EARLY][4], f2[4];
            mbar_wait(sb + BAR_W, 1);
#pragma unroll
            for (int nb = 0; nb < W2_EARLY; nb++) lds128(u[nb][0], u[nb][1], u[nb][2], u[nb][3], row + nb * 6144);
            named_bar(12, NTHREADS);
            PROF(3);
            stage = sb + SM_RING + (cur.slot + 3) % NSLOT * SLOT_BYTES + w4 * WARP_BYTES;
            if (K_XPOS == 0) stage_x();
            lds128(f2[0], f2[1], f2[2], f2[3], s_fac + cw * 64 + (lane16 >> 7) * 16);
            lds32(inv_rho2, s_red + RED_INV_RHO);
#pragma unroll
            for (int nb = 0; nb < 12; nb++) {
                uint32_t v[4];
                if (nb < W2_EARLY) { v[0] = u[nb % W2_EARLY][0]; v[1] = u[nb % W2_EARLY][1]; v[2] = u[nb % W2_EARLY][2]; v[3] = u[nb % W2_EARLY][3]; }
                else lds128(v[0], v[1], v[2], v[3], row + nb * 6144);
                sts128(row + nb * 6144, h_round8(h_mul(v[0], f2[0])), h_round8(h_mul(v[1], f2[1])), h_round8(h_mul(v[2], f2[2])), h_round8(h_mul(v[3], f2[3])));
            }
            fence_async();
            if (K_XPOS == 1) stage_x();
            named_bar(3, NTHREADS);
        }
        PROF(4);
        {
            load_bias(acc);
            if (wgi > 0) named_bar(8 + wgi, 256);
            pin(k1); pin(k2); pin(k3);
            wg_fence();
            gemm2_chunk<288>(acc, k3, ds);
            wg_commit();
            gemm2_chunk<(K_SWAP ? 192 : 96)>(acc, K_SWAP ? k2 : k1, ds);
            if (K_FINE) wg_commit();
            gemm2_chunk<(K_SWAP ? 96 : 192)>(acc, K_SWAP ? k1 : k2, ds);
            wg_commit();
            if (!K_LATE && wgi + 1 < NCONS) named_arrive(9 + wgi, 256);
            wg_wait<1 + K_FINE>();
            uint32_t k0[24];
#pragma unroll
            for (int q = 0; q < 6; q++)
                lds128(k0[4 * q], k0[4 * q + 1], k0[4 * q + 2], k0[4 * q + 3], sb + SM_RING + cur.slot * SLOT_BYTES + w4 * REGION_BYTES + lane16 + q * 512);
            pin(k0);
            wg_fence();
            gemm2_chunk<0>(acc, k0, ds);
            wg_commit();
            if (K_LATE && wgi + 1 < NCONS) named_arrive(9 + wgi, 256);
            if (wgi == 0) named_arrive(8, 256);
            wg_wait<1 + K_FINE>();
            load_first();
            if (lane16 == 0) mbar_arrive(sb + BAR_PIN);
            mbar_wait(bar_r, rpar);
            wg_wait<0>();
            first = wg - 4;
        }
    }
    {
        const int nrest = ntiles - NCONS;
        auto lent = [&](uint32_t entry) { return &sc->lent[((wk.index * 4 + w4) * LENT + (entry & 3) - 1) * (8 * 96)]; };
        for (int jt = first; jt < nrest; jt += 4) {
            if (jt >= 0) {
            tile_off = next_off;
            lds32(next_off, sb + SM_TILES + (jt + 4) * 4);
            if (tile_off & 3) {
                uint32_t gl[2][24];
                const uint4* src = lent(tile_off) + (lane16 >> 4);
                auto fetch = [&](uint32_t (&v)[24], int c) {
#pragma unroll
                    for (int s = 0; s < 6; s++) ldg128(reinterpret_cast<uint32_t (&)[4]>(v[4 * s]), src + (6 * c + s) * 32);
                };
                tile_off &= ~3u;
                next_off = __shfl_sync(~0u, next_off, 0);
                stage_x();
                if (elect_one()) prefetch_l2(reinterpret_cast<const char*>(out) + next_off + w4 * WARP_BYTES, WARP_BYTES);
                load_bias(acc);
#pragma unroll
                for (int half = 0; half < 2; half++) {
                    fetch(gl[0], 2 * half);
                    fetch(gl[1], 2 * half + 1);
                    if (!half) {
                        named_bar(4 + wg, 256);
                        named_arrive(4 + ((wg + 1) & 3), 256);
                    }
                    pin(gl[0]); pin(gl[1]);
                    wg_fence();
                    if (half) gemm2_chunk<192>(acc, gl[0], ds); else gemm2_chunk<0>(acc, gl[0], ds);
                    if (half) gemm2_chunk<288>(acc, gl[1], ds); else gemm2_chunk<96>(acc, gl[1], ds);
                    wg_commit();
                    wg_wait<0>();
                }
                load_first();
                mbar_wait(bar_r, rpar);
            } else {
            uint32_t d0[12], d1[12], g0[12], g1[12];
            if (jt >= S2_FIRST && jt < nrest - K_TAIL) named_bar(4 + wg, 256);
            wg_fence();
            gemm1_chunk<0>(d0, a, ds, 0);
            wg_commit();
            gemm1_chunk<48>(d1, a, ds, 0);
            wg_commit();
            load_bias(acc);
            next_off = __shfl_sync(~0u, next_off, 0);
            const bool more = jt + 4 < nrest && !(next_off & 3);
            wg_wait<1>();
#define CNX_PASS if (jt + 1 >= S2_FIRST && jt + 1 < nrest - K_TAIL) named_arrive(4 + ((wg + 1) & 3), 256);
#define CNX_STEP(C, D, G)                                              \
    gelu_to(G, D);                                                     \
    if (C == 0 && jt == 0) {                                           \
        named_bar(3, NTHREADS);                                        \
        load_bias(acc);                                                \
    }                                                                  \
    wg_fence();                                                        \
    if (C < 6) gemm1_chunk<48 * (C < 6 ? C + 2 : 0)>(D, a, ds, zero); \
    gemm2_chunk<48 * C>(acc, G, ds);                                  \
    wg_commit();                                                       \
    if (C == S2_PASS) { CNX_PASS }                                     \
    wg_wait<(C < 7 ? 1 : 0)>();
            CNX_STEP(0, d0, g0)
            CNX_STEP(1, d1, g1)
            if (jt == 0) named_bar(8, 256);
            stage_x();
            if (elect_one()) {
                if (more) prefetch_l2(reinterpret_cast<const char*>(out) + next_off + w4 * WARP_BYTES, WARP_BYTES);
                else if (next_off & 3) prefetch_l2(lent(next_off), 8 * 96 * 16);
            }
            CNX_STEP(2, d0, g0)
            CNX_STEP(3, d1, g1)
            CNX_STEP(4, d0, g0)
            CNX_STEP(5, d1, g1)
            CNX_STEP(6, d0, g0)
            load_frags(more);
            if (lane16 == 0) mbar_arrive(sb + BAR_PIN);
            mbar_wait(bar_r, rpar);
            CNX_STEP(7, d1, g1)
#undef CNX_STEP
            }
            }
            epilogue(acc);
        }
    }
    PROF(5);
}

}

typedef CUresult (*EncodeTiledFn)(CUtensorMap*, CUtensorMapDataType, cuuint32_t, void*, const cuuint64_t*, const cuuint64_t*,
                                  const cuuint32_t*, const cuuint32_t*, CUtensorMapInterleave, CUtensorMapSwizzle,
                                  CUtensorMapL2promotion, CUtensorMapFloatOOBfill);

extern "C" void kernel_launch(void* const* d_in, const int* in_sizes, int n_in, void* d_out, int out_size) {
    using namespace cnx;
    static EncodeTiledFn encode = nullptr;
    static int num_sms = 0;
    static Scratch* scratch = nullptr;
    if (!encode) {
        void* fn = nullptr;
        cudaDriverEntryPointQueryResult qr;
        cudaGetDriverEntryPoint("cuTensorMapEncodeTiled", &fn, cudaEnableDefault, &qr);
        encode = (EncodeTiledFn)fn;
        cudaGetSymbolAddress((void**)&scratch, g_scratch);
        int dev = 0;
        cudaGetDevice(&dev);
        cudaDeviceGetAttribute(&num_sms, cudaDevAttrMultiProcessorCount, dev);
        if (num_sms > MAX_CTAS) num_sms = MAX_CTAS;
        cudaFuncSetAttribute(block_kernel, cudaFuncAttributeMaxDynamicSharedMemorySize, SM_TOTAL);
    }
    CUtensorMap tm;
    cuuint64_t dims[3] = {(cuuint64_t)CH, (cuuint64_t)IMG_W, (cuuint64_t)IMG_H};
    cuuint64_t strides[2] = {(cuuint64_t)CH * 2, (cuuint64_t)CH * 2 * IMG_W};
    cuuint32_t box[3] = {(cuuint32_t)CH, (cuuint32_t)REGION_PX, 1};
    cuuint32_t estr[3] = {1, 1, 1};
    encode(&tm, CU_TENSOR_MAP_DATA_TYPE_BFLOAT16, 3, d_in[0], dims, strides, box, estr, CU_TENSOR_MAP_INTERLEAVE_NONE,
           CU_TENSOR_MAP_SWIZZLE_NONE, CU_TENSOR_MAP_L2_PROMOTION_L2_128B, CU_TENSOR_MAP_FLOAT_OOB_FILL_NONE);
    Descs ds;
    for (int c = 0; c < 8; c++)
        for (int k = 0; k < 6; k++) ds.w1[c][k] = make_desc(SB + SM_W1 + c * 6 * 1536 + k * 256, 128, 1536);
    for (int k = 0; k < 24; k++) ds.w2[k] = make_desc(SB + SM_W2 + k * 256, 128, 6144);
    ds.ones = make_desc(SB + SM_ONES, 0, 0);
    CUtensorMap tw;
    cuuint64_t wdims[2] = {(cuuint64_t)EX, (cuuint64_t)CH};
    cuuint64_t wstrides[1] = {(cuuint64_t)EX * 2};
    cuuint32_t wbox[2] = {64, (cuuint32_t)CH};
    encode(&tw, CU_TENSOR_MAP_DATA_TYPE_BFLOAT16, 2, d_in[2], wdims, wstrides, wbox, estr, CU_TENSOR_MAP_INTERLEAVE_NONE,
           CU_TENSOR_MAP_SWIZZLE_128B, CU_TENSOR_MAP_L2_PROMOTION_L2_128B, CU_TENSOR_MAP_FLOAT_OOB_FILL_NONE);
    Split sp = {NTILES / num_sms, NTILES % num_sms, 1, 1 << 16, 0};
    if (sp.per_cta + 9 > MAX_ROWS) return;
    if (sp.extra && sp.extra * (8 * LENT + 1) <= num_sms && sp.per_cta >= 5 * LENT + 7) {
        sp.period = num_sms / sp.extra;
        sp.inv_period = 65535 / sp.period + 1;
        sp.lenders = sp.extra;
        for (int l = 0; l < sp.extra; l++)
            if (get_work((l + 1) * sp.period - sp.period / 2 - 1, sp).nA < 2 * LENT) sp.lenders = 0;
    }
    block_kernel<<<num_sms, NTHREADS, SM_TOTAL>>>(tm, tw, (const __nv_bfloat16*)d_in[0], (const __nv_bfloat16*)d_in[1],
                                             (const __nv_bfloat16*)d_in[3],
                                             (const __nv_bfloat16*)d_in[4], (const __nv_bfloat16*)d_in[5], (__nv_bfloat16*)d_out,
                                             scratch, ds, 0, sp);
}
```

```cpp
#include <cuda_runtime.h>
#include <cuda_bf16.h>
#include <cuda_fp16.h>
#include <cuda.h>
#include <stdint.h>

namespace cnx {

constexpr int IMG_H = 512, IMG_W = 512, CH = 96, EX = 384;
constexpr int TILE_W = 64;
constexpr int NTILES = (IMG_W / TILE_W) * IMG_H;
constexpr int NSLOT = 6;
constexpr int REGION_PX = 18;
constexpr int REGION_BYTES = REGION_PX * CH * 2;
constexpr int SLOT_BYTES = 4 * REGION_BYTES;
constexpr int A_LBO = 144, A_SBO = 12 * A_LBO;
constexpr int PREFETCH_ROWS = 3;
constexpr int NCONS = 3;
constexpr int CONS_THREADS = 128 * NCONS;
constexpr int NTHREADS = 128 + CONS_THREADS;
constexpr int MAX_ROWS = 52;
constexpr int TILE_BYTES = TILE_W * CH * 2, WARP_BYTES = TILE_BYTES / 4;
constexpr int S1_PASS = 1, S2_PASS = 1;
#define K_PASS 4
#define K_WAIT 20
#define K_STG 6
#define K_REL 6
#define K_ANCH 2
#define K_CVT 0
#define K_XPOS 1
#define K_CHAIN 3
#define K_OP 0
#define K_QS 0
#define K_GS 0
#define K_QR 0
#define K_GR 0
#define K_PD 0
#define K_PQ 0
#define K_PS 0
#define K_LATE 1
#define K_FINE 1
#define K_SWAP 0
#define K_TAIL 0
#define W2_EARLY 6
#define S2_FIRST 2
#define ORDER_P 3
#define ORDER_Q 1
static_assert(MAX_ROWS <= 128, "one table entry per producer thread");
static_assert(2 * A_SBO == REGION_BYTES && REGION_BYTES % 128 == 0, "region layout");

constexpr uint32_t SB = 1024;
constexpr int SM_W1 = 0;
constexpr int SM_W2 = SM_W1 + CH * EX * 2;
constexpr int SM_RING = SM_W2 + CH * EX * 2;
constexpr int SM_BIASH = SM_RING + NSLOT * SLOT_BYTES;
constexpr int SM_RED = SM_BIASH + 384;
constexpr int RED_MAX = 0, RED_LAUNCH = 4, RED_SQ_EXP = 8, RED_SUM_EXP = 12, RED_INV_RHO = 16;
constexpr int SM_TILES = SM_RED + 256;
constexpr int SM_ONES = SM_TILES + MAX_ROWS * 4;
constexpr int SM_BAR = SM_ONES + 128;
constexpr int BAR_X = SM_BAR;
constexpr int BAR_A = BAR_X + NSLOT * 4 * 8;
constexpr int BAR_E = BAR_A + NSLOT * 4 * 8;
constexpr int BAR_PIN = BAR_E + NSLOT * 4 * 8;
constexpr int BAR_W = BAR_PIN + 8;
constexpr int BAR_F = BAR_W + 6 * 8;
constexpr int BAR_R = BAR_F + 8;
constexpr int SM_TOTAL = BAR_R + 16 * 8;
constexpr int SM_FILTER = SM_RING + (NSLOT - 1) * SLOT_BYTES + 9 * 128;
constexpr int SM_SQ = SM_W2;
constexpr int SQ_ROW = 128 * 16, SQ_WG = 6 * SQ_ROW;
static_assert(SM_ONES % 16 == 0 && SM_TOTAL <= 232448, "shared memory budget");

constexpr float KZ = 0.3292034911525734f;
constexpr uint32_t GELU_C2 = 0x40d940d9u;
constexpr float INV_2KZ = 0.5f / KZ;
constexpr unsigned SPIN_LIMIT = 1u << 19;

constexpr int MAX_CTAS = 255;
constexpr int W2_GROUPS = EX / 8;
#define K_LENT 3
constexpr int LENT = K_LENT, MAX_LENDERS = MAX_CTAS / (8 * LENT + 1);
struct Scratch {
    uint32_t w2h[EX * CH / 2];
    float w2max[EX];
    float bias[CH + 32];
    unsigned long long sums[EX / 4][32];
    __device__ __forceinline__ unsigned long long* sum(int e) { return &sums[e >> 2][e & 3]; }
    uint4 lent[MAX_LENDERS * LENT * 8 * 4 * 3 * 32];
    unsigned launch, pad0[31], early, pad1[31], prep, pad2[31], lent_out, pad3[31];
};
__device__ __align__(128) Scratch g_scratch;

#define PROF(k)

__device__ __forceinline__ uint32_t smem_u32(const void* p) { return (uint32_t)__cvta_generic_to_shared(p); }
__device__ __forceinline__ void mbar_init(uint32_t bar, uint32_t cnt) {
    asm volatile("mbarrier.init.shared::cta.b64 [%0], %1;" ::"r"(bar), "r"(cnt) : "memory");
}
__device__ __forceinline__ void mbar_arrive(uint32_t bar) {
    asm volatile("mbarrier.arrive.shared::cta.b64 _, [%0];" ::"r"(bar) : "memory");
}
__device__ __forceinline__ void mbar_expect_tx(uint32_t bar, uint32_t bytes) {
    asm volatile("mbarrier.arrive.expect_tx.shared::cta.b64 _, [%0], %1;" ::"r"(bar), "r"(bytes) : "memory");
}
__device__ __forceinline__ bool mbar_try(uint32_t bar, uint32_t par) {
    uint32_t ok;
    asm volatile("{\n.reg .pred p;\nmbarrier.try_wait.parity.shared::cta.b64 p, [%1], %2;\nselp.u32 %0, 1, 0, p;\n}\n"
                 : "=r"(ok) : "r"(bar), "r"(par) : "memory");
    return ok != 0;
}
__device__ __forceinline__ void mbar_wait(uint32_t bar, uint32_t par) {
    unsigned n = 0;
    while (!mbar_try(bar, par)) {
        if (++n > SPIN_LIMIT) __trap();
    }
}
__device__ __forceinline__ bool mbar_test(uint32_t bar, uint32_t par) {
    uint32_t ok;
    asm volatile("{\n.reg .pred p;\nmbarrier.test_wait.parity.shared::cta.b64 p, [%1], %2;\nselp.u32 %0, 1, 0, p;\n}\n"
                 : "=r"(ok) : "r"(bar), "r"(par) : "memory");
    return ok != 0;
}
__device__ __forceinline__ bool elect_one() {
    uint32_t ok;
    asm volatile("{\n.reg .pred p;\nelect.sync _|p, 0xffffffff;\nselp.u32 %0, 1, 0, p;\n}\n" : "=r"(ok));
    return ok != 0;
}
__device__ __forceinline__ uint32_t opaque(uint32_t v) { return __shfl_sync(~0u, v, threadIdx.x & 31); }
__device__ __forceinline__ uint32_t opaque_uniform(uint32_t v) { return __shfl_sync(~0u, v, 0); }
__device__ __forceinline__ void named_bar(int id, int n) { asm volatile("bar.sync %0, %1;" ::"r"(id), "r"(n) : "memory"); }
__device__ __forceinline__ void named_arrive(int id, int n) { asm volatile("bar.arrive %0, %1;" ::"r"(id), "r"(n) : "memory"); }
__device__ __forceinline__ void fence_async() { asm volatile("fence.proxy.async.shared::cta;" ::: "memory"); }
__device__ __forceinline__ uint64_t evict_first() {
    uint64_t p;
    asm("createpolicy.fractional.L2::evict_first.b64 %0, 1.0;" : "=l"(p));
    return p;
}
__device__ __forceinline__ void tma_row(uint32_t dst, const CUtensorMap* tm, uint32_t bar, int x, int y) {
    asm volatile("cp.async.bulk.tensor.3d.shared::cluster.global.mbarrier::complete_tx::bytes.L2::cache_hint [%0], [%1, {%3, %4, %5}], [%2], %6;"
                 ::"r"(dst), "l"(tm), "r"(bar), "r"(0), "r"(x), "r"(y), "l"(evict_first()) : "memory");
}
__device__ __forceinline__ void bulk_load_stream(uint32_t dst, const void* src, uint32_t bytes, uint32_t bar) {
    asm volatile("cp.async.bulk.shared::cluster.global.mbarrier::complete_tx::bytes.L2::cache_hint [%0], [%1], %2, [%3], %4;"
                 ::"r"(dst), "l"(src), "r"(bytes), "r"(bar), "l"(evict_first()) : "memory");
}
__device__ __forceinline__ void prefetch_l2(const void* src, uint32_t bytes) {
    asm volatile("cp.async.bulk.prefetch.L2.global [%0], %1;" ::"l"(src), "r"(bytes) : "memory");
}
__device__ __forceinline__ void tma_2d(uint32_t dst, const CUtensorMap* tm, uint32_t bar, int x, int y) {
    asm volatile("cp.async.bulk.tensor.2d.shared::cluster.global.mbarrier::complete_tx::bytes [%0], [%1, {%3, %4}], [%2];"
                 ::"r"(dst), "l"(tm), "r"(bar), "r"(x), "r"(y) : "memory");
}
__device__ __forceinline__ void bulk_load(uint32_t dst, const void* src, uint32_t bytes, uint32_t bar) {
    asm volatile("cp.async.bulk.shared::cluster.global.mbarrier::complete_tx::bytes [%0], [%1], %2, [%3];"
                 ::"r"(dst), "l"(src), "r"(bytes), "r"(bar) : "memory");
}
__device__ __forceinline__ void wg_fence() { asm volatile("wgmma.fence.sync.aligned;" ::: "memory"); }
__device__ __forceinline__ void wg_commit() { asm volatile("wgmma.commit_group.sync.aligned;" ::: "memory"); }
template <int N> __device__ __forceinline__ void wg_wait() { asm volatile("wgmma.wait_group.sync.aligned %0;" ::"n"(N) : "memory"); }
template <int N> __device__ __forceinline__ void pin(uint32_t (&d)[N]) {
#pragma unroll
    for (int q = 0; q < N; q++) asm volatile("" : "+r"(d[q])::"memory");
}
__device__ __forceinline__ void stg128(void* p, const uint32_t (&v)[4]) {
    asm volatile("st.global.v4.u32 [%0], {%1, %2, %3, %4};" ::"l"(p), "r"(v[0]), "r"(v[1]), "r"(v[2]), "r"(v[3]) : "memory");
}
__device__ __forceinline__ void ldg128(uint32_t (&v)[4], const void* p) {
    asm volatile("ld.global.L1::no_allocate.v4.u32 {%0, %1, %2, %3}, [%4];" : "=r"(v[0]), "=r"(v[1]), "=r"(v[2]), "=r"(v[3]) : "l"(p) : "memory");
}
__device__ __forceinline__ void ldg128_if(bool on, uint32_t (&v)[4], const void* p) {
    asm volatile("{\n.reg .pred p;\nsetp.ne.b32 p, %5, 0;\n@p ld.global.L1::no_allocate.v4.u32 {%0, %1, %2, %3}, [%4];\n}\n"
                 : "+r"(v[0]), "+r"(v[1]), "+r"(v[2]), "+r"(v[3]) : "l"(p), "r"((int)on) : "memory");
}
__device__ __forceinline__ uint4 ldg128_ordered(const void* p) {
    uint4 v;
    asm volatile("ld.global.nc.v4.u32 {%0, %1, %2, %3}, [%4];" : "=r"(v.x), "=r"(v.y), "=r"(v.z), "=r"(v.w) : "l"(p) : "memory");
    return v;
}
__host__ __device__ constexpr uint64_t make_desc(uint32_t addr, uint32_t lbo, uint32_t sbo) {
    return (uint64_t)((addr & 0x3FFFF) >> 4) | ((uint64_t)(lbo >> 4) << 16) | ((uint64_t)(sbo >> 4) << 32);
}
__device__ __forceinline__ void wgmma(uint32_t (&d)[12], uint32_t a0, uint32_t a1, uint32_t a2, uint32_t a3, uint64_t db, int acc) {
    asm volatile("{\n.reg .pred p;\nsetp.ne.b32 p, %17, 0;\n"
                 "wgmma.mma_async.sync.aligned.m64n48k16.f16.f16.f16 "
                 "{%0, %1, %2, %3, %4, %5, %6, %7, %8, %9, %10, %11}, "
                 "{%12, %13, %14, %15}, %16, p, 1, 1, 0;\n}\n"
                 : "+r"(d[0]), "+r"(d[1]), "+r"(d[2]), "+r"(d[3]), "+r"(d[4]), "+r"(d[5]), "+r"(d[6]), "+r"(d[7]), "+r"(d[8]), "+r"(d[9]), "+r"(d[10]), "+r"(d[11])
                 : "r"(a0), "r"(a1), "r"(a2), "r"(a3), "l"(db), "r"(acc));
}
__device__ __forceinline__ void wgmma(uint32_t (&d)[24], uint32_t a0, uint32_t a1, uint32_t a2, uint32_t a3, uint64_t db, int acc) {
    asm volatile("{\n.reg .pred p;\nsetp.ne.b32 p, %29, 0;\n"
                 "wgmma.mma_async.sync.aligned.m64n96k16.f16.f16.f16 "
                 "{%0, %1, %2, %3, %4, %5, %6, %7, %8, %9, %10, %11, %12, %13, %14, %15, %16, %17, %18, %19, %20, %21, %22, %23}, "
                 "{%24, %25, %26, %27}, %28, p, 1, 1, 0;\n}\n"
                 : "+r"(d[0]), "+r"(d[1]), "+r"(d[2]), "+r"(d[3]), "+r"(d[4]), "+r"(d[5]), "+r"(d[6]), "+r"(d[7]), "+r"(d[8]), "+r"(d[9]), "+r"(d[10]), "+r"(d[11]), "+r"(d[12]), "+r"(d[13]), "+r"(d[14]), "+r"(d[15]), "+r"(d[16]), "+r"(d[17]), "+r"(d[18]), "+r"(d[19]), "+r"(d[20]), "+r"(d[21]), "+r"(d[22]), "+r"(d[23])
                 : "r"(a0), "r"(a1), "r"(a2), "r"(a3), "l"(db), "r"(acc));
}
template <int ACC>
__device__ __forceinline__ void wgmma_rowsum(float (&d)[4], const uint32_t (&a)[4], uint64_t ones) {
    asm volatile("{\n.reg .pred p;\nsetp.ne.b32 p, %9, 0;\n"
                 "wgmma.mma_async.sync.aligned.m64n8k16.f32.bf16.bf16 {%0, %1, %2, %3}, {%4, %5, %6, %7}, %8, p, 1, 1, 0;\n}\n"
                 : "+f"(d[0]), "+f"(d[1]), "+f"(d[2]), "+f"(d[3])
                 : "r"(a[0]), "r"(a[1]), "r"(a[2]), "r"(a[3]), "l"(ones), "n"(ACC));
}
__device__ __forceinline__ void ldsm4(uint32_t (&r)[4], uint32_t addr) {
    asm volatile("ldmatrix.sync.aligned.m8n8.x4.shared.b16 {%0, %1, %2, %3}, [%4];"
                 : "=r"(r[0]), "=r"(r[1]), "=r"(r[2]), "=r"(r[3]) : "r"(addr) : "memory");
}
__device__ __forceinline__ void ldsm4_t(uint32_t (&r)[4], uint32_t addr) {
    asm volatile("ldmatrix.sync.aligned.m8n8.x4.trans.shared.b16 {%0, %1, %2, %3}, [%4];"
                 : "=r"(r[0]), "=r"(r[1]), "=r"(r[2]), "=r"(r[3]) : "r"(addr) : "memory");
}
__device__ __forceinline__ void stsm4(uint32_t addr, uint32_t a, uint32_t b, uint32_t c, uint32_t d) {
    asm volatile("stmatrix.sync.aligned.m8n8.x4.shared.b16 [%0], {%1, %2, %3, %4};"
                 ::"r"(addr), "r"(a), "r"(b), "r"(c), "r"(d) : "memory");
}
__device__ __forceinline__ uint32_t transpose8x8(uint32_t v) {
    uint32_t d; asm volatile("movmatrix.sync.aligned.m8n8.trans.b16 %0, %1;" : "=r"(d) : "r"(v)); return d;
}
__device__ __forceinline__ void spin_until(const unsigned* counter, unsigned target) {
    unsigned n = 0, c;
    do {
        asm volatile("ld.acquire.gpu.global.u32 %0, [%1];" : "=r"(c) : "l"(counter) : "memory");
        if (++n > SPIN_LIMIT) __trap();
    } while ((int)(c - target) < 0);
}
__device__ __forceinline__ void signal(unsigned* counter) {
    __syncwarp();
    if (elect_one()) asm volatile("red.release.gpu.global.add.u32 [%0], 1;" ::"l"(counter) : "memory");
    __syncwarp();
}
__device__ __forceinline__ void lds128(uint32_t& a, uint32_t& b, uint32_t& c, uint32_t& d, uint32_t addr) {
    asm volatile("ld.shared.v4.u32 {%0, %1, %2, %3}, [%4];" : "=r"(a), "=r"(b), "=r"(c), "=r"(d) : "r"(addr) : "memory");
}
__device__ __forceinline__ void lds64(uint32_t& a, uint32_t& b, uint32_t addr) {
    asm volatile("ld.shared.v2.u32 {%0, %1}, [%2];" : "=r"(a), "=r"(b) : "r"(addr) : "memory");
}
__device__ __forceinline__ void lds32(uint32_t& a, uint32_t addr) {
    asm volatile("ld.shared.u32 %0, [%1];" : "=r"(a) : "r"(addr) : "memory");
}
__device__ __forceinline__ int ldsi(uint32_t addr) {
    uint32_t v;
    lds32(v, addr);
    return (int)v;
}
__device__ __forceinline__ float ldsf(uint32_t addr) {
    uint32_t v;
    lds32(v, addr);
    return __uint_as_float(v);
}
__device__ __forceinline__ void sts32(uint32_t addr, uint32_t a) {
    asm volatile("st.shared.u32 [%0], %1;" ::"r"(addr), "r"(a) : "memory");
}
__device__ __forceinline__ void sts128(uint32_t addr, uint32_t a, uint32_t b, uint32_t c, uint32_t d) {
    asm volatile("st.shared.v4.u32 [%0], {%1, %2, %3, %4};" ::"r"(addr), "r"(a), "r"(b), "r"(c), "r"(d) : "memory");
}
__device__ __forceinline__ void sts64(uint32_t addr, uint32_t a, uint32_t b) {
    asm volatile("st.shared.v2.u32 [%0], {%1, %2};" ::"r"(addr), "r"(a), "r"(b) : "memory");
}
__device__ __forceinline__ void anchor(uint32_t addr, uint32_t a, uint32_t b, uint32_t c, uint32_t d) {
    asm volatile("{\n.reg .pred p;\nsetp.eq.b32 p, %0, 0;\n@p st.shared.v4.u32 [%0], {%1, %2, %3, %4};\n}\n"
                 ::"r"(addr), "r"(a), "r"(b), "r"(c), "r"(d) : "memory");
}
__device__ __forceinline__ uint32_t bf_fma(uint32_t a, uint32_t b, uint32_t c) {
    uint32_t d; asm("fma.rn.bf16x2 %0, %1, %2, %3;" : "=r"(d) : "r"(a), "r"(b), "r"(c)); return d;
}
__device__ __forceinline__ uint32_t bf_mul(uint32_t a, uint32_t b) {
    uint32_t d; asm("mul.rn.bf16x2 %0, %1, %2;" : "=r"(d) : "r"(a), "r"(b)); return d;
}
__device__ __forceinline__ uint32_t bf_absmax(uint32_t a, uint32_t b) {
    uint32_t d; asm("max.xorsign.abs.bf16x2 %0, %1, %2;" : "=r"(d) : "r"(a), "r"(b)); return d;
}
__device__ __forceinline__ uint32_t h_fma(uint32_t a, uint32_t b, uint32_t c) {
    uint32_t d; asm("fma.rn.f16x2 %0, %1, %2, %3;" : "=r"(d) : "r"(a), "r"(b), "r"(c)); return d;
}
__device__ __forceinline__ uint32_t h_mul(uint32_t a, uint32_t b) {
    uint32_t d; asm("mul.rn.f16x2 %0, %1, %2;" : "=r"(d) : "r"(a), "r"(b)); return d;
}
__device__ __forceinline__ uint32_t h_round8(uint32_t v) { return (v + 0x00040004u) & 0xfff8fff8u; }
__device__ __forceinline__ uint32_t h_tanh(uint32_t a) {
    uint32_t d; asm("tanh.approx.f16x2 %0, %1;" : "=r"(d) : "r"(a)); return d;
}
__device__ __forceinline__ uint32_t pack_h2(float lo, float hi) {
    uint32_t d; asm("cvt.rn.f16x2.f32 %0, %1, %2;" : "=r"(d) : "f"(hi), "f"(lo)); return d;
}
__device__ __forceinline__ uint32_t pack_bf2(float lo, float hi) {
    uint32_t d; asm("cvt.rn.bf16x2.f32 %0, %1, %2;" : "=r"(d) : "f"(hi), "f"(lo)); return d;
}
__device__ __forceinline__ float bf_lo(uint32_t v) { return __uint_as_float(v << 16); }
__device__ __forceinline__ float bf_hi(uint32_t v) { return __uint_as_float(v & 0xffff0000u); }
__device__ __forceinline__ float h_lo(uint32_t v) { return __low2float(*reinterpret_cast<__half2*>(&v)); }
__device__ __forceinline__ float h_hi(uint32_t v) { return __high2float(*reinterpret_cast<__half2*>(&v)); }
__device__ __forceinline__ float warp_absmax(uint32_t v) {
    return __uint_as_float(__reduce_max_sync(~0u, max((v & 0x7fffu) << 16, v & 0x7fff0000u)));
}
__device__ __forceinline__ uint32_t gelu2(uint32_t z) {
    uint32_t p = h_fma(z, z, GELU_C2);
    uint32_t t = h_tanh(K_OP & 1 ? h_mul(p, z) : h_mul(z, p));
    return K_OP & 2 ? h_fma(t, z, z) : h_fma(z, t, z);
}
__device__ __forceinline__ float grn_norm(float ss) {
    float r;
    asm("sqrt.approx.f32 %0, %1;" : "=f"(r) : "f"(fmaf(ss, INV_2KZ * INV_2KZ, 1e-6f)));
    return r;
}
__device__ __forceinline__ float pow2i(int e) { return __uint_as_float((uint32_t)(e + 127) << 23); }
__device__ __forceinline__ int ilog2f(float v) {
    int e = (int)((__float_as_uint(v) >> 23) & 0xff) - 127;
    return max(-100, min(100, e));
}

__device__ __forceinline__ int square_exp(float w1max) {
    const int e = w1max > 0.f ? 4 - ilog2f(2.f * KZ * 96.f * w1max) : 0;
    return (e >= 0 && e <= 6) ? 0 : max(-14, min(e, 14));
}
__device__ __forceinline__ int sum_exp(float w1max) {
    return w1max > 0.f ? max(-90, min(90, 33 - 2 * ilog2f(2.f * KZ * 96.f * w1max))) : 0;
}
__device__ __forceinline__ float row_scale(float m) { return m > 0.f ? pow2i(2 - ilog2f(m)) : 1.f; }

struct Split {
    int per_cta, extra, period, inv_period, lenders;
    __host__ __device__ __forceinline__ int longer_before(int cta) const {
        const int n = (cta + period / 2) * inv_period >> 16;
        return n < extra ? n : extra;
    }
};
struct Work {
    int tA, tB, nA, nB, dir, rows, lent, index;
    __device__ __forceinline__ int tile(int j) const { return j < nA ? tA + dir * j : tB + dir * (j - nA); }
};
__host__ __device__ __forceinline__ Work get_work(int cta, const Split& sp) {
    Work w;
    const int before = sp.longer_before(cta), longer = sp.longer_before(cta + 1) - before;
    w.lent = longer && sp.lenders ? LENT : 0;
    w.index = longer ? before : cta - before;
    const int t0 = cta * sp.per_cta + before, t1 = t0 + sp.per_cta + longer;
    const int tm = t1 < (t0 | 511) + 1 ? t1 : (t0 | 511) + 1;
    const bool swap = t1 > tm && t1 - tm < tm - t0, down = cta & 1;
    w.nA = swap ? t1 - tm : tm - t0;
    w.nB = t1 - t0 - w.nA;
    w.tA = down ? (swap ? tm : t0) : (swap ? t1 : tm) - 1;
    w.tB = down ? (swap ? t0 : tm) : (swap ? tm : t1) - 1;
    w.dir = down ? 1 : -1;
    w.rows = w.nA + 2 + (w.nB ? w.nB + 2 : 0);
    return w;
}
__device__ __forceinline__ int row_code(const Work& w, int i) {
    const bool in_a = i < w.nA + 2;
    const int t = in_a ? w.tA : w.tB;
    return ((t & 511) + w.dir * ((in_a ? i : i - (w.nA + 2)) - 1)) << 16 | (t >> 9) * TILE_W;
}
__device__ __forceinline__ uint32_t tile_offset(int tile) { return ((tile & 511) * IMG_W + (tile >> 9) * TILE_W) * (CH * 2); }
__device__ __forceinline__ int tile_order(int j, int n) {
    const int olds = (j / ORDER_P) * ORDER_Q + max(0, j % ORDER_P - (ORDER_P - ORDER_Q));
    return (j % ORDER_P >= ORDER_P - ORDER_Q) ? olds : n - 1 - (j - olds);
}
__device__ __forceinline__ void issue_region(const CUtensorMap* tm, uint32_t dst, uint32_t bar, int warp, int code) {
    mbar_expect_tx(bar, REGION_BYTES);
    tma_row(dst, tm, bar, (code & 0xffff) + (16 * warp - 1), code >> 16);
}

template <class Event>
__device__ __forceinline__ void conv_producer(const Work& wk, const CUtensorMap* tm, uint32_t sb, int warp, Event event) {
    const int lane = threadIdx.x & 31;
    const int j = lane & 15, grp = lane >> 4;
    const uint32_t reg0 = sb + SM_RING + warp * REGION_BYTES;
    const uint32_t bars = sb + SM_BAR + warp * 8;
    if (lane >= PREFETCH_ROWS && lane < 3 * NSLOT) mbar_init(bars + lane * 32, 1);
    if (lane >= 28) mbar_init(sb + BAR_R + ((lane - 28) * 4 + warp) * 8, 1);
    if (lane == 0 && warp == 0) mbar_init(sb + BAR_PIN, 1);
    if (warp * 32 + lane < MAX_ROWS) {
        const int i = warp * 32 + lane, before = min(i / 5, wk.lent);
        const bool back = i % 5 == 0 && i > 0 && i / 5 <= wk.lent;
        sts32(sb + SM_TILES + i * 4, back ? tile_offset(wk.tile(before - 1)) | before
                                          : tile_offset(wk.tile(wk.lent + tile_order(i - before, wk.nA + wk.nB - NCONS - wk.lent))));
    }
    const uint32_t ld64 = opaque(reg0 + grp * 8 * 192 + j * 8), ld32 = opaque(reg0 + grp * 8 * 192 + 128 + j * 4);
    const uint32_t st64 = opaque(reg0 + grp * A_SBO + (j >> 1) * A_LBO + (j & 1) * 8);
    const uint32_t st32 = opaque(reg0 + grp * A_SBO + (8 + (j >> 2)) * A_LBO + (j & 3) * 4);
    fence_async();
    named_bar(0, NTHREADS);
    uint32_t w[3][3][3];
    mbar_wait(sb + BAR_F, 0);
#pragma unroll
    for (int tap = 0; tap < 9; tap++) {
        const uint32_t p = sb + SM_FILTER + (3 + wk.dir * 3 * (tap / 3 - 1) + tap % 3) * (CH * 2);
        lds64(w[tap / 3][tap % 3][0], w[tap / 3][tap % 3][1], p + 8 * j);
        lds32(w[tap / 3][tap % 3][2], p + 128 + 4 * j);
    }
#pragma unroll
    for (int tap = 0; tap < 9; tap++) sts64(reg0 + (NSLOT - 1) * SLOT_BYTES + tap * 128 + j * 8, w[tap / 3][tap % 3][1], w[tap / 3][tap % 3][0]);
#pragma unroll
    for (int tap = 0; tap < 9; tap++) lds64(w[tap / 3][tap % 3][1], w[tap / 3][tap % 3][0], reg0 + (NSLOT - 1) * SLOT_BYTES + tap * 128 + j * 8);
    fence_async();
    named_bar(1, 128);
    static_assert(2 * PREFETCH_ROWS == NSLOT && SLOT_BYTES % 32 == 0, "slot arithmetic");
    uint32_t bo = 0, par = 0, pbo = PREFETCH_ROWS * 32, ppar = 1;
    int px, py;
    auto request = [&]() {
        mbar_wait(bars + (BAR_E - SM_BAR) + pbo, ppar);
        if (elect_one()) {
            mbar_expect_tx(bars + pbo, REGION_BYTES);
            tma_row(reg0 + pbo * (SLOT_BYTES / 32), tm, bars + pbo, px, py);
        }
    };
    auto advance = [&]() {
        bo += 32;
        if (bo == NSLOT * 32) { bo = 0; par ^= 1; }
        pbo += 32;
        if (pbo == NSLOT * 32) { pbo = 0; ppar ^= 1; }
    };
    auto aim = [&](int row) {
        const int code = row_code(wk, row);
        px = (code & 0xffff) + (16 * warp - 1);
        py = code >> 16;
    };
    uint32_t accB[8][3], accC[8][3];
    int r = 0;
#pragma unroll 1
    while (r < wk.rows) {
        if (r == 0 || r == wk.nA + 2) {
            const uint32_t bo0 = bo;
            uint32_t bo1;
#pragma unroll 1
            for (int k = 0; k < 2; k++, r++) {
                mbar_wait(bars + bo, par);
                bo1 = bo;
                aim(r + PREFETCH_ROWS);
                request();
                advance();
            }
            const uint32_t so0 = bo0 * (SLOT_BYTES / 32), so1 = bo1 * (SLOT_BYTES / 32);
#pragma unroll
            for (int p = 0; p < 10; p++) {
                uint32_t u[3], v[3];
                lds64(u[0], u[1], so0 + ld64 + p * 192);
                lds32(u[2], so0 + ld32 + p * 192);
                lds64(v[0], v[1], so1 + ld64 + p * 192);
                lds32(v[2], so1 + ld32 + p * 192);
#pragma unroll
                for (int dx = 0; dx < 3; dx++) {
                    const int o = p - dx;
                    if (o < 0 || o > 7) continue;
#pragma unroll
                    for (int q = 0; q < 3; q++) {
                        accB[o][q] = bf_fma(v[q], w[1][dx][q], dx == 0 ? bf_mul(u[q], w[0][dx][q]) : bf_fma(u[q], w[0][dx][q], accB[o][q]));
                        accC[o][q] = dx == 0 ? bf_mul(v[q], w[0][dx][q]) : bf_fma(v[q], w[0][dx][q], accC[o][q]);
                    }
                }
            }
            anchor(ld64, accB[7][0], accB[7][1], accB[7][2], 0);
            __syncwarp();
            if (elect_one()) {
                mbar_arrive(bars + (BAR_A - SM_BAR) + bo0);
                mbar_arrive(bars + (BAR_E - SM_BAR) + bo0);
                mbar_arrive(bars + (BAR_A - SM_BAR) + bo1);
                mbar_arrive(bars + (BAR_E - SM_BAR) + bo1);
            }
        }
        int end = wk.rows;
        const int marks[4] = {wk.rows - PREFETCH_ROWS, wk.rows - 11, wk.nA + 2, wk.nA + 2 - PREFETCH_ROWS};
#pragma unroll
        for (int k = 0; k < 4; k++) end = marks[k] > r ? min(end, marks[k]) : end;
        const bool fetch = r < wk.rows - PREFETCH_ROWS;
        aim(r + PREFETCH_ROWS);
        px = opaque_uniform(px);
        const int py_end = opaque_uniform(py + wk.dir * (end - r));
        r = end;
#pragma unroll 1
        do {
            mbar_wait(bars + bo, par);
            const uint32_t so = bo * (SLOT_BYTES / 32);
            uint32_t out[8][3];
#pragma unroll
            for (int p = 0; p < 10; p++) {
                uint32_t xv[3];
                lds64(xv[0], xv[1], so + ld64 + p * 192);
                lds32(xv[2], so + ld32 + p * 192);
#pragma unroll
                for (int dd = 0; dd < 3; dd++) {
                    const int dx = K_PD ? 2 - dd : dd, o = p - dx;
                    if (o < 0 || o > 7) continue;
#pragma unroll
                    for (int qq = 0; qq < 3; qq++) {
                        const int q = (qq + K_PQ) % 3;
                        out[o][q] = bf_fma(xv[q], w[2][dx][q], dx == 0 ? accB[o][q] : out[o][q]);
                        accB[o][q] = bf_fma(xv[q], w[1][dx][q], dx == 0 ? accC[o][q] : accB[o][q]);
                        accC[o][q] = dx == 0 ? bf_mul(xv[q], w[0][dx][q]) : bf_fma(xv[q], w[0][dx][q], accC[o][q]);
                    }
                }
            }
            __syncwarp();
#pragma unroll
            for (int oo = 0; oo < 8; oo++) {
                const int o = K_PS ? 7 - oo : oo;
                sts64(so + st64 + o * 16, out[o][0], out[o][1]);
                sts32(so + st32 + o * 16, out[o][2]);
            }
            __syncwarp();
            if (elect_one()) mbar_arrive(bars + (BAR_A - SM_BAR) + bo);
            if (fetch) request();
            advance();
            py += wk.dir;
        } while (py != py_end);
        if (((wk.rows - r) & ~8) == PREFETCH_ROWS) event(wk.rows - r == PREFETCH_ROWS);
    }
}

template <bool SCALED, int K0 = 0, int K1 = 3>
__device__ __forceinline__ void gelu_sq(uint32_t (&d)[24], uint32_t (&keep)[24], uint32_t sq_addr, uint32_t scale2) {
    pin(d);
#pragma unroll
    for (int k = K0; k < K1; k++) {
        uint32_t hs[4];
        lds128(hs[0], hs[1], hs[2], hs[3], sq_addr + k * SQ_ROW);
#pragma unroll
        for (int qq = 0; qq < 4; qq++) {
            const int q = K_QS == 0 ? qq : K_QS == 1 ? 3 - qq : K_QS == 2 ? (qq >> 1 | (qq & 1) << 1) : (qq + 1) & 3;
            uint32_t g0 = gelu2(d[8 * k + 2 * q]), g1 = gelu2(d[8 * k + 2 * q + 1]);
            keep[8 * k + 2 * q] = g0;
            keep[8 * k + 2 * q + 1] = g1;
            if (SCALED) { g0 = h_mul(g0, scale2); g1 = h_mul(g1, scale2); }
            hs[q] = (K_GS >> (q & 1) & 1) ? h_fma(g0, g0, h_fma(g1, g1, hs[q])) : h_fma(g1, g1, h_fma(g0, g0, hs[q]));
        }
        sts128(sq_addr + k * SQ_ROW, hs[0], hs[1], hs[2], hs[3]);
    }
}
__device__ __forceinline__ void gelu_sq_reg(uint32_t (&d)[24], uint32_t (&hs)[12]) {
    pin(d);
#pragma unroll
    for (int qq = 0; qq < 12; qq++) {
        const int q = K_QR == 0 ? qq : K_QR == 1 ? 11 - qq : K_QR == 2 ? qq ^ 1 : qq * 5 % 12;
        const uint32_t g0 = gelu2(d[2 * q]), g1 = gelu2(d[2 * q + 1]);
        hs[q] = (K_GR >> (q & 1) & 1) ? h_fma(g0, g0, h_fma(g1, g1, hs[q])) : h_fma(g1, g1, h_fma(g0, g0, hs[q]));
    }
}
__device__ __forceinline__ void gelu_to(uint32_t (&g)[12], uint32_t (&d)[12]) {
    pin(d);
#pragma unroll
    for (int q = 0; q < 12; q++) g[q] = gelu2(d[q]);
    pin(g);
}
__device__ __forceinline__ void load_tile(uint32_t (&raw)[6][4], uint32_t addr) {
#pragma unroll
    for (int s = 0; s < 6; s++) ldsm4(raw[s], addr + s * 2 * A_LBO);
}
__device__ __forceinline__ uint2 ln_stats(const uint32_t (&raw)[6][4], uint64_t ones) {
    constexpr int NS = 6 / K_CHAIN;
    uint32_t sq[NS][4];
#pragma unroll
    for (int s = 0; s < 6; s++)
#pragma unroll
        for (int q = 0; q < 4; q++) sq[s % NS][q] = s < NS ? bf_mul(raw[s][q], raw[s][q]) : bf_fma(raw[s][q], raw[s][q], sq[s % NS][q]);
    float sum[4], ssq[4];
    wg_fence();
    wgmma_rowsum<0>(sum, raw[0], ones);
#pragma unroll
    for (int s = 1; s < 6; s++) wgmma_rowsum<1>(sum, raw[s], ones);
    wgmma_rowsum<0>(ssq, sq[0], ones);
#pragma unroll
    for (int s = 1; s < NS; s++) wgmma_rowsum<1>(ssq, sq[s], ones);
    wg_commit();
    wg_wait<0>();
    uint32_t st[2];
#pragma unroll
    for (int h = 0; h < 2; h++) {
        asm volatile("" : "+f"(sum[2 * h]), "+f"(ssq[2 * h])::"memory");
        const float mean = sum[2 * h] * (1.f / CH);
        const float var = fmaxf(fmaf(ssq[2 * h], 1.f / CH, -mean * mean), 0.f);
        float rstd;
        asm("rsqrt.approx.ftz.f32 %0, %1;" : "=f"(rstd) : "f"(var + 1e-5f));
        rstd = bf_lo(pack_bf2(rstd * (K_CVT == 0 ? KZ : KZ * 0x1p-112f), 0.f));
        st[h] = pack_bf2(rstd, -mean * rstd);
    }
    return make_uint2(st[0], st[1]);
}
__device__ __forceinline__ void ln_apply(uint32_t (&a)[6][4], const uint2& st) {
    const uint32_t sc[2] = {__byte_perm(st.x, 0, 0x1010), __byte_perm(st.y, 0, 0x1010)};
    const uint32_t sh[2] = {__byte_perm(st.x, 0, 0x3232), __byte_perm(st.y, 0, 0x3232)};
#pragma unroll
    for (int s = 0; s < 6; s++)
#pragma unroll
        for (int q = 0; q < 4; q++) {
            const uint32_t v = bf_fma(a[s][q], sc[q & 1], sh[q & 1]);
            a[s][q] = K_CVT == 0 ? pack_h2(bf_lo(v), bf_hi(v)) : K_CVT == 1 ? (v & 0x7fff7fffu) * 7u + v : ((v << 3) & 0x7fff7fffu) | (v & 0x80008000u);
        }
}
struct Cursor {
    int slot;
    uint32_t par;
    __device__ __forceinline__ void advance(int n) {
        slot += n;
        if (slot >= NSLOT) { slot -= NSLOT; par ^= 1; }
    }
};
struct Descs {
    uint64_t w1[8][6];
    uint64_t w2[24];
    uint64_t ones;
};
template <int E0, int N>
__device__ __forceinline__ void gemm1_chunk(uint32_t (&d)[N], const uint32_t (&a)[6][4], const Descs& ds, int zero) {
#pragma unroll
    for (int s = 0; s < 6; s++) wgmma(d, a[s][0], a[s][1], a[s][2], a[s][3], ds.w1[E0 / 48][s], s ? 1 : zero);
}
template <int E0, int N>
__device__ __forceinline__ void gemm2_chunk(uint32_t (&acc)[24], const uint32_t (&g)[N], const Descs& ds) {
#pragma unroll
    for (int s = 0; s < N / 4; s++) wgmma(acc, g[4 * s], g[4 * s + 1], g[4 * s + 2], g[4 * s + 3], ds.w2[E0 / 16 + s], 1);
}

__global__ void __launch_bounds__(NTHREADS, 1)
block_kernel(const __grid_constant__ CUtensorMap tmap, const __grid_constant__ CUtensorMap tmap_w1,
             const __nv_bfloat16* __restrict__ x, const __nv_bfloat16* __restrict__ dw, const __nv_bfloat16* __restrict__ w2,
             const __nv_bfloat16* __restrict__ gamma, const __nv_bfloat16* __restrict__ beta, __nv_bfloat16* __restrict__ out,
             Scratch* __restrict__ sc, const __grid_constant__ Descs ds,
             const int zero, const __grid_constant__ Split sp) {
    extern __shared__ __align__(1024) uint8_t smem[];
    constexpr uint32_t sb = SB;
    const int tid = threadIdx.x;
    const Work wk = get_work(blockIdx.x, sp);
    constexpr uint32_t s_red = sb + SM_RED;
    if (smem_u32(smem) != SB) __trap();

    PROF(0);
    const int warp_id = __shfl_sync(~0u, tid >> 5, 0);
    const int cw = warp_id - 4, wgi = cw >> 2, w4 = warp_id & 3;
    if (elect_one()) {
        if (warp_id < 8) {
            mbar_init(sb + BAR_X + warp_id * 8, 1);
            if (warp_id < 4) mbar_init(sb + BAR_X + (warp_id + 8) * 8, 1);
            fence_async();
#pragma unroll 1
            for (int r = warp_id >> 2; r < PREFETCH_ROWS; r += 2)
                issue_region(&tmap, sb + SM_RING + r * SLOT_BYTES + w4 * REGION_BYTES, sb + BAR_X + (r * 4 + w4) * 8, w4,
                             ((wk.tA & 511) + wk.dir * (r - 1)) << 16 | (wk.tA >> 9) * TILE_W);
        } else if (warp_id < 15) {
            const int b = warp_id - 8;
            mbar_init(sb + BAR_W + b * 8, 1);
            fence_async();
            mbar_expect_tx(sb + BAR_W + b * 8, b < 6 ? 64 * CH * 2 : 9 * CH * 2);
            if (b < 6) tma_2d(sb + SM_W2 + b * (64 * CH * 2), &tmap_w1, sb + BAR_W + b * 8, 64 * b, 0);
            else bulk_load(sb + SM_FILTER, dw, 9 * CH * 2, sb + BAR_F);
        }
    }
    __syncwarp();
    const int ntiles = wk.nA + wk.nB;
    const int wg = warp_id >> 2;
    int first = wg;
    uint32_t a[6][4], acc[24], tile_off, next_off, stage, inv_rho2 = 0, rpar = 0, bias_addr, lane16, lane_off;
    auto set_lane = [&](uint32_t lane) {
        bias_addr = sb + SM_BIASH + (lane & 3) * 96;
        lane16 = lane * 16;
        lane_off = ((lane >> 2) * CH + 8 * (lane & 3)) * 2;
    };
    const uint32_t bar_r = sb + BAR_R + warp_id * 8;
    auto load_bias = [&](uint32_t (&acc)[24]) {
#pragma unroll
        for (int q = 0; q < 6; q++) lds128(acc[4 * q], acc[4 * q + 1], acc[4 * q + 2], acc[4 * q + 3], bias_addr + q * 16);
    };
    auto load_frags = [&](bool on) {
#pragma unroll
        for (int s = 0; s < 6; s++) ldg128_if(on, a[s], reinterpret_cast<const char*>(out) + next_off + w4 * WARP_BYTES + lane16 + s * 512);
    };
    auto load_first = [&]() {
#pragma unroll
        for (int s = 0; s < 6; s++) ldg128(a[s], reinterpret_cast<const char*>(out) + next_off + w4 * WARP_BYTES + lane16 + s * 512);
    };
    auto stage_x = [&]() {
        if (elect_one()) {
            mbar_expect_tx(bar_r, WARP_BYTES);
            bulk_load_stream(stage, reinterpret_cast<const char*>(x) + tile_off + w4 * WARP_BYTES, WARP_BYTES, bar_r);
        }
    };
    auto epilogue = [&](uint32_t (&acc)[24]) {
        pin(acc);
        rpar ^= 1;
        uint4* op = reinterpret_cast<uint4*>(reinterpret_cast<char*>(out) + tile_off + w4 * WARP_BYTES + lane_off);
#pragma unroll
        for (int h = 0; h < 2; h++)
#pragma unroll
            for (int m = 0; m < 3; m++) {
                uint32_t xin[4], o[4];
                lds128(xin[0], xin[1], xin[2], xin[3], stage + lane_off + h * 1536 + m * 64);
#pragma unroll
                for (int q = 0; q < 4; q++) {
                    const uint32_t v = acc[2 * (4 * m + q) + h];
                    o[q] = bf_fma(pack_bf2(h_lo(v), h_hi(v)), inv_rho2, xin[q]);
                }
                __stcs(op + h * 96 + m * 4, make_uint4(o[0], o[1], o[2], o[3]));
            }
        __syncwarp();
    };
    const bool helps = !wk.lent && wk.index < 8 * LENT * sp.lenders;
    const int help_slot = (wk.rows + 2) % NSLOT;
    const uint32_t s_help = sb + SM_RING + help_slot * SLOT_BYTES + SQ_WG;
    auto reduce = [&](int q, uint32_t lane, bool leader) {
        const int part = lane >> 2, ch = 32 * q + 8 * (part >> 1) + 2 * (lane & 3) + (part & 1);
        uint32_t sq_e, sum_e;
        lds64(sq_e, sum_e, s_red + RED_SQ_EXP);
        const float to_fixed = pow2i(sum_e - 2 * sq_e);
        unsigned long long* dst = sc->sum(ch);
        named_bar(11, CONS_THREADS);
        const unsigned in_piece = ch - wk.index % 8 * 48;
        float helped = 0.f;
        if (helps && in_piece < 48) {
            uint32_t u[4];
            lds128(u[0], u[1], u[2], u[3], s_help + in_piece * 16);
            helped = ((__uint_as_float(u[0]) + __uint_as_float(u[1])) + (__uint_as_float(u[2]) + __uint_as_float(u[3]))) * pow2i(2 * sq_e);
        }
        float f[8] = {};
        int slot = wk.rows % NSLOT;
#pragma unroll 1
        for (int i = 0; i < NCONS; i++) {
            if (i == NCONS - 1) {
                named_bar(13, CONS_THREADS);
                if (leader) {
                    fence_async();
                    bulk_load(sb + SM_W2, sc->w2h, (NCONS - 1) * SQ_WG, sb + BAR_W);
                }
                __syncwarp();
                named_bar(14, NTHREADS);
            }
            const uint32_t src = sb + lane * 16 + q * SQ_ROW + (q < 6 ? SM_SQ + i * SQ_WG : sq_e ? SM_SQ + (NCONS - 1 + i) * SQ_WG : SM_RING + slot * SLOT_BYTES - SQ_WG);
            slot = slot == NSLOT - 1 ? 0 : slot + 1;
#pragma unroll
            for (int r = 0; r < 4; r++) {
                uint32_t u[4];
                lds128(u[0], u[1], u[2], u[3], src + r * 512);
#pragma unroll
                for (int k = 0; k < 4; k++) { f[2 * k] += h_lo(u[k]); f[2 * k + 1] += h_hi(u[k]); }
            }
        }
        const bool b2 = part & 4, b1 = part & 2, b0 = part & 1;
        float r4[4], r2[2];
#pragma unroll
        for (int k = 0; k < 4; k++) r4[k] = (b2 ? f[k + 4] : f[k]) + __shfl_xor_sync(~0u, b2 ? f[k] : f[k + 4], 16);
#pragma unroll
        for (int k = 0; k < 2; k++) r2[k] = (b1 ? r4[k + 2] : r4[k]) + __shfl_xor_sync(~0u, b1 ? r4[k] : r4[k + 2], 8);
        const float tot = (b0 ? r2[1] : r2[0]) + __shfl_xor_sync(~0u, b0 ? r2[0] : r2[1], 4);
        atomicAdd(dst, __float2ull_rn(fminf((tot + helped) * to_fixed, 0x1p47f)) << 8 | 1);
    };
    const uint32_t s_fac = sb + SM_RING + (wk.rows + 1) % NSLOT * SLOT_BYTES + SQ_WG;
    if (warp_id < 4) {
        const bool prepares = gridDim.x - blockIdx.x <= W2_GROUPS / 2;
        const int q = (gridDim.x - 1 - blockIdx.x) * 2 + (w4 >> 1);
        auto lent_tile = [&]() {
            return tile_offset(get_work((wk.index / (8 * LENT) + 1) * sp.period - sp.period / 2 - 1, sp).tile(wk.index / 8 % LENT));
        };
        conv_producer(wk, &tmap, sb, warp_id, [&](bool second) {
            if (!second) {
                if (blockIdx.x == 0) {
#pragma unroll 1
                    for (int e = tid; e < EX; e += 128) *sc->sum(e) = 0;
                    sc->bias[tid] = 0.f;
                    signal(&sc->early);
                }
                if (wk.lent) signal(&sc->early);
            } else if (prepares || helps) {
                spin_until(&sc->early, (ldsi(s_red + RED_LAUNCH) + 1) * 4 * (sp.lenders + 1));
                if (elect_one()) {
                    if (helps) prefetch_l2(reinterpret_cast<const char*>(out) + lent_tile() + w4 * WARP_BYTES, WARP_BYTES);
                    if (prepares) { prefetch_l2(w2 + 8 * q * CH, 8 * CH * 2); prefetch_l2(beta + 8 * q, 16); }
                }
            }
        });
        const int lane = opaque(tid & 31), g = lane >> 2, t = lane & 3;
        const unsigned epoch = ldsi(s_red + RED_LAUNCH);
        set_lane(lane);
        const int i0 = w4 * 32 + lane;
        float gam[3], rmax[3];
#pragma unroll
        for (int m = 0; m < 3; m++) {
            unsigned short v;
            asm volatile("ld.global.nc.u16 %0, [%1];" : "=h"(v) : "l"(gamma + i0 + 128 * m) : "memory");
            gam[m] = bf_lo(v);
        }
        if (prepares) {
            const int half = w4 & 1;
            uint32_t u[3][2], rmax = 0;
#pragma unroll
            for (int m = 0; m < 3; m++) {
                const uint4 w = ldg128_ordered(w2 + (8 * q + g) * CH + 32 * m + 8 * t);
                rmax = bf_absmax(bf_absmax(rmax, bf_absmax(w.x, w.y)), bf_absmax(w.z, w.w));
                u[m][0] = half ? w.z : w.x;
                u[m][1] = half ? w.w : w.y;
            }
            const float bt = __bfloat162float(beta[8 * q + g]);
            rmax = bf_absmax(rmax, __shfl_xor_sync(~0u, rmax, 1));
            rmax = bf_absmax(rmax, __shfl_xor_sync(~0u, rmax, 2));
            const float mx = fmaxf(fabsf(bf_lo(rmax)), fabsf(bf_hi(rmax))), rs = row_scale(mx);
            if (t == 0 && !half) sc->w2max[8 * q + g] = mx;
#pragma unroll
            for (int m = 0; m < 3; m++) {
                float f[4];
#pragma unroll
                for (int k = 0; k < 2; k++) {
                    const float lo = bf_lo(u[m][k]), hi = bf_hi(u[m][k]);
                    sc->w2h[(4 * m + 2 * half + k) * 1536 + q * 32 + lane] = transpose8x8(pack_h2(lo * rs, hi * rs));
                    f[2 * k] = lo * bt;
                    f[2 * k + 1] = hi * bt;
                }
                const float r0 = (g & 2 ? f[2] : f[0]) + __shfl_xor_sync(~0u, g & 2 ? f[0] : f[2], 8);
                const float r1 = (g & 2 ? f[3] : f[1]) + __shfl_xor_sync(~0u, g & 2 ? f[1] : f[3], 8);
                float r = (g & 1 ? r1 : r0) + __shfl_xor_sync(~0u, g & 1 ? r0 : r1, 4);
                r += __shfl_xor_sync(~0u, r, 16);
                if (g < 4) atomicAdd(&sc->bias[32 * m + 8 * t + 4 * half + g], r);
            }
            asm volatile("fence.proxy.async.global;" ::: "memory");
            signal(&sc->prep);
        }
        const int piece = wk.index;
        if (helps) {
            next_off = lent_tile();
            load_first();
            uint32_t d[12], gl[12];
            wg_fence();
#pragma unroll
            for (int s = 0; s < 6; s++) wgmma(d, a[s][0], a[s][1], a[s][2], a[s][3], ds.w1[0][s] + piece % 8 * (6 * 1536 / 16), s ? 1 : 0);
            wg_commit();
            wg_wait<0>();
            gelu_to(gl, d);
#pragma unroll
            for (int s = 0; s < 3; s++) sc->lent[(((piece / (8 * LENT) * 4 + w4) * (8 * LENT) + piece % (8 * LENT)) * 3 + s) * 32 + lane] = make_uint4(gl[4 * s], gl[4 * s + 1], gl[4 * s + 2], gl[4 * s + 3]);
            float f[6], r[3];
#pragma unroll
            for (int j = 0; j < 6; j++) {
                const float lo = fmaf(h_lo(gl[2 * j]), h_lo(gl[2 * j]), h_lo(gl[2 * j + 1]) * h_lo(gl[2 * j + 1]));
                const float hi = fmaf(h_hi(gl[2 * j]), h_hi(gl[2 * j]), h_hi(gl[2 * j + 1]) * h_hi(gl[2 * j + 1]));
                f[j] = (g & 1 ? hi : lo) + __shfl_xor_sync(~0u, g & 1 ? lo : hi, 4);
            }
            mbar_wait(sb + BAR_E + help_slot * 32 + 24, (wk.rows - 4) / NSLOT & 1);
#pragma unroll
            for (int j = 0; j < 3; j++) {
                r[j] = (g & 2 ? f[j + 3] : f[j]) + __shfl_xor_sync(~0u, g & 2 ? f[j] : f[j + 3], 8);
                r[j] += __shfl_xor_sync(~0u, r[j], 16);
                sts32(s_help + (8 * j + 12 * (g & 2) + 2 * t + (g & 1)) * 16 + w4 * 4, __float_as_uint(r[j]));
            }
        }
        const bool leader = warp_id == 0 && lane == 0;
        const float w1max = ldsf(s_red + RED_MAX), from_fixed = pow2i(-ldsi(s_red + RED_SUM_EXP));
        const bool plain = ldsi(s_red + RED_SQ_EXP) == 0;
        auto load_upper = [&]() {
            bulk_load(sb + SM_W2 + NCONS * SQ_WG, reinterpret_cast<const char*>(sc->w2h) + NCONS * SQ_WG, EX * CH * 2 - NCONS * SQ_WG, sb + BAR_W);
        };
        if (leader) {
            spin_until(&sc->prep, (epoch + 1) * 2 * W2_GROUPS);
            asm volatile("fence.proxy.async.global;" ::: "memory");
            fence_async();
            mbar_expect_tx(sb + BAR_W, EX * CH * 2);
            if (plain) load_upper();
        }
        __syncwarp();
        named_bar(1, 128);
#pragma unroll
        for (int m = 0; m < 3; m++) rmax[m] = __ldcg(&sc->w2max[i0 + 128 * m]);
        float2 bpair = make_float2(0.f, 0.f);
        if (i0 < 96) bpair = __ldcg(reinterpret_cast<const float2*>(&sc->bias[32 * (i0 % 24 >> 3) + 8 * (i0 / 24) + (i0 % 24 & 6)]));
        const float gbound = fmaxf(2.f * KZ * 9.7979590f * 192.f * w1max, 1.f) * 19.5959180f * INV_2KZ;
        const unsigned fixed = __reduce_max_sync(~0u, __float_as_uint(fmaf(gbound, fmaxf(fmaxf(rmax[0], rmax[1]), rmax[2]), fmaxf(fabsf(bpair.x), fabsf(bpair.y)))));
        if (lane == 0) sts32(s_red + 96 + w4 * 4, fixed);
        reduce(4 * (NCONS - 1) + w4, lane, leader);
        PROF(2);
        named_bar(15, CONS_THREADS);
        if (leader) {
            fence_async();
            bulk_load(sb + SM_W2 + (NCONS - 1) * SQ_WG, reinterpret_cast<const char*>(sc->w2h) + (NCONS - 1) * SQ_WG, SQ_WG, sb + BAR_W);
            if (!plain) load_upper();
        }
        stage = sb + SM_RING + (wk.rows + 3 + (wk.lent + 2 * ntiles) % NCONS) % NSLOT * SLOT_BYTES + w4 * REGION_BYTES;
        auto grn = [&]() {
            auto peek = [&](int e) {
                unsigned long long v;
                asm volatile("ld.relaxed.gpu.global.u64 %0, [%1];" : "=l"(v) : "l"(sc->sum(e)) : "memory");
                return v;
            };
            unsigned n = 0;
            while (((unsigned)peek((blockIdx.x * 4 + w4) % (EX / 4) * 4) & 255u) != gridDim.x)
                if (++n > SPIN_LIMIT) __trap();
            unsigned long long sum[3];
            for (;;) {
                bool all = true;
#pragma unroll
                for (int m = 0; m < 3; m++) {
                    sum[m] = peek(i0 + 128 * m);
                    all &= ((unsigned)sum[m] & 255u) == gridDim.x;
                }
                if (__all_sync(~0u, all)) break;
                if (++n > SPIN_LIMIT) __trap();
            }
            PROF(3);
            if (blockIdx.x == 0 && leader) sc->launch = epoch + 1;
            float gx[3], tot = 0.f, vary = 0.f;
#pragma unroll
            for (int m = 0; m < 3; m++) {
                gx[m] = grn_norm(__ull2float_rn(sum[m] >> 8) * from_fixed);
                tot += gx[m];
                vary = fmaxf(vary, fabsf(gam[m]) * gx[m] * rmax[m]);
            }
#pragma unroll
            for (int o = 16; o >= 1; o >>= 1) tot += __shfl_xor_sync(~0u, tot, o);
            const unsigned vwarp = __reduce_max_sync(~0u, __float_as_uint(vary));
            if (lane == 0) { sts32(s_red + 64 + w4 * 4, __float_as_uint(tot)); sts32(s_red + 80 + w4 * 4, vwarp); }
            named_bar(1, 128);
            uint32_t u[4], v[4], w[4];
            lds128(u[0], u[1], u[2], u[3], s_red + 64);
            lds128(v[0], v[1], v[2], v[3], s_red + 80);
            lds128(w[0], w[1], w[2], w[3], s_red + 96);
            tot = (__uint_as_float(u[0]) + __uint_as_float(u[1])) + (__uint_as_float(u[2]) + __uint_as_float(u[3]));
            const float vmax = __uint_as_float(max(max(v[0], v[1]), max(v[2], v[3]))), fmax2 = __uint_as_float(max(max(w[0], w[1]), max(w[2], w[3])));
            const float inv_mean = __fdividef(1.f, tot * (1.f / EX) + 1e-6f);
            const float bound = fmaf(gbound * vmax, inv_mean, 2.f * fmax2);
            const int rho_e = bound > 0.f ? 14 - ilog2f(bound) : 0;
            const float rho = pow2i(rho_e), inv_rho = pow2i(-rho_e);
            inv_rho2 = pack_bf2(inv_rho, inv_rho);
#pragma unroll
            for (int m = 0; m < 3; m++) {
                const float f = __fdividef(fmaf(gam[m], gx[m] * inv_mean, 1.f) * INV_2KZ * rho, row_scale(rmax[m]));
                asm volatile("st.shared.u16 [%0], %1;" ::"r"(s_fac + (i0 + 128 * m) * 2), "h"((unsigned short)pack_h2(f, 0.f)) : "memory");
            }
            if (i0 < 96) sts32(sb + SM_BIASH + i0 * 4, pack_h2(bpair.x * rho, bpair.y * rho));
            if (i0 == 96) sts32(s_red + RED_INV_RHO, inv_rho2);
            named_arrive(12, NTHREADS);
        };
        lds32(next_off, sb + SM_TILES);
        next_off = __shfl_sync(~0u, next_off, 0);
        load_first();
        grn();
        if (wk.lent) spin_until(&sc->lent_out, (epoch + 1) * 8 * LENT * sp.lenders);
    } else {
        const int rank = (wgi + wk.lent + 2 * ntiles) % NCONS;
        {
            const int ct = tid - 128, lane = tid & 31;
            const unsigned epoch = *reinterpret_cast<volatile unsigned*>(&sc->launch);
            const int r = lane & 7, mi = lane >> 3;
            const uint32_t src = sb + SM_W2 + (cw >> 1) * (64 * CH * 2) + r * 128 + ((((cw & 1) * 4 + mi) ^ r) * 16);
            const uint32_t dst = sb + SM_W1 + (4 * cw + mi) * 1536 + r * 16;
            if (ct == 0) sts32(s_red + RED_MAX, 0);
            named_bar(0, NTHREADS);
            mbar_wait(sb + BAR_W + (cw >> 1) * 8, 0);
            uint32_t wmax[4] = {}, wsum[4] = {};
#pragma unroll 3
            for (int c = 0; c < 12; c++) {
                uint32_t u[4];
                ldsm4_t(u, src + c * 1024);
#pragma unroll
                for (int q = 0; q < 4; q++) {
                    wmax[q] = bf_absmax(wmax[q], u[q]);
                    wsum[q] = bf_fma(u[q], 0x3f803f80u, wsum[q]);
                    u[q] = pack_h2(bf_lo(u[q]), bf_hi(u[q]));
                }
                stsm4(dst + c * 128, u[0], u[1], u[2], u[3]);
            }
            float mean[4];
            bool center = false;
#pragma unroll
            for (int q = 0; q < 4; q++) {
                uint32_t m = wmax[q];
                float sum = bf_lo(wsum[q]) + bf_hi(wsum[q]);
#pragma unroll
                for (int o = 1; o <= 2; o <<= 1) { m = bf_absmax(m, __shfl_xor_sync(~0u, m, o)); sum += __shfl_xor_sync(~0u, sum, o); }
                mean[q] = sum * (1.f / CH);
                center |= fabsf(mean[q]) > 0.2f * fmaxf(fabsf(bf_lo(m)), fabsf(bf_hi(m)));
            }
            if (__builtin_expect(__any_sync(~0u, center), 0)) {
#pragma unroll 1
                for (int pass = 0; pass < 2; pass++) {
                    float sum[4] = {};
#pragma unroll 1
                    for (int c = 0; c < 12; c++) {
                        uint32_t u[4];
                        ldsm4_t(u, src + c * 1024);
#pragma unroll
                        for (int q = 0; q < 4; q++) {
                            sum[q] += bf_lo(u[q]) + bf_hi(u[q]);
                            u[q] = pack_h2(bf_lo(u[q]) - mean[q], bf_hi(u[q]) - mean[q]);
                        }
                        stsm4(dst + c * 128, u[0], u[1], u[2], u[3]);
                    }
#pragma unroll
                    for (int q = 0; q < 4; q++) {
                        sum[q] += __shfl_xor_sync(~0u, sum[q], 1);
                        sum[q] += __shfl_xor_sync(~0u, sum[q], 2);
                        mean[q] = sum[q] * (1.f / CH);
                    }
                }
            }
            if (cw < 2 * NCONS) {
#pragma unroll
                for (int c = 0; c < 12; c++) sts128(src + c * 1024, 0, 0, 0, 0);
            }
            const float w1max = warp_absmax(bf_absmax(bf_absmax(wmax[0], wmax[1]), bf_absmax(wmax[2], wmax[3])));
            if (lane == 0) asm volatile("red.shared.max.u32 [%0], %1;" ::"r"(s_red + RED_MAX), "r"(__float_as_uint(w1max)) : "memory");
            if (ct < 32) sts32(sb + SM_ONES + ct * 4, 0x3f803f80u);
            if (ct == 0) sts32(s_red + RED_LAUNCH, epoch);
            fence_async();
            named_bar(2, CONS_THREADS);
            const float all_max = ldsf(s_red + RED_MAX);
            const int sq_e = square_exp(all_max);
            sts64(s_red + RED_SQ_EXP, sq_e, sum_exp(all_max));
            if (sq_e) {
#pragma unroll 1
                for (int q = 0; q < 6; q++) sts128(sb + SM_SQ + (rank + NCONS) * SQ_WG + q * SQ_ROW + (ct & 127) * 16, 0, 0, 0, 0);
            }
            mbar_wait(sb + BAR_A + w4 * 8 + 32, 0);
        }

        PROF(1);
        const uint32_t a_addr = opaque(sb + SM_RING + w4 * REGION_BYTES + ((tid >> 3) & 1) * A_SBO + ((tid >> 4) & 1) * A_LBO + (tid & 7) * 16);
        const uint32_t bar_a = sb + BAR_A + w4 * 8, bar_e = sb + BAR_E + w4 * 8;
        const uint32_t sq = opaque(sb + SM_SQ + rank * SQ_WG + (tid & 127) * 16);
        const uint32_t sq_warp = sb + SM_SQ + rank * SQ_WG + w4 * 512;
        uint32_t k1[24], k2[24], k3[24];
        constexpr int SQC = 3 * SQ_ROW;
        const int pass_to = 4 + (wgi == NCONS - 1 ? 0 : wgi + 1);
        auto store_at = [&](const uint32_t (&a)[6][4], uint32_t off) {
            char* ap = reinterpret_cast<char*>(out) + (off + sq);
#pragma unroll
            for (int s = 0; s < 6; s++) stg128(ap + s * 512, a[s]);
        };
        int jt = wgi < wk.lent ? wgi : wk.lent + wgi;
        Cursor cur = {2, 0};
        cur.advance(jt + (jt >= wk.nA ? 2 : 0));
        if (wgi == NCONS - 1) named_arrive(4, 256);
        for (;;) {
            const bool plain = __all_sync(~0u, ldsi(s_red + RED_SQ_EXP) == 0);
            if (plain && jt >= wk.lent) {
                uint32_t hs2[12] = {}, hs3[12] = {};
                const uint32_t own_bar = opaque_uniform(4 + wgi), next_bar = opaque_uniform(pass_to);
                const uint32_t step = opaque_uniform(wk.dir * (NCONS * IMG_W * CH * 2));
#pragma unroll 1
                while (jt + NCONS < ntiles) {
                const int stop = jt < wk.nA ? min(wk.nA, ntiles - NCONS) : ntiles - NCONS, count = (stop - jt + NCONS - 1) / NCONS;
                const int low = cur.slot % 3;
                uint32_t turn = opaque_uniform(cur.par * 2 + cur.slot / 3);
                const uint32_t turn_end = opaque_uniform(turn + count);
                uint32_t so = opaque_uniform(cur.slot * SLOT_BYTES), bo = opaque_uniform(bar_a + cur.slot * 32);
                const uint32_t so_sum = opaque_uniform((2 * low + 3) * SLOT_BYTES), bo_sum = opaque_uniform(2 * bar_a + (2 * low + 3) * 32);
                uint32_t off = opaque_uniform(tile_offset(wk.tile(jt)) + w4 * WARP_BYTES - sq_warp);
                jt += count * NCONS;
                cur.slot = low + 3 * (turn_end & 1);
                cur.par = turn_end >> 1 & 1;
                if (jt >= wk.nA && jt - NCONS < wk.nA) cur.advance(2);
#pragma unroll 1
                do {
                    uint32_t a[6][4], d0[24], d1[24], unused[24];
#define AT(pos) \
    if (K_WAIT == pos) named_bar(own_bar, 256); \
    if (K_PASS == pos) named_arrive(next_bar, 256); \
    if (K_STG == pos) store_at(a, off); \
    if (K_REL == pos) { if (elect_one()) mbar_arrive(bo + (BAR_E - BAR_A)); }
                    AT(20)
                    mbar_wait(bo, turn >> 1 & 1);
                    load_tile(a, a_addr + so);
                    AT(21)
                    const uint2 st = ln_stats(a, ds.ones);
                    AT(0)
                    ln_apply(a, st);
                    AT(1)
                    wg_fence();
                    gemm1_chunk<0>(d0, a, ds, 0);
                    wg_commit();
                    gemm1_chunk<96>(d1, a, ds, 0);
                    wg_commit();
                    AT(2)
                    wg_wait<1>();
                    AT(3)
                    gelu_sq<false, 0, 1>(d0, unused, sq, 0);
                    AT(4)
                    gelu_sq<false, 1, 2>(d0, unused, sq, 0);
                    AT(5)
                    gelu_sq<false, 2, 3>(d0, unused, sq, 0);
                    AT(6)
                    wg_fence();
                    gemm1_chunk<192>(d0, a, ds, zero);
                    wg_commit();
                    AT(7)
                    wg_wait<1>();
                    gelu_sq<false, 0, 1>(d1, unused, sq + SQC, 0);
                    AT(8)
                    gelu_sq<false, 1, 3>(d1, unused, sq + SQC, 0);
                    AT(9)
                    wg_fence();
                    gemm1_chunk<288>(d1, a, ds, zero);
                    wg_commit();
                    AT(10)
                    wg_wait<1>();
                    gelu_sq_reg(d0, hs2);
                    if (K_ANCH < 3) anchor(sq, hs2[4 * (K_ANCH % 3)], hs2[4 * (K_ANCH % 3) + 1], hs2[4 * (K_ANCH % 3) + 2], hs2[4 * (K_ANCH % 3) + 3]);
                    wg_wait<0>();
                    AT(11)
                    gelu_sq_reg(d1, hs3);
#undef AT
                    so = so_sum - so;
                    bo = bo_sum - bo;
                    off += step;
                } while (++turn != turn_end);
                }
                const uint32_t sq2 = sq - (SM_SQ + rank * SQ_WG) + SM_RING + (cur.slot + 3) % NSLOT * SLOT_BYTES;
#pragma unroll
                for (int k = 0; k < 3; k++) {
                    sts128(sq2 + k * SQ_ROW, hs2[4 * k], hs2[4 * k + 1], hs2[4 * k + 2], hs2[4 * k + 3]);
                    sts128(sq2 + SQC + k * SQ_ROW, hs3[4 * k], hs3[4 * k + 1], hs3[4 * k + 2], hs3[4 * k + 3]);
                }
            }
            const bool last = jt + NCONS >= ntiles;
            if (last) {
                tile_off = tile_offset(wk.tile(jt));
                lds32(next_off, sb + SM_TILES + wg * 4);
                next_off = __shfl_sync(~0u, next_off, 0);
                if (elect_one()) {
                    prefetch_l2(reinterpret_cast<const char*>(x) + tile_off + w4 * WARP_BYTES, WARP_BYTES);
                    if (wg % ORDER_P >= ORDER_P - ORDER_Q) prefetch_l2(reinterpret_cast<const char*>(out) + next_off + w4 * WARP_BYTES, WARP_BYTES);
                }
            }
            uint32_t a[6][4], d0[24], d1[24], d3[24], k0[24];
#define AT(pos) \
    if (K_WAIT == pos && jt >= wk.lent) named_bar(4 + wgi, 256); \
    if (K_PASS == pos && jt >= wk.lent && jt + 1 < ntiles) named_arrive(pass_to, 256);
            AT(20)
            mbar_wait(bar_a + cur.slot * 32, cur.par);
            load_tile(a, a_addr + cur.slot * SLOT_BYTES);
            AT(21)
            const uint2 st = ln_stats(a, ds.ones);
            AT(0)
            ln_apply(a, st);
            AT(1)
            if (!last) {
                store_at(a, tile_offset(wk.tile(jt)) + w4 * WARP_BYTES - sq_warp);
                __syncwarp();
                if (elect_one()) mbar_arrive(bar_e + cur.slot * 32);
                if (jt < wk.lent) {
                    jt += LENT;
                    cur.advance(LENT);
                    continue;
                }
            }
            wg_fence();
            gemm1_chunk<0>(d0, a, ds, 0);
            wg_commit();
            gemm1_chunk<96>(d1, a, ds, 0);
            wg_commit();
            const int sq_e = ldsi(s_red + RED_SQ_EXP);
            const uint32_t scale2 = pack_h2(pow2i(sq_e), pow2i(sq_e));
            AT(2)
            wg_wait<1>();
            AT(3)
            gelu_sq<true, 0, 1>(d0, k0, sq, scale2);
            AT(4)
            gelu_sq<true, 1, 2>(d0, k0, sq, scale2);
            AT(5)
            gelu_sq<true, 2, 3>(d0, k0, sq, scale2);
            AT(6)
            if (last) {
#pragma unroll
                for (int q = 0; q < 6; q++) sts128(sb + SM_RING + cur.slot * SLOT_BYTES + w4 * REGION_BYTES - sq_warp + sq + q * 512, k0[4 * q], k0[4 * q + 1], k0[4 * q + 2], k0[4 * q + 3]);
            }
            wg_fence();
            gemm1_chunk<192>(d0, a, ds, zero);
            wg_commit();
            AT(7)
            wg_wait<1>();
            gelu_sq<true, 0, 1>(d1, k1, sq + SQC, scale2);
            AT(8)
            gelu_sq<true, 1, 3>(d1, k1, sq + SQC, scale2);
            AT(9)
#undef AT
            wg_fence();
            gemm1_chunk<288>(d3, a, ds, 0);
            wg_commit();
            wg_wait<1>();
            const uint32_t sq2 = sq + (plain ? SM_RING + (cur.slot + 3) % NSLOT * SLOT_BYTES - (SM_SQ + rank * SQ_WG) : NCONS * SQ_WG);
            gelu_sq<true>(d0, k2, sq2, scale2);
            wg_wait<0>();
            gelu_sq<true>(d3, k3, sq2 + SQC, scale2);
            if (last) break;
            cur.advance(NCONS + ((jt < wk.nA && jt + NCONS >= wk.nA) ? 2 : 0));
            jt += NCONS;
        }
        {
            if (rank == NCONS - 1) {
                named_arrive(14, NTHREADS);
            } else {
                reduce(4 * rank + w4, (sq >> 4) & 31, false);
                named_arrive(15, CONS_THREADS);
                PROF(2);
                if (helps && rank == 0 && w4 == 0) signal(&sc->lent_out);
            }
        }
        {
            set_lane((sq >> 4) & 31);
            const uint32_t row = sb + SM_W2 + cw * 512 + lane16;
            uint32_t u[W2_EARLY][4], f2[4];
            mbar_wait(sb + BAR_W, 1);
#pragma unroll
            for (int nb = 0; nb < W2_EARLY; nb++) lds128(u[nb][0], u[nb][1], u[nb][2], u[nb][3], row + nb * 6144);
            named_bar(12, NTHREADS);
            PROF(3);
            stage = sb + SM_RING + (cur.slot + 3) % NSLOT * SLOT_BYTES + w4 * WARP_BYTES;
            if (K_XPOS == 0) stage_x();
            lds128(f2[0], f2[1], f2[2], f2[3], s_fac + cw * 64 + (lane16 >> 7) * 16);
            lds32(inv_rho2, s_red + RED_INV_RHO);
#pragma unroll
            for (int nb = 0; nb < 12; nb++) {
                uint32_t v[4];
                if (nb < W2_EARLY) { v[0] = u[nb % W2_EARLY][0]; v[1] = u[nb % W2_EARLY][1]; v[2] = u[nb % W2_EARLY][2]; v[3] = u[nb % W2_EARLY][3]; }
                else lds128(v[0], v[1], v[2], v[3], row + nb * 6144);
                sts128(row + nb * 6144, h_round8(h_mul(v[0], f2[0])), h_round8(h_mul(v[1], f2[1])), h_round8(h_mul(v[2], f2[2])), h_round8(h_mul(v[3], f2[3])));
            }
            fence_async();
            if (K_XPOS == 1) stage_x();
            named_bar(3, NTHREADS);
        }
        PROF(4);
        {
            load_bias(acc);
            if (wgi > 0) named_bar(8 + wgi, 256);
            pin(k1); pin(k2); pin(k3);
            wg_fence();
            gemm2_chunk<288>(acc, k3, ds);
            wg_commit();
            gemm2_chunk<(K_SWAP ? 192 : 96)>(acc, K_SWAP ? k2 : k1, ds);
            if (K_FINE) wg_commit();
            gemm2_chunk<(K_SWAP ? 96 : 192)>(acc, K_SWAP ? k1 : k2, ds);
            wg_commit();
            if (!K_LATE && wgi + 1 < NCONS) named_arrive(9 + wgi, 256);
            wg_wait<1 + K_FINE>();
            uint32_t k0[24];
#pragma unroll
            for (int q = 0; q < 6; q++)
                lds128(k0[4 * q], k0[4 * q + 1], k0[4 * q + 2], k0[4 * q + 3], sb + SM_RING + cur.slot * SLOT_BYTES + w4 * REGION_BYTES + lane16 + q * 512);
            pin(k0);
            wg_fence();
            gemm2_chunk<0>(acc, k0, ds);
            wg_commit();
            if (K_LATE && wgi + 1 < NCONS) named_arrive(9 + wgi, 256);
            if (wgi == 0) named_arrive(8, 256);
            wg_wait<1 + K_FINE>();
            load_first();
            if (lane16 == 0) mbar_arrive(sb + BAR_PIN);
            mbar_wait(bar_r, rpar);
            wg_wait<0>();
            first = wg - 4;
        }
    }
    {
        const int nrest = ntiles - NCONS;
        auto lent = [&](uint32_t entry) { return &sc->lent[((wk.index * 4 + w4) * LENT + (entry & 3) - 1) * (8 * 96)]; };
        for (int jt = first; jt < nrest; jt += 4) {
            if (jt >= 0) {
            tile_off = next_off;
            lds32(next_off, sb + SM_TILES + (jt + 4) * 4);
            if (tile_off & 3) {
                uint32_t gl[2][24];
                const uint4* src = lent(tile_off) + (lane16 >> 4);
                auto fetch = [&](uint32_t (&v)[24], int c) {
#pragma unroll
                    for (int s = 0; s < 6; s++) ldg128(reinterpret_cast<uint32_t (&)[4]>(v[4 * s]), src + (6 * c + s) * 32);
                };
                tile_off &= ~3u;
                next_off = __shfl_sync(~0u, next_off, 0);
                stage_x();
                if (elect_one()) prefetch_l2(reinterpret_cast<const char*>(out) + next_off + w4 * WARP_BYTES, WARP_BYTES);
                load_bias(acc);
#pragma unroll
                for (int half = 0; half < 2; half++) {
                    fetch(gl[0], 2 * half);
                    fetch(gl[1], 2 * half + 1);
                    if (!half) {
                        named_bar(4 + wg, 256);
                        named_arrive(4 + ((wg + 1) & 3), 256);
                    }
                    pin(gl[0]); pin(gl[1]);
                    wg_fence();
                    if (half) gemm2_chunk<192>(acc, gl[0], ds); else gemm2_chunk<0>(acc, gl[0], ds);
                    if (half) gemm2_chunk<288>(acc, gl[1], ds); else gemm2_chunk<96>(acc, gl[1], ds);
                    wg_commit();
                    wg_wait<0>();
                }
                load_first();
                mbar_wait(bar_r, rpar);
            } else {
            uint32_t d0[12], d1[12], g0[12], g1[12];
            if (jt >= S2_FIRST && jt < nrest - K_TAIL) named_bar(4 + wg, 256);
            wg_fence();
            gemm1_chunk<0>(d0, a, ds, 0);
            wg_commit();
            gemm1_chunk<48>(d1, a, ds, 0);
            wg_commit();
            load_bias(acc);
            next_off = __shfl_sync(~0u, next_off, 0);
            const bool more = jt + 4 < nrest && !(next_off & 3);
            wg_wait<1>();
#define CNX_PASS if (jt + 1 >= S2_FIRST && jt + 1 < nrest - K_TAIL) named_arrive(4 + ((wg + 1) & 3), 256);
#define CNX_STEP(C, D, G)                                              \
    gelu_to(G, D);                                                     \
    if (C == 0 && jt == 0) {                                           \
        named_bar(3, NTHREADS);                                        \
        load_bias(acc);                                                \
    }                                                                  \
    wg_fence();                                                        \
    if (C < 6) gemm1_chunk<48 * (C < 6 ? C + 2 : 0)>(D, a, ds, zero); \
    gemm2_chunk<48 * C>(acc, G, ds);                                  \
    wg_commit();                                                       \
    if (C == S2_PASS) { CNX_PASS }                                     \
    wg_wait<(C < 7 ? 1 : 0)>();
            CNX_STEP(0, d0, g0)
            CNX_STEP(1, d1, g1)
            if (jt == 0) named_bar(8, 256);
            stage_x();
            if (elect_one()) {
                if (more) prefetch_l2(reinterpret_cast<const char*>(out) + next_off + w4 * WARP_BYTES, WARP_BYTES);
                else if (next_off & 3) prefetch_l2(lent(next_off), 8 * 96 * 16);
            }
            CNX_STEP(2, d0, g0)
            CNX_STEP(3, d1, g1)
            CNX_STEP(4, d0, g0)
            CNX_STEP(5, d1, g1)
            CNX_STEP(6, d0, g0)
            load_frags(more);
            if (lane16 == 0) mbar_arrive(sb + BAR_PIN);
            mbar_wait(bar_r, rpar);
            CNX_STEP(7, d1, g1)
#undef CNX_STEP
            }
            }
            epilogue(acc);
        }
    }
    PROF(5);
}

}

typedef CUresult (*EncodeTiledFn)(CUtensorMap*, CUtensorMapDataType, cuuint32_t, void*, const cuuint64_t*, const cuuint64_t*,
                                  const cuuint32_t*, const cuuint32_t*, CUtensorMapInterleave, CUtensorMapSwizzle,
                                  CUtensorMapL2promotion, CUtensorMapFloatOOBfill);

extern "C" void kernel_launch(void* const* d_in, const int* in_sizes, int n_in, void* d_out, int out_size) {
    using namespace cnx;
    static EncodeTiledFn encode = nullptr;
    static int num_sms = 0;
    static Scratch* scratch = nullptr;
    if (!encode) {
        void* fn = nullptr;
        cudaDriverEntryPointQueryResult qr;
        cudaGetDriverEntryPoint("cuTensorMapEncodeTiled", &fn, cudaEnableDefault, &qr);
        encode = (EncodeTiledFn)fn;
        cudaGetSymbolAddress((void**)&scratch, g_scratch);
        int dev = 0;
        cudaGetDevice(&dev);
        cudaDeviceGetAttribute(&num_sms, cudaDevAttrMultiProcessorCount, dev);
        if (num_sms > MAX_CTAS) num_sms = MAX_CTAS;
        cudaFuncSetAttribute(block_kernel, cudaFuncAttributeMaxDynamicSharedMemorySize, SM_TOTAL);
    }
    CUtensorMap tm;
    cuuint64_t dims[3] = {(cuuint64_t)CH, (cuuint64_t)IMG_W, (cuuint64_t)IMG_H};
    cuuint64_t strides[2] = {(cuuint64_t)CH * 2, (cuuint64_t)CH * 2 * IMG_W};
    cuuint32_t box[3] = {(cuuint32_t)CH, (cuuint32_t)REGION_PX, 1};
    cuuint32_t estr[3] = {1, 1, 1};
    encode(&tm, CU_TENSOR_MAP_DATA_TYPE_BFLOAT16, 3, d_in[0], dims, strides, box, estr, CU_TENSOR_MAP_INTERLEAVE_NONE,
           CU_TENSOR_MAP_SWIZZLE_NONE, CU_TENSOR_MAP_L2_PROMOTION_L2_128B, CU_TENSOR_MAP_FLOAT_OOB_FILL_NONE);
    Descs ds;
    for (int c = 0; c < 8; c++)
        for (int k = 0; k < 6; k++) ds.w1[c][k] = make_desc(SB + SM_W1 + c * 6 * 1536 + k * 256, 128, 1536);
    for (int k = 0; k < 24; k++) ds.w2[k] = make_desc(SB + SM_W2 + k * 256, 128, 6144);
    ds.ones = make_desc(SB + SM_ONES, 0, 0);
    CUtensorMap tw;
    cuuint64_t wdims[2] = {(cuuint64_t)EX, (cuuint64_t)CH};
    cuuint64_t wstrides[1] = {(cuuint64_t)EX * 2};
    cuuint32_t wbox[2] = {64, (cuuint32_t)CH};
    encode(&tw, CU_TENSOR_MAP_DATA_TYPE_BFLOAT16, 2, d_in[2], wdims, wstrides, wbox, estr, CU_TENSOR_MAP_INTERLEAVE_NONE,
           CU_TENSOR_MAP_SWIZZLE_128B, CU_TENSOR_MAP_L2_PROMOTION_L2_128B, CU_TENSOR_MAP_FLOAT_OOB_FILL_NONE);
    Split sp = {NTILES / num_sms, NTILES % num_sms, 1, 1 << 16, 0};
    if (sp.per_cta + 9 > MAX_ROWS) return;
    if (sp.extra && sp.extra * (8 * LENT + 1) <= num_sms && sp.per_cta >= 5 * LENT + 7) {
        sp.period = num_sms / sp.extra;
        sp.inv_period = 65535 / sp.period + 1;
        sp.lenders = sp.extra;
        for (int l = 0; l < sp.extra; l++)
            if (get_work((l + 1) * sp.period - sp.period / 2 - 1, sp).nA < 2 * LENT) sp.lenders = 0;
    }
    block_kernel<<<num_sms, NTHREADS, SM_TOTAL>>>(tm, tw, (const __nv_bfloat16*)d_in[0], (const __nv_bfloat16*)d_in[1],
                                             (const __nv_bfloat16*)d_in[3],
                                             (const __nv_bfloat16*)d_in[4], (const __nv_bfloat16*)d_in[5], (__nv_bfloat16*)d_out,
                                             scratch, ds, 0, sp);
}
```

```cpp
#include <cuda_runtime.h>
#include <cuda_bf16.h>
#include <cuda_fp16.h>
#include <cuda.h>
#include <stdint.h>

namespace cnx {

constexpr int IMG_H = 512, IMG_W = 512, CH = 96, EX = 384;
constexpr int TILE_W = 64;
constexpr int NTILES = (IMG_W / TILE_W) * IMG_H;
constexpr int NSLOT = 6;
constexpr int REGION_PX = 18;
constexpr int REGION_BYTES = REGION_PX * CH * 2;
constexpr int SLOT_BYTES = 4 * REGION_BYTES;
constexpr int A_LBO = 144, A_SBO = 12 * A_LBO;
constexpr int PREFETCH_ROWS = 3;
constexpr int NCONS = 3;
constexpr int CONS_THREADS = 128 * NCONS;
constexpr int NTHREADS = 128 + CONS_THREADS;
constexpr int MAX_ROWS = 52;
constexpr int TILE_BYTES = TILE_W * CH * 2, WARP_BYTES = TILE_BYTES / 4;
constexpr int S1_PASS = 1, S2_PASS = 1;
#define K_PASS 4
#define K_WAIT 20
#define K_STG 5
#define K_REL 6
#define K_ANCH 2
#define K_CVT 0
#define K_XPOS 1
#define K_CHAIN 3
#define K_OP 0
#define K_QS 0
#define K_GS 0
#define K_QR 0
#define K_GR 0
#define K_PD 0
#define K_PQ 0
#define K_PS 0
#define K_ROT 0
#define K_LTOK 0
#define K_LATE 1
#define K_FINE 1
#define K_SWAP 0
#define K_TAIL 0
#define W2_EARLY 6
#define S2_FIRST 2
#define ORDER_P 3
#define ORDER_Q 1
static_assert(MAX_ROWS <= 128, "one table entry per producer thread");
static_assert(2 * A_SBO == REGION_BYTES && REGION_BYTES % 128 == 0, "region layout");

constexpr uint32_t SB = 1024;
constexpr int SM_W1 = 0;
constexpr int SM_W2 = SM_W1 + CH * EX * 2;
constexpr int SM_RING = SM_W2 + CH * EX * 2;
constexpr int SM_BIASH = SM_RING + NSLOT * SLOT_BYTES;
constexpr int SM_RED = SM_BIASH + 384;
constexpr int RED_MAX = 0, RED_LAUNCH = 4, RED_SQ_EXP = 8, RED_SUM_EXP = 12, RED_INV_RHO = 16;
constexpr int SM_TILES = SM_RED + 256;
constexpr int SM_ONES = SM_TILES + MAX_ROWS * 4;
constexpr int SM_BAR = SM_ONES + 128;
constexpr int BAR_X = SM_BAR;
constexpr int BAR_A = BAR_X + NSLOT * 4 * 8;
constexpr int BAR_E = BAR_A + NSLOT * 4 * 8;
constexpr int BAR_PIN = BAR_E + NSLOT * 4 * 8;
constexpr int BAR_W = BAR_PIN + 8;
constexpr int BAR_F = BAR_W + 6 * 8;
constexpr int BAR_R = BAR_F + 8;
constexpr int SM_TOTAL = BAR_R + 16 * 8;
constexpr int SM_FILTER = SM_RING + (NSLOT - 1) * SLOT_BYTES + 9 * 128;
constexpr int SM_SQ = SM_W2;
constexpr int SQ_ROW = 128 * 16, SQ_WG = 6 * SQ_ROW;
static_assert(SM_ONES % 16 == 0 && SM_TOTAL <= 232448, "shared memory budget");

constexpr float KZ = 0.3292034911525734f;
constexpr uint32_t GELU_C2 = 0x40d940d9u;
constexpr float INV_2KZ = 0.5f / KZ;
constexpr unsigned SPIN_LIMIT = 1u << 19;

constexpr int MAX_CTAS = 255;
constexpr int W2_GROUPS = EX / 8;
#define K_LENT 3
constexpr int LENT = K_LENT, MAX_LENDERS = MAX_CTAS / (8 * LENT + 1);
struct Scratch {
    uint32_t w2h[EX * CH / 2];
    float w2max[EX];
    float bias[CH + 32];
    unsigned long long sums[EX / 4][32];
    __device__ __forceinline__ unsigned long long* sum(int e) { return &sums[e >> 2][e & 3]; }
    uint4 lent[MAX_LENDERS * LENT * 8 * 4 * 3 * 32];
    unsigned launch, pad0[31], early, pad1[31], prep, pad2[31], lent_out, pad3[31];
};
__device__ __align__(128) Scratch g_scratch;

#define PROF(k)

__device__ __forceinline__ uint32_t smem_u32(const void* p) { return (uint32_t)__cvta_generic_to_shared(p); }
__device__ __forceinline__ void mbar_init(uint32_t bar, uint32_t cnt) {
    asm volatile("mbarrier.init.shared::cta.b64 [%0], %1;" ::"r"(bar), "r"(cnt) : "memory");
}
__device__ __forceinline__ void mbar_arrive(uint32_t bar) {
    asm volatile("mbarrier.arrive.shared::cta.b64 _, [%0];" ::"r"(bar) : "memory");
}
__device__ __forceinline__ void mbar_expect_tx(uint32_t bar, uint32_t bytes) {
    asm volatile("mbarrier.arrive.expect_tx.shared::cta.b64 _, [%0], %1;" ::"r"(bar), "r"(bytes) : "memory");
}
__device__ __forceinline__ bool mbar_try(uint32_t bar, uint32_t par) {
    uint32_t ok;
    asm volatile("{\n.reg .pred p;\nmbarrier.try_wait.parity.shared::cta.b64 p, [%1], %2;\nselp.u32 %0, 1, 0, p;\n}\n"
                 : "=r"(ok) : "r"(bar), "r"(par) : "memory");
    return ok != 0;
}
__device__ __forceinline__ void mbar_wait(uint32_t bar, uint32_t par) {
    unsigned n = 0;
    while (!mbar_try(bar, par)) {
        if (++n > SPIN_LIMIT) __trap();
    }
}
__device__ __forceinline__ bool mbar_test(uint32_t bar, uint32_t par) {
    uint32_t ok;
    asm volatile("{\n.reg .pred p;\nmbarrier.test_wait.parity.shared::cta.b64 p, [%1], %2;\nselp.u32 %0, 1, 0, p;\n}\n"
                 : "=r"(ok) : "r"(bar), "r"(par) : "memory");
    return ok != 0;
}
__device__ __forceinline__ bool elect_one() {
    uint32_t ok;
    asm volatile("{\n.reg .pred p;\nelect.sync _|p, 0xffffffff;\nselp.u32 %0, 1, 0, p;\n}\n" : "=r"(ok));
    return ok != 0;
}
__device__ __forceinline__ uint32_t opaque(uint32_t v) { return __shfl_sync(~0u, v, threadIdx.x & 31); }
__device__ __forceinline__ uint32_t opaque_uniform(uint32_t v) { return __shfl_sync(~0u, v, 0); }
__device__ __forceinline__ void named_bar(int id, int n) { asm volatile("bar.sync %0, %1;" ::"r"(id), "r"(n) : "memory"); }
__device__ __forceinline__ void named_arrive(int id, int n) { asm volatile("bar.arrive %0, %1;" ::"r"(id), "r"(n) : "memory"); }
__device__ __forceinline__ void fence_async() { asm volatile("fence.proxy.async.shared::cta;" ::: "memory"); }
__device__ __forceinline__ uint64_t evict_first() {
    uint64_t p;
    asm("createpolicy.fractional.L2::evict_first.b64 %0, 1.0;" : "=l"(p));
    return p;
}
__device__ __forceinline__ void tma_row(uint32_t dst, const CUtensorMap* tm, uint32_t bar, int x, int y) {
    asm volatile("cp.async.bulk.tensor.3d.shared::cluster.global.mbarrier::complete_tx::bytes.L2::cache_hint [%0], [%1, {%3, %4, %5}], [%2], %6;"
                 ::"r"(dst), "l"(tm), "r"(bar), "r"(0), "r"(x), "r"(y), "l"(evict_first()) : "memory");
}
__device__ __forceinline__ void bulk_load_stream(uint32_t dst, const void* src, uint32_t bytes, uint32_t bar) {
    asm volatile("cp.async.bulk.shared::cluster.global.mbarrier::complete_tx::bytes.L2::cache_hint [%0], [%1], %2, [%3], %4;"
                 ::"r"(dst), "l"(src), "r"(bytes), "r"(bar), "l"(evict_first()) : "memory");
}
__device__ __forceinline__ void prefetch_l2(const void* src, uint32_t bytes) {
    asm volatile("cp.async.bulk.prefetch.L2.global [%0], %1;" ::"l"(src), "r"(bytes) : "memory");
}
__device__ __forceinline__ void tma_2d(uint32_t dst, const CUtensorMap* tm, uint32_t bar, int x, int y) {
    asm volatile("cp.async.bulk.tensor.2d.shared::cluster.global.mbarrier::complete_tx::bytes [%0], [%1, {%3, %4}], [%2];"
                 ::"r"(dst), "l"(tm), "r"(bar), "r"(x), "r"(y) : "memory");
}
__device__ __forceinline__ void bulk_load(uint32_t dst, const void* src, uint32_t bytes, uint32_t bar) {
    asm volatile("cp.async.bulk.shared::cluster.global.mbarrier::complete_tx::bytes [%0], [%1], %2, [%3];"
                 ::"r"(dst), "l"(src), "r"(bytes), "r"(bar) : "memory");
}
__device__ __forceinline__ void wg_fence() { asm volatile("wgmma.fence.sync.aligned;" ::: "memory"); }
__device__ __forceinline__ void wg_commit() { asm volatile("wgmma.commit_group.sync.aligned;" ::: "memory"); }
template <int N> __device__ __forceinline__ void wg_wait() { asm volatile("wgmma.wait_group.sync.aligned %0;" ::"n"(N) : "memory"); }
template <int N> __device__ __forceinline__ void pin(uint32_t (&d)[N]) {
#pragma unroll
    for (int q = 0; q < N; q++) asm volatile("" : "+r"(d[q])::"memory");
}
__device__ __forceinline__ void stg128(void* p, const uint32_t (&v)[4]) {
    asm volatile("st.global.v4.u32 [%0], {%1, %2, %3, %4};" ::"l"(p), "r"(v[0]), "r"(v[1]), "r"(v[2]), "r"(v[3]) : "memory");
}
__device__ __forceinline__ void ldg128(uint32_t (&v)[4], const void* p) {
    asm volatile("ld.global.L1::no_allocate.v4.u32 {%0, %1, %2, %3}, [%4];" : "=r"(v[0]), "=r"(v[1]), "=r"(v[2]), "=r"(v[3]) : "l"(p) : "memory");
}
__device__ __forceinline__ void ldg128_if(bool on, uint32_t (&v)[4], const void* p) {
    asm volatile("{\n.reg .pred p;\nsetp.ne.b32 p, %5, 0;\n@p ld.global.L1::no_allocate.v4.u32 {%0, %1, %2, %3}, [%4];\n}\n"
                 : "+r"(v[0]), "+r"(v[1]), "+r"(v[2]), "+r"(v[3]) : "l"(p), "r"((int)on) : "memory");
}
__device__ __forceinline__ uint4 ldg128_ordered(const void* p) {
    uint4 v;
    asm volatile("ld.global.nc.v4.u32 {%0, %1, %2, %3}, [%4];" : "=r"(v.x), "=r"(v.y), "=r"(v.z), "=r"(v.w) : "l"(p) : "memory");
    return v;
}
__host__ __device__ constexpr uint64_t make_desc(uint32_t addr, uint32_t lbo, uint32_t sbo) {
    return (uint64_t)((addr & 0x3FFFF) >> 4) | ((uint64_t)(lbo >> 4) << 16) | ((uint64_t)(sbo >> 4) << 32);
}
__device__ __forceinline__ void wgmma(uint32_t (&d)[12], uint32_t a0, uint32_t a1, uint32_t a2, uint32_t a3, uint64_t db, int acc) {
    asm volatile("{\n.reg .pred p;\nsetp.ne.b32 p, %17, 0;\n"
                 "wgmma.mma_async.sync.aligned.m64n48k16.f16.f16.f16 "
                 "{%0, %1, %2, %3, %4, %5, %6, %7, %8, %9, %10, %11}, "
                 "{%12, %13, %14, %15}, %16, p, 1, 1, 0;\n}\n"
                 : "+r"(d[0]), "+r"(d[1]), "+r"(d[2]), "+r"(d[3]), "+r"(d[4]), "+r"(d[5]), "+r"(d[6]), "+r"(d[7]), "+r"(d[8]), "+r"(d[9]), "+r"(d[10]), "+r"(d[11])
                 : "r"(a0), "r"(a1), "r"(a2), "r"(a3), "l"(db), "r"(acc));
}
__device__ __forceinline__ void wgmma(uint32_t (&d)[24], uint32_t a0, uint32_t a1, uint32_t a2, uint32_t a3, uint64_t db, int acc) {
    asm volatile("{\n.reg .pred p;\nsetp.ne.b32 p, %29, 0;\n"
                 "wgmma.mma_async.sync.aligned.m64n96k16.f16.f16.f16 "
                 "{%0, %1, %2, %3, %4, %5, %6, %7, %8, %9, %10, %11, %12, %13, %14, %15, %16, %17, %18, %19, %20, %21, %22, %23}, "
                 "{%24, %25, %26, %27}, %28, p, 1, 1, 0;\n}\n"
                 : "+r"(d[0]), "+r"(d[1]), "+r"(d[2]), "+r"(d[3]), "+r"(d[4]), "+r"(d[5]), "+r"(d[6]), "+r"(d[7]), "+r"(d[8]), "+r"(d[9]), "+r"(d[10]), "+r"(d[11]), "+r"(d[12]), "+r"(d[13]), "+r"(d[14]), "+r"(d[15]), "+r"(d[16]), "+r"(d[17]), "+r"(d[18]), "+r"(d[19]), "+r"(d[20]), "+r"(d[21]), "+r"(d[22]), "+r"(d[23])
                 : "r"(a0), "r"(a1), "r"(a2), "r"(a3), "l"(db), "r"(acc));
}
template <int ACC>
__device__ __forceinline__ void wgmma_rowsum(float (&d)[4], const uint32_t (&a)[4], uint64_t ones) {
    asm volatile("{\n.reg .pred p;\nsetp.ne.b32 p, %9, 0;\n"
                 "wgmma.mma_async.sync.aligned.m64n8k16.f32.bf16.bf16 {%0, %1, %2, %3}, {%4, %5, %6, %7}, %8, p, 1, 1, 0;\n}\n"
                 : "+f"(d[0]), "+f"(d[1]), "+f"(d[2]), "+f"(d[3])
                 : "r"(a[0]), "r"(a[1]), "r"(a[2]), "r"(a[3]), "l"(ones), "n"(ACC));
}
__device__ __forceinline__ void ldsm4(uint32_t (&r)[4], uint32_t addr) {
    asm volatile("ldmatrix.sync.aligned.m8n8.x4.shared.b16 {%0, %1, %2, %3}, [%4];"
                 : "=r"(r[0]), "=r"(r[1]), "=r"(r[2]), "=r"(r[3]) : "r"(addr) : "memory");
}
__device__ __forceinline__ void ldsm4_t(uint32_t (&r)[4], uint32_t addr) {
    asm volatile("ldmatrix.sync.aligned.m8n8.x4.trans.shared.b16 {%0, %1, %2, %3}, [%4];"
                 : "=r"(r[0]), "=r"(r[1]), "=r"(r[2]), "=r"(r[3]) : "r"(addr) : "memory");
}
__device__ __forceinline__ void stsm4(uint32_t addr, uint32_t a, uint32_t b, uint32_t c, uint32_t d) {
    asm volatile("stmatrix.sync.aligned.m8n8.x4.shared.b16 [%0], {%1, %2, %3, %4};"
                 ::"r"(addr), "r"(a), "r"(b), "r"(c), "r"(d) : "memory");
}
__device__ __forceinline__ uint32_t transpose8x8(uint32_t v) {
    uint32_t d; asm volatile("movmatrix.sync.aligned.m8n8.trans.b16 %0, %1;" : "=r"(d) : "r"(v)); return d;
}
__device__ __forceinline__ void spin_until(const unsigned* counter, unsigned target) {
    unsigned n = 0, c;
    do {
        asm volatile("ld.acquire.gpu.global.u32 %0, [%1];" : "=r"(c) : "l"(counter) : "memory");
        if (++n > SPIN_LIMIT) __trap();
    } while ((int)(c - target) < 0);
}
__device__ __forceinline__ void signal(unsigned* counter) {
    __syncwarp();
    if (elect_one()) asm volatile("red.release.gpu.global.add.u32 [%0], 1;" ::"l"(counter) : "memory");
    __syncwarp();
}
__device__ __forceinline__ void lds128(uint32_t& a, uint32_t& b, uint32_t& c, uint32_t& d, uint32_t addr) {
    asm volatile("ld.shared.v4.u32 {%0, %1, %2, %3}, [%4];" : "=r"(a), "=r"(b), "=r"(c), "=r"(d) : "r"(addr) : "memory");
}
__device__ __forceinline__ void lds64(uint32_t& a, uint32_t& b, uint32_t addr) {
    asm volatile("ld.shared.v2.u32 {%0, %1}, [%2];" : "=r"(a), "=r"(b) : "r"(addr) : "memory");
}
__device__ __forceinline__ void lds32(uint32_t& a, uint32_t addr) {
    asm volatile("ld.shared.u32 %0, [%1];" : "=r"(a) : "r"(addr) : "memory");
}
__device__ __forceinline__ int ldsi(uint32_t addr) {
    uint32_t v;
    lds32(v, addr);
    return (int)v;
}
__device__ __forceinline__ float ldsf(uint32_t addr) {
    uint32_t v;
    lds32(v, addr);
    return __uint_as_float(v);
}
__device__ __forceinline__ void sts32(uint32_t addr, uint32_t a) {
    asm volatile("st.shared.u32 [%0], %1;" ::"r"(addr), "r"(a) : "memory");
}
__device__ __forceinline__ void sts128(uint32_t addr, uint32_t a, uint32_t b, uint32_t c, uint32_t d) {
    asm volatile("st.shared.v4.u32 [%0], {%1, %2, %3, %4};" ::"r"(addr), "r"(a), "r"(b), "r"(c), "r"(d) : "memory");
}
__device__ __forceinline__ void sts64(uint32_t addr, uint32_t a, uint32_t b) {
    asm volatile("st.shared.v2.u32 [%0], {%1, %2};" ::"r"(addr), "r"(a), "r"(b) : "memory");
}
__device__ __forceinline__ void anchor(uint32_t addr, uint32_t a, uint32_t b, uint32_t c, uint32_t d) {
    asm volatile("{\n.reg .pred p;\nsetp.eq.b32 p, %0, 0;\n@p st.shared.v4.u32 [%0], {%1, %2, %3, %4};\n}\n"
                 ::"r"(addr), "r"(a), "r"(b), "r"(c), "r"(d) : "memory");
}
__device__ __forceinline__ uint32_t bf_fma(uint32_t a, uint32_t b, uint32_t c) {
    uint32_t d; asm("fma.rn.bf16x2 %0, %1, %2, %3;" : "=r"(d) : "r"(a), "r"(b), "r"(c)); return d;
}
__device__ __forceinline__ uint32_t bf_mul(uint32_t a, uint32_t b) {
    uint32_t d; asm("mul.rn.bf16x2 %0, %1, %2;" : "=r"(d) : "r"(a), "r"(b)); return d;
}
__device__ __forceinline__ uint32_t bf_absmax(uint32_t a, uint32_t b) {
    uint32_t d; asm("max.xorsign.abs.bf16x2 %0, %1, %2;" : "=r"(d) : "r"(a), "r"(b)); return d;
}
__device__ __forceinline__ uint32_t h_fma(uint32_t a, uint32_t b, uint32_t c) {
    uint32_t d; asm("fma.rn.f16x2 %0, %1, %2, %3;" : "=r"(d) : "r"(a), "r"(b), "r"(c)); return d;
}
__device__ __forceinline__ uint32_t h_mul(uint32_t a, uint32_t b) {
    uint32_t d; asm("mul.rn.f16x2 %0, %1, %2;" : "=r"(d) : "r"(a), "r"(b)); return d;
}
__device__ __forceinline__ uint32_t h_round8(uint32_t v) { return (v + 0x00040004u) & 0xfff8fff8u; }
__device__ __forceinline__ uint32_t h_tanh(uint32_t a) {
    uint32_t d; asm("tanh.approx.f16x2 %0, %1;" : "=r"(d) : "r"(a)); return d;
}
__device__ __forceinline__ uint32_t pack_h2(float lo, float hi) {
    uint32_t d; asm("cvt.rn.f16x2.f32 %0, %1, %2;" : "=r"(d) : "f"(hi), "f"(lo)); return d;
}
__device__ __forceinline__ uint32_t pack_bf2(float lo, float hi) {
    uint32_t d; asm("cvt.rn.bf16x2.f32 %0, %1, %2;" : "=r"(d) : "f"(hi), "f"(lo)); return d;
}
__device__ __forceinline__ float bf_lo(uint32_t v) { return __uint_as_float(v << 16); }
__device__ __forceinline__ float bf_hi(uint32_t v) { return __uint_as_float(v & 0xffff0000u); }
__device__ __forceinline__ float h_lo(uint32_t v) { return __low2float(*reinterpret_cast<__half2*>(&v)); }
__device__ __forceinline__ float h_hi(uint32_t v) { return __high2float(*reinterpret_cast<__half2*>(&v)); }
__device__ __forceinline__ float warp_absmax(uint32_t v) {
    return __uint_as_float(__reduce_max_sync(~0u, max((v & 0x7fffu) << 16, v & 0x7fff0000u)));
}
__device__ __forceinline__ uint32_t gelu2(uint32_t z) {
    uint32_t p = h_fma(z, z, GELU_C2);
    uint32_t t = h_tanh(K_OP & 1 ? h_mul(p, z) : h_mul(z, p));
    return K_OP & 2 ? h_fma(t, z, z) : h_fma(z, t, z);
}
__device__ __forceinline__ float grn_norm(float ss) {
    float r;
    asm("sqrt.approx.f32 %0, %1;" : "=f"(r) : "f"(fmaf(ss, INV_2KZ * INV_2KZ, 1e-6f)));
    return r;
}
__device__ __forceinline__ float pow2i(int e) { return __uint_as_float((uint32_t)(e + 127) << 23); }
__device__ __forceinline__ int ilog2f(float v) {
    int e = (int)((__float_as_uint(v) >> 23) & 0xff) - 127;
    return max(-100, min(100, e));
}

__device__ __forceinline__ int square_exp(float w1max) {
    const int e = w1max > 0.f ? 4 - ilog2f(2.f * KZ * 96.f * w1max) : 0;
    return (e >= 0 && e <= 6) ? 0 : max(-14, min(e, 14));
}
__device__ __forceinline__ int sum_exp(float w1max) {
    return w1max > 0.f ? max(-90, min(90, 33 - 2 * ilog2f(2.f * KZ * 96.f * w1max))) : 0;
}
__device__ __forceinline__ float row_scale(float m) { return m > 0.f ? pow2i(2 - ilog2f(m)) : 1.f; }

struct Split {
    int per_cta, extra, period, inv_period, lenders;
    __host__ __device__ __forceinline__ int longer_before(int cta) const {
        const int n = (cta + period / 2) * inv_period >> 16;
        return n < extra ? n : extra;
    }
};
struct Work {
    int tA, tB, nA, nB, dir, rows, lent, index;
    __device__ __forceinline__ int tile(int j) const { return j < nA ? tA + dir * j : tB + dir * (j - nA); }
};
__host__ __device__ __forceinline__ Work get_work(int cta, const Split& sp) {
    Work w;
    const int before = sp.longer_before(cta), longer = sp.longer_before(cta + 1) - before;
    w.lent = longer && sp.lenders ? LENT : 0;
    w.index = longer ? before : cta - before;
    const int t0 = cta * sp.per_cta + before, t1 = t0 + sp.per_cta + longer;
    const int tm = t1 < (t0 | 511) + 1 ? t1 : (t0 | 511) + 1;
    const bool swap = t1 > tm && t1 - tm < tm - t0, down = cta & 1;
    w.nA = swap ? t1 - tm : tm - t0;
    w.nB = t1 - t0 - w.nA;
    w.tA = down ? (swap ? tm : t0) : (swap ? t1 : tm) - 1;
    w.tB = down ? (swap ? t0 : tm) : (swap ? tm : t1) - 1;
    w.dir = down ? 1 : -1;
    w.rows = w.nA + 2 + (w.nB ? w.nB + 2 : 0);
    return w;
}
__device__ __forceinline__ int row_code(const Work& w, int i) {
    const bool in_a = i < w.nA + 2;
    const int t = in_a ? w.tA : w.tB;
    return ((t & 511) + w.dir * ((in_a ? i : i - (w.nA + 2)) - 1)) << 16 | (t >> 9) * TILE_W;
}
__device__ __forceinline__ uint32_t tile_offset(int tile) { return ((tile & 511) * IMG_W + (tile >> 9) * TILE_W) * (CH * 2); }
__device__ __forceinline__ int tile_order(int j, int n) {
    const int olds = (j / ORDER_P) * ORDER_Q + max(0, j % ORDER_P - (ORDER_P - ORDER_Q));
    return (j % ORDER_P >= ORDER_P - ORDER_Q) ? olds : n - 1 - (j - olds);
}
__device__ __forceinline__ void issue_region(const CUtensorMap* tm, uint32_t dst, uint32_t bar, int warp, int code) {
    mbar_expect_tx(bar, REGION_BYTES);
    tma_row(dst, tm, bar, (code & 0xffff) + (16 * warp - 1), code >> 16);
}

template <class Event>
__device__ __forceinline__ void conv_producer(const Work& wk, const CUtensorMap* tm, uint32_t sb, int warp, Event event) {
    const int lane = threadIdx.x & 31;
    const int j = lane & 15, grp = lane >> 4;
    const uint32_t reg0 = sb + SM_RING + warp * REGION_BYTES;
    const uint32_t bars = sb + SM_BAR + warp * 8;
    if (lane >= PREFETCH_ROWS && lane < 3 * NSLOT) mbar_init(bars + lane * 32, 1);
    if (lane >= 28) mbar_init(sb + BAR_R + ((lane - 28) * 4 + warp) * 8, 1);
    if (lane == 0 && warp == 0) mbar_init(sb + BAR_PIN, 1);
    if (warp * 32 + lane < MAX_ROWS) {
        const int i = warp * 32 + lane, before = min(i / 5, wk.lent);
        const bool back = i % 5 == 0 && i > 0 && i / 5 <= wk.lent;
        sts32(sb + SM_TILES + i * 4, back ? tile_offset(wk.tile(before - 1)) | before
                                          : tile_offset(wk.tile(wk.lent + tile_order(i - before, wk.nA + wk.nB - NCONS - wk.lent))));
    }
    const uint32_t ld64 = opaque(reg0 + grp * 8 * 192 + j * 8), ld32 = opaque(reg0 + grp * 8 * 192 + 128 + j * 4);
    const uint32_t st64 = opaque(reg0 + grp * A_SBO + (j >> 1) * A_LBO + (j & 1) * 8);
    const uint32_t st32 = opaque(reg0 + grp * A_SBO + (8 + (j >> 2)) * A_LBO + (j & 3) * 4);
    fence_async();
    named_bar(0, NTHREADS);
    uint32_t w[3][3][3];
    mbar_wait(sb + BAR_F, 0);
#pragma unroll
    for (int tap = 0; tap < 9; tap++) {
        const uint32_t p = sb + SM_FILTER + (3 + wk.dir * 3 * (tap / 3 - 1) + tap % 3) * (CH * 2);
        lds64(w[tap / 3][tap % 3][0], w[tap / 3][tap % 3][1], p + 8 * j);
        lds32(w[tap / 3][tap % 3][2], p + 128 + 4 * j);
    }
#pragma unroll
    for (int tap = 0; tap < 9; tap++) sts64(reg0 + (NSLOT - 1) * SLOT_BYTES + tap * 128 + j * 8, w[tap / 3][tap % 3][1], w[tap / 3][tap % 3][0]);
#pragma unroll
    for (int tap = 0; tap < 9; tap++) lds64(w[tap / 3][tap % 3][1], w[tap / 3][tap % 3][0], reg0 + (NSLOT - 1) * SLOT_BYTES + tap * 128 + j * 8);
    fence_async();
    named_bar(1, 128);
    static_assert(2 * PREFETCH_ROWS == NSLOT && SLOT_BYTES % 32 == 0, "slot arithmetic");
    uint32_t bo = 0, par = 0, pbo = PREFETCH_ROWS * 32, ppar = 1;
    int px, py;
    auto request = [&]() {
        mbar_wait(bars + (BAR_E - SM_BAR) + pbo, ppar);
        if (elect_one()) {
            mbar_expect_tx(bars + pbo, REGION_BYTES);
            tma_row(reg0 + pbo * (SLOT_BYTES / 32), tm, bars + pbo, px, py);
        }
    };
    auto advance = [&]() {
        bo += 32;
        if (bo == NSLOT * 32) { bo = 0; par ^= 1; }
        pbo += 32;
        if (pbo == NSLOT * 32) { pbo = 0; ppar ^= 1; }
    };
    auto aim = [&](int row) {
        const int code = row_code(wk, row);
        px = (code & 0xffff) + (16 * warp - 1);
        py = code >> 16;
    };
    uint32_t accB[8][3], accC[8][3];
    int r = 0;
#pragma unroll 1
    while (r < wk.rows) {
        if (r == 0 || r == wk.nA + 2) {
            const uint32_t bo0 = bo;
            uint32_t bo1;
#pragma unroll 1
            for (int k = 0; k < 2; k++, r++) {
                mbar_wait(bars + bo, par);
                bo1 = bo;
                aim(r + PREFETCH_ROWS);
                request();
                advance();
            }
            const uint32_t so0 = bo0 * (SLOT_BYTES / 32), so1 = bo1 * (SLOT_BYTES / 32);
#pragma unroll
            for (int p = 0; p < 10; p++) {
                uint32_t u[3], v[3];
                lds64(u[0], u[1], so0 + ld64 + p * 192);
                lds32(u[2], so0 + ld32 + p * 192);
                lds64(v[0], v[1], so1 + ld64 + p * 192);
                lds32(v[2], so1 + ld32 + p * 192);
#pragma unroll
                for (int dx = 0; dx < 3; dx++) {
                    const int o = p - dx;
                    if (o < 0 || o > 7) continue;
#pragma unroll
                    for (int q = 0; q < 3; q++) {
                        accB[o][q] = bf_fma(v[q], w[1][dx][q], dx == 0 ? bf_mul(u[q], w[0][dx][q]) : bf_fma(u[q], w[0][dx][q], accB[o][q]));
                        accC[o][q] = dx == 0 ? bf_mul(v[q], w[0][dx][q]) : bf_fma(v[q], w[0][dx][q], accC[o][q]);
                    }
                }
            }
            anchor(ld64, accB[7][0], accB[7][1], accB[7][2], 0);
            __syncwarp();
            if (elect_one()) {
                mbar_arrive(bars + (BAR_A - SM_BAR) + bo0);
                mbar_arrive(bars + (BAR_E - SM_BAR) + bo0);
                mbar_arrive(bars + (BAR_A - SM_BAR) + bo1);
                mbar_arrive(bars + (BAR_E - SM_BAR) + bo1);
            }
        }
        int end = wk.rows;
        const int marks[4] = {wk.rows - PREFETCH_ROWS, wk.rows - 11, wk.nA + 2, wk.nA + 2 - PREFETCH_ROWS};
#pragma unroll
        for (int k = 0; k < 4; k++) end = marks[k] > r ? min(end, marks[k]) : end;
        const bool fetch = r < wk.rows - PREFETCH_ROWS;
        aim(r + PREFETCH_ROWS);
        px = opaque_uniform(px);
        const int py_end = opaque_uniform(py + wk.dir * (end - r));
        r = end;
#pragma unroll 1
        do {
            mbar_wait(bars + bo, par);
            const uint32_t so = bo * (SLOT_BYTES / 32);
            uint32_t out[8][3];
#pragma unroll
            for (int p = 0; p < 10; p++) {
                uint32_t xv[3];
                lds64(xv[0], xv[1], so + ld64 + p * 192);
                lds32(xv[2], so + ld32 + p * 192);
#pragma unroll
                for (int dd = 0; dd < 3; dd++) {
                    const int dx = K_PD ? 2 - dd : dd, o = p - dx;
                    if (o < 0 || o > 7) continue;
#pragma unroll
                    for (int qq = 0; qq < 3; qq++) {
                        const int q = (qq + K_PQ) % 3;
                        out[o][q] = bf_fma(xv[q], w[2][dx][q], dx == 0 ? accB[o][q] : out[o][q]);
                        accB[o][q] = bf_fma(xv[q], w[1][dx][q], dx == 0 ? accC[o][q] : accB[o][q]);
                        accC[o][q] = dx == 0 ? bf_mul(xv[q], w[0][dx][q]) : bf_fma(xv[q], w[0][dx][q], accC[o][q]);
                    }
                }
            }
            __syncwarp();
#pragma unroll
            for (int oo = 0; oo < 8; oo++) {
                const int o = K_PS ? 7 - oo : oo;
                sts64(so + st64 + o * 16, out[o][0], out[o][1]);
                sts32(so + st32 + o * 16, out[o][2]);
            }
            __syncwarp();
            if (elect_one()) mbar_arrive(bars + (BAR_A - SM_BAR) + bo);
            if (fetch) request();
            advance();
            py += wk.dir;
        } while (py != py_end);
        if (((wk.rows - r) & ~8) == PREFETCH_ROWS) event(wk.rows - r == PREFETCH_ROWS);
    }
}

template <bool SCALED, int K0 = 0, int K1 = 3>
__device__ __forceinline__ void gelu_sq(uint32_t (&d)[24], uint32_t (&keep)[24], uint32_t sq_addr, uint32_t scale2) {
    pin(d);
#pragma unroll
    for (int k = K0; k < K1; k++) {
        uint32_t hs[4];
        lds128(hs[0], hs[1], hs[2], hs[3], sq_addr + k * SQ_ROW);
#pragma unroll
        for (int qq = 0; qq < 4; qq++) {
            const int q = K_QS == 0 ? qq : K_QS == 1 ? 3 - qq : K_QS == 2 ? (qq >> 1 | (qq & 1) << 1) : (qq + 1) & 3;
            uint32_t g0 = gelu2(d[8 * k + 2 * q]), g1 = gelu2(d[8 * k + 2 * q + 1]);
            keep[8 * k + 2 * q] = g0;
            keep[8 * k + 2 * q + 1] = g1;
            if (SCALED) { g0 = h_mul(g0, scale2); g1 = h_mul(g1, scale2); }
            hs[q] = (K_GS >> (q & 1) & 1) ? h_fma(g0, g0, h_fma(g1, g1, hs[q])) : h_fma(g1, g1, h_fma(g0, g0, hs[q]));
        }
        sts128(sq_addr + k * SQ_ROW, hs[0], hs[1], hs[2], hs[3]);
    }
}
__device__ __forceinline__ void gelu_sq_reg(uint32_t (&d)[24], uint32_t (&hs)[12]) {
    pin(d);
#pragma unroll
    for (int qq = 0; qq < 12; qq++) {
        const int q = K_QR == 0 ? qq : K_QR == 1 ? 11 - qq : K_QR == 2 ? qq ^ 1 : qq * 5 % 12;
        const uint32_t g0 = gelu2(d[2 * q]), g1 = gelu2(d[2 * q + 1]);
        hs[q] = (K_GR >> (q & 1) & 1) ? h_fma(g0, g0, h_fma(g1, g1, hs[q])) : h_fma(g1, g1, h_fma(g0, g0, hs[q]));
    }
}
__device__ __forceinline__ void gelu_to(uint32_t (&g)[12], uint32_t (&d)[12]) {
    pin(d);
#pragma unroll
    for (int q = 0; q < 12; q++) g[q] = gelu2(d[q]);
    pin(g);
}
__device__ __forceinline__ void load_tile(uint32_t (&raw)[6][4], uint32_t addr) {
#pragma unroll
    for (int s = 0; s < 6; s++) ldsm4(raw[s], addr + s * 2 * A_LBO);
}
__device__ __forceinline__ uint2 ln_stats(const uint32_t (&raw)[6][4], uint64_t ones) {
    constexpr int NS = 6 / K_CHAIN;
    uint32_t sq[NS][4];
#pragma unroll
    for (int s = 0; s < 6; s++)
#pragma unroll
        for (int q = 0; q < 4; q++) sq[s % NS][q] = s < NS ? bf_mul(raw[s][q], raw[s][q]) : bf_fma(raw[s][q], raw[s][q], sq[s % NS][q]);
    float sum[4], ssq[4];
    wg_fence();
    wgmma_rowsum<0>(sum, raw[0], ones);
#pragma unroll
    for (int s = 1; s < 6; s++) wgmma_rowsum<1>(sum, raw[s], ones);
    wgmma_rowsum<0>(ssq, sq[0], ones);
#pragma unroll
    for (int s = 1; s < NS; s++) wgmma_rowsum<1>(ssq, sq[s], ones);
    wg_commit();
    wg_wait<0>();
    uint32_t st[2];
#pragma unroll
    for (int h = 0; h < 2; h++) {
        asm volatile("" : "+f"(sum[2 * h]), "+f"(ssq[2 * h])::"memory");
        const float mean = sum[2 * h] * (1.f / CH);
        const float var = fmaxf(fmaf(ssq[2 * h], 1.f / CH, -mean * mean), 0.f);
        float rstd;
        asm("rsqrt.approx.ftz.f32 %0, %1;" : "=f"(rstd) : "f"(var + 1e-5f));
        rstd = bf_lo(pack_bf2(rstd * (K_CVT == 0 ? KZ : KZ * 0x1p-112f), 0.f));
        st[h] = pack_bf2(rstd, -mean * rstd);
    }
    return make_uint2(st[0], st[1]);
}
__device__ __forceinline__ void ln_apply(uint32_t (&a)[6][4], const uint2& st) {
    const uint32_t sc[2] = {__byte_perm(st.x, 0, 0x1010), __byte_perm(st.y, 0, 0x1010)};
    const uint32_t sh[2] = {__byte_perm(st.x, 0, 0x3232), __byte_perm(st.y, 0, 0x3232)};
#pragma unroll
    for (int s = 0; s < 6; s++)
#pragma unroll
        for (int q = 0; q < 4; q++) {
            const uint32_t v = bf_fma(a[s][q], sc[q & 1], sh[q & 1]);
            a[s][q] = K_CVT == 0 ? pack_h2(bf_lo(v), bf_hi(v)) : K_CVT == 1 ? (v & 0x7fff7fffu) * 7u + v : ((v << 3) & 0x7fff7fffu) | (v & 0x80008000u);
        }
}
struct Cursor {
    int slot;
    uint32_t par;
    __device__ __forceinline__ void advance(int n) {
        slot += n;
        if (slot >= NSLOT) { slot -= NSLOT; par ^= 1; }
    }
};
struct Descs {
    uint64_t w1[8][6];
    uint64_t w2[24];
    uint64_t ones;
};
template <int E0, int N>
__device__ __forceinline__ void gemm1_chunk(uint32_t (&d)[N], const uint32_t (&a)[6][4], const Descs& ds, int zero) {
#pragma unroll
    for (int s = 0; s < 6; s++) wgmma(d, a[s][0], a[s][1], a[s][2], a[s][3], ds.w1[E0 / 48][s], s ? 1 : zero);
}
template <int E0, int N>
__device__ __forceinline__ void gemm2_chunk(uint32_t (&acc)[24], const uint32_t (&g)[N], const Descs& ds) {
#pragma unroll
    for (int s = 0; s < N / 4; s++) wgmma(acc, g[4 * s], g[4 * s + 1], g[4 * s + 2], g[4 * s + 3], ds.w2[E0 / 16 + s], 1);
}

__global__ void __launch_bounds__(NTHREADS, 1)
block_kernel(const __grid_constant__ CUtensorMap tmap, const __grid_constant__ CUtensorMap tmap_w1,
             const __nv_bfloat16* __restrict__ x, const __nv_bfloat16* __restrict__ dw, const __nv_bfloat16* __restrict__ w2,
             const __nv_bfloat16* __restrict__ gamma, const __nv_bfloat16* __restrict__ beta, __nv_bfloat16* __restrict__ out,
             Scratch* __restrict__ sc, const __grid_constant__ Descs ds,
             const int zero, const __grid_constant__ Split sp) {
    extern __shared__ __align__(1024) uint8_t smem[];
    constexpr uint32_t sb = SB;
    const int tid = K_ROT < 4 ? (threadIdx.x + 128 * K_ROT) & (NTHREADS - 1) : threadIdx.x ^ 384;
    const Work wk = get_work(blockIdx.x, sp);
    constexpr uint32_t s_red = sb + SM_RED;
    if (smem_u32(smem) != SB) __trap();

    PROF(0);
    const int warp_id = __shfl_sync(~0u, tid >> 5, 0);
    const int cw = warp_id - 4, wgi = cw >> 2, w4 = warp_id & 3;
    if (elect_one()) {
        if (warp_id < 8) {
            mbar_init(sb + BAR_X + warp_id * 8, 1);
            if (warp_id < 4) mbar_init(sb + BAR_X + (warp_id + 8) * 8, 1);
            fence_async();
#pragma unroll 1
            for (int r = warp_id >> 2; r < PREFETCH_ROWS; r += 2)
                issue_region(&tmap, sb + SM_RING + r * SLOT_BYTES + w4 * REGION_BYTES, sb + BAR_X + (r * 4 + w4) * 8, w4,
                             ((wk.tA & 511) + wk.dir * (r - 1)) << 16 | (wk.tA >> 9) * TILE_W);
        } else if (warp_id < 15) {
            const int b = warp_id - 8;
            mbar_init(sb + BAR_W + b * 8, 1);
            fence_async();
            mbar_expect_tx(sb + BAR_W + b * 8, b < 6 ? 64 * CH * 2 : 9 * CH * 2);
            if (b < 6) tma_2d(sb + SM_W2 + b * (64 * CH * 2), &tmap_w1, sb + BAR_W + b * 8, 64 * b, 0);
            else bulk_load(sb + SM_FILTER, dw, 9 * CH * 2, sb + BAR_F);
        }
    }
    __syncwarp();
    const int ntiles = wk.nA + wk.nB;
    const int wg = warp_id >> 2;
    int first = wg;
    uint32_t a[6][4], acc[24], tile_off, next_off, stage, inv_rho2 = 0, rpar = 0, bias_addr, lane16, lane_off;
    auto set_lane = [&](uint32_t lane) {
        bias_addr = sb + SM_BIASH + (lane & 3) * 96;
        lane16 = lane * 16;
        lane_off = ((lane >> 2) * CH + 8 * (lane & 3)) * 2;
    };
    const uint32_t bar_r = sb + BAR_R + warp_id * 8;
    auto load_bias = [&](uint32_t (&acc)[24]) {
#pragma unroll
        for (int q = 0; q < 6; q++) lds128(acc[4 * q], acc[4 * q + 1], acc[4 * q + 2], acc[4 * q + 3], bias_addr + q * 16);
    };
    auto load_frags = [&](bool on) {
#pragma unroll
        for (int s = 0; s < 6; s++) ldg128_if(on, a[s], reinterpret_cast<const char*>(out) + next_off + w4 * WARP_BYTES + lane16 + s * 512);
    };
    auto load_first = [&]() {
#pragma unroll
        for (int s = 0; s < 6; s++) ldg128(a[s], reinterpret_cast<const char*>(out) + next_off + w4 * WARP_BYTES + lane16 + s * 512);
    };
    auto stage_x = [&]() {
        if (elect_one()) {
            mbar_expect_tx(bar_r, WARP_BYTES);
            bulk_load_stream(stage, reinterpret_cast<const char*>(x) + tile_off + w4 * WARP_BYTES, WARP_BYTES, bar_r);
        }
    };
    auto epilogue = [&](uint32_t (&acc)[24]) {
        pin(acc);
        rpar ^= 1;
        uint4* op = reinterpret_cast<uint4*>(reinterpret_cast<char*>(out) + tile_off + w4 * WARP_BYTES + lane_off);
#pragma unroll
        for (int h = 0; h < 2; h++)
#pragma unroll
            for (int m = 0; m < 3; m++) {
                uint32_t xin[4], o[4];
                lds128(xin[0], xin[1], xin[2], xin[3], stage + lane_off + h * 1536 + m * 64);
#pragma unroll
                for (int q = 0; q < 4; q++) {
                    const uint32_t v = acc[2 * (4 * m + q) + h];
                    o[q] = bf_fma(pack_bf2(h_lo(v), h_hi(v)), inv_rho2, xin[q]);
                }
                __stcs(op + h * 96 + m * 4, make_uint4(o[0], o[1], o[2], o[3]));
            }
        __syncwarp();
    };
    const bool helps = !wk.lent && wk.index < 8 * LENT * sp.lenders;
    const int help_slot = (wk.rows + 2) % NSLOT;
    const uint32_t s_help = sb + SM_RING + help_slot * SLOT_BYTES + SQ_WG;
    auto reduce = [&](int q, uint32_t lane, bool leader) {
        const int g = lane >> 2, t = lane & 3, ch = 32 * q + 8 * t + 2 * (g & 3) + (g >> 2);
        const uint32_t pick = (g >> 1 & 1) == (t & 1) ? (g & 1 ? 0x3c000000u : 0x00003c00u) : 0;
        uint32_t sq_e, sum_e;
        lds64(sq_e, sum_e, s_red + RED_SQ_EXP);
        const float to_fixed = pow2i(sum_e - 2 * sq_e);
        unsigned long long* dst = sc->sum(ch);
        named_bar(11, CONS_THREADS);
        const unsigned in_piece = ch - wk.index % 8 * 48;
        float helped = 0.f;
        if (helps && in_piece < 48) {
            uint32_t u[4];
            lds128(u[0], u[1], u[2], u[3], s_help + in_piece * 16);
            helped = ((__uint_as_float(u[0]) + __uint_as_float(u[1])) + (__uint_as_float(u[2]) + __uint_as_float(u[3]))) * pow2i(2 * sq_e);
        }
        float f[2][4] = {};
        int slot = wk.rows % NSLOT;
#pragma unroll 1
        for (int i = 0; i < NCONS; i++) {
            if (i == NCONS - 1) {
                named_bar(13, CONS_THREADS);
                if (leader) {
                    fence_async();
                    bulk_load(sb + SM_W2, sc->w2h, (NCONS - 1) * SQ_WG, sb + BAR_W);
                }
                __syncwarp();
                named_bar(14, NTHREADS);
            }
            const uint32_t src = sb + lane * 16 + q * SQ_ROW + (q < 6 ? SM_SQ + i * SQ_WG : sq_e ? SM_SQ + (NCONS - 1 + i) * SQ_WG : SM_RING + slot * SLOT_BYTES - SQ_WG);
            slot = slot == NSLOT - 1 ? 0 : slot + 1;
#pragma unroll
            for (int r = 0; r < 4; r++) {
                uint32_t u[4];
                ldsm4_t(u, src + r * 512);
#pragma unroll
                for (int k = 0; k < 2; k++)
                    asm volatile("mma.sync.aligned.m16n8k16.row.col.f32.f16.f16.f32 {%0, %1, %2, %3}, {%4, %5, %4, %5}, {%6, %7}, {%0, %1, %2, %3};"
                                 : "+f"(f[k][0]), "+f"(f[k][1]), "+f"(f[k][2]), "+f"(f[k][3]) : "r"(pick), "r"(0), "r"(u[2 * k]), "r"(u[2 * k + 1]));
            }
        }
        const float tot = g < 4 ? f[0][0] + f[1][0] : f[0][1] + f[1][1];
        atomicAdd(dst, __float2ull_rn(fminf((tot + helped) * to_fixed, 0x1p47f)) << 8 | 1);
    };
    const uint32_t s_fac = sb + SM_RING + (wk.rows + 1) % NSLOT * SLOT_BYTES + SQ_WG;
    if (warp_id < 4) {
        const bool prepares = gridDim.x - blockIdx.x <= W2_GROUPS / 2;
        const int q = (gridDim.x - 1 - blockIdx.x) * 2 + (w4 >> 1);
        auto lent_tile = [&]() {
            return tile_offset(get_work((wk.index / (8 * LENT) + 1) * sp.period - sp.period / 2 - 1, sp).tile(wk.index / 8 % LENT));
        };
        conv_producer(wk, &tmap, sb, warp_id, [&](bool second) {
            if (!second) {
                if (blockIdx.x == 0) {
#pragma unroll 1
                    for (int e = tid; e < EX; e += 128) *sc->sum(e) = 0;
                    sc->bias[tid] = 0.f;
                    signal(&sc->early);
                }
                if (wk.lent) signal(&sc->early);
            } else if (prepares || helps) {
                spin_until(&sc->early, (ldsi(s_red + RED_LAUNCH) + 1) * 4 * (sp.lenders + 1));
                if (elect_one()) {
                    if (helps) prefetch_l2(reinterpret_cast<const char*>(out) + lent_tile() + w4 * WARP_BYTES, WARP_BYTES);
                    if (prepares) { prefetch_l2(w2 + 8 * q * CH, 8 * CH * 2); prefetch_l2(beta + 8 * q, 16); }
                }
            }
        });
        const int lane = opaque(tid & 31), g = lane >> 2, t = lane & 3;
        const unsigned epoch = ldsi(s_red + RED_LAUNCH);
        set_lane(lane);
        const int i0 = w4 * 32 + lane;
        float gam[3], rmax[3];
#pragma unroll
        for (int m = 0; m < 3; m++) {
            unsigned short v;
            asm volatile("ld.global.nc.u16 %0, [%1];" : "=h"(v) : "l"(gamma + i0 + 128 * m) : "memory");
            gam[m] = bf_lo(v);
        }
        if (prepares) {
            const int half = w4 & 1;
            uint32_t u[3][2], rmax = 0;
#pragma unroll
            for (int m = 0; m < 3; m++) {
                const uint4 w = ldg128_ordered(w2 + (8 * q + g) * CH + 32 * m + 8 * t);
                rmax = bf_absmax(bf_absmax(rmax, bf_absmax(w.x, w.y)), bf_absmax(w.z, w.w));
                u[m][0] = half ? w.z : w.x;
                u[m][1] = half ? w.w : w.y;
            }
            const float bt = __bfloat162float(beta[8 * q + g]);
            rmax = bf_absmax(rmax, __shfl_xor_sync(~0u, rmax, 1));
            rmax = bf_absmax(rmax, __shfl_xor_sync(~0u, rmax, 2));
            const float mx = fmaxf(fabsf(bf_lo(rmax)), fabsf(bf_hi(rmax))), rs = row_scale(mx);
            if (t == 0 && !half) sc->w2max[8 * q + g] = mx;
#pragma unroll
            for (int m = 0; m < 3; m++) {
                float f[4];
#pragma unroll
                for (int k = 0; k < 2; k++) {
                    const float lo = bf_lo(u[m][k]), hi = bf_hi(u[m][k]);
                    sc->w2h[(4 * m + 2 * half + k) * 1536 + q * 32 + lane] = transpose8x8(pack_h2(lo * rs, hi * rs));
                    f[2 * k] = lo * bt;
                    f[2 * k + 1] = hi * bt;
                }
                const float r0 = (g & 2 ? f[2] : f[0]) + __shfl_xor_sync(~0u, g & 2 ? f[0] : f[2], 8);
                const float r1 = (g & 2 ? f[3] : f[1]) + __shfl_xor_sync(~0u, g & 2 ? f[1] : f[3], 8);
                float r = (g & 1 ? r1 : r0) + __shfl_xor_sync(~0u, g & 1 ? r0 : r1, 4);
                r += __shfl_xor_sync(~0u, r, 16);
                if (g < 4) atomicAdd(&sc->bias[32 * m + 8 * t + 4 * half + g], r);
            }
            asm volatile("fence.proxy.async.global;" ::: "memory");
            signal(&sc->prep);
        }
        const int piece = wk.index;
        if (helps) {
            next_off = lent_tile();
            load_first();
            uint32_t d[12], gl[12];
            wg_fence();
#pragma unroll
            for (int s = 0; s < 6; s++) wgmma(d, a[s][0], a[s][1], a[s][2], a[s][3], ds.w1[0][s] + piece % 8 * (6 * 1536 / 16), s ? 1 : 0);
            wg_commit();
            wg_wait<0>();
            gelu_to(gl, d);
#pragma unroll
            for (int s = 0; s < 3; s++) sc->lent[(((piece / (8 * LENT) * 4 + w4) * (8 * LENT) + piece % (8 * LENT)) * 3 + s) * 32 + lane] = make_uint4(gl[4 * s], gl[4 * s + 1], gl[4 * s + 2], gl[4 * s + 3]);
            float f[6], r[3];
#pragma unroll
            for (int j = 0; j < 6; j++) {
                const float lo = fmaf(h_lo(gl[2 * j]), h_lo(gl[2 * j]), h_lo(gl[2 * j + 1]) * h_lo(gl[2 * j + 1]));
                const float hi = fmaf(h_hi(gl[2 * j]), h_hi(gl[2 * j]), h_hi(gl[2 * j + 1]) * h_hi(gl[2 * j + 1]));
                f[j] = (g & 1 ? hi : lo) + __shfl_xor_sync(~0u, g & 1 ? lo : hi, 4);
            }
            mbar_wait(sb + BAR_E + help_slot * 32 + 24, (wk.rows - 4) / NSLOT & 1);
#pragma unroll
            for (int j = 0; j < 3; j++) {
                r[j] = (g & 2 ? f[j + 3] : f[j]) + __shfl_xor_sync(~0u, g & 2 ? f[j] : f[j + 3], 8);
                r[j] += __shfl_xor_sync(~0u, r[j], 16);
                sts32(s_help + (8 * j + 12 * (g & 2) + 2 * t + (g & 1)) * 16 + w4 * 4, __float_as_uint(r[j]));
            }
        }
        const bool leader = warp_id == 0 && lane == 0;
        const float w1max = ldsf(s_red + RED_MAX), from_fixed = pow2i(-ldsi(s_red + RED_SUM_EXP));
        const bool plain = ldsi(s_red + RED_SQ_EXP) == 0;
        auto load_upper = [&]() {
            bulk_load(sb + SM_W2 + NCONS * SQ_WG, reinterpret_cast<const char*>(sc->w2h) + NCONS * SQ_WG, EX * CH * 2 - NCONS * SQ_WG, sb + BAR_W);
        };
        if (leader) {
            spin_until(&sc->prep, (epoch + 1) * 2 * W2_GROUPS);
            asm volatile("fence.proxy.async.global;" ::: "memory");
            fence_async();
            mbar_expect_tx(sb + BAR_W, EX * CH * 2);
            if (plain) load_upper();
        }
        __syncwarp();
        named_bar(1, 128);
#pragma unroll
        for (int m = 0; m < 3; m++) rmax[m] = __ldcg(&sc->w2max[i0 + 128 * m]);
        float2 bpair = make_float2(0.f, 0.f);
        if (i0 < 96) bpair = __ldcg(reinterpret_cast<const float2*>(&sc->bias[32 * (i0 % 24 >> 3) + 8 * (i0 / 24) + (i0 % 24 & 6)]));
        const float gbound = fmaxf(2.f * KZ * 9.7979590f * 192.f * w1max, 1.f) * 19.5959180f * INV_2KZ;
        const unsigned fixed = __reduce_max_sync(~0u, __float_as_uint(fmaf(gbound, fmaxf(fmaxf(rmax[0], rmax[1]), rmax[2]), fmaxf(fabsf(bpair.x), fabsf(bpair.y)))));
        if (lane == 0) sts32(s_red + 96 + w4 * 4, fixed);
        reduce(4 * (NCONS - 1) + w4, lane, leader);
        PROF(2);
        named_bar(15, CONS_THREADS);
        if (leader) {
            fence_async();
            bulk_load(sb + SM_W2 + (NCONS - 1) * SQ_WG, reinterpret_cast<const char*>(sc->w2h) + (NCONS - 1) * SQ_WG, SQ_WG, sb + BAR_W);
            if (!plain) load_upper();
        }
        stage = sb + SM_RING + (wk.rows + 3 + (wk.lent + 2 * ntiles) % NCONS) % NSLOT * SLOT_BYTES + w4 * REGION_BYTES;
        auto grn = [&]() {
            auto peek = [&](int e) {
                unsigned long long v;
                asm volatile("ld.relaxed.gpu.global.u64 %0, [%1];" : "=l"(v) : "l"(sc->sum(e)) : "memory");
                return v;
            };
            unsigned n = 0;
            while (((unsigned)peek((blockIdx.x * 4 + w4) % (EX / 4) * 4) & 255u) != gridDim.x)
                if (++n > SPIN_LIMIT) __trap();
            unsigned long long sum[3];
            for (;;) {
                bool all = true;
#pragma unroll
                for (int m = 0; m < 3; m++) {
                    sum[m] = peek(i0 + 128 * m);
                    all &= ((unsigned)sum[m] & 255u) == gridDim.x;
                }
                if (__all_sync(~0u, all)) break;
                if (++n > SPIN_LIMIT) __trap();
            }
            PROF(3);
            if (blockIdx.x == 0 && leader) sc->launch = epoch + 1;
            float gx[3], tot = 0.f, vary = 0.f;
#pragma unroll
            for (int m = 0; m < 3; m++) {
                gx[m] = grn_norm(__ull2float_rn(sum[m] >> 8) * from_fixed);
                tot += gx[m];
                vary = fmaxf(vary, fabsf(gam[m]) * gx[m] * rmax[m]);
            }
#pragma unroll
            for (int o = 16; o >= 1; o >>= 1) tot += __shfl_xor_sync(~0u, tot, o);
            const unsigned vwarp = __reduce_max_sync(~0u, __float_as_uint(vary));
            if (lane == 0) { sts32(s_red + 64 + w4 * 4, __float_as_uint(tot)); sts32(s_red + 80 + w4 * 4, vwarp); }
            named_bar(1, 128);
            uint32_t u[4], v[4], w[4];
            lds128(u[0], u[1], u[2], u[3], s_red + 64);
            lds128(v[0], v[1], v[2], v[3], s_red + 80);
            lds128(w[0], w[1], w[2], w[3], s_red + 96);
            tot = (__uint_as_float(u[0]) + __uint_as_float(u[1])) + (__uint_as_float(u[2]) + __uint_as_float(u[3]));
            const float vmax = __uint_as_float(max(max(v[0], v[1]), max(v[2], v[3]))), fmax2 = __uint_as_float(max(max(w[0], w[1]), max(w[2], w[3])));
            const float inv_mean = __fdividef(1.f, tot * (1.f / EX) + 1e-6f);
            const float bound = fmaf(gbound * vmax, inv_mean, 2.f * fmax2);
            const int rho_e = bound > 0.f ? 14 - ilog2f(bound) : 0;
            const float rho = pow2i(rho_e), inv_rho = pow2i(-rho_e);
            inv_rho2 = pack_bf2(inv_rho, inv_rho);
#pragma unroll
            for (int m = 0; m < 3; m++) {
                const float f = __fdividef(fmaf(gam[m], gx[m] * inv_mean, 1.f) * INV_2KZ * rho, row_scale(rmax[m]));
                asm volatile("st.shared.u16 [%0], %1;" ::"r"(s_fac + (i0 + 128 * m) * 2), "h"((unsigned short)pack_h2(f, 0.f)) : "memory");
            }
            if (i0 < 96) sts32(sb + SM_BIASH + i0 * 4, pack_h2(bpair.x * rho, bpair.y * rho));
            if (i0 == 96) sts32(s_red + RED_INV_RHO, inv_rho2);
            named_arrive(12, NTHREADS);
        };
        lds32(next_off, sb + SM_TILES);
        next_off = __shfl_sync(~0u, next_off, 0);
        load_first();
        grn();
        if (wk.lent) spin_until(&sc->lent_out, (epoch + 1) * 8 * LENT * sp.lenders);
    } else {
        const int rank = (wgi + wk.lent + 2 * ntiles) % NCONS;
        {
            const int ct = tid - 128, lane = tid & 31;
            const unsigned epoch = *reinterpret_cast<volatile unsigned*>(&sc->launch);
            const int r = lane & 7, mi = lane >> 3;
            const uint32_t src = sb + SM_W2 + (cw >> 1) * (64 * CH * 2) + r * 128 + ((((cw & 1) * 4 + mi) ^ r) * 16);
            const uint32_t dst = sb + SM_W1 + (4 * cw + mi) * 1536 + r * 16;
            if (ct == 0) sts32(s_red + RED_MAX, 0);
            named_bar(0, NTHREADS);
            mbar_wait(sb + BAR_W + (cw >> 1) * 8, 0);
            uint32_t wmax[4] = {}, wsum[4] = {};
#pragma unroll 3
            for (int c = 0; c < 12; c++) {
                uint32_t u[4];
                ldsm4_t(u, src + c * 1024);
#pragma unroll
                for (int q = 0; q < 4; q++) {
                    wmax[q] = bf_absmax(wmax[q], u[q]);
                    wsum[q] = bf_fma(u[q], 0x3f803f80u, wsum[q]);
                    u[q] = pack_h2(bf_lo(u[q]), bf_hi(u[q]));
                }
                stsm4(dst + c * 128, u[0], u[1], u[2], u[3]);
            }
            float mean[4];
            bool center = false;
#pragma unroll
            for (int q = 0; q < 4; q++) {
                uint32_t m = wmax[q];
                float sum = bf_lo(wsum[q]) + bf_hi(wsum[q]);
#pragma unroll
                for (int o = 1; o <= 2; o <<= 1) { m = bf_absmax(m, __shfl_xor_sync(~0u, m, o)); sum += __shfl_xor_sync(~0u, sum, o); }
                mean[q] = sum * (1.f / CH);
                center |= fabsf(mean[q]) > 0.2f * fmaxf(fabsf(bf_lo(m)), fabsf(bf_hi(m)));
            }
            if (__builtin_expect(__any_sync(~0u, center), 0)) {
#pragma unroll 1
                for (int pass = 0; pass < 2; pass++) {
                    float sum[4] = {};
#pragma unroll 1
                    for (int c = 0; c < 12; c++) {
                        uint32_t u[4];
                        ldsm4_t(u, src + c * 1024);
#pragma unroll
                        for (int q = 0; q < 4; q++) {
                            sum[q] += bf_lo(u[q]) + bf_hi(u[q]);
                            u[q] = pack_h2(bf_lo(u[q]) - mean[q], bf_hi(u[q]) - mean[q]);
                        }
                        stsm4(dst + c * 128, u[0], u[1], u[2], u[3]);
                    }
#pragma unroll
                    for (int q = 0; q < 4; q++) {
                        sum[q] += __shfl_xor_sync(~0u, sum[q], 1);
                        sum[q] += __shfl_xor_sync(~0u, sum[q], 2);
                        mean[q] = sum[q] * (1.f / CH);
                    }
                }
            }
            if (cw < 2 * NCONS) {
#pragma unroll
                for (int c = 0; c < 12; c++) sts128(src + c * 1024, 0, 0, 0, 0);
            }
            const float w1max = warp_absmax(bf_absmax(bf_absmax(wmax[0], wmax[1]), bf_absmax(wmax[2], wmax[3])));
            if (lane == 0) asm volatile("red.shared.max.u32 [%0], %1;" ::"r"(s_red + RED_MAX), "r"(__float_as_uint(w1max)) : "memory");
            if (ct < 32) sts32(sb + SM_ONES + ct * 4, 0x3f803f80u);
            if (ct == 0) sts32(s_red + RED_LAUNCH, epoch);
            fence_async();
            named_bar(2, CONS_THREADS);
            const float all_max = ldsf(s_red + RED_MAX);
            const int sq_e = square_exp(all_max);
            sts64(s_red + RED_SQ_EXP, sq_e, sum_exp(all_max));
            if (sq_e) {
#pragma unroll 1
                for (int q = 0; q < 6; q++) sts128(sb + SM_SQ + (rank + NCONS) * SQ_WG + q * SQ_ROW + (ct & 127) * 16, 0, 0, 0, 0);
            }
            mbar_wait(sb + BAR_A + w4 * 8 + 32, 0);
        }

        PROF(1);
        const uint32_t a_addr = opaque(sb + SM_RING + w4 * REGION_BYTES + ((tid >> 3) & 1) * A_SBO + ((tid >> 4) & 1) * A_LBO + (tid & 7) * 16);
        const uint32_t bar_a = sb + BAR_A + w4 * 8, bar_e = sb + BAR_E + w4 * 8;
        const uint32_t sq = opaque(sb + SM_SQ + rank * SQ_WG + (tid & 127) * 16);
        const uint32_t sq_warp = sb + SM_SQ + rank * SQ_WG + w4 * 512;
        uint32_t k1[24], k2[24], k3[24];
        constexpr int SQC = 3 * SQ_ROW;
        const int pass_to = 4 + (wgi == NCONS - 1 ? 0 : wgi + 1);
        auto store_at = [&](const uint32_t (&a)[6][4], uint32_t off) {
            char* ap = reinterpret_cast<char*>(out) + (off + sq);
#pragma unroll
            for (int s = 0; s < 6; s++) stg128(ap + s * 512, a[s]);
        };
        int jt = wgi < wk.lent ? wgi : wk.lent + wgi;
        Cursor cur = {2, 0};
        cur.advance(jt + (jt >= wk.nA ? 2 : 0));
        if (wgi == NCONS - 1) named_arrive(4, 256);
        for (;;) {
            const bool plain = __all_sync(~0u, ldsi(s_red + RED_SQ_EXP) == 0);
            if (plain && jt >= wk.lent) {
                uint32_t hs2[12] = {}, hs3[12] = {};
                const uint32_t own_bar = opaque_uniform(4 + wgi), next_bar = opaque_uniform(pass_to);
                const uint32_t step = opaque_uniform(wk.dir * (NCONS * IMG_W * CH * 2));
#pragma unroll 1
                while (jt + NCONS < ntiles) {
                const int stop = jt < wk.nA ? min(wk.nA, ntiles - NCONS) : ntiles - NCONS, count = (stop - jt + NCONS - 1) / NCONS;
                const int low = cur.slot % 3;
                uint32_t turn = opaque_uniform(cur.par * 2 + cur.slot / 3);
                const uint32_t turn_end = opaque_uniform(turn + count);
                uint32_t so = opaque_uniform(cur.slot * SLOT_BYTES), bo = opaque_uniform(bar_a + cur.slot * 32);
                const uint32_t so_sum = opaque_uniform((2 * low + 3) * SLOT_BYTES), bo_sum = opaque_uniform(2 * bar_a + (2 * low + 3) * 32);
                uint32_t off = opaque_uniform(tile_offset(wk.tile(jt)) + w4 * WARP_BYTES - sq_warp);
                jt += count * NCONS;
                cur.slot = low + 3 * (turn_end & 1);
                cur.par = turn_end >> 1 & 1;
                if (jt >= wk.nA && jt - NCONS < wk.nA) cur.advance(2);
#pragma unroll 1
                do {
                    uint32_t a[6][4], d0[24], d1[24], unused[24];
#define AT(pos) \
    if (K_WAIT == pos) named_bar(own_bar, 256); \
    if (K_PASS == pos) named_arrive(next_bar, 256); \
    if (K_STG == pos) store_at(a, off); \
    if (K_REL == pos) { if (elect_one()) mbar_arrive(bo + (BAR_E - BAR_A)); }
                    AT(20)
                    mbar_wait(bo, turn >> 1 & 1);
                    load_tile(a, a_addr + so);
                    AT(21)
                    const uint2 st = ln_stats(a, ds.ones);
                    AT(0)
                    ln_apply(a, st);
                    AT(1)
                    wg_fence();
                    gemm1_chunk<0>(d0, a, ds, 0);
                    wg_commit();
                    gemm1_chunk<96>(d1, a, ds, 0);
                    wg_commit();
                    AT(2)
                    wg_wait<1>();
                    AT(3)
                    gelu_sq<false, 0, 1>(d0, unused, sq, 0);
                    AT(4)
                    gelu_sq<false, 1, 2>(d0, unused, sq, 0);
                    AT(5)
                    gelu_sq<false, 2, 3>(d0, unused, sq, 0);
                    AT(6)
                    wg_fence();
                    gemm1_chunk<192>(d0, a, ds, zero);
                    wg_commit();
                    AT(7)
                    wg_wait<1>();
                    gelu_sq<false, 0, 1>(d1, unused, sq + SQC, 0);
                    AT(8)
                    gelu_sq<false, 1, 3>(d1, unused, sq + SQC, 0);
                    AT(9)
                    wg_fence();
                    gemm1_chunk<288>(d1, a, ds, zero);
                    wg_commit();
                    AT(10)
                    wg_wait<1>();
                    gelu_sq_reg(d0, hs2);
                    if (K_ANCH < 3) anchor(sq, hs2[4 * (K_ANCH % 3)], hs2[4 * (K_ANCH % 3) + 1], hs2[4 * (K_ANCH % 3) + 2], hs2[4 * (K_ANCH % 3) + 3]);
                    wg_wait<0>();
                    AT(11)
                    gelu_sq_reg(d1, hs3);
#undef AT
                    so = so_sum - so;
                    bo = bo_sum - bo;
                    off += step;
                } while (++turn != turn_end);
                }
                const uint32_t sq2 = sq - (SM_SQ + rank * SQ_WG) + SM_RING + (cur.slot + 3) % NSLOT * SLOT_BYTES;
#pragma unroll
                for (int k = 0; k < 3; k++) {
                    sts128(sq2 + k * SQ_ROW, hs2[4 * k], hs2[4 * k + 1], hs2[4 * k + 2], hs2[4 * k + 3]);
                    sts128(sq2 + SQC + k * SQ_ROW, hs3[4 * k], hs3[4 * k + 1], hs3[4 * k + 2], hs3[4 * k + 3]);
                }
            }
            const bool last = jt + NCONS >= ntiles;
            if (last) {
                tile_off = tile_offset(wk.tile(jt));
                lds32(next_off, sb + SM_TILES + wg * 4);
                next_off = __shfl_sync(~0u, next_off, 0);
                if (elect_one()) {
                    prefetch_l2(reinterpret_cast<const char*>(x) + tile_off + w4 * WARP_BYTES, WARP_BYTES);
                    if (wg % ORDER_P >= ORDER_P - ORDER_Q) prefetch_l2(reinterpret_cast<const char*>(out) + next_off + w4 * WARP_BYTES, WARP_BYTES);
                }
            }
            uint32_t a[6][4], d0[24], d1[24], d3[24], k0[24];
#define AT(pos) \
    if (K_WAIT == pos && jt >= wk.lent) named_bar(4 + wgi, 256); \
    if ((K_LTOK ? K_LTOK : K_PASS) == pos && jt >= wk.lent && jt + 1 < ntiles) named_arrive(pass_to, 256);
            AT(20)
            mbar_wait(bar_a + cur.slot * 32, cur.par);
            load_tile(a, a_addr + cur.slot * SLOT_BYTES);
            AT(21)
            const uint2 st = ln_stats(a, ds.ones);
            AT(0)
            ln_apply(a, st);
            AT(1)
            if (!last) {
                store_at(a, tile_offset(wk.tile(jt)) + w4 * WARP_BYTES - sq_warp);
                __syncwarp();
                if (elect_one()) mbar_arrive(bar_e + cur.slot * 32);
                if (jt < wk.lent) {
                    jt += LENT;
                    cur.advance(LENT);
                    continue;
                }
            }
            wg_fence();
            gemm1_chunk<0>(d0, a, ds, 0);
            wg_commit();
            gemm1_chunk<96>(d1, a, ds, 0);
            wg_commit();
            const int sq_e = ldsi(s_red + RED_SQ_EXP);
            const uint32_t scale2 = pack_h2(pow2i(sq_e), pow2i(sq_e));
            AT(2)
            wg_wait<1>();
            AT(3)
            gelu_sq<true, 0, 1>(d0, k0, sq, scale2);
            AT(4)
            gelu_sq<true, 1, 2>(d0, k0, sq, scale2);
            AT(5)
            gelu_sq<true, 2, 3>(d0, k0, sq, scale2);
            AT(6)
            if (last) {
#pragma unroll
                for (int q = 0; q < 6; q++) sts128(sb + SM_RING + cur.slot * SLOT_BYTES + w4 * REGION_BYTES - sq_warp + sq + q * 512, k0[4 * q], k0[4 * q + 1], k0[4 * q + 2], k0[4 * q + 3]);
            }
            wg_fence();
            gemm1_chunk<192>(d0, a, ds, zero);
            wg_commit();
            AT(7)
            wg_wait<1>();
            gelu_sq<true, 0, 1>(d1, k1, sq + SQC, scale2);
            AT(8)
            gelu_sq<true, 1, 3>(d1, k1, sq + SQC, scale2);
            AT(9)
#undef AT
            wg_fence();
            gemm1_chunk<288>(d3, a, ds, 0);
            wg_commit();
            wg_wait<1>();
            const uint32_t sq2 = sq + (plain ? SM_RING + (cur.slot + 3) % NSLOT * SLOT_BYTES - (SM_SQ + rank * SQ_WG) : NCONS * SQ_WG);
            gelu_sq<true>(d0, k2, sq2, scale2);
            wg_wait<0>();
            gelu_sq<true>(d3, k3, sq2 + SQC, scale2);
            if (last) break;
            cur.advance(NCONS + ((jt < wk.nA && jt + NCONS >= wk.nA) ? 2 : 0));
            jt += NCONS;
        }
        {
            if (rank == NCONS - 1) {
                named_arrive(14, NTHREADS);
            } else {
                reduce(4 * rank + w4, (sq >> 4) & 31, false);
                named_arrive(15, CONS_THREADS);
                PROF(2);
                if (helps && rank == 0 && w4 == 0) signal(&sc->lent_out);
            }
        }
        {
            set_lane((sq >> 4) & 31);
            const uint32_t row = sb + SM_W2 + cw * 512 + lane16;
            uint32_t u[W2_EARLY][4], f2[4];
            mbar_wait(sb + BAR_W, 1);
#pragma unroll
            for (int nb = 0; nb < W2_EARLY; nb++) lds128(u[nb][0], u[nb][1], u[nb][2], u[nb][3], row + nb * 6144);
            named_bar(12, NTHREADS);
            PROF(3);
            stage = sb + SM_RING + (cur.slot + 3) % NSLOT * SLOT_BYTES + w4 * WARP_BYTES;
            if (K_XPOS == 0) stage_x();
            lds128(f2[0], f2[1], f2[2], f2[3], s_fac + cw * 64 + (lane16 >> 7) * 16);
            lds32(inv_rho2, s_red + RED_INV_RHO);
#pragma unroll
            for (int nb = 0; nb < 12; nb++) {
                uint32_t v[4];
                if (nb < W2_EARLY) { v[0] = u[nb % W2_EARLY][0]; v[1] = u[nb % W2_EARLY][1]; v[2] = u[nb % W2_EARLY][2]; v[3] = u[nb % W2_EARLY][3]; }
                else lds128(v[0], v[1], v[2], v[3], row + nb * 6144);
                sts128(row + nb * 6144, h_round8(h_mul(v[0], f2[0])), h_round8(h_mul(v[1], f2[1])), h_round8(h_mul(v[2], f2[2])), h_round8(h_mul(v[3], f2[3])));
            }
            fence_async();
            if (K_XPOS == 1) stage_x();
            named_bar(3, NTHREADS);
        }
        PROF(4);
        {
            load_bias(acc);
            if (wgi > 0) named_bar(8 + wgi, 256);
            pin(k1); pin(k2); pin(k3);
            wg_fence();
            gemm2_chunk<288>(acc, k3, ds);
            wg_commit();
            gemm2_chunk<(K_SWAP ? 192 : 96)>(acc, K_SWAP ? k2 : k1, ds);
            if (K_FINE) wg_commit();
            gemm2_chunk<(K_SWAP ? 96 : 192)>(acc, K_SWAP ? k1 : k2, ds);
            wg_commit();
            if (!K_LATE && wgi + 1 < NCONS) named_arrive(9 + wgi, 256);
            wg_wait<1 + K_FINE>();
            uint32_t k0[24];
#pragma unroll
            for (int q = 0; q < 6; q++)
                lds128(k0[4 * q], k0[4 * q + 1], k0[4 * q + 2], k0[4 * q + 3], sb + SM_RING + cur.slot * SLOT_BYTES + w4 * REGION_BYTES + lane16 + q * 512);
            pin(k0);
            wg_fence();
            gemm2_chunk<0>(acc, k0, ds);
            wg_commit();
            if (K_LATE && wgi + 1 < NCONS) named_arrive(9 + wgi, 256);
            if (wgi == 0) named_arrive(8, 256);
            wg_wait<1 + K_FINE>();
            load_first();
            if (lane16 == 0) mbar_arrive(sb + BAR_PIN);
            mbar_wait(bar_r, rpar);
            wg_wait<0>();
            first = wg - 4;
        }
    }
    {
        const int nrest = ntiles - NCONS;
        auto lent = [&](uint32_t entry) { return &sc->lent[((wk.index * 4 + w4) * LENT + (entry & 3) - 1) * (8 * 96)]; };
        for (int jt = first; jt < nrest; jt += 4) {
            if (jt >= 0) {
            tile_off = next_off;
            lds32(next_off, sb + SM_TILES + (jt + 4) * 4);
            if (tile_off & 3) {
                uint32_t gl[2][24];
                const uint4* src = lent(tile_off) + (lane16 >> 4);
                auto fetch = [&](uint32_t (&v)[24], int c) {
#pragma unroll
                    for (int s = 0; s < 6; s++) ldg128(reinterpret_cast<uint32_t (&)[4]>(v[4 * s]), src + (6 * c + s) * 32);
                };
                tile_off &= ~3u;
                next_off = __shfl_sync(~0u, next_off, 0);
                stage_x();
                if (elect_one()) prefetch_l2(reinterpret_cast<const char*>(out) + next_off + w4 * WARP_BYTES, WARP_BYTES);
                load_bias(acc);
#pragma unroll
                for (int half = 0; half < 2; half++) {
                    fetch(gl[0], 2 * half);
                    fetch(gl[1], 2 * half + 1);
                    if (!half) {
                        named_bar(4 + wg, 256);
                        named_arrive(4 + ((wg + 1) & 3), 256);
                    }
                    pin(gl[0]); pin(gl[1]);
                    wg_fence();
                    if (half) gemm2_chunk<192>(acc, gl[0], ds); else gemm2_chunk<0>(acc, gl[0], ds);
                    if (half) gemm2_chunk<288>(acc, gl[1], ds); else gemm2_chunk<96>(acc, gl[1], ds);
                    wg_commit();
                    wg_wait<0>();
                }
                load_first();
                mbar_wait(bar_r, rpar);
            } else {
            uint32_t d0[12], d1[12], g0[12], g1[12];
            if (jt >= S2_FIRST && jt < nrest - K_TAIL) named_bar(4 + wg, 256);
            wg_fence();
            gemm1_chunk<0>(d0, a, ds, 0);
            wg_commit();
            gemm1_chunk<48>(d1, a, ds, 0);
            wg_commit();
            load_bias(acc);
            next_off = __shfl_sync(~0u, next_off, 0);
            const bool more = jt + 4 < nrest && !(next_off & 3);
            wg_wait<1>();
#define CNX_PASS if (jt + 1 >= S2_FIRST && jt + 1 < nrest - K_TAIL) named_arrive(4 + ((wg + 1) & 3), 256);
#define CNX_STEP(C, D, G)                                              \
    gelu_to(G, D);                                                     \
    if (C == 0 && jt == 0) {                                           \
        named_bar(3, NTHREADS);                                        \
        load_bias(acc);                                                \
    }                                                                  \
    wg_fence();                                                        \
    if (C < 6) gemm1_chunk<48 * (C < 6 ? C + 2 : 0)>(D, a, ds, zero); \
    gemm2_chunk<48 * C>(acc, G, ds);                                  \
    wg_commit();                                                       \
    if (C == S2_PASS) { CNX_PASS }                                     \
    wg_wait<(C < 7 ? 1 : 0)>();
            CNX_STEP(0, d0, g0)
            CNX_STEP(1, d1, g1)
            if (jt == 0) named_bar(8, 256);
            stage_x();
            if (elect_one()) {
                if (more) prefetch_l2(reinterpret_cast<const char*>(out) + next_off + w4 * WARP_BYTES, WARP_BYTES);
                else if (next_off & 3) prefetch_l2(lent(next_off), 8 * 96 * 16);
            }
            CNX_STEP(2, d0, g0)
            CNX_STEP(3, d1, g1)
            CNX_STEP(4, d0, g0)
            CNX_STEP(5, d1, g1)
            CNX_STEP(6, d0, g0)
            load_frags(more);
            if (lane16 == 0) mbar_arrive(sb + BAR_PIN);
            mbar_wait(bar_r, rpar);
            CNX_STEP(7, d1, g1)
#undef CNX_STEP
            }
            }
            epilogue(acc);
        }
    }
    PROF(5);
}

}

typedef CUresult (*EncodeTiledFn)(CUtensorMap*, CUtensorMapDataType, cuuint32_t, void*, const cuuint64_t*, const cuuint64_t*,
                                  const cuuint32_t*, const cuuint32_t*, CUtensorMapInterleave, CUtensorMapSwizzle,
                                  CUtensorMapL2promotion, CUtensorMapFloatOOBfill);

extern "C" void kernel_launch(void* const* d_in, const int* in_sizes, int n_in, void* d_out, int out_size) {
    using namespace cnx;
    static EncodeTiledFn encode = nullptr;
    static int num_sms = 0;
    static Scratch* scratch = nullptr;
    if (!encode) {
        void* fn = nullptr;
        cudaDriverEntryPointQueryResult qr;
        cudaGetDriverEntryPoint("cuTensorMapEncodeTiled", &fn, cudaEnableDefault, &qr);
        encode = (EncodeTiledFn)fn;
        cudaGetSymbolAddress((void**)&scratch, g_scratch);
        int dev = 0;
        cudaGetDevice(&dev);
        cudaDeviceGetAttribute(&num_sms, cudaDevAttrMultiProcessorCount, dev);
        if (num_sms > MAX_CTAS) num_sms = MAX_CTAS;
        cudaFuncSetAttribute(block_kernel, cudaFuncAttributeMaxDynamicSharedMemorySize, SM_TOTAL);
    }
    CUtensorMap tm;
    cuuint64_t dims[3] = {(cuuint64_t)CH, (cuuint64_t)IMG_W, (cuuint64_t)IMG_H};
    cuuint64_t strides[2] = {(cuuint64_t)CH * 2, (cuuint64_t)CH * 2 * IMG_W};
    cuuint32_t box[3] = {(cuuint32_t)CH, (cuuint32_t)REGION_PX, 1};
    cuuint32_t estr[3] = {1, 1, 1};
    encode(&tm, CU_TENSOR_MAP_DATA_TYPE_BFLOAT16, 3, d_in[0], dims, strides, box, estr, CU_TENSOR_MAP_INTERLEAVE_NONE,
           CU_TENSOR_MAP_SWIZZLE_NONE, CU_TENSOR_MAP_L2_PROMOTION_L2_128B, CU_TENSOR_MAP_FLOAT_OOB_FILL_NONE);
    Descs ds;
    for (int c = 0; c < 8; c++)
        for (int k = 0; k < 6; k++) ds.w1[c][k] = make_desc(SB + SM_W1 + c * 6 * 1536 + k * 256, 128, 1536);
    for (int k = 0; k < 24; k++) ds.w2[k] = make_desc(SB + SM_W2 + k * 256, 128, 6144);
    ds.ones = make_desc(SB + SM_ONES, 0, 0);
    CUtensorMap tw;
    cuuint64_t wdims[2] = {(cuuint64_t)EX, (cuuint64_t)CH};
    cuuint64_t wstrides[1] = {(cuuint64_t)EX * 2};
    cuuint32_t wbox[2] = {64, (cuuint32_t)CH};
    encode(&tw, CU_TENSOR_MAP_DATA_TYPE_BFLOAT16, 2, d_in[2], wdims, wstrides, wbox, estr, CU_TENSOR_MAP_INTERLEAVE_NONE,
           CU_TENSOR_MAP_SWIZZLE_128B, CU_TENSOR_MAP_L2_PROMOTION_L2_128B, CU_TENSOR_MAP_FLOAT_OOB_FILL_NONE);
    Split sp = {NTILES / num_sms, NTILES % num_sms, 1, 1 << 16, 0};
    if (sp.per_cta + 9 > MAX_ROWS) return;
    if (sp.extra && sp.extra * (8 * LENT + 1) <= num_sms && sp.per_cta >= 5 * LENT + 7) {
        sp.period = num_sms / sp.extra;
        sp.inv_period = 65535 / sp.period + 1;
        sp.lenders = sp.extra;
        for (int l = 0; l < sp.extra; l++)
            if (get_work((l + 1) * sp.period - sp.period / 2 - 1, sp).nA < 2 * LENT) sp.lenders = 0;
    }
    block_kernel<<<num_sms, NTHREADS, SM_TOTAL>>>(tm, tw, (const __nv_bfloat16*)d_in[0], (const __nv_bfloat16*)d_in[1],
                                             (const __nv_bfloat16*)d_in[3],
                                             (const __nv_bfloat16*)d_in[4], (const __nv_bfloat16*)d_in[5], (__nv_bfloat16*)d_out,
                                             scratch, ds, 0, sp);
}
```

```cpp
#include <cuda_runtime.h>
#include <cuda_bf16.h>
#include <cuda_fp16.h>
#include <cuda.h>
#include <stdint.h>

namespace cnx {

constexpr int IMG_H = 512, IMG_W = 512, CH = 96, EX = 384;
constexpr int TILE_W = 64;
constexpr int NTILES = (IMG_W / TILE_W) * IMG_H;
constexpr int NSLOT = 6;
constexpr int REGION_PX = 18;
constexpr int REGION_BYTES = REGION_PX * CH * 2;
constexpr int SLOT_BYTES = 4 * REGION_BYTES;
constexpr int A_LBO = 144, A_SBO = 12 * A_LBO;
constexpr int PREFETCH_ROWS = 3;
constexpr int NCONS = 3;
constexpr int CONS_THREADS = 128 * NCONS;
constexpr int NTHREADS = 128 + CONS_THREADS;
constexpr int MAX_ROWS = 52;
constexpr int TILE_BYTES = TILE_W * CH * 2, WARP_BYTES = TILE_BYTES / 4;
constexpr int S1_PASS = 1, S2_PASS = 1;
#define K_PASS 4
#define K_WAIT 20
#define K_STG 5
#define K_REL 6
#define K_ANCH 2
#define K_CVT 0
#define K_XPOS 1
#define K_CHAIN 3
#define K_OP 0
#define K_QS 0
#define K_GS 0
#define K_QR 0
#define K_GR 0
#define K_PD 0
#define K_PQ 0
#define K_PS 0
#define K_ROT 0
#define K_LTOK 0
#define K_REQ 1
#define K_LATE 1
#define K_FINE 1
#define K_SWAP 0
#define K_TAIL 0
#define W2_EARLY 6
#define S2_FIRST 2
#define ORDER_P 3
#define ORDER_Q 1
static_assert(MAX_ROWS <= 128, "one table entry per producer thread");
static_assert(2 * A_SBO == REGION_BYTES && REGION_BYTES % 128 == 0, "region layout");

constexpr uint32_t SB = 1024;
constexpr int SM_W1 = 0;
constexpr int SM_W2 = SM_W1 + CH * EX * 2;
constexpr int SM_RING = SM_W2 + CH * EX * 2;
constexpr int SM_BIASH = SM_RING + NSLOT * SLOT_BYTES;
constexpr int SM_RED = SM_BIASH + 384;
constexpr int RED_MAX = 0, RED_LAUNCH = 4, RED_INV_RHO = 8;
constexpr int SM_TILES = SM_RED + 256;
constexpr int SM_RUNS = SM_TILES + MAX_ROWS * 4;
constexpr int SM_ONES = SM_RUNS + NCONS * 64;
constexpr int SM_BAR = SM_ONES + 128;
constexpr int BAR_X = SM_BAR;
constexpr int BAR_A = BAR_X + NSLOT * 4 * 8;
constexpr int BAR_E = BAR_A + NSLOT * 4 * 8;
constexpr int BAR_PIN = BAR_E + NSLOT * 4 * 8;
constexpr int BAR_W = BAR_PIN + 8;
constexpr int BAR_F = BAR_W + 6 * 8;
constexpr int BAR_R = BAR_F + 8;
constexpr int SM_TOTAL = BAR_R + 16 * 8;
constexpr int SM_FILTER = SM_RING + (NSLOT - 1) * SLOT_BYTES + 9 * 128;
constexpr int SM_SQ = SM_W2;
constexpr int SQ_ROW = 128 * 16, SQ_WG = 6 * SQ_ROW;
static_assert(SM_ONES % 16 == 0 && SM_TOTAL <= 232448, "shared memory budget");

constexpr float KZ = 0.3292034911525734f;
constexpr uint32_t GELU_C2 = 0x40d940d9u;
constexpr float INV_2KZ = 0.5f / KZ;
constexpr unsigned SPIN_LIMIT = 1u << 19;

constexpr int MAX_CTAS = 255;
constexpr int W2_GROUPS = EX / 8;
#define K_LENT 3
constexpr int LENT = K_LENT, MAX_LENDERS = MAX_CTAS / (8 * LENT + 1);
struct Scratch {
    uint32_t w2h[EX * CH / 2];
    float w2max[EX];
    float bias[CH + 32];
    unsigned long long sums[EX / 4][32];
    __device__ __forceinline__ unsigned long long* sum(int e) { return &sums[e >> 2][e & 3]; }
    uint4 lent[MAX_LENDERS * LENT * 8 * 4 * 3 * 32];
    unsigned launch, pad0[31], early, pad1[31], prep, pad2[31], lent_out, pad3[31];
};
__device__ __align__(128) Scratch g_scratch;

#define PROF(k)

__device__ __forceinline__ uint32_t smem_u32(const void* p) { return (uint32_t)__cvta_generic_to_shared(p); }
__device__ __forceinline__ void mbar_init(uint32_t bar, uint32_t cnt) {
    asm volatile("mbarrier.init.shared::cta.b64 [%0], %1;" ::"r"(bar), "r"(cnt) : "memory");
}
__device__ __forceinline__ void mbar_arrive(uint32_t bar) {
    asm volatile("mbarrier.arrive.shared::cta.b64 _, [%0];" ::"r"(bar) : "memory");
}
__device__ __forceinline__ void mbar_expect_tx(uint32_t bar, uint32_t bytes) {
    asm volatile("mbarrier.arrive.expect_tx.shared::cta.b64 _, [%0], %1;" ::"r"(bar), "r"(bytes) : "memory");
}
__device__ __forceinline__ bool mbar_try(uint32_t bar, uint32_t par) {
    uint32_t ok;
    asm volatile("{\n.reg .pred p;\nmbarrier.try_wait.parity.shared::cta.b64 p, [%1], %2;\nselp.u32 %0, 1, 0, p;\n}\n"
                 : "=r"(ok) : "r"(bar), "r"(par) : "memory");
    return ok != 0;
}
__device__ __forceinline__ void mbar_wait(uint32_t bar, uint32_t par) {
    unsigned n = 0;
    while (!mbar_try(bar, par)) {
        if (++n > SPIN_LIMIT) __trap();
    }
}
__device__ __forceinline__ bool mbar_test(uint32_t bar, uint32_t par) {
    uint32_t ok;
    asm volatile("{\n.reg .pred p;\nmbarrier.test_wait.parity.shared::cta.b64 p, [%1], %2;\nselp.u32 %0, 1, 0, p;\n}\n"
                 : "=r"(ok) : "r"(bar), "r"(par) : "memory");
    return ok != 0;
}
__device__ __forceinline__ bool elect_one() {
    uint32_t ok;
    asm volatile("{\n.reg .pred p;\nelect.sync _|p, 0xffffffff;\nselp.u32 %0, 1, 0, p;\n}\n" : "=r"(ok));
    return ok != 0;
}
__device__ __forceinline__ uint32_t opaque(uint32_t v) { return __shfl_sync(~0u, v, threadIdx.x & 31); }
__device__ __forceinline__ uint32_t opaque_uniform(uint32_t v) { return __shfl_sync(~0u, v, 0); }
__device__ __forceinline__ void named_bar(int id, int n) { asm volatile("bar.sync %0, %1;" ::"r"(id), "r"(n) : "memory"); }
__device__ __forceinline__ void named_arrive(int id, int n) { asm volatile("bar.arrive %0, %1;" ::"r"(id), "r"(n) : "memory"); }
__device__ __forceinline__ void fence_async() { asm volatile("fence.proxy.async.shared::cta;" ::: "memory"); }
__device__ __forceinline__ uint64_t evict_first() {
    uint64_t p;
    asm("createpolicy.fractional.L2::evict_first.b64 %0, 1.0;" : "=l"(p));
    return p;
}
__device__ __forceinline__ void tma_row(uint32_t dst, const CUtensorMap* tm, uint32_t bar, int x, int y) {
    asm volatile("cp.async.bulk.tensor.3d.shared::cluster.global.mbarrier::complete_tx::bytes.L2::cache_hint [%0], [%1, {%3, %4, %5}], [%2], %6;"
                 ::"r"(dst), "l"(tm), "r"(bar), "r"(0), "r"(x), "r"(y), "l"(evict_first()) : "memory");
}
__device__ __forceinline__ void bulk_load_stream(uint32_t dst, const void* src, uint32_t bytes, uint32_t bar) {
    asm volatile("cp.async.bulk.shared::cluster.global.mbarrier::complete_tx::bytes.L2::cache_hint [%0], [%1], %2, [%3], %4;"
                 ::"r"(dst), "l"(src), "r"(bytes), "r"(bar), "l"(evict_first()) : "memory");
}
__device__ __forceinline__ void prefetch_l2(const void* src, uint32_t bytes) {
    asm volatile("cp.async.bulk.prefetch.L2.global [%0], %1;" ::"l"(src), "r"(bytes) : "memory");
}
__device__ __forceinline__ void tma_2d(uint32_t dst, const CUtensorMap* tm, uint32_t bar, int x, int y) {
    asm volatile("cp.async.bulk.tensor.2d.shared::cluster.global.mbarrier::complete_tx::bytes [%0], [%1, {%3, %4}], [%2];"
                 ::"r"(dst), "l"(tm), "r"(bar), "r"(x), "r"(y) : "memory");
}
__device__ __forceinline__ void bulk_load(uint32_t dst, const void* src, uint32_t bytes, uint32_t bar) {
    asm volatile("cp.async.bulk.shared::cluster.global.mbarrier::complete_tx::bytes [%0], [%1], %2, [%3];"
                 ::"r"(dst), "l"(src), "r"(bytes), "r"(bar) : "memory");
}
__device__ __forceinline__ void wg_fence() { asm volatile("wgmma.fence.sync.aligned;" ::: "memory"); }
__device__ __forceinline__ void wg_commit() { asm volatile("wgmma.commit_group.sync.aligned;" ::: "memory"); }
template <int N> __device__ __forceinline__ void wg_wait() { asm volatile("wgmma.wait_group.sync.aligned %0;" ::"n"(N) : "memory"); }
template <int N> __device__ __forceinline__ void pin(uint32_t (&d)[N]) {
#pragma unroll
    for (int q = 0; q < N; q++) asm volatile("" : "+r"(d[q])::"memory");
}
__device__ __forceinline__ void stg128(void* p, const uint32_t (&v)[4]) {
    asm volatile("st.global.v4.u32 [%0], {%1, %2, %3, %4};" ::"l"(p), "r"(v[0]), "r"(v[1]), "r"(v[2]), "r"(v[3]) : "memory");
}
__device__ __forceinline__ void ldg128(uint32_t (&v)[4], const void* p) {
    asm volatile("ld.global.L1::no_allocate.v4.u32 {%0, %1, %2, %3}, [%4];" : "=r"(v[0]), "=r"(v[1]), "=r"(v[2]), "=r"(v[3]) : "l"(p) : "memory");
}
__device__ __forceinline__ void ldg128_if(bool on, uint32_t (&v)[4], const void* p) {
    asm volatile("{\n.reg .pred p;\nsetp.ne.b32 p, %5, 0;\n@p ld.global.L1::no_allocate.v4.u32 {%0, %1, %2, %3}, [%4];\n}\n"
                 : "+r"(v[0]), "+r"(v[1]), "+r"(v[2]), "+r"(v[3]) : "l"(p), "r"((int)on) : "memory");
}
__device__ __forceinline__ uint4 ldg128_ordered(const void* p) {
    uint4 v;
    asm volatile("ld.global.nc.v4.u32 {%0, %1, %2, %3}, [%4];" : "=r"(v.x), "=r"(v.y), "=r"(v.z), "=r"(v.w) : "l"(p) : "memory");
    return v;
}
__host__ __device__ constexpr uint64_t make_desc(uint32_t addr, uint32_t lbo, uint32_t sbo) {
    return (uint64_t)((addr & 0x3FFFF) >> 4) | ((uint64_t)(lbo >> 4) << 16) | ((uint64_t)(sbo >> 4) << 32);
}
__device__ __forceinline__ void wgmma(uint32_t (&d)[12], uint32_t a0, uint32_t a1, uint32_t a2, uint32_t a3, uint64_t db, int acc) {
    asm volatile("{\n.reg .pred p;\nsetp.ne.b32 p, %17, 0;\n"
                 "wgmma.mma_async.sync.aligned.m64n48k16.f16.f16.f16 "
                 "{%0, %1, %2, %3, %4, %5, %6, %7, %8, %9, %10, %11}, "
                 "{%12, %13, %14, %15}, %16, p, 1, 1, 0;\n}\n"
                 : "+r"(d[0]), "+r"(d[1]), "+r"(d[2]), "+r"(d[3]), "+r"(d[4]), "+r"(d[5]), "+r"(d[6]), "+r"(d[7]), "+r"(d[8]), "+r"(d[9]), "+r"(d[10]), "+r"(d[11])
                 : "r"(a0), "r"(a1), "r"(a2), "r"(a3), "l"(db), "r"(acc));
}
__device__ __forceinline__ void wgmma(uint32_t (&d)[24], uint32_t a0, uint32_t a1, uint32_t a2, uint32_t a3, uint64_t db, int acc) {
    asm volatile("{\n.reg .pred p;\nsetp.ne.b32 p, %29, 0;\n"
                 "wgmma.mma_async.sync.aligned.m64n96k16.f16.f16.f16 "
                 "{%0, %1, %2, %3, %4, %5, %6, %7, %8, %9, %10, %11, %12, %13, %14, %15, %16, %17, %18, %19, %20, %21, %22, %23}, "
                 "{%24, %25, %26, %27}, %28, p, 1, 1, 0;\n}\n"
                 : "+r"(d[0]), "+r"(d[1]), "+r"(d[2]), "+r"(d[3]), "+r"(d[4]), "+r"(d[5]), "+r"(d[6]), "+r"(d[7]), "+r"(d[8]), "+r"(d[9]), "+r"(d[10]), "+r"(d[11]), "+r"(d[12]), "+r"(d[13]), "+r"(d[14]), "+r"(d[15]), "+r"(d[16]), "+r"(d[17]), "+r"(d[18]), "+r"(d[19]), "+r"(d[20]), "+r"(d[21]), "+r"(d[22]), "+r"(d[23])
                 : "r"(a0), "r"(a1), "r"(a2), "r"(a3), "l"(db), "r"(acc));
}
template <int ACC>
__device__ __forceinline__ void wgmma_rowsum(float (&d)[4], const uint32_t (&a)[4], uint64_t ones) {
    asm volatile("{\n.reg .pred p;\nsetp.ne.b32 p, %9, 0;\n"
                 "wgmma.mma_async.sync.aligned.m64n8k16.f32.bf16.bf16 {%0, %1, %2, %3}, {%4, %5, %6, %7}, %8, p, 1, 1, 0;\n}\n"
                 : "+f"(d[0]), "+f"(d[1]), "+f"(d[2]), "+f"(d[3])
                 : "r"(a[0]), "r"(a[1]), "r"(a[2]), "r"(a[3]), "l"(ones), "n"(ACC));
}
__device__ __forceinline__ void ldsm4(uint32_t (&r)[4], uint32_t addr) {
    asm volatile("ldmatrix.sync.aligned.m8n8.x4.shared.b16 {%0, %1, %2, %3}, [%4];"
                 : "=r"(r[0]), "=r"(r[1]), "=r"(r[2]), "=r"(r[3]) : "r"(addr) : "memory");
}
__device__ __forceinline__ void ldsm4_t(uint32_t (&r)[4], uint32_t addr) {
    asm volatile("ldmatrix.sync.aligned.m8n8.x4.trans.shared.b16 {%0, %1, %2, %3}, [%4];"
                 : "=r"(r[0]), "=r"(r[1]), "=r"(r[2]), "=r"(r[3]) : "r"(addr) : "memory");
}
__device__ __forceinline__ void stsm4(uint32_t addr, uint32_t a, uint32_t b, uint32_t c, uint32_t d) {
    asm volatile("stmatrix.sync.aligned.m8n8.x4.shared.b16 [%0], {%1, %2, %3, %4};"
                 ::"r"(addr), "r"(a), "r"(b), "r"(c), "r"(d) : "memory");
}
__device__ __forceinline__ uint32_t transpose8x8(uint32_t v) {
    uint32_t d; asm volatile("movmatrix.sync.aligned.m8n8.trans.b16 %0, %1;" : "=r"(d) : "r"(v)); return d;
}
__device__ __forceinline__ void spin_until(const unsigned* counter, unsigned target) {
    unsigned n = 0, c;
    do {
        asm volatile("ld.acquire.gpu.global.u32 %0, [%1];" : "=r"(c) : "l"(counter) : "memory");
        if (++n > SPIN_LIMIT) __trap();
    } while ((int)(c - target) < 0);
}
__device__ __forceinline__ void signal(unsigned* counter) {
    __syncwarp();
    if (elect_one()) asm volatile("red.release.gpu.global.add.u32 [%0], 1;" ::"l"(counter) : "memory");
    __syncwarp();
}
__device__ __forceinline__ void lds128(uint32_t& a, uint32_t& b, uint32_t& c, uint32_t& d, uint32_t addr) {
    asm volatile("ld.shared.v4.u32 {%0, %1, %2, %3}, [%4];" : "=r"(a), "=r"(b), "=r"(c), "=r"(d) : "r"(addr) : "memory");
}
__device__ __forceinline__ void lds64(uint32_t& a, uint32_t& b, uint32_t addr) {
    asm volatile("ld.shared.v2.u32 {%0, %1}, [%2];" : "=r"(a), "=r"(b) : "r"(addr) : "memory");
}
__device__ __forceinline__ void lds32(uint32_t& a, uint32_t addr) {
    asm volatile("ld.shared.u32 %0, [%1];" : "=r"(a) : "r"(addr) : "memory");
}
__device__ __forceinline__ int ldsi(uint32_t addr) {
    uint32_t v;
    lds32(v, addr);
    return (int)v;
}
__device__ __forceinline__ float ldsf(uint32_t addr) {
    uint32_t v;
    lds32(v, addr);
    return __uint_as_float(v);
}
__device__ __forceinline__ void sts32(uint32_t addr, uint32_t a) {
    asm volatile("st.shared.u32 [%0], %1;" ::"r"(addr), "r"(a) : "memory");
}
__device__ __forceinline__ void sts128(uint32_t addr, uint32_t a, uint32_t b, uint32_t c, uint32_t d) {
    asm volatile("st.shared.v4.u32 [%0], {%1, %2, %3, %4};" ::"r"(addr), "r"(a), "r"(b), "r"(c), "r"(d) : "memory");
}
__device__ __forceinline__ void sts64(uint32_t addr, uint32_t a, uint32_t b) {
    asm volatile("st.shared.v2.u32 [%0], {%1, %2};" ::"r"(addr), "r"(a), "r"(b) : "memory");
}
__device__ __forceinline__ void anchor(uint32_t addr, uint32_t a, uint32_t b, uint32_t c, uint32_t d) {
    asm volatile("{\n.reg .pred p;\nsetp.eq.b32 p, %0, 0;\n@p st.shared.v4.u32 [%0], {%1, %2, %3, %4};\n}\n"
                 ::"r"(addr), "r"(a), "r"(b), "r"(c), "r"(d) : "memory");
}
__device__ __forceinline__ uint32_t bf_fma(uint32_t a, uint32_t b, uint32_t c) {
    uint32_t d; asm("fma.rn.bf16x2 %0, %1, %2, %3;" : "=r"(d) : "r"(a), "r"(b), "r"(c)); return d;
}
__device__ __forceinline__ uint32_t bf_mul(uint32_t a, uint32_t b) {
    uint32_t d; asm("mul.rn.bf16x2 %0, %1, %2;" : "=r"(d) : "r"(a), "r"(b)); return d;
}
__device__ __forceinline__ uint32_t bf_absmax(uint32_t a, uint32_t b) {
    uint32_t d; asm("max.xorsign.abs.bf16x2 %0, %1, %2;" : "=r"(d) : "r"(a), "r"(b)); return d;
}
__device__ __forceinline__ uint32_t h_fma(uint32_t a, uint32_t b, uint32_t c) {
    uint32_t d; asm("fma.rn.f16x2 %0, %1, %2, %3;" : "=r"(d) : "r"(a), "r"(b), "r"(c)); return d;
}
__device__ __forceinline__ uint32_t h_mul(uint32_t a, uint32_t b) {
    uint32_t d; asm("mul.rn.f16x2 %0, %1, %2;" : "=r"(d) : "r"(a), "r"(b)); return d;
}
__device__ __forceinline__ uint32_t h_round8(uint32_t v) { return (v + 0x00040004u) & 0xfff8fff8u; }
__device__ __forceinline__ uint32_t h_tanh(uint32_t a) {
    uint32_t d; asm("tanh.approx.f16x2 %0, %1;" : "=r"(d) : "r"(a)); return d;
}
__device__ __forceinline__ uint32_t pack_h2(float lo, float hi) {
    uint32_t d; asm("cvt.rn.f16x2.f32 %0, %1, %2;" : "=r"(d) : "f"(hi), "f"(lo)); return d;
}
__device__ __forceinline__ uint32_t pack_bf2(float lo, float hi) {
    uint32_t d; asm("cvt.rn.bf16x2.f32 %0, %1, %2;" : "=r"(d) : "f"(hi), "f"(lo)); return d;
}
__device__ __forceinline__ float bf_lo(uint32_t v) { return __uint_as_float(v << 16); }
__device__ __forceinline__ float bf_hi(uint32_t v) { return __uint_as_float(v & 0xffff0000u); }
__device__ __forceinline__ float h_lo(uint32_t v) { return __low2float(*reinterpret_cast<__half2*>(&v)); }
__device__ __forceinline__ float h_hi(uint32_t v) { return __high2float(*reinterpret_cast<__half2*>(&v)); }
__device__ __forceinline__ float warp_absmax(uint32_t v) {
    return __uint_as_float(__reduce_max_sync(~0u, max((v & 0x7fffu) << 16, v & 0x7fff0000u)));
}
__device__ __forceinline__ uint32_t gelu2(uint32_t z) {
    uint32_t p = h_fma(z, z, GELU_C2);
    uint32_t t = h_tanh(K_OP & 1 ? h_mul(p, z) : h_mul(z, p));
    return K_OP & 2 ? h_fma(t, z, z) : h_fma(z, t, z);
}
__device__ __forceinline__ float grn_norm(float ss) {
    float r;
    asm("sqrt.approx.f32 %0, %1;" : "=f"(r) : "f"(fmaf(ss, INV_2KZ * INV_2KZ, 1e-6f)));
    return r;
}
__device__ __forceinline__ float pow2i(int e) { return __uint_as_float((uint32_t)(e + 127) << 23); }
__device__ __forceinline__ int ilog2f(float v) {
    int e = (int)((__float_as_uint(v) >> 23) & 0xff) - 127;
    return max(-100, min(100, e));
}

__device__ __forceinline__ int bound_exp(float w1max) { return w1max > 0.f ? ilog2f(2.f * KZ * 96.f * w1max) : 0; }
__device__ __forceinline__ bool plain_squares(int e) { return (unsigned)(4 - e) <= 6; }
__device__ __forceinline__ int square_exp(int e) { return plain_squares(e) ? 0 : max(-14, min(4 - e, 14)); }
__device__ __forceinline__ int sum_exp(int e) { return max(-90, min(90, 33 - 2 * e)); }
__device__ __forceinline__ float row_scale(float m) { return m > 0.f ? pow2i(2 - ilog2f(m)) : 1.f; }

struct Split {
    int per_cta, extra, period, inv_period, lenders;
    __host__ __device__ __forceinline__ int longer_before(int cta) const {
        const int n = (cta + period / 2) * inv_period >> 16;
        return n < extra ? n : extra;
    }
};
struct Work {
    int tA, tB, nA, nB, dir, rows, lent, index;
    __device__ __forceinline__ int tile(int j) const { return j < nA ? tA + dir * j : tB + dir * (j - nA); }
};
__host__ __device__ __forceinline__ Work get_work(int cta, const Split& sp) {
    Work w;
    const int before = sp.longer_before(cta), longer = sp.longer_before(cta + 1) - before;
    w.lent = longer && sp.lenders ? LENT : 0;
    w.index = longer ? before : cta - before;
    const int t0 = cta * sp.per_cta + before, t1 = t0 + sp.per_cta + longer;
    const int tm = t1 < (t0 | 511) + 1 ? t1 : (t0 | 511) + 1;
    const bool swap = t1 > tm && t1 - tm < tm - t0, down = cta & 1;
    w.nA = swap ? t1 - tm : tm - t0;
    w.nB = t1 - t0 - w.nA;
    w.tA = down ? (swap ? tm : t0) : (swap ? t1 : tm) - 1;
    w.tB = down ? (swap ? t0 : tm) : (swap ? tm : t1) - 1;
    w.dir = down ? 1 : -1;
    w.rows = w.nA + 2 + (w.nB ? w.nB + 2 : 0);
    return w;
}
__device__ __forceinline__ int row_code(const Work& w, int i) {
    const bool in_a = i < w.nA + 2;
    const int t = in_a ? w.tA : w.tB;
    return ((t & 511) + w.dir * ((in_a ? i : i - (w.nA + 2)) - 1)) << 16 | (t >> 9) * TILE_W;
}
__device__ __forceinline__ uint32_t tile_offset(int tile) { return ((tile & 511) * IMG_W + (tile >> 9) * TILE_W) * (CH * 2); }
__device__ __forceinline__ int tile_order(int j, int n) {
    const int olds = (j / ORDER_P) * ORDER_Q + max(0, j % ORDER_P - (ORDER_P - ORDER_Q));
    return (j % ORDER_P >= ORDER_P - ORDER_Q) ? olds : n - 1 - (j - olds);
}
__device__ __forceinline__ void issue_region(const CUtensorMap* tm, uint32_t dst, uint32_t bar, int warp, int code) {
    mbar_expect_tx(bar, REGION_BYTES);
    tma_row(dst, tm, bar, (code & 0xffff) + (16 * warp - 1), code >> 16);
}

template <class Event>
__device__ __forceinline__ void conv_producer(const Work& wk, const CUtensorMap* tm, uint32_t sb, int warp, Event event) {
    const int lane = threadIdx.x & 31;
    const int j = lane & 15, grp = lane >> 4;
    const uint32_t reg0 = sb + SM_RING + warp * REGION_BYTES;
    const uint32_t bars = sb + SM_BAR + warp * 8;
    if (lane >= 2 && lane < 3 * NSLOT) mbar_init(bars + lane * 32, 1);
    if (lane >= 28) mbar_init(sb + BAR_R + ((lane - 28) * 4 + warp) * 8, 1);
    if (lane == 0 && warp == 0) mbar_init(sb + BAR_PIN, 1);
    if (warp * 32 + lane < MAX_ROWS) {
        const int i = warp * 32 + lane, before = min(i / 5, wk.lent);
        const bool back = i % 5 == 0 && i > 0 && i / 5 <= wk.lent;
        sts32(sb + SM_TILES + i * 4, back ? tile_offset(wk.tile(before - 1)) | before
                                          : tile_offset(wk.tile(wk.lent + tile_order(i - before, wk.nA + wk.nB - NCONS - wk.lent))));
    }
    const uint32_t ld64 = opaque(reg0 + grp * 8 * 192 + j * 8), ld32 = opaque(reg0 + grp * 8 * 192 + 128 + j * 4);
    const uint32_t st64 = opaque(reg0 + grp * A_SBO + (j >> 1) * A_LBO + (j & 1) * 8);
    const uint32_t st32 = opaque(reg0 + grp * A_SBO + (8 + (j >> 2)) * A_LBO + (j & 3) * 4);
    fence_async();
    named_bar(0, NTHREADS);
    uint32_t w[3][3][3];
    mbar_wait(sb + BAR_F, 0);
#pragma unroll
    for (int tap = 0; tap < 9; tap++) {
        const uint32_t p = sb + SM_FILTER + (3 + wk.dir * 3 * (tap / 3 - 1) + tap % 3) * (CH * 2);
        lds64(w[tap / 3][tap % 3][0], w[tap / 3][tap % 3][1], p + 8 * j);
        lds32(w[tap / 3][tap % 3][2], p + 128 + 4 * j);
    }
#pragma unroll
    for (int tap = 0; tap < 9; tap++) sts64(reg0 + (NSLOT - 1) * SLOT_BYTES + tap * 128 + j * 8, w[tap / 3][tap % 3][1], w[tap / 3][tap % 3][0]);
#pragma unroll
    for (int tap = 0; tap < 9; tap++) lds64(w[tap / 3][tap % 3][1], w[tap / 3][tap % 3][0], reg0 + (NSLOT - 1) * SLOT_BYTES + tap * 128 + j * 8);
    fence_async();
    named_bar(1, 128);
    static_assert(2 * PREFETCH_ROWS == NSLOT && SLOT_BYTES % 32 == 0, "slot arithmetic");
    uint32_t bo = 0, par = 0, pbo = PREFETCH_ROWS * 32, ppar = 1;
    int px, py;
    auto request = [&]() {
        mbar_wait(bars + (BAR_E - SM_BAR) + pbo, ppar);
        if (elect_one()) {
            mbar_expect_tx(bars + pbo, REGION_BYTES);
            tma_row(reg0 + pbo * (SLOT_BYTES / 32), tm, bars + pbo, px, py);
        }
    };
    auto advance = [&]() {
        bo += 32;
        if (bo == NSLOT * 32) { bo = 0; par ^= 1; }
        pbo += 32;
        if (pbo == NSLOT * 32) { pbo = 0; ppar ^= 1; }
    };
    auto aim = [&](int row) {
        const int code = row_code(wk, row);
        px = (code & 0xffff) + (16 * warp - 1);
        py = code >> 16;
    };
    uint32_t accB[8][3], accC[8][3];
    int r = 0;
#pragma unroll 1
    while (r < wk.rows) {
        if (r == 0 || r == wk.nA + 2) {
            const uint32_t bo0 = bo;
            uint32_t bo1;
#pragma unroll 1
            for (int k = 0; k < 2; k++, r++) {
                mbar_wait(bars + bo, par);
                bo1 = bo;
                if (r >= 2) {
                    aim(r + PREFETCH_ROWS);
                    request();
                }
                advance();
            }
            const uint32_t so0 = bo0 * (SLOT_BYTES / 32), so1 = bo1 * (SLOT_BYTES / 32);
#pragma unroll
            for (int p = 0; p < 10; p++) {
                uint32_t u[3], v[3];
                lds64(u[0], u[1], so0 + ld64 + p * 192);
                lds32(u[2], so0 + ld32 + p * 192);
                lds64(v[0], v[1], so1 + ld64 + p * 192);
                lds32(v[2], so1 + ld32 + p * 192);
#pragma unroll
                for (int dx = 0; dx < 3; dx++) {
                    const int o = p - dx;
                    if (o < 0 || o > 7) continue;
#pragma unroll
                    for (int q = 0; q < 3; q++) {
                        accB[o][q] = bf_fma(v[q], w[1][dx][q], dx == 0 ? bf_mul(u[q], w[0][dx][q]) : bf_fma(u[q], w[0][dx][q], accB[o][q]));
                        accC[o][q] = dx == 0 ? bf_mul(v[q], w[0][dx][q]) : bf_fma(v[q], w[0][dx][q], accC[o][q]);
                    }
                }
            }
            anchor(ld64, accB[7][0], accB[7][1], accB[7][2], 0);
            __syncwarp();
            if (elect_one()) {
                mbar_arrive(bars + (BAR_A - SM_BAR) + bo0);
                mbar_arrive(bars + (BAR_E - SM_BAR) + bo0);
                mbar_arrive(bars + (BAR_A - SM_BAR) + bo1);
                mbar_arrive(bars + (BAR_E - SM_BAR) + bo1);
            }
        }
        int end = wk.rows;
        const int marks[4] = {wk.rows - PREFETCH_ROWS, wk.rows - 11, wk.nA + 2, wk.nA + 2 - PREFETCH_ROWS};
#pragma unroll
        for (int k = 0; k < 4; k++) end = marks[k] > r ? min(end, marks[k]) : end;
        const bool fetch = r < wk.rows - PREFETCH_ROWS;
        aim(r + PREFETCH_ROWS);
        px = opaque_uniform(px);
        const int py_end = opaque_uniform(py + wk.dir * (end - r));
        r = end;
#pragma unroll 1
        do {
            mbar_wait(bars + bo, par);
            const uint32_t so = bo * (SLOT_BYTES / 32);
            uint32_t out[8][3];
#pragma unroll
            for (int p = 0; p < 10; p++) {
                uint32_t xv[3];
                lds64(xv[0], xv[1], so + ld64 + p * 192);
                lds32(xv[2], so + ld32 + p * 192);
#pragma unroll
                for (int dd = 0; dd < 3; dd++) {
                    const int dx = K_PD ? 2 - dd : dd, o = p - dx;
                    if (o < 0 || o > 7) continue;
#pragma unroll
                    for (int qq = 0; qq < 3; qq++) {
                        const int q = (qq + K_PQ) % 3;
                        out[o][q] = bf_fma(xv[q], w[2][dx][q], dx == 0 ? accB[o][q] : out[o][q]);
                        accB[o][q] = bf_fma(xv[q], w[1][dx][q], dx == 0 ? accC[o][q] : accB[o][q]);
                        accC[o][q] = dx == 0 ? bf_mul(xv[q], w[0][dx][q]) : bf_fma(xv[q], w[0][dx][q], accC[o][q]);
                    }
                }
            }
            __syncwarp();
#pragma unroll
            for (int oo = 0; oo < 8; oo++) {
                const int o = K_PS ? 7 - oo : oo;
                sts64(so + st64 + o * 16, out[o][0], out[o][1]);
                sts32(so + st32 + o * 16, out[o][2]);
            }
            __syncwarp();
            if (elect_one()) mbar_arrive(bars + (BAR_A - SM_BAR) + bo);
            if (fetch) request();
            advance();
            py += wk.dir;
        } while (py != py_end);
        if (((wk.rows - r) & ~8) == PREFETCH_ROWS) event(wk.rows - r == PREFETCH_ROWS);
    }
}

template <bool SCALED, int K0 = 0, int K1 = 3>
__device__ __forceinline__ void gelu_sq(uint32_t (&d)[24], uint32_t (&keep)[24], uint32_t sq_addr, uint32_t scale2) {
    pin(d);
#pragma unroll
    for (int k = K0; k < K1; k++) {
        uint32_t hs[4];
        lds128(hs[0], hs[1], hs[2], hs[3], sq_addr + k * SQ_ROW);
#pragma unroll
        for (int qq = 0; qq < 4; qq++) {
            const int q = K_QS == 0 ? qq : K_QS == 1 ? 3 - qq : K_QS == 2 ? (qq >> 1 | (qq & 1) << 1) : (qq + 1) & 3;
            uint32_t g0 = gelu2(d[8 * k + 2 * q]), g1 = gelu2(d[8 * k + 2 * q + 1]);
            keep[8 * k + 2 * q] = g0;
            keep[8 * k + 2 * q + 1] = g1;
            if (SCALED) { g0 = h_mul(g0, scale2); g1 = h_mul(g1, scale2); }
            hs[q] = (K_GS >> (q & 1) & 1) ? h_fma(g0, g0, h_fma(g1, g1, hs[q])) : h_fma(g1, g1, h_fma(g0, g0, hs[q]));
        }
        sts128(sq_addr + k * SQ_ROW, hs[0], hs[1], hs[2], hs[3]);
    }
}
__device__ __forceinline__ void gelu_sq_reg(uint32_t (&d)[24], uint32_t (&hs)[12]) {
    pin(d);
#pragma unroll
    for (int qq = 0; qq < 12; qq++) {
        const int q = K_QR == 0 ? qq : K_QR == 1 ? 11 - qq : K_QR == 2 ? qq ^ 1 : qq * 5 % 12;
        const uint32_t g0 = gelu2(d[2 * q]), g1 = gelu2(d[2 * q + 1]);
        hs[q] = (K_GR >> (q & 1) & 1) ? h_fma(g0, g0, h_fma(g1, g1, hs[q])) : h_fma(g1, g1, h_fma(g0, g0, hs[q]));
    }
}
__device__ __forceinline__ void gelu_to(uint32_t (&g)[12], uint32_t (&d)[12]) {
    pin(d);
#pragma unroll
    for (int q = 0; q < 12; q++) g[q] = gelu2(d[q]);
    pin(g);
}
__device__ __forceinline__ void load_tile(uint32_t (&raw)[6][4], uint32_t addr) {
#pragma unroll
    for (int s = 0; s < 6; s++) ldsm4(raw[s], addr + s * 2 * A_LBO);
}
__device__ __forceinline__ uint2 ln_stats(const uint32_t (&raw)[6][4], uint64_t ones) {
    constexpr int NS = 6 / K_CHAIN;
    uint32_t sq[NS][4];
#pragma unroll
    for (int s = 0; s < 6; s++)
#pragma unroll
        for (int q = 0; q < 4; q++) sq[s % NS][q] = s < NS ? bf_mul(raw[s][q], raw[s][q]) : bf_fma(raw[s][q], raw[s][q], sq[s % NS][q]);
    float sum[4], ssq[4];
    wg_fence();
    wgmma_rowsum<0>(sum, raw[0], ones);
#pragma unroll
    for (int s = 1; s < 6; s++) wgmma_rowsum<1>(sum, raw[s], ones);
    wgmma_rowsum<0>(ssq, sq[0], ones);
#pragma unroll
    for (int s = 1; s < NS; s++) wgmma_rowsum<1>(ssq, sq[s], ones);
    wg_commit();
    wg_wait<0>();
    uint32_t st[2];
#pragma unroll
    for (int h = 0; h < 2; h++) {
        asm volatile("" : "+f"(sum[2 * h]), "+f"(ssq[2 * h])::"memory");
        const float mean = sum[2 * h] * (1.f / CH);
        const float var = fmaxf(fmaf(ssq[2 * h], 1.f / CH, -mean * mean), 0.f);
        float rstd;
        asm("rsqrt.approx.ftz.f32 %0, %1;" : "=f"(rstd) : "f"(var + 1e-5f));
        rstd = bf_lo(pack_bf2(rstd * (K_CVT == 0 ? KZ : KZ * 0x1p-112f), 0.f));
        st[h] = pack_bf2(rstd, -mean * rstd);
    }
    return make_uint2(st[0], st[1]);
}
__device__ __forceinline__ void ln_apply(uint32_t (&a)[6][4], const uint2& st) {
    const uint32_t sc[2] = {__byte_perm(st.x, 0, 0x1010), __byte_perm(st.y, 0, 0x1010)};
    const uint32_t sh[2] = {__byte_perm(st.x, 0, 0x3232), __byte_perm(st.y, 0, 0x3232)};
#pragma unroll
    for (int s = 0; s < 6; s++)
#pragma unroll
        for (int q = 0; q < 4; q++) {
            const uint32_t v = bf_fma(a[s][q], sc[q & 1], sh[q & 1]);
            a[s][q] = K_CVT == 0 ? pack_h2(bf_lo(v), bf_hi(v)) : K_CVT == 1 ? (v & 0x7fff7fffu) * 7u + v : ((v << 3) & 0x7fff7fffu) | (v & 0x80008000u);
        }
}
struct Cursor {
    int slot;
    uint32_t par;
    __device__ __forceinline__ void advance(int n) {
        slot += n;
        if (slot >= NSLOT) { slot -= NSLOT; par ^= 1; }
    }
};
struct Descs {
    uint64_t w1[8][6];
    uint64_t w2[24];
    uint64_t ones;
};
template <int E0, int N>
__device__ __forceinline__ void gemm1_chunk(uint32_t (&d)[N], const uint32_t (&a)[6][4], const Descs& ds, int zero) {
#pragma unroll
    for (int s = 0; s < 6; s++) wgmma(d, a[s][0], a[s][1], a[s][2], a[s][3], ds.w1[E0 / 48][s], s ? 1 : zero);
}
template <int E0, int N>
__device__ __forceinline__ void gemm2_chunk(uint32_t (&acc)[24], const uint32_t (&g)[N], const Descs& ds) {
#pragma unroll
    for (int s = 0; s < N / 4; s++) wgmma(acc, g[4 * s], g[4 * s + 1], g[4 * s + 2], g[4 * s + 3], ds.w2[E0 / 16 + s], 1);
}

__global__ void __launch_bounds__(NTHREADS, 1)
block_kernel(const __grid_constant__ CUtensorMap tmap, const __grid_constant__ CUtensorMap tmap_w1,
             const __nv_bfloat16* __restrict__ x, const __nv_bfloat16* __restrict__ dw, const __nv_bfloat16* __restrict__ w2,
             const __nv_bfloat16* __restrict__ gamma, const __nv_bfloat16* __restrict__ beta, __nv_bfloat16* __restrict__ out,
             Scratch* __restrict__ sc, const __grid_constant__ Descs ds,
             const int zero, const __grid_constant__ Split sp) {
    extern __shared__ __align__(1024) uint8_t smem[];
    constexpr uint32_t sb = SB;
    const int tid = K_ROT < 4 ? (threadIdx.x + 128 * K_ROT) & (NTHREADS - 1) : threadIdx.x ^ 384;
    const Work wk = get_work(blockIdx.x, sp);
    constexpr uint32_t s_red = sb + SM_RED;
    if (smem_u32(smem) != SB) __trap();

    PROF(0);
    const int warp_id = __shfl_sync(~0u, tid >> 5, 0);
    const int cw = warp_id - 4, wgi = cw >> 2, w4 = warp_id & 3;
    if (elect_one()) {
        if (warp_id < 8) {
            mbar_init(sb + BAR_X + warp_id * 8, 1);
            fence_async();
            issue_region(&tmap, sb + SM_RING + warp_id * REGION_BYTES, sb + BAR_X + warp_id * 8, w4,
                         ((wk.tA & 511) + wk.dir * wgi) << 16 | (wk.tA >> 9) * TILE_W);
        } else if (warp_id < 15) {
            const int b = warp_id - 8;
            mbar_init(sb + BAR_W + b * 8, 1);
            fence_async();
            mbar_expect_tx(sb + BAR_W + b * 8, b < 6 ? 64 * CH * 2 : 9 * CH * 2);
            if (b < 6) tma_2d(sb + SM_W2 + b * (64 * CH * 2), &tmap_w1, sb + BAR_W + b * 8, 64 * b, 0);
            else bulk_load(sb + SM_FILTER, dw, 9 * CH * 2, sb + BAR_F);
        }
    }
    __syncwarp();
    const int ntiles = wk.nA + wk.nB;
    const int wg = warp_id >> 2;
    int first = wg;
    uint32_t a[6][4], acc[24], tile_off, next_off, stage, inv_rho2 = 0, rpar = 0, bias_addr, lane16, lane_off;
    auto set_lane = [&](uint32_t lane) {
        bias_addr = sb + SM_BIASH + (lane & 3) * 96;
        lane16 = lane * 16;
        lane_off = ((lane >> 2) * CH + 8 * (lane & 3)) * 2;
    };
    const uint32_t bar_r = sb + BAR_R + warp_id * 8;
    auto load_bias = [&](uint32_t (&acc)[24]) {
#pragma unroll
        for (int q = 0; q < 6; q++) lds128(acc[4 * q], acc[4 * q + 1], acc[4 * q + 2], acc[4 * q + 3], bias_addr + q * 16);
    };
    auto load_frags = [&](bool on) {
#pragma unroll
        for (int s = 0; s < 6; s++) ldg128_if(on, a[s], reinterpret_cast<const char*>(out) + next_off + w4 * WARP_BYTES + lane16 + s * 512);
    };
    auto load_first = [&]() {
#pragma unroll
        for (int s = 0; s < 6; s++) ldg128(a[s], reinterpret_cast<const char*>(out) + next_off + w4 * WARP_BYTES + lane16 + s * 512);
    };
    auto stage_x = [&]() {
        if (elect_one()) {
            mbar_expect_tx(bar_r, WARP_BYTES);
            bulk_load_stream(stage, reinterpret_cast<const char*>(x) + tile_off + w4 * WARP_BYTES, WARP_BYTES, bar_r);
        }
    };
    auto epilogue = [&](uint32_t (&acc)[24]) {
        pin(acc);
        rpar ^= 1;
        uint4* op = reinterpret_cast<uint4*>(reinterpret_cast<char*>(out) + tile_off + w4 * WARP_BYTES + lane_off);
#pragma unroll
        for (int h = 0; h < 2; h++)
#pragma unroll
            for (int m = 0; m < 3; m++) {
                uint32_t xin[4], o[4];
                lds128(xin[0], xin[1], xin[2], xin[3], stage + lane_off + h * 1536 + m * 64);
#pragma unroll
                for (int q = 0; q < 4; q++) {
                    const uint32_t v = acc[2 * (4 * m + q) + h];
                    o[q] = bf_fma(pack_bf2(h_lo(v), h_hi(v)), inv_rho2, xin[q]);
                }
                __stcs(op + h * 96 + m * 4, make_uint4(o[0], o[1], o[2], o[3]));
            }
        __syncwarp();
    };
    const bool helps = !wk.lent && wk.index < 8 * LENT * sp.lenders;
    const int help_slot = (wk.rows + 2) % NSLOT;
    const uint32_t s_help = sb + SM_RING + help_slot * SLOT_BYTES + SQ_WG;
    auto reduce = [&](int q, uint32_t lane, bool leader) {
        const int g = lane >> 2, t = lane & 3, ch = 32 * q + 8 * t + 2 * (g & 3) + (g >> 2);
        const uint32_t pick = (g >> 1 & 1) == (t & 1) ? (g & 1 ? 0x3c000000u : 0x00003c00u) : 0;
        const int be = bound_exp(ldsf(s_red + RED_MAX)), sq_e = square_exp(be);
        const float to_fixed = pow2i(sum_exp(be) - 2 * sq_e);
        unsigned long long* dst = sc->sum(ch);
        named_bar(11, CONS_THREADS);
        const unsigned in_piece = ch - wk.index % 8 * 48;
        float helped = 0.f;
        if (helps && in_piece < 48) {
            uint32_t u[4];
            lds128(u[0], u[1], u[2], u[3], s_help + in_piece * 16);
            helped = ((__uint_as_float(u[0]) + __uint_as_float(u[1])) + (__uint_as_float(u[2]) + __uint_as_float(u[3]))) * pow2i(2 * sq_e);
        }
        float f[2][4] = {};
        int slot = wk.rows % NSLOT;
#pragma unroll 1
        for (int i = 0; i < NCONS; i++) {
            if (i == NCONS - 1) {
                named_bar(13, CONS_THREADS);
                if (leader) {
                    fence_async();
                    bulk_load(sb + SM_W2, sc->w2h, (NCONS - 1) * SQ_WG, sb + BAR_W);
                }
                __syncwarp();
                named_bar(14, NTHREADS);
            }
            const uint32_t src = sb + lane * 16 + q * SQ_ROW + (q < 6 ? SM_SQ + i * SQ_WG : sq_e ? SM_SQ + (NCONS - 1 + i) * SQ_WG : SM_RING + slot * SLOT_BYTES - SQ_WG);
            slot = slot == NSLOT - 1 ? 0 : slot + 1;
#pragma unroll
            for (int r = 0; r < 4; r++) {
                uint32_t u[4];
                ldsm4_t(u, src + r * 512);
#pragma unroll
                for (int k = 0; k < 2; k++)
                    asm volatile("mma.sync.aligned.m16n8k16.row.col.f32.f16.f16.f32 {%0, %1, %2, %3}, {%4, %5, %4, %5}, {%6, %7}, {%0, %1, %2, %3};"
                                 : "+f"(f[k][0]), "+f"(f[k][1]), "+f"(f[k][2]), "+f"(f[k][3]) : "r"(pick), "r"(0), "r"(u[2 * k]), "r"(u[2 * k + 1]));
            }
        }
        const float tot = g < 4 ? f[0][0] + f[1][0] : f[0][1] + f[1][1];
        atomicAdd(dst, __float2ull_rn(fminf((tot + helped) * to_fixed, 0x1p47f)) << 8 | 1);
    };
    const uint32_t s_fac = sb + SM_RING + (wk.rows + 1) % NSLOT * SLOT_BYTES + SQ_WG;
    if (warp_id < 4) {
        const bool prepares = gridDim.x - blockIdx.x <= W2_GROUPS / 2;
        const int q = (gridDim.x - 1 - blockIdx.x) * 2 + (w4 >> 1);
        auto lent_tile = [&]() {
            return tile_offset(get_work((wk.index / (8 * LENT) + 1) * sp.period - sp.period / 2 - 1, sp).tile(wk.index / 8 % LENT));
        };
        conv_producer(wk, &tmap, sb, warp_id, [&](bool second) {
            if (!second) {
                if (blockIdx.x == 0) {
#pragma unroll 1
                    for (int e = tid; e < EX; e += 128) *sc->sum(e) = 0;
                    sc->bias[tid] = 0.f;
                    signal(&sc->early);
                }
                if (wk.lent) signal(&sc->early);
            } else if (prepares || helps) {
                spin_until(&sc->early, (ldsi(s_red + RED_LAUNCH) + 1) * 4 * (sp.lenders + 1));
                if (elect_one()) {
                    if (helps) prefetch_l2(reinterpret_cast<const char*>(out) + lent_tile() + w4 * WARP_BYTES, WARP_BYTES);
                    if (prepares) { prefetch_l2(w2 + 8 * q * CH, 8 * CH * 2); prefetch_l2(beta + 8 * q, 16); }
                }
            }
        });
        const int lane = opaque(tid & 31), g = lane >> 2, t = lane & 3;
        const unsigned epoch = ldsi(s_red + RED_LAUNCH);
        set_lane(lane);
        const int i0 = w4 * 32 + lane;
        float gam[3], rmax[3];
#pragma unroll
        for (int m = 0; m < 3; m++) {
            unsigned short v;
            asm volatile("ld.global.nc.u16 %0, [%1];" : "=h"(v) : "l"(gamma + i0 + 128 * m) : "memory");
            gam[m] = bf_lo(v);
        }
        if (prepares) {
            const int half = w4 & 1;
            uint32_t u[3][2], rmax = 0;
#pragma unroll
            for (int m = 0; m < 3; m++) {
                const uint4 w = ldg128_ordered(w2 + (8 * q + g) * CH + 32 * m + 8 * t);
                rmax = bf_absmax(bf_absmax(rmax, bf_absmax(w.x, w.y)), bf_absmax(w.z, w.w));
                u[m][0] = half ? w.z : w.x;
                u[m][1] = half ? w.w : w.y;
            }
            const float bt = __bfloat162float(beta[8 * q + g]);
            rmax = bf_absmax(rmax, __shfl_xor_sync(~0u, rmax, 1));
            rmax = bf_absmax(rmax, __shfl_xor_sync(~0u, rmax, 2));
            const float mx = fmaxf(fabsf(bf_lo(rmax)), fabsf(bf_hi(rmax))), rs = row_scale(mx);
            if (t == 0 && !half) sc->w2max[8 * q + g] = mx;
#pragma unroll
            for (int m = 0; m < 3; m++) {
                float f[4];
#pragma unroll
                for (int k = 0; k < 2; k++) {
                    const float lo = bf_lo(u[m][k]), hi = bf_hi(u[m][k]);
                    sc->w2h[(4 * m + 2 * half + k) * 1536 + q * 32 + lane] = transpose8x8(pack_h2(lo * rs, hi * rs));
                    f[2 * k] = lo * bt;
                    f[2 * k + 1] = hi * bt;
                }
                const float r0 = (g & 2 ? f[2] : f[0]) + __shfl_xor_sync(~0u, g & 2 ? f[0] : f[2], 8);
                const float r1 = (g & 2 ? f[3] : f[1]) + __shfl_xor_sync(~0u, g & 2 ? f[1] : f[3], 8);
                float r = (g & 1 ? r1 : r0) + __shfl_xor_sync(~0u, g & 1 ? r0 : r1, 4);
                r += __shfl_xor_sync(~0u, r, 16);
                if (g < 4) atomicAdd(&sc->bias[32 * m + 8 * t + 4 * half + g], r);
            }
            asm volatile("fence.proxy.async.global;" ::: "memory");
            signal(&sc->prep);
        }
        const int piece = wk.index;
        if (helps) {
            next_off = lent_tile();
            load_first();
            uint32_t d[12], gl[12];
            wg_fence();
#pragma unroll
            for (int s = 0; s < 6; s++) wgmma(d, a[s][0], a[s][1], a[s][2], a[s][3], ds.w1[0][s] + piece % 8 * (6 * 1536 / 16), s ? 1 : 0);
            wg_commit();
            wg_wait<0>();
            gelu_to(gl, d);
#pragma unroll
            for (int s = 0; s < 3; s++) sc->lent[(((piece / (8 * LENT) * 4 + w4) * (8 * LENT) + piece % (8 * LENT)) * 3 + s) * 32 + lane] = make_uint4(gl[4 * s], gl[4 * s + 1], gl[4 * s + 2], gl[4 * s + 3]);
            float f[6], r[3];
#pragma unroll
            for (int j = 0; j < 6; j++) {
                const float lo = fmaf(h_lo(gl[2 * j]), h_lo(gl[2 * j]), h_lo(gl[2 * j + 1]) * h_lo(gl[2 * j + 1]));
                const float hi = fmaf(h_hi(gl[2 * j]), h_hi(gl[2 * j]), h_hi(gl[2 * j + 1]) * h_hi(gl[2 * j + 1]));
                f[j] = (g & 1 ? hi : lo) + __shfl_xor_sync(~0u, g & 1 ? lo : hi, 4);
            }
            mbar_wait(sb + BAR_E + help_slot * 32 + 24, (wk.rows - 4) / NSLOT & 1);
#pragma unroll
            for (int j = 0; j < 3; j++) {
                r[j] = (g & 2 ? f[j + 3] : f[j]) + __shfl_xor_sync(~0u, g & 2 ? f[j] : f[j + 3], 8);
                r[j] += __shfl_xor_sync(~0u, r[j], 16);
                sts32(s_help + (8 * j + 12 * (g & 2) + 2 * t + (g & 1)) * 16 + w4 * 4, __float_as_uint(r[j]));
            }
        }
        const bool leader = warp_id == 0 && lane == 0;
        const float w1max = ldsf(s_red + RED_MAX), from_fixed = pow2i(-sum_exp(bound_exp(w1max)));
        const bool plain = plain_squares(bound_exp(w1max));
        auto load_upper = [&]() {
            bulk_load(sb + SM_W2 + NCONS * SQ_WG, reinterpret_cast<const char*>(sc->w2h) + NCONS * SQ_WG, EX * CH * 2 - NCONS * SQ_WG, sb + BAR_W);
        };
        if (leader) {
            spin_until(&sc->prep, (epoch + 1) * 2 * W2_GROUPS);
            asm volatile("fence.proxy.async.global;" ::: "memory");
            fence_async();
            mbar_expect_tx(sb + BAR_W, EX * CH * 2);
            if (plain) load_upper();
        }
        __syncwarp();
        named_bar(1, 128);
#pragma unroll
        for (int m = 0; m < 3; m++) rmax[m] = __ldcg(&sc->w2max[i0 + 128 * m]);
        float2 bpair = make_float2(0.f, 0.f);
        if (i0 < 96) bpair = __ldcg(reinterpret_cast<const float2*>(&sc->bias[32 * (i0 % 24 >> 3) + 8 * (i0 / 24) + (i0 % 24 & 6)]));
        const float gbound = fmaxf(2.f * KZ * 9.7979590f * 192.f * w1max, 1.f) * 19.5959180f * INV_2KZ;
        const unsigned fixed = __reduce_max_sync(~0u, __float_as_uint(fmaf(gbound, fmaxf(fmaxf(rmax[0], rmax[1]), rmax[2]), fmaxf(fabsf(bpair.x), fabsf(bpair.y)))));
        if (lane == 0) sts32(s_red + 96 + w4 * 4, fixed);
        reduce(4 * (NCONS - 1) + w4, lane, leader);
        PROF(2);
        named_bar(15, CONS_THREADS);
        if (leader) {
            fence_async();
            bulk_load(sb + SM_W2 + (NCONS - 1) * SQ_WG, reinterpret_cast<const char*>(sc->w2h) + (NCONS - 1) * SQ_WG, SQ_WG, sb + BAR_W);
            if (!plain) load_upper();
        }
        stage = sb + SM_RING + (wk.rows + 3 + (wk.lent + 2 * ntiles) % NCONS) % NSLOT * SLOT_BYTES + w4 * REGION_BYTES;
        auto grn = [&]() {
            auto peek = [&](int e) {
                unsigned long long v;
                asm volatile("ld.relaxed.gpu.global.u64 %0, [%1];" : "=l"(v) : "l"(sc->sum(e)) : "memory");
                return v;
            };
            unsigned n = 0;
            while (((unsigned)peek((blockIdx.x * 4 + w4) % (EX / 4) * 4) & 255u) != gridDim.x)
                if (++n > SPIN_LIMIT) __trap();
            unsigned long long sum[3];
            for (;;) {
                bool all = true;
#pragma unroll
                for (int m = 0; m < 3; m++) {
                    sum[m] = peek(i0 + 128 * m);
                    all &= ((unsigned)sum[m] & 255u) == gridDim.x;
                }
                if (__all_sync(~0u, all)) break;
                if (++n > SPIN_LIMIT) __trap();
            }
            PROF(3);
            if (blockIdx.x == 0 && leader) sc->launch = epoch + 1;
            float gx[3], tot = 0.f, vary = 0.f;
#pragma unroll
            for (int m = 0; m < 3; m++) {
                gx[m] = grn_norm(__ull2float_rn(sum[m] >> 8) * from_fixed);
                tot += gx[m];
                vary = fmaxf(vary, fabsf(gam[m]) * gx[m] * rmax[m]);
            }
#pragma unroll
            for (int o = 16; o >= 1; o >>= 1) tot += __shfl_xor_sync(~0u, tot, o);
            const unsigned vwarp = __reduce_max_sync(~0u, __float_as_uint(vary));
            if (lane == 0) { sts32(s_red + 64 + w4 * 4, __float_as_uint(tot)); sts32(s_red + 80 + w4 * 4, vwarp); }
            named_bar(1, 128);
            uint32_t u[4], v[4], w[4];
            lds128(u[0], u[1], u[2], u[3], s_red + 64);
            lds128(v[0], v[1], v[2], v[3], s_red + 80);
            lds128(w[0], w[1], w[2], w[3], s_red + 96);
            tot = (__uint_as_float(u[0]) + __uint_as_float(u[1])) + (__uint_as_float(u[2]) + __uint_as_float(u[3]));
            const float vmax = __uint_as_float(max(max(v[0], v[1]), max(v[2], v[3]))), fmax2 = __uint_as_float(max(max(w[0], w[1]), max(w[2], w[3])));
            const float inv_mean = __fdividef(1.f, tot * (1.f / EX) + 1e-6f);
            const float bound = fmaf(gbound * vmax, inv_mean, 2.f * fmax2);
            const int rho_e = bound > 0.f ? 14 - ilog2f(bound) : 0;
            const float rho = pow2i(rho_e), inv_rho = pow2i(-rho_e);
            inv_rho2 = pack_bf2(inv_rho, inv_rho);
#pragma unroll
            for (int m = 0; m < 3; m++) {
                const float f = __fdividef(fmaf(gam[m], gx[m] * inv_mean, 1.f) * INV_2KZ * rho, row_scale(rmax[m]));
                asm volatile("st.shared.u16 [%0], %1;" ::"r"(s_fac + (i0 + 128 * m) * 2), "h"((unsigned short)pack_h2(f, 0.f)) : "memory");
            }
            if (i0 < 96) sts32(sb + SM_BIASH + i0 * 4, pack_h2(bpair.x * rho, bpair.y * rho));
            if (i0 == 96) sts32(s_red + RED_INV_RHO, inv_rho2);
            named_arrive(12, NTHREADS);
        };
        lds32(next_off, sb + SM_TILES);
        next_off = __shfl_sync(~0u, next_off, 0);
        load_first();
        grn();
        if (wk.lent) spin_until(&sc->lent_out, (epoch + 1) * 8 * LENT * sp.lenders);
    } else {
        const int rank = (wgi + wk.lent + 2 * ntiles) % NCONS;
        const uint32_t a_addr = opaque(sb + SM_RING + w4 * REGION_BYTES + ((tid >> 3) & 1) * A_SBO + ((tid >> 4) & 1) * A_LBO + (tid & 7) * 16);
        const uint32_t bar_a = sb + BAR_A + w4 * 8, bar_e = sb + BAR_E + w4 * 8;
        const uint32_t sq = opaque(sb + SM_SQ + rank * SQ_WG + (tid & 127) * 16);
        const uint32_t sq_warp = sb + SM_SQ + rank * SQ_WG + w4 * 512;
        if (wgi == NCONS - 1) named_arrive(4, 256);
        {
            const int ct = tid - 128, lane = tid & 31;
            const unsigned epoch = *reinterpret_cast<volatile unsigned*>(&sc->launch);
            const int r = lane & 7, mi = lane >> 3;
            const uint32_t src = sb + SM_W2 + (cw >> 1) * (64 * CH * 2) + r * 128 + ((((cw & 1) * 4 + mi) ^ r) * 16);
            const uint32_t dst = sb + SM_W1 + (4 * cw + mi) * 1536 + r * 16;
            if (ct == 0) sts32(s_red + RED_MAX, 0);
            const int code = row_code(wk, PREFETCH_ROWS - 1 + wgi);
            if (w4 == 0 && lane < 2) {
                const int j0 = wk.lent + wgi, split = min(wk.nA, ntiles - NCONS), in_a = max(split - j0 + NCONS - 1, 0) / NCONS;
                const int j = lane ? j0 + in_a * NCONS : j0, count = lane ? max(ntiles - 1 - j, 0) / NCONS : in_a;
                const int row = j + (lane && wk.nB ? 4 : 2), slot = row % NSLOT, both = 2 * (row % 3) + 3;
                sts128(sb + SM_RUNS + wgi * 64 + lane * 32, row / 3, row / 3 + count, slot * SLOT_BYTES, both * SLOT_BYTES);
                sts128(sb + SM_RUNS + wgi * 64 + lane * 32 + 16, slot * 32, both * 32, tile_offset(wk.tile(j)), 0);
            }
            named_bar(0, NTHREADS);
            if (wgi < K_REQ && elect_one())
                issue_region(&tmap, sb + SM_RING + (PREFETCH_ROWS - 1 + wgi) * SLOT_BYTES + w4 * REGION_BYTES, sb + BAR_X + (cw + 8) * 8, w4, code);
            __syncwarp();
            mbar_wait(sb + BAR_W + (cw >> 1) * 8, 0);
            if (wgi >= K_REQ && elect_one())
                issue_region(&tmap, sb + SM_RING + (PREFETCH_ROWS - 1 + wgi) * SLOT_BYTES + w4 * REGION_BYTES, sb + BAR_X + (cw + 8) * 8, w4, code);
            __syncwarp();
            uint32_t wmax[4] = {}, wsum[4] = {};
#pragma unroll 3
            for (int c = 0; c < 12; c++) {
                uint32_t u[4];
                ldsm4_t(u, src + c * 1024);
#pragma unroll
                for (int q = 0; q < 4; q++) {
                    wmax[q] = bf_absmax(wmax[q], u[q]);
                    wsum[q] = bf_fma(u[q], 0x3f803f80u, wsum[q]);
                    u[q] = pack_h2(bf_lo(u[q]), bf_hi(u[q]));
                }
                stsm4(dst + c * 128, u[0], u[1], u[2], u[3]);
            }
            float mean[4];
            bool center = false;
#pragma unroll
            for (int q = 0; q < 4; q++) {
                uint32_t m = wmax[q];
                float sum = bf_lo(wsum[q]) + bf_hi(wsum[q]);
#pragma unroll
                for (int o = 1; o <= 2; o <<= 1) { m = bf_absmax(m, __shfl_xor_sync(~0u, m, o)); sum += __shfl_xor_sync(~0u, sum, o); }
                mean[q] = sum * (1.f / CH);
                center |= fabsf(mean[q]) > 0.2f * fmaxf(fabsf(bf_lo(m)), fabsf(bf_hi(m)));
            }
            if (__builtin_expect(__any_sync(~0u, center), 0)) {
#pragma unroll 1
                for (int pass = 0; pass < 2; pass++) {
                    float sum[4] = {};
#pragma unroll 1
                    for (int c = 0; c < 12; c++) {
                        uint32_t u[4];
                        ldsm4_t(u, src + c * 1024);
#pragma unroll
                        for (int q = 0; q < 4; q++) {
                            sum[q] += bf_lo(u[q]) + bf_hi(u[q]);
                            u[q] = pack_h2(bf_lo(u[q]) - mean[q], bf_hi(u[q]) - mean[q]);
                        }
                        stsm4(dst + c * 128, u[0], u[1], u[2], u[3]);
                    }
#pragma unroll
                    for (int q = 0; q < 4; q++) {
                        sum[q] += __shfl_xor_sync(~0u, sum[q], 1);
                        sum[q] += __shfl_xor_sync(~0u, sum[q], 2);
                        mean[q] = sum[q] * (1.f / CH);
                    }
                }
            }
            if (cw < 2 * NCONS) {
#pragma unroll
                for (int c = 0; c < 12; c++) sts128(src + c * 1024, 0, 0, 0, 0);
            }
            const float w1max = warp_absmax(bf_absmax(bf_absmax(wmax[0], wmax[1]), bf_absmax(wmax[2], wmax[3])));
            if (lane == 0) asm volatile("red.shared.max.u32 [%0], %1;" ::"r"(s_red + RED_MAX), "r"(__float_as_uint(w1max)) : "memory");
            if (ct < 32) sts32(sb + SM_ONES + ct * 4, 0x3f803f80u);
            if (ct == 0) sts32(s_red + RED_LAUNCH, epoch);
            fence_async();
            named_bar(2, CONS_THREADS);
        }
        PROF(1);
        uint32_t k1[24], k2[24], k3[24];
        constexpr int SQC = 3 * SQ_ROW;
        const int pass_to = 4 + (wgi == NCONS - 1 ? 0 : wgi + 1);
        auto store_at = [&](const uint32_t (&a)[6][4], uint32_t off) {
            char* ap = reinterpret_cast<char*>(out) + (off + sq);
#pragma unroll
            for (int s = 0; s < 6; s++) stg128(ap + s * 512, a[s]);
        };
        int jt = wgi < wk.lent ? wgi : wk.lent + wgi;
        Cursor cur = {2, 0};
        cur.advance(jt + (jt >= wk.nA ? 2 : 0));
        const bool plain = __all_sync(~0u, plain_squares(bound_exp(ldsf(s_red + RED_MAX))));
        if (!plain) {
#pragma unroll 1
            for (int q = 0; q < 6; q++) sts128(sq + NCONS * SQ_WG + q * SQ_ROW, 0, 0, 0, 0);
        }
        for (;;) {
            if (plain && jt >= wk.lent) {
                uint32_t hs2[12] = {}, hs3[12] = {};
                const uint32_t own_bar = opaque_uniform(4 + wgi), next_bar = opaque_uniform(pass_to);
                const uint32_t step = opaque_uniform(wk.dir * (NCONS * IMG_W * CH * 2));
#pragma unroll 1
                for (int seg = 0; seg < 2; seg++) {
                const uint32_t rec = ldsi(sb + SM_RUNS + wgi * 64 + seg * 32 + (sq >> 2 & 28));
                uint32_t turn = __shfl_sync(~0u, rec, 0), so = __shfl_sync(~0u, rec, 2), bo = __shfl_sync(~0u, rec, 4) + bar_a;
                const uint32_t turn_end = __shfl_sync(~0u, rec, 1), so_sum = __shfl_sync(~0u, rec, 3), bo_sum = __shfl_sync(~0u, rec, 5) + 2 * bar_a;
                uint32_t off = __shfl_sync(~0u, rec, 6) + w4 * WARP_BYTES - sq_warp;
                if (turn == turn_end) continue;
#pragma unroll 1
                do {
                    uint32_t a[6][4], d0[24], d1[24], unused[24];
#define AT(pos) \
    if (K_WAIT == pos) named_bar(own_bar, 256); \
    if (K_PASS == pos) named_arrive(next_bar, 256); \
    if (K_STG == pos) store_at(a, off); \
    if (K_REL == pos) { if (elect_one()) mbar_arrive(bo + (BAR_E - BAR_A)); }
                    AT(20)
                    mbar_wait(bo, turn >> 1 & 1);
                    load_tile(a, a_addr + so);
                    AT(21)
                    const uint2 st = ln_stats(a, ds.ones);
                    AT(0)
                    ln_apply(a, st);
                    AT(1)
                    wg_fence();
                    gemm1_chunk<0>(d0, a, ds, 0);
                    wg_commit();
                    gemm1_chunk<96>(d1, a, ds, 0);
                    wg_commit();
                    AT(2)
                    wg_wait<1>();
                    AT(3)
                    gelu_sq<false, 0, 1>(d0, unused, sq, 0);
                    AT(4)
                    gelu_sq<false, 1, 2>(d0, unused, sq, 0);
                    AT(5)
                    gelu_sq<false, 2, 3>(d0, unused, sq, 0);
                    AT(6)
                    wg_fence();
                    gemm1_chunk<192>(d0, a, ds, zero);
                    wg_commit();
                    AT(7)
                    wg_wait<1>();
                    gelu_sq<false, 0, 1>(d1, unused, sq + SQC, 0);
                    AT(8)
                    gelu_sq<false, 1, 3>(d1, unused, sq + SQC, 0);
                    AT(9)
                    wg_fence();
                    gemm1_chunk<288>(d1, a, ds, zero);
                    wg_commit();
                    AT(10)
                    wg_wait<1>();
                    gelu_sq_reg(d0, hs2);
                    if (K_ANCH < 3) anchor(sq, hs2[4 * (K_ANCH % 3)], hs2[4 * (K_ANCH % 3) + 1], hs2[4 * (K_ANCH % 3) + 2], hs2[4 * (K_ANCH % 3) + 3]);
                    wg_wait<0>();
                    AT(11)
                    gelu_sq_reg(d1, hs3);
#undef AT
                    so = so_sum - so;
                    bo = bo_sum - bo;
                    off += step;
                } while (++turn != turn_end);
                }
                jt = ntiles - NCONS + rank;
                cur.slot = (wk.rows - NCONS + rank) % NSLOT;
                cur.par = (wk.rows - NCONS + rank) / NSLOT & 1;
                const uint32_t sq2 = sq - (SM_SQ + rank * SQ_WG) + SM_RING + (cur.slot + 3) % NSLOT * SLOT_BYTES;
#pragma unroll
                for (int k = 0; k < 3; k++) {
                    sts128(sq2 + k * SQ_ROW, hs2[4 * k], hs2[4 * k + 1], hs2[4 * k + 2], hs2[4 * k + 3]);
                    sts128(sq2 + SQC + k * SQ_ROW, hs3[4 * k], hs3[4 * k + 1], hs3[4 * k + 2], hs3[4 * k + 3]);
                }
            }
            const bool last = jt + NCONS >= ntiles;
            if (last) {
                tile_off = tile_offset(wk.tile(jt));
                lds32(next_off, sb + SM_TILES + wg * 4);
                next_off = __shfl_sync(~0u, next_off, 0);
                if (elect_one()) {
                    prefetch_l2(reinterpret_cast<const char*>(x) + tile_off + w4 * WARP_BYTES, WARP_BYTES);
                    if (wg % ORDER_P >= ORDER_P - ORDER_Q) prefetch_l2(reinterpret_cast<const char*>(out) + next_off + w4 * WARP_BYTES, WARP_BYTES);
                }
            }
            uint32_t a[6][4], d0[24], d1[24], d3[24], k0[24];
#define AT(pos) \
    if (K_WAIT == pos && jt >= wk.lent) named_bar(4 + wgi, 256); \
    if ((K_LTOK ? K_LTOK : K_PASS) == pos && jt >= wk.lent && jt + 1 < ntiles) named_arrive(pass_to, 256);
            AT(20)
            mbar_wait(bar_a + cur.slot * 32, cur.par);
            load_tile(a, a_addr + cur.slot * SLOT_BYTES);
            AT(21)
            const uint2 st = ln_stats(a, ds.ones);
            AT(0)
            ln_apply(a, st);
            AT(1)
            if (!last) {
                store_at(a, tile_offset(wk.tile(jt)) + w4 * WARP_BYTES - sq_warp);
                __syncwarp();
                if (elect_one()) mbar_arrive(bar_e + cur.slot * 32);
                if (jt < wk.lent) {
                    jt += LENT;
                    cur.advance(LENT);
                    continue;
                }
            }
            wg_fence();
            gemm1_chunk<0>(d0, a, ds, 0);
            wg_commit();
            gemm1_chunk<96>(d1, a, ds, 0);
            wg_commit();
            const int sq_e = square_exp(bound_exp(ldsf(s_red + RED_MAX)));
            const uint32_t scale2 = pack_h2(pow2i(sq_e), pow2i(sq_e));
            AT(2)
            wg_wait<1>();
            AT(3)
            gelu_sq<true, 0, 1>(d0, k0, sq, scale2);
            AT(4)
            gelu_sq<true, 1, 2>(d0, k0, sq, scale2);
            AT(5)
            gelu_sq<true, 2, 3>(d0, k0, sq, scale2);
            AT(6)
            if (last) {
#pragma unroll
                for (int q = 0; q < 6; q++) sts128(sb + SM_RING + cur.slot * SLOT_BYTES + w4 * REGION_BYTES - sq_warp + sq + q * 512, k0[4 * q], k0[4 * q + 1], k0[4 * q + 2], k0[4 * q + 3]);
            }
            wg_fence();
            gemm1_chunk<192>(d0, a, ds, zero);
            wg_commit();
            AT(7)
            wg_wait<1>();
            gelu_sq<true, 0, 1>(d1, k1, sq + SQC, scale2);
            AT(8)
            gelu_sq<true, 1, 3>(d1, k1, sq + SQC, scale2);
            AT(9)
#undef AT
            wg_fence();
            gemm1_chunk<288>(d3, a, ds, 0);
            wg_commit();
            wg_wait<1>();
            const uint32_t sq2 = sq + (plain ? SM_RING + (cur.slot + 3) % NSLOT * SLOT_BYTES - (SM_SQ + rank * SQ_WG) : NCONS * SQ_WG);
            gelu_sq<true>(d0, k2, sq2, scale2);
            wg_wait<0>();
            gelu_sq<true>(d3, k3, sq2 + SQC, scale2);
            if (last) break;
            cur.advance(NCONS + ((jt < wk.nA && jt + NCONS >= wk.nA) ? 2 : 0));
            jt += NCONS;
        }
        {
            if (rank == NCONS - 1) {
                named_arrive(14, NTHREADS);
            } else {
                reduce(4 * rank + w4, (sq >> 4) & 31, false);
                named_arrive(15, CONS_THREADS);
                PROF(2);
                if (helps && rank == 0 && w4 == 0) signal(&sc->lent_out);
            }
        }
        {
            set_lane((sq >> 4) & 31);
            const uint32_t row = sb + SM_W2 + cw * 512 + lane16;
            uint32_t u[W2_EARLY][4], f2[4];
            mbar_wait(sb + BAR_W, 1);
#pragma unroll
            for (int nb = 0; nb < W2_EARLY; nb++) lds128(u[nb][0], u[nb][1], u[nb][2], u[nb][3], row + nb * 6144);
            named_bar(12, NTHREADS);
            PROF(3);
            stage = sb + SM_RING + (cur.slot + 3) % NSLOT * SLOT_BYTES + w4 * WARP_BYTES;
            if (K_XPOS == 0) stage_x();
            lds128(f2[0], f2[1], f2[2], f2[3], s_fac + cw * 64 + (lane16 >> 7) * 16);
            lds32(inv_rho2, s_red + RED_INV_RHO);
#pragma unroll
            for (int nb = 0; nb < 12; nb++) {
                uint32_t v[4];
                if (nb < W2_EARLY) { v[0] = u[nb % W2_EARLY][0]; v[1] = u[nb % W2_EARLY][1]; v[2] = u[nb % W2_EARLY][2]; v[3] = u[nb % W2_EARLY][3]; }
                else lds128(v[0], v[1], v[2], v[3], row + nb * 6144);
                sts128(row + nb * 6144, h_round8(h_mul(v[0], f2[0])), h_round8(h_mul(v[1], f2[1])), h_round8(h_mul(v[2], f2[2])), h_round8(h_mul(v[3], f2[3])));
            }
            fence_async();
            if (K_XPOS == 1) stage_x();
            named_bar(3, NTHREADS);
        }
        PROF(4);
        {
            load_bias(acc);
            if (wgi > 0) named_bar(8 + wgi, 256);
            pin(k1); pin(k2); pin(k3);
            wg_fence();
            gemm2_chunk<288>(acc, k3, ds);
            wg_commit();
            gemm2_chunk<(K_SWAP ? 192 : 96)>(acc, K_SWAP ? k2 : k1, ds);
            if (K_FINE) wg_commit();
            gemm2_chunk<(K_SWAP ? 96 : 192)>(acc, K_SWAP ? k1 : k2, ds);
            wg_commit();
            if (!K_LATE && wgi + 1 < NCONS) named_arrive(9 + wgi, 256);
            wg_wait<1 + K_FINE>();
            uint32_t k0[24];
#pragma unroll
            for (int q = 0; q < 6; q++)
                lds128(k0[4 * q], k0[4 * q + 1], k0[4 * q + 2], k0[4 * q + 3], sb + SM_RING + cur.slot * SLOT_BYTES + w4 * REGION_BYTES + lane16 + q * 512);
            pin(k0);
            wg_fence();
            gemm2_chunk<0>(acc, k0, ds);
            wg_commit();
            if (K_LATE && wgi + 1 < NCONS) named_arrive(9 + wgi, 256);
            if (wgi == 0) named_arrive(8, 256);
            wg_wait<1 + K_FINE>();
            load_first();
            if (lane16 == 0) mbar_arrive(sb + BAR_PIN);
            mbar_wait(bar_r, rpar);
            wg_wait<0>();
            first = wg - 4;
        }
    }
    {
        const int nrest = ntiles - NCONS;
        auto lent = [&](uint32_t entry) { return &sc->lent[((wk.index * 4 + w4) * LENT + (entry & 3) - 1) * (8 * 96)]; };
        for (int jt = first; jt < nrest; jt += 4) {
            if (jt >= 0) {
            tile_off = next_off;
            lds32(next_off, sb + SM_TILES + (jt + 4) * 4);
            if (tile_off & 3) {
                uint32_t gl[2][24];
                const uint4* src = lent(tile_off) + (lane16 >> 4);
                auto fetch = [&](uint32_t (&v)[24], int c) {
#pragma unroll
                    for (int s = 0; s < 6; s++) ldg128(reinterpret_cast<uint32_t (&)[4]>(v[4 * s]), src + (6 * c + s) * 32);
                };
                tile_off &= ~3u;
                next_off = __shfl_sync(~0u, next_off, 0);
                stage_x();
                if (elect_one()) prefetch_l2(reinterpret_cast<const char*>(out) + next_off + w4 * WARP_BYTES, WARP_BYTES);
                load_bias(acc);
#pragma unroll
                for (int half = 0; half < 2; half++) {
                    fetch(gl[0], 2 * half);
                    fetch(gl[1], 2 * half + 1);
                    if (!half) {
                        named_bar(4 + wg, 256);
                        named_arrive(4 + ((wg + 1) & 3), 256);
                    }
                    pin(gl[0]); pin(gl[1]);
                    wg_fence();
                    if (half) gemm2_chunk<192>(acc, gl[0], ds); else gemm2_chunk<0>(acc, gl[0], ds);
                    if (half) gemm2_chunk<288>(acc, gl[1], ds); else gemm2_chunk<96>(acc, gl[1], ds);
                    wg_commit();
                    wg_wait<0>();
                }
                load_first();
                mbar_wait(bar_r, rpar);
            } else {
            uint32_t d0[12], d1[12], g0[12], g1[12];
            if (jt >= S2_FIRST && jt < nrest - K_TAIL) named_bar(4 + wg, 256);
            wg_fence();
            gemm1_chunk<0>(d0, a, ds, 0);
            wg_commit();
            gemm1_chunk<48>(d1, a, ds, 0);
            wg_commit();
            load_bias(acc);
            next_off = __shfl_sync(~0u, next_off, 0);
            const bool more = jt + 4 < nrest && !(next_off & 3);
            wg_wait<1>();
#define CNX_PASS if (jt + 1 >= S2_FIRST && jt + 1 < nrest - K_TAIL) named_arrive(4 + ((wg + 1) & 3), 256);
#define CNX_STEP(C, D, G)                                              \
    gelu_to(G, D);                                                     \
    if (C == 0 && jt == 0) {                                           \
        named_bar(3, NTHREADS);                                        \
        load_bias(acc);                                                \
    }                                                                  \
    wg_fence();                                                        \
    if (C < 6) gemm1_chunk<48 * (C < 6 ? C + 2 : 0)>(D, a, ds, zero); \
    gemm2_chunk<48 * C>(acc, G, ds);                                  \
    wg_commit();                                                       \
    if (C == S2_PASS) { CNX_PASS }                                     \
    wg_wait<(C < 7 ? 1 : 0)>();
            CNX_STEP(0, d0, g0)
            CNX_STEP(1, d1, g1)
            if (jt == 0) named_bar(8, 256);
            stage_x();
            if (elect_one()) {
                if (more) prefetch_l2(reinterpret_cast<const char*>(out) + next_off + w4 * WARP_BYTES, WARP_BYTES);
                else if (next_off & 3) prefetch_l2(lent(next_off), 8 * 96 * 16);
            }
            CNX_STEP(2, d0, g0)
            CNX_STEP(3, d1, g1)
            CNX_STEP(4, d0, g0)
            CNX_STEP(5, d1, g1)
            CNX_STEP(6, d0, g0)
            load_frags(more);
            if (lane16 == 0) mbar_arrive(sb + BAR_PIN);
            mbar_wait(bar_r, rpar);
            CNX_STEP(7, d1, g1)
#undef CNX_STEP
            }
            }
            epilogue(acc);
        }
    }
    PROF(5);
}

}

typedef CUresult (*EncodeTiledFn)(CUtensorMap*, CUtensorMapDataType, cuuint32_t, void*, const cuuint64_t*, const cuuint64_t*,
                                  const cuuint32_t*, const cuuint32_t*, CUtensorMapInterleave, CUtensorMapSwizzle,
                                  CUtensorMapL2promotion, CUtensorMapFloatOOBfill);

extern "C" void kernel_launch(void* const* d_in, const int* in_sizes, int n_in, void* d_out, int out_size) {
    using namespace cnx;
    static EncodeTiledFn encode = nullptr;
    static int num_sms = 0;
    static Scratch* scratch = nullptr;
    if (!encode) {
        void* fn = nullptr;
        cudaDriverEntryPointQueryResult qr;
        cudaGetDriverEntryPoint("cuTensorMapEncodeTiled", &fn, cudaEnableDefault, &qr);
        encode = (EncodeTiledFn)fn;
        cudaGetSymbolAddress((void**)&scratch, g_scratch);
        int dev = 0;
        cudaGetDevice(&dev);
        cudaDeviceGetAttribute(&num_sms, cudaDevAttrMultiProcessorCount, dev);
        if (num_sms > MAX_CTAS) num_sms = MAX_CTAS;
        cudaFuncSetAttribute(block_kernel, cudaFuncAttributeMaxDynamicSharedMemorySize, SM_TOTAL);
    }
    CUtensorMap tm;
    cuuint64_t dims[3] = {(cuuint64_t)CH, (cuuint64_t)IMG_W, (cuuint64_t)IMG_H};
    cuuint64_t strides[2] = {(cuuint64_t)CH * 2, (cuuint64_t)CH * 2 * IMG_W};
    cuuint32_t box[3] = {(cuuint32_t)CH, (cuuint32_t)REGION_PX, 1};
    cuuint32_t estr[3] = {1, 1, 1};
    encode(&tm, CU_TENSOR_MAP_DATA_TYPE_BFLOAT16, 3, d_in[0], dims, strides, box, estr, CU_TENSOR_MAP_INTERLEAVE_NONE,
           CU_TENSOR_MAP_SWIZZLE_NONE, CU_TENSOR_MAP_L2_PROMOTION_L2_128B, CU_TENSOR_MAP_FLOAT_OOB_FILL_NONE);
    Descs ds;
    for (int c = 0; c < 8; c++)
        for (int k = 0; k < 6; k++) ds.w1[c][k] = make_desc(SB + SM_W1 + c * 6 * 1536 + k * 256, 128, 1536);
    for (int k = 0; k < 24; k++) ds.w2[k] = make_desc(SB + SM_W2 + k * 256, 128, 6144);
    ds.ones = make_desc(SB + SM_ONES, 0, 0);
    CUtensorMap tw;
    cuuint64_t wdims[2] = {(cuuint64_t)EX, (cuuint64_t)CH};
    cuuint64_t wstrides[1] = {(cuuint64_t)EX * 2};
    cuuint32_t wbox[2] = {64, (cuuint32_t)CH};
    encode(&tw, CU_TENSOR_MAP_DATA_TYPE_BFLOAT16, 2, d_in[2], wdims, wstrides, wbox, estr, CU_TENSOR_MAP_INTERLEAVE_NONE,
           CU_TENSOR_MAP_SWIZZLE_128B, CU_TENSOR_MAP_L2_PROMOTION_L2_128B, CU_TENSOR_MAP_FLOAT_OOB_FILL_NONE);
    Split sp = {NTILES / num_sms, NTILES % num_sms, 1, 1 << 16, 0};
    if (sp.per_cta + 9 > MAX_ROWS) return;
    if (sp.extra && sp.extra * (8 * LENT + 1) <= num_sms && sp.per_cta >= 5 * LENT + 7) {
        sp.period = num_sms / sp.extra;
        sp.inv_period = 65535 / sp.period + 1;
        sp.lenders = sp.extra;
        for (int l = 0; l < sp.extra; l++)
            if (get_work((l + 1) * sp.period - sp.period / 2 - 1, sp).nA < 2 * LENT) sp.lenders = 0;
    }
    block_kernel<<<num_sms, NTHREADS, SM_TOTAL>>>(tm, tw, (const __nv_bfloat16*)d_in[0], (const __nv_bfloat16*)d_in[1],
                                             (const __nv_bfloat16*)d_in[3],
                                             (const __nv_bfloat16*)d_in[4], (const __nv_bfloat16*)d_in[5], (__nv_bfloat16*)d_out,
                                             scratch, ds, 0, sp);
}
```

```cpp
#include <cuda_runtime.h>
#include <cuda_bf16.h>
#include <cuda_fp16.h>
#include <cuda.h>
#include <stdint.h>

namespace cnx {

constexpr int IMG_H = 512, IMG_W = 512, CH = 96, EX = 384;
constexpr int TILE_W = 64;
constexpr int NTILES = (IMG_W / TILE_W) * IMG_H;
constexpr int NSLOT = 6;
constexpr int REGION_PX = 18;
constexpr int REGION_BYTES = REGION_PX * CH * 2;
constexpr int SLOT_BYTES = 4 * REGION_BYTES;
constexpr int A_LBO = 144, A_SBO = 12 * A_LBO;
constexpr int PREFETCH_ROWS = 3;
constexpr int NCONS = 3;
constexpr int CONS_THREADS = 128 * NCONS;
constexpr int NTHREADS = 128 + CONS_THREADS;
constexpr int MAX_ROWS = 52;
constexpr int TILE_BYTES = TILE_W * CH * 2, WARP_BYTES = TILE_BYTES / 4;
constexpr int S1_PASS = 1, S2_PASS = 1;
#define K_PASS 4
#define K_WAIT 20
#define K_STG 5
#define K_REL 6
#define K_ANCH 2
#define K_CVT 0
#define K_XPOS 1
#define K_CHAIN 3
#define K_OP 0
#define K_QS 0
#define K_GS 0
#define K_QR 0
#define K_GR 0
#define K_PD 0
#define K_PQ 0
#define K_PS 0
#define K_ROT 0
#define K_LTOK 0
#define K_REQ 0x310
#define K_INIT 0
#define K_IM 1
#define K_UNRV 6
constexpr int K_UNR = K_UNRV;
#define K_LATE 1
#define K_FINE 1
#define K_SWAP 0
#define K_TAIL 0
#define W2_EARLY 6
#define S2_FIRST 2
#define ORDER_P 3
#define ORDER_Q 1
static_assert(MAX_ROWS <= 128, "one table entry per producer thread");
static_assert(2 * A_SBO == REGION_BYTES && REGION_BYTES % 128 == 0, "region layout");

constexpr uint32_t SB = 1024;
constexpr int SM_W1 = 0;
constexpr int SM_W2 = SM_W1 + CH * EX * 2;
constexpr int SM_RING = SM_W2 + CH * EX * 2;
constexpr int SM_BIASH = SM_RING + NSLOT * SLOT_BYTES;
constexpr int SM_RED = SM_BIASH + 384;
constexpr int RED_MAX = 0, RED_LAUNCH = 48, RED_INV_RHO = 52;
constexpr int SM_TILES = SM_RED + 256;
constexpr int SM_ONES = SM_TILES + MAX_ROWS * 4;
constexpr int SM_BAR = SM_ONES + 128;
constexpr int BAR_X = SM_BAR;
constexpr int BAR_A = BAR_X + NSLOT * 4 * 8;
constexpr int BAR_E = BAR_A + NSLOT * 4 * 8;
constexpr int BAR_PIN = BAR_E + NSLOT * 4 * 8;
constexpr int BAR_W = BAR_PIN + 8;
constexpr int BAR_F = BAR_W + 6 * 8;
constexpr int BAR_R = BAR_F + 8;
constexpr int SM_TOTAL = BAR_R + 16 * 8;
constexpr int SM_FILTER = SM_RING + (NSLOT - 1) * SLOT_BYTES + 9 * 128;
constexpr int SM_SQ = SM_W2;
constexpr int SQ_ROW = 128 * 16, SQ_WG = 6 * SQ_ROW;
static_assert(SM_ONES % 16 == 0 && SM_TOTAL <= 232448, "shared memory budget");

constexpr float KZ = 0.3292034911525734f;
constexpr uint32_t GELU_C2 = 0x40d940d9u;
constexpr float INV_2KZ = 0.5f / KZ;
constexpr unsigned SPIN_LIMIT = 1u << 19;

constexpr int MAX_CTAS = 255;
constexpr int W2_GROUPS = EX / 8;
#define K_LENT 3
constexpr int LENT = K_LENT, MAX_LENDERS = MAX_CTAS / (8 * LENT + 1);
struct Scratch {
    uint32_t w2h[EX * CH / 2];
    float w2max[EX];
    float bias[CH + 32];
    unsigned long long sums[EX / 4][32];
    __device__ __forceinline__ unsigned long long* sum(int e) { return &sums[e >> 2][e & 3]; }
    uint4 lent[MAX_LENDERS * LENT * 8 * 4 * 3 * 32];
    unsigned launch, pad0[31], early, pad1[31], prep, pad2[31], lent_out, pad3[31];
};
__device__ __align__(128) Scratch g_scratch;

#define PROF(k)

__device__ __forceinline__ uint32_t smem_u32(const void* p) { return (uint32_t)__cvta_generic_to_shared(p); }
__device__ __forceinline__ void mbar_init(uint32_t bar, uint32_t cnt) {
    asm volatile("mbarrier.init.shared::cta.b64 [%0], %1;" ::"r"(bar), "r"(cnt) : "memory");
}
__device__ __forceinline__ void mbar_arrive(uint32_t bar) {
    asm volatile("mbarrier.arrive.shared::cta.b64 _, [%0];" ::"r"(bar) : "memory");
}
__device__ __forceinline__ void mbar_expect_tx(uint32_t bar, uint32_t bytes) {
    asm volatile("mbarrier.arrive.expect_tx.shared::cta.b64 _, [%0], %1;" ::"r"(bar), "r"(bytes) : "memory");
}
__device__ __forceinline__ bool mbar_try(uint32_t bar, uint32_t par) {
    uint32_t ok;
    asm volatile("{\n.reg .pred p;\nmbarrier.try_wait.parity.shared::cta.b64 p, [%1], %2;\nselp.u32 %0, 1, 0, p;\n}\n"
                 : "=r"(ok) : "r"(bar), "r"(par) : "memory");
    return ok != 0;
}
__device__ __forceinline__ void mbar_wait(uint32_t bar, uint32_t par) {
    unsigned n = 0;
    while (!mbar_try(bar, par)) {
        if (++n > SPIN_LIMIT) __trap();
    }
}
__device__ __forceinline__ bool mbar_test(uint32_t bar, uint32_t par) {
    uint32_t ok;
    asm volatile("{\n.reg .pred p;\nmbarrier.test_wait.parity.shared::cta.b64 p, [%1], %2;\nselp.u32 %0, 1, 0, p;\n}\n"
                 : "=r"(ok) : "r"(bar), "r"(par) : "memory");
    return ok != 0;
}
__device__ __forceinline__ bool elect_one() {
    uint32_t ok;
    asm volatile("{\n.reg .pred p;\nelect.sync _|p, 0xffffffff;\nselp.u32 %0, 1, 0, p;\n}\n" : "=r"(ok));
    return ok != 0;
}
__device__ __forceinline__ uint32_t opaque(uint32_t v) { return __shfl_sync(~0u, v, threadIdx.x & 31); }
__device__ __forceinline__ uint32_t opaque_uniform(uint32_t v) { return __shfl_sync(~0u, v, 0); }
__device__ __forceinline__ void named_bar(int id, int n) { asm volatile("bar.sync %0, %1;" ::"r"(id), "r"(n) : "memory"); }
__device__ __forceinline__ void named_arrive(int id, int n) { asm volatile("bar.arrive %0, %1;" ::"r"(id), "r"(n) : "memory"); }
__device__ __forceinline__ void fence_async() { asm volatile("fence.proxy.async.shared::cta;" ::: "memory"); }
__device__ __forceinline__ uint64_t evict_first() {
    uint64_t p;
    asm("createpolicy.fractional.L2::evict_first.b64 %0, 1.0;" : "=l"(p));
    return p;
}
__device__ __forceinline__ void tma_row(uint32_t dst, const CUtensorMap* tm, uint32_t bar, int x, int y) {
    asm volatile("cp.async.bulk.tensor.3d.shared::cluster.global.mbarrier::complete_tx::bytes.L2::cache_hint [%0], [%1, {%3, %4, %5}], [%2], %6;"
                 ::"r"(dst), "l"(tm), "r"(bar), "r"(0), "r"(x), "r"(y), "l"(evict_first()) : "memory");
}
__device__ __forceinline__ void bulk_load_stream(uint32_t dst, const void* src, uint32_t bytes, uint32_t bar) {
    asm volatile("cp.async.bulk.shared::cluster.global.mbarrier::complete_tx::bytes.L2::cache_hint [%0], [%1], %2, [%3], %4;"
                 ::"r"(dst), "l"(src), "r"(bytes), "r"(bar), "l"(evict_first()) : "memory");
}
__device__ __forceinline__ void prefetch_l2(const void* src, uint32_t bytes) {
    asm volatile("cp.async.bulk.prefetch.L2.global [%0], %1;" ::"l"(src), "r"(bytes) : "memory");
}
__device__ __forceinline__ void tma_2d(uint32_t dst, const CUtensorMap* tm, uint32_t bar, int x, int y) {
    asm volatile("cp.async.bulk.tensor.2d.shared::cluster.global.mbarrier::complete_tx::bytes [%0], [%1, {%3, %4}], [%2];"
                 ::"r"(dst), "l"(tm), "r"(bar), "r"(x), "r"(y) : "memory");
}
__device__ __forceinline__ void bulk_load(uint32_t dst, const void* src, uint32_t bytes, uint32_t bar) {
    asm volatile("cp.async.bulk.shared::cluster.global.mbarrier::complete_tx::bytes [%0], [%1], %2, [%3];"
                 ::"r"(dst), "l"(src), "r"(bytes), "r"(bar) : "memory");
}
__device__ __forceinline__ void wg_fence() { asm volatile("wgmma.fence.sync.aligned;" ::: "memory"); }
__device__ __forceinline__ void wg_commit() { asm volatile("wgmma.commit_group.sync.aligned;" ::: "memory"); }
template <int N> __device__ __forceinline__ void wg_wait() { asm volatile("wgmma.wait_group.sync.aligned %0;" ::"n"(N) : "memory"); }
template <int N> __device__ __forceinline__ void pin(uint32_t (&d)[N]) {
#pragma unroll
    for (int q = 0; q < N; q++) asm volatile("" : "+r"(d[q])::"memory");
}
__device__ __forceinline__ void stg128(void* p, const uint32_t (&v)[4]) {
    asm volatile("st.global.v4.u32 [%0], {%1, %2, %3, %4};" ::"l"(p), "r"(v[0]), "r"(v[1]), "r"(v[2]), "r"(v[3]) : "memory");
}
__device__ __forceinline__ void ldg128(uint32_t (&v)[4], const void* p) {
    asm volatile("ld.global.L1::no_allocate.v4.u32 {%0, %1, %2, %3}, [%4];" : "=r"(v[0]), "=r"(v[1]), "=r"(v[2]), "=r"(v[3]) : "l"(p) : "memory");
}
__device__ __forceinline__ void ldg128_if(bool on, uint32_t (&v)[4], const void* p) {
    asm volatile("{\n.reg .pred p;\nsetp.ne.b32 p, %5, 0;\n@p ld.global.L1::no_allocate.v4.u32 {%0, %1, %2, %3}, [%4];\n}\n"
                 : "+r"(v[0]), "+r"(v[1]), "+r"(v[2]), "+r"(v[3]) : "l"(p), "r"((int)on) : "memory");
}
__device__ __forceinline__ uint4 ldg128_ordered(const void* p) {
    uint4 v;
    asm volatile("ld.global.nc.v4.u32 {%0, %1, %2, %3}, [%4];" : "=r"(v.x), "=r"(v.y), "=r"(v.z), "=r"(v.w) : "l"(p) : "memory");
    return v;
}
__host__ __device__ constexpr uint64_t make_desc(uint32_t addr, uint32_t lbo, uint32_t sbo) {
    return (uint64_t)((addr & 0x3FFFF) >> 4) | ((uint64_t)(lbo >> 4) << 16) | ((uint64_t)(sbo >> 4) << 32);
}
__device__ __forceinline__ void wgmma(uint32_t (&d)[12], uint32_t a0, uint32_t a1, uint32_t a2, uint32_t a3, uint64_t db, int acc) {
    asm volatile("{\n.reg .pred p;\nsetp.ne.b32 p, %17, 0;\n"
                 "wgmma.mma_async.sync.aligned.m64n48k16.f16.f16.f16 "
                 "{%0, %1, %2, %3, %4, %5, %6, %7, %8, %9, %10, %11}, "
                 "{%12, %13, %14, %15}, %16, p, 1, 1, 0;\n}\n"
                 : "+r"(d[0]), "+r"(d[1]), "+r"(d[2]), "+r"(d[3]), "+r"(d[4]), "+r"(d[5]), "+r"(d[6]), "+r"(d[7]), "+r"(d[8]), "+r"(d[9]), "+r"(d[10]), "+r"(d[11])
                 : "r"(a0), "r"(a1), "r"(a2), "r"(a3), "l"(db), "r"(acc));
}
__device__ __forceinline__ void wgmma(uint32_t (&d)[24], uint32_t a0, uint32_t a1, uint32_t a2, uint32_t a3, uint64_t db, int acc) {
    asm volatile("{\n.reg .pred p;\nsetp.ne.b32 p, %29, 0;\n"
                 "wgmma.mma_async.sync.aligned.m64n96k16.f16.f16.f16 "
                 "{%0, %1, %2, %3, %4, %5, %6, %7, %8, %9, %10, %11, %12, %13, %14, %15, %16, %17, %18, %19, %20, %21, %22, %23}, "
                 "{%24, %25, %26, %27}, %28, p, 1, 1, 0;\n}\n"
                 : "+r"(d[0]), "+r"(d[1]), "+r"(d[2]), "+r"(d[3]), "+r"(d[4]), "+r"(d[5]), "+r"(d[6]), "+r"(d[7]), "+r"(d[8]), "+r"(d[9]), "+r"(d[10]), "+r"(d[11]), "+r"(d[12]), "+r"(d[13]), "+r"(d[14]), "+r"(d[15]), "+r"(d[16]), "+r"(d[17]), "+r"(d[18]), "+r"(d[19]), "+r"(d[20]), "+r"(d[21]), "+r"(d[22]), "+r"(d[23])
                 : "r"(a0), "r"(a1), "r"(a2), "r"(a3), "l"(db), "r"(acc));
}
template <int ACC>
__device__ __forceinline__ void wgmma_rowsum(float (&d)[4], const uint32_t (&a)[4], uint64_t ones) {
    asm volatile("{\n.reg .pred p;\nsetp.ne.b32 p, %9, 0;\n"
                 "wgmma.mma_async.sync.aligned.m64n8k16.f32.bf16.bf16 {%0, %1, %2, %3}, {%4, %5, %6, %7}, %8, p, 1, 1, 0;\n}\n"
                 : "+f"(d[0]), "+f"(d[1]), "+f"(d[2]), "+f"(d[3])
                 : "r"(a[0]), "r"(a[1]), "r"(a[2]), "r"(a[3]), "l"(ones), "n"(ACC));
}
__device__ __forceinline__ void ldsm4(uint32_t (&r)[4], uint32_t addr) {
    asm volatile("ldmatrix.sync.aligned.m8n8.x4.shared.b16 {%0, %1, %2, %3}, [%4];"
                 : "=r"(r[0]), "=r"(r[1]), "=r"(r[2]), "=r"(r[3]) : "r"(addr) : "memory");
}
__device__ __forceinline__ void ldsm4_t(uint32_t (&r)[4], uint32_t addr) {
    asm volatile("ldmatrix.sync.aligned.m8n8.x4.trans.shared.b16 {%0, %1, %2, %3}, [%4];"
                 : "=r"(r[0]), "=r"(r[1]), "=r"(r[2]), "=r"(r[3]) : "r"(addr) : "memory");
}
__device__ __forceinline__ void stsm4(uint32_t addr, uint32_t a, uint32_t b, uint32_t c, uint32_t d) {
    asm volatile("stmatrix.sync.aligned.m8n8.x4.shared.b16 [%0], {%1, %2, %3, %4};"
                 ::"r"(addr), "r"(a), "r"(b), "r"(c), "r"(d) : "memory");
}
__device__ __forceinline__ uint32_t transpose8x8(uint32_t v) {
    uint32_t d; asm volatile("movmatrix.sync.aligned.m8n8.trans.b16 %0, %1;" : "=r"(d) : "r"(v)); return d;
}
__device__ __forceinline__ void spin_until(const unsigned* counter, unsigned target) {
    unsigned n = 0, c;
    do {
        asm volatile("ld.acquire.gpu.global.u32 %0, [%1];" : "=r"(c) : "l"(counter) : "memory");
        if (++n > SPIN_LIMIT) __trap();
    } while ((int)(c - target) < 0);
}
__device__ __forceinline__ void signal(unsigned* counter) {
    __syncwarp();
    if (elect_one()) asm volatile("red.release.gpu.global.add.u32 [%0], 1;" ::"l"(counter) : "memory");
    __syncwarp();
}
__device__ __forceinline__ void lds128(uint32_t& a, uint32_t& b, uint32_t& c, uint32_t& d, uint32_t addr) {
    asm volatile("ld.shared.v4.u32 {%0, %1, %2, %3}, [%4];" : "=r"(a), "=r"(b), "=r"(c), "=r"(d) : "r"(addr) : "memory");
}
__device__ __forceinline__ void lds64(uint32_t& a, uint32_t& b, uint32_t addr) {
    asm volatile("ld.shared.v2.u32 {%0, %1}, [%2];" : "=r"(a), "=r"(b) : "r"(addr) : "memory");
}
__device__ __forceinline__ void lds32(uint32_t& a, uint32_t addr) {
    asm volatile("ld.shared.u32 %0, [%1];" : "=r"(a) : "r"(addr) : "memory");
}
__device__ __forceinline__ int ldsi(uint32_t addr) {
    uint32_t v;
    lds32(v, addr);
    return (int)v;
}
__device__ __forceinline__ float ldsf(uint32_t addr) {
    uint32_t v;
    lds32(v, addr);
    return __uint_as_float(v);
}
__device__ __forceinline__ void sts32(uint32_t addr, uint32_t a) {
    asm volatile("st.shared.u32 [%0], %1;" ::"r"(addr), "r"(a) : "memory");
}
__device__ __forceinline__ void sts128(uint32_t addr, uint32_t a, uint32_t b, uint32_t c, uint32_t d) {
    asm volatile("st.shared.v4.u32 [%0], {%1, %2, %3, %4};" ::"r"(addr), "r"(a), "r"(b), "r"(c), "r"(d) : "memory");
}
__device__ __forceinline__ void sts64(uint32_t addr, uint32_t a, uint32_t b) {
    asm volatile("st.shared.v2.u32 [%0], {%1, %2};" ::"r"(addr), "r"(a), "r"(b) : "memory");
}
__device__ __forceinline__ void anchor(uint32_t addr, uint32_t a, uint32_t b, uint32_t c, uint32_t d) {
    asm volatile("{\n.reg .pred p;\nsetp.eq.b32 p, %0, 0;\n@p st.shared.v4.u32 [%0], {%1, %2, %3, %4};\n}\n"
                 ::"r"(addr), "r"(a), "r"(b), "r"(c), "r"(d) : "memory");
}
__device__ __forceinline__ uint32_t bf_fma(uint32_t a, uint32_t b, uint32_t c) {
    uint32_t d; asm("fma.rn.bf16x2 %0, %1, %2, %3;" : "=r"(d) : "r"(a), "r"(b), "r"(c)); return d;
}
__device__ __forceinline__ uint32_t bf_mul(uint32_t a, uint32_t b) {
    uint32_t d; asm("mul.rn.bf16x2 %0, %1, %2;" : "=r"(d) : "r"(a), "r"(b)); return d;
}
__device__ __forceinline__ uint32_t bf_absmax(uint32_t a, uint32_t b) {
    uint32_t d; asm("max.xorsign.abs.bf16x2 %0, %1, %2;" : "=r"(d) : "r"(a), "r"(b)); return d;
}
__device__ __forceinline__ uint32_t h_fma(uint32_t a, uint32_t b, uint32_t c) {
    uint32_t d; asm("fma.rn.f16x2 %0, %1, %2, %3;" : "=r"(d) : "r"(a), "r"(b), "r"(c)); return d;
}
__device__ __forceinline__ uint32_t h_mul(uint32_t a, uint32_t b) {
    uint32_t d; asm("mul.rn.f16x2 %0, %1, %2;" : "=r"(d) : "r"(a), "r"(b)); return d;
}
__device__ __forceinline__ uint32_t h_round8(uint32_t v) { return (v + 0x00040004u) & 0xfff8fff8u; }
__device__ __forceinline__ uint32_t h_tanh(uint32_t a) {
    uint32_t d; asm("tanh.approx.f16x2 %0, %1;" : "=r"(d) : "r"(a)); return d;
}
__device__ __forceinline__ uint32_t pack_h2(float lo, float hi) {
    uint32_t d; asm("cvt.rn.f16x2.f32 %0, %1, %2;" : "=r"(d) : "f"(hi), "f"(lo)); return d;
}
__device__ __forceinline__ uint32_t pack_bf2(float lo, float hi) {
    uint32_t d; asm("cvt.rn.bf16x2.f32 %0, %1, %2;" : "=r"(d) : "f"(hi), "f"(lo)); return d;
}
__device__ __forceinline__ float bf_lo(uint32_t v) { return __uint_as_float(v << 16); }
__device__ __forceinline__ float bf_hi(uint32_t v) { return __uint_as_float(v & 0xffff0000u); }
__device__ __forceinline__ float h_lo(uint32_t v) { return __low2float(*reinterpret_cast<__half2*>(&v)); }
__device__ __forceinline__ float h_hi(uint32_t v) { return __high2float(*reinterpret_cast<__half2*>(&v)); }
__device__ __forceinline__ float warp_absmax(uint32_t v) {
    return __uint_as_float(__reduce_max_sync(~0u, max((v & 0x7fffu) << 16, v & 0x7fff0000u)));
}
__device__ __forceinline__ uint32_t gelu2(uint32_t z) {
    uint32_t p = h_fma(z, z, GELU_C2);
    uint32_t t = h_tanh(K_OP & 1 ? h_mul(p, z) : h_mul(z, p));
    return K_OP & 2 ? h_fma(t, z, z) : h_fma(z, t, z);
}
__device__ __forceinline__ float grn_norm(float ss) {
    float r;
    asm("sqrt.approx.f32 %0, %1;" : "=f"(r) : "f"(fmaf(ss, INV_2KZ * INV_2KZ, 1e-6f)));
    return r;
}
__device__ __forceinline__ float pow2i(int e) { return __uint_as_float((uint32_t)(e + 127) << 23); }
__device__ __forceinline__ int ilog2f(float v) {
    int e = (int)((__float_as_uint(v) >> 23) & 0xff) - 127;
    return max(-100, min(100, e));
}

__device__ __forceinline__ int bound_exp(float w1max) { return w1max > 0.f ? ilog2f(2.f * KZ * 96.f * w1max) : 0; }
__device__ __forceinline__ bool plain_squares(int e) { return (unsigned)(4 - e) <= 6; }
__device__ __forceinline__ int square_exp(int e) { return plain_squares(e) ? 0 : max(-14, min(4 - e, 14)); }
__device__ __forceinline__ int sum_exp(int e) { return max(-90, min(90, 33 - 2 * e)); }
__device__ __forceinline__ float row_scale(float m) { return m > 0.f ? pow2i(2 - ilog2f(m)) : 1.f; }

struct Split {
    int per_cta, extra, period, inv_period, lenders;
    uint32_t lent_off[MAX_LENDERS * LENT];
    __host__ __device__ __forceinline__ int longer_before(int cta) const {
        const int n = (cta + period / 2) * inv_period >> 16;
        return n < extra ? n : extra;
    }
};
struct Work {
    int tA, tB, nA, nB, dir, rows, lent, index;
    __host__ __device__ __forceinline__ int tile(int j) const { return j < nA ? tA + dir * j : tB + dir * (j - nA); }
};
__host__ __device__ __forceinline__ Work get_work(int cta, const Split& sp) {
    Work w;
    const int before = sp.longer_before(cta), longer = sp.longer_before(cta + 1) - before;
    w.lent = longer && sp.lenders ? LENT : 0;
    w.index = longer ? before : cta - before;
    const int t0 = cta * sp.per_cta + before, t1 = t0 + sp.per_cta + longer;
    const int tm = t1 < (t0 | 511) + 1 ? t1 : (t0 | 511) + 1;
    const bool swap = t1 > tm && t1 - tm < tm - t0, down = cta & 1;
    w.nA = swap ? t1 - tm : tm - t0;
    w.nB = t1 - t0 - w.nA;
    w.tA = down ? (swap ? tm : t0) : (swap ? t1 : tm) - 1;
    w.tB = down ? (swap ? t0 : tm) : (swap ? tm : t1) - 1;
    w.dir = down ? 1 : -1;
    w.rows = w.nA + 2 + (w.nB ? w.nB + 2 : 0);
    return w;
}
__device__ __forceinline__ int row_code(const Work& w, int i) {
    const bool in_a = i < w.nA + 2;
    const int t = in_a ? w.tA : w.tB;
    return ((t & 511) + w.dir * ((in_a ? i : i - (w.nA + 2)) - 1)) << 16 | (t >> 9) * TILE_W;
}
__host__ __device__ __forceinline__ uint32_t tile_offset(int tile) { return ((tile & 511) * IMG_W + (tile >> 9) * TILE_W) * (CH * 2); }
__device__ __forceinline__ int tile_order(int j, int n) {
    const int olds = (j / ORDER_P) * ORDER_Q + max(0, j % ORDER_P - (ORDER_P - ORDER_Q));
    return (j % ORDER_P >= ORDER_P - ORDER_Q) ? olds : n - 1 - (j - olds);
}
__device__ __forceinline__ void issue_region(const CUtensorMap* tm, uint32_t dst, uint32_t bar, int warp, int code) {
    mbar_expect_tx(bar, REGION_BYTES);
    tma_row(dst, tm, bar, (code & 0xffff) + (16 * warp - 1), code >> 16);
}

template <class Event>
__device__ __forceinline__ void conv_producer(const Work& wk, const CUtensorMap* tm, uint32_t sb, int warp, Event event) {
    const int lane = threadIdx.x & 31;
    const int j = lane & 15, grp = lane >> 4;
    const uint32_t reg0 = sb + SM_RING + warp * REGION_BYTES;
    const uint32_t bars = sb + SM_BAR + warp * 8;
    if (warp * 32 + lane < MAX_ROWS) {
        const int i = warp * 32 + lane, before = min(i / 5, wk.lent);
        const bool back = i % 5 == 0 && i > 0 && i / 5 <= wk.lent;
        sts32(sb + SM_TILES + i * 4, back ? tile_offset(wk.tile(before - 1)) | before
                                          : tile_offset(wk.tile(wk.lent + tile_order(i - before, wk.nA + wk.nB - NCONS - wk.lent))));
    }
    const uint32_t ld64 = opaque(reg0 + grp * 8 * 192 + j * 8), ld32 = opaque(reg0 + grp * 8 * 192 + 128 + j * 4);
    const uint32_t st64 = opaque(reg0 + grp * A_SBO + (j >> 1) * A_LBO + (j & 1) * 8);
    const uint32_t st32 = opaque(reg0 + grp * A_SBO + (8 + (j >> 2)) * A_LBO + (j & 3) * 4);
    named_bar(0, NTHREADS);
    uint32_t w[3][3][3];
    mbar_wait(sb + BAR_F, 0);
#pragma unroll
    for (int tap = 0; tap < 9; tap++) {
        const uint32_t p = sb + SM_FILTER + (3 + wk.dir * 3 * (tap / 3 - 1) + tap % 3) * (CH * 2);
        lds64(w[tap / 3][tap % 3][0], w[tap / 3][tap % 3][1], p + 8 * j);
        lds32(w[tap / 3][tap % 3][2], p + 128 + 4 * j);
    }
#pragma unroll
    for (int tap = 0; tap < 9; tap++) sts64(reg0 + (NSLOT - 1) * SLOT_BYTES + tap * 128 + j * 8, w[tap / 3][tap % 3][1], w[tap / 3][tap % 3][0]);
    named_bar(1, 128);
#pragma unroll
    for (int tap = 0; tap < 9; tap++) lds64(w[tap / 3][tap % 3][1], w[tap / 3][tap % 3][0], reg0 + (NSLOT - 1) * SLOT_BYTES + tap * 128 + j * 8);
    static_assert(2 * PREFETCH_ROWS == NSLOT && SLOT_BYTES % 32 == 0, "slot arithmetic");
    uint32_t bo = 0, par = 0, pbo = PREFETCH_ROWS * 32, ppar = 1;
    int px, py;
    auto request = [&]() {
        mbar_wait(bars + (BAR_E - SM_BAR) + pbo, ppar);
        if (elect_one()) {
            mbar_expect_tx(bars + pbo, REGION_BYTES);
            tma_row(reg0 + pbo * (SLOT_BYTES / 32), tm, bars + pbo, px, py);
        }
    };
    auto advance = [&]() {
        bo += 32;
        if (bo == NSLOT * 32) { bo = 0; par ^= 1; }
        pbo += 32;
        if (pbo == NSLOT * 32) { pbo = 0; ppar ^= 1; }
    };
    auto aim = [&](int row) {
        const int code = row_code(wk, row);
        px = (code & 0xffff) + (16 * warp - 1);
        py = code >> 16;
    };
    uint32_t accB[8][3], accC[8][3];
    int r = 0;
#pragma unroll 1
    while (r < wk.rows) {
        if (r == 0 || r == wk.nA + 2) {
            const uint32_t bo0 = bo;
            uint32_t bo1;
#pragma unroll 1
            for (int k = 0; k < 2; k++, r++) {
                mbar_wait(bars + bo, par);
                bo1 = bo;
                if (r >= 2) {
                    aim(r + PREFETCH_ROWS);
                    request();
                }
                advance();
            }
            const uint32_t so0 = bo0 * (SLOT_BYTES / 32), so1 = bo1 * (SLOT_BYTES / 32);
#pragma unroll
            for (int p = 0; p < 10; p++) {
                uint32_t u[3], v[3];
                lds64(u[0], u[1], so0 + ld64 + p * 192);
                lds32(u[2], so0 + ld32 + p * 192);
                lds64(v[0], v[1], so1 + ld64 + p * 192);
                lds32(v[2], so1 + ld32 + p * 192);
#pragma unroll
                for (int dx = 0; dx < 3; dx++) {
                    const int o = p - dx;
                    if (o < 0 || o > 7) continue;
#pragma unroll
                    for (int q = 0; q < 3; q++) {
                        accB[o][q] = bf_fma(v[q], w[1][dx][q], dx == 0 ? bf_mul(u[q], w[0][dx][q]) : bf_fma(u[q], w[0][dx][q], accB[o][q]));
                        accC[o][q] = dx == 0 ? bf_mul(v[q], w[0][dx][q]) : bf_fma(v[q], w[0][dx][q], accC[o][q]);
                    }
                }
            }
            anchor(ld64, accB[7][0], accB[7][1], accB[7][2], 0);
            __syncwarp();
            if (elect_one()) {
                mbar_arrive(bars + (BAR_A - SM_BAR) + bo0);
                mbar_arrive(bars + (BAR_E - SM_BAR) + bo0);
                mbar_arrive(bars + (BAR_A - SM_BAR) + bo1);
                mbar_arrive(bars + (BAR_E - SM_BAR) + bo1);
            }
        }
        int end = wk.rows;
        const int marks[4] = {wk.rows - PREFETCH_ROWS, wk.rows - 11, wk.nA + 2, wk.nA + 2 - PREFETCH_ROWS};
#pragma unroll
        for (int k = 0; k < 4; k++) end = marks[k] > r ? min(end, marks[k]) : end;
        const bool fetch = r < wk.rows - PREFETCH_ROWS;
        aim(r + PREFETCH_ROWS);
        px = opaque_uniform(px);
        const int py_end = opaque_uniform(py + wk.dir * (end - r));
        r = end;
#pragma unroll 1
        do {
            mbar_wait(bars + bo, par);
            const uint32_t so = bo * (SLOT_BYTES / 32);
            uint32_t out[8][3];
#pragma unroll
            for (int p = 0; p < 10; p++) {
                uint32_t xv[3];
                lds64(xv[0], xv[1], so + ld64 + p * 192);
                lds32(xv[2], so + ld32 + p * 192);
#pragma unroll
                for (int dd = 0; dd < 3; dd++) {
                    const int dx = K_PD ? 2 - dd : dd, o = p - dx;
                    if (o < 0 || o > 7) continue;
#pragma unroll
                    for (int qq = 0; qq < 3; qq++) {
                        const int q = (qq + K_PQ) % 3;
                        out[o][q] = bf_fma(xv[q], w[2][dx][q], dx == 0 ? accB[o][q] : out[o][q]);
                        accB[o][q] = bf_fma(xv[q], w[1][dx][q], dx == 0 ? accC[o][q] : accB[o][q]);
                        accC[o][q] = dx == 0 ? bf_mul(xv[q], w[0][dx][q]) : bf_fma(xv[q], w[0][dx][q], accC[o][q]);
                    }
                }
            }
            __syncwarp();
#pragma unroll
            for (int oo = 0; oo < 8; oo++) {
                const int o = K_PS ? 7 - oo : oo;
                sts64(so + st64 + o * 16, out[o][0], out[o][1]);
                sts32(so + st32 + o * 16, out[o][2]);
            }
            __syncwarp();
            if (elect_one()) mbar_arrive(bars + (BAR_A - SM_BAR) + bo);
            if (fetch) request();
            advance();
            py += wk.dir;
        } while (py != py_end);
        if (((wk.rows - r) & ~8) == PREFETCH_ROWS) event(wk.rows - r == PREFETCH_ROWS);
    }
}

template <bool SCALED, int K0 = 0, int K1 = 3>
__device__ __forceinline__ void gelu_sq(uint32_t (&d)[24], uint32_t (&keep)[24], uint32_t sq_addr, uint32_t scale2) {
    pin(d);
#pragma unroll
    for (int k = K0; k < K1; k++) {
        uint32_t hs[4];
        lds128(hs[0], hs[1], hs[2], hs[3], sq_addr + k * SQ_ROW);
#pragma unroll
        for (int qq = 0; qq < 4; qq++) {
            const int q = K_QS == 0 ? qq : K_QS == 1 ? 3 - qq : K_QS == 2 ? (qq >> 1 | (qq & 1) << 1) : (qq + 1) & 3;
            uint32_t g0 = gelu2(d[8 * k + 2 * q]), g1 = gelu2(d[8 * k + 2 * q + 1]);
            keep[8 * k + 2 * q] = g0;
            keep[8 * k + 2 * q + 1] = g1;
            if (SCALED) { g0 = h_mul(g0, scale2); g1 = h_mul(g1, scale2); }
            hs[q] = (K_GS >> (q & 1) & 1) ? h_fma(g0, g0, h_fma(g1, g1, hs[q])) : h_fma(g1, g1, h_fma(g0, g0, hs[q]));
        }
        sts128(sq_addr + k * SQ_ROW, hs[0], hs[1], hs[2], hs[3]);
    }
}
__device__ __forceinline__ void gelu_sq_reg(uint32_t (&d)[24], uint32_t (&hs)[12]) {
    pin(d);
#pragma unroll
    for (int qq = 0; qq < 12; qq++) {
        const int q = K_QR == 0 ? qq : K_QR == 1 ? 11 - qq : K_QR == 2 ? qq ^ 1 : qq * 5 % 12;
        const uint32_t g0 = gelu2(d[2 * q]), g1 = gelu2(d[2 * q + 1]);
        hs[q] = (K_GR >> (q & 1) & 1) ? h_fma(g0, g0, h_fma(g1, g1, hs[q])) : h_fma(g1, g1, h_fma(g0, g0, hs[q]));
    }
}
__device__ __forceinline__ void gelu_to(uint32_t (&g)[12], uint32_t (&d)[12]) {
    pin(d);
#pragma unroll
    for (int q = 0; q < 12; q++) g[q] = gelu2(d[q]);
    pin(g);
}
__device__ __forceinline__ void load_tile(uint32_t (&raw)[6][4], uint32_t addr) {
#pragma unroll
    for (int s = 0; s < 6; s++) ldsm4(raw[s], addr + s * 2 * A_LBO);
}
__device__ __forceinline__ uint2 ln_stats(const uint32_t (&raw)[6][4], uint64_t ones) {
    constexpr int NS = 6 / K_CHAIN;
    uint32_t sq[NS][4];
#pragma unroll
    for (int s = 0; s < 6; s++)
#pragma unroll
        for (int q = 0; q < 4; q++) sq[s % NS][q] = s < NS ? bf_mul(raw[s][q], raw[s][q]) : bf_fma(raw[s][q], raw[s][q], sq[s % NS][q]);
    float sum[4], ssq[4];
    wg_fence();
    wgmma_rowsum<0>(sum, raw[0], ones);
#pragma unroll
    for (int s = 1; s < 6; s++) wgmma_rowsum<1>(sum, raw[s], ones);
    wgmma_rowsum<0>(ssq, sq[0], ones);
#pragma unroll
    for (int s = 1; s < NS; s++) wgmma_rowsum<1>(ssq, sq[s], ones);
    wg_commit();
    wg_wait<0>();
    uint32_t st[2];
#pragma unroll
    for (int h = 0; h < 2; h++) {
        asm volatile("" : "+f"(sum[2 * h]), "+f"(ssq[2 * h])::"memory");
        const float mean = sum[2 * h] * (1.f / CH);
        const float var = fmaxf(fmaf(ssq[2 * h], 1.f / CH, -mean * mean), 0.f);
        float rstd;
        asm("rsqrt.approx.ftz.f32 %0, %1;" : "=f"(rstd) : "f"(var + 1e-5f));
        rstd = bf_lo(pack_bf2(rstd * (K_CVT == 0 ? KZ : KZ * 0x1p-112f), 0.f));
        st[h] = pack_bf2(rstd, -mean * rstd);
    }
    return make_uint2(st[0], st[1]);
}
__device__ __forceinline__ void ln_apply(uint32_t (&a)[6][4], const uint2& st) {
    const uint32_t sc[2] = {__byte_perm(st.x, 0, 0x1010), __byte_perm(st.y, 0, 0x1010)};
    const uint32_t sh[2] = {__byte_perm(st.x, 0, 0x3232), __byte_perm(st.y, 0, 0x3232)};
#pragma unroll
    for (int s = 0; s < 6; s++)
#pragma unroll
        for (int q = 0; q < 4; q++) {
            const uint32_t v = bf_fma(a[s][q], sc[q & 1], sh[q & 1]);
            a[s][q] = K_CVT == 0 ? pack_h2(bf_lo(v), bf_hi(v)) : K_CVT == 1 ? (v & 0x7fff7fffu) * 7u + v : ((v << 3) & 0x7fff7fffu) | (v & 0x80008000u);
        }
}
struct Cursor {
    int slot;
    uint32_t par;
    __device__ __forceinline__ void advance(int n) {
        slot += n;
        if (slot >= NSLOT) { slot -= NSLOT; par ^= 1; }
    }
};
struct Descs {
    uint64_t w1[8][6];
    uint64_t w2[24];
    uint64_t ones;
};
template <int E0, int N>
__device__ __forceinline__ void gemm1_chunk(uint32_t (&d)[N], const uint32_t (&a)[6][4], const Descs& ds, int zero) {
#pragma unroll
    for (int s = 0; s < 6; s++) wgmma(d, a[s][0], a[s][1], a[s][2], a[s][3], ds.w1[E0 / 48][s], s ? 1 : zero);
}
template <int E0, int N>
__device__ __forceinline__ void gemm2_chunk(uint32_t (&acc)[24], const uint32_t (&g)[N], const Descs& ds) {
#pragma unroll
    for (int s = 0; s < N / 4; s++) wgmma(acc, g[4 * s], g[4 * s + 1], g[4 * s + 2], g[4 * s + 3], ds.w2[E0 / 16 + s], 1);
}

struct __align__(64) Params {
    Split sp;
    int zero;
    const __nv_bfloat16 *x, *dw, *w2, *gamma, *beta;
    __nv_bfloat16* out;
    Scratch* sc;
    Descs ds;
};

__global__ void __launch_bounds__(NTHREADS, 1)
block_kernel(const __grid_constant__ CUtensorMap tmap, const __grid_constant__ CUtensorMap tmap_w1, const __grid_constant__ Params pm) {
    const Split& sp = pm.sp;
    const Descs& ds = pm.ds;
    const int& zero = pm.zero;
    const __nv_bfloat16 *const &x = pm.x, *const &dw = pm.dw, *const &w2 = pm.w2, *const &gamma = pm.gamma, *const &beta = pm.beta;
    __nv_bfloat16* const& out = pm.out;
    Scratch* const& sc = pm.sc;
    extern __shared__ __align__(1024) uint8_t smem[];
    constexpr uint32_t sb = SB;
    const int tid = K_ROT < 4 ? (threadIdx.x + 128 * K_ROT) & (NTHREADS - 1) : threadIdx.x ^ 384;
    const Work wk = get_work(blockIdx.x, sp);
    constexpr uint32_t s_red = sb + SM_RED;
    if (smem_u32(smem) != SB) __trap();

    PROF(0);
    const int warp_id = __shfl_sync(~0u, tid >> 5, 0);
    const int cw = warp_id - 4, wgi = cw >> 2, w4 = warp_id & 3;
    if (elect_one()) {
        static_assert(3 * NSLOT * 4 == 8 + 4 * 16 && BAR_F == BAR_W + 48, "barrier shares");
        const int b = warp_id - 8;
        const uint32_t bar = b < 0 ? sb + BAR_X + warp_id * 8 : b < 7 ? sb + BAR_W + b * 8 : sb + BAR_PIN;
        mbar_init(bar, 1);
        if (!K_INIT) {
#pragma unroll
            for (int k = 0; k < 4; k++) mbar_init(sb + BAR_X + (8 + 4 * warp_id + k) * 8, 1);
            mbar_init(sb + BAR_R + warp_id * 8, 1);
        }
        fence_async();
        if (b < 0) {
            issue_region(&tmap, sb + SM_RING + warp_id * REGION_BYTES, bar, w4, ((wk.tA & 511) + wk.dir * wgi) << 16 | (wk.tA >> 9) * TILE_W);
        } else if (b < 6) {
            mbar_expect_tx(bar, 64 * CH * 2);
            tma_2d(sb + SM_W2 + b * (64 * CH * 2), &tmap_w1, bar, 64 * b, 0);
        } else if (b == 6) {
            mbar_expect_tx(bar, 9 * CH * 2);
            bulk_load(sb + SM_FILTER, dw, 9 * CH * 2, bar);
        }
        if (K_INIT) {
#pragma unroll
            for (int k = 0; k < 4; k++) mbar_init(sb + BAR_X + (8 + 4 * warp_id + k) * 8, 1);
            mbar_init(sb + BAR_R + warp_id * 8, 1);
            fence_async();
        }
    }
    __syncwarp();
    const int ntiles = wk.nA + wk.nB;
    const int wg = warp_id >> 2;
    int first = wg;
    uint32_t a[6][4], acc[24], tile_off, next_off, stage, inv_rho2 = 0, rpar = 0, bias_addr, lane16, lane_off;
    auto set_lane = [&](uint32_t lane) {
        bias_addr = sb + SM_BIASH + (lane & 3) * 96;
        lane16 = lane * 16;
        lane_off = ((lane >> 2) * CH + 8 * (lane & 3)) * 2;
    };
    const uint32_t bar_r = sb + BAR_R + warp_id * 8;
    auto load_bias = [&](uint32_t (&acc)[24]) {
#pragma unroll
        for (int q = 0; q < 6; q++) lds128(acc[4 * q], acc[4 * q + 1], acc[4 * q + 2], acc[4 * q + 3], bias_addr + q * 16);
    };
    auto load_frags = [&](bool on) {
#pragma unroll
        for (int s = 0; s < 6; s++) ldg128_if(on, a[s], reinterpret_cast<const char*>(out) + next_off + w4 * WARP_BYTES + lane16 + s * 512);
    };
    auto load_first = [&]() {
#pragma unroll
        for (int s = 0; s < 6; s++) ldg128(a[s], reinterpret_cast<const char*>(out) + next_off + w4 * WARP_BYTES + lane16 + s * 512);
    };
    auto stage_x = [&]() {
        if (elect_one()) {
            mbar_expect_tx(bar_r, WARP_BYTES);
            bulk_load_stream(stage, reinterpret_cast<const char*>(x) + tile_off + w4 * WARP_BYTES, WARP_BYTES, bar_r);
        }
    };
    auto epilogue = [&](uint32_t (&acc)[24]) {
        pin(acc);
        rpar ^= 1;
        uint4* op = reinterpret_cast<uint4*>(reinterpret_cast<char*>(out) + tile_off + w4 * WARP_BYTES + lane_off);
#pragma unroll
        for (int h = 0; h < 2; h++)
#pragma unroll
            for (int m = 0; m < 3; m++) {
                uint32_t xin[4], o[4];
                lds128(xin[0], xin[1], xin[2], xin[3], stage + lane_off + h * 1536 + m * 64);
#pragma unroll
                for (int q = 0; q < 4; q++) {
                    const uint32_t v = acc[2 * (4 * m + q) + h];
                    o[q] = bf_fma(pack_bf2(h_lo(v), h_hi(v)), inv_rho2, xin[q]);
                }
                __stcs(op + h * 96 + m * 4, make_uint4(o[0], o[1], o[2], o[3]));
            }
        __syncwarp();
    };
    auto max_w1 = [&](uint32_t lane) { return __uint_as_float(__reduce_max_sync(~0u, lane < 4 * NCONS ? ldsi(s_red + RED_MAX + lane * 4) : 0)); };
    const bool helps = !wk.lent && wk.index < 8 * LENT * sp.lenders;
    const int help_slot = (wk.rows + 2) % NSLOT;
    const uint32_t s_help = sb + SM_RING + help_slot * SLOT_BYTES + SQ_WG;
    auto reduce = [&](int q, uint32_t lane, bool leader) {
        const int g = lane >> 2, t = lane & 3, ch = 32 * q + 8 * t + 2 * (g & 3) + (g >> 2);
        const uint32_t pick = (g >> 1 & 1) == (t & 1) ? (g & 1 ? 0x3c000000u : 0x00003c00u) : 0;
        const int be = bound_exp(max_w1(lane)), sq_e = square_exp(be);
        const float to_fixed = pow2i(sum_exp(be) - 2 * sq_e);
        unsigned long long* dst = sc->sum(ch);
        named_bar(11, CONS_THREADS);
        const unsigned in_piece = ch - wk.index % 8 * 48;
        float helped = 0.f;
        if (helps && in_piece < 48) {
            uint32_t u[4];
            lds128(u[0], u[1], u[2], u[3], s_help + in_piece * 16);
            helped = ((__uint_as_float(u[0]) + __uint_as_float(u[1])) + (__uint_as_float(u[2]) + __uint_as_float(u[3]))) * pow2i(2 * sq_e);
        }
        float f[2][4] = {};
        int slot = wk.rows % NSLOT;
#pragma unroll 1
        for (int i = 0; i < NCONS; i++) {
            if (i == NCONS - 1) {
                named_bar(13, CONS_THREADS);
                if (leader) {
                    fence_async();
                    bulk_load(sb + SM_W2, sc->w2h, (NCONS - 1) * SQ_WG, sb + BAR_W);
                }
                __syncwarp();
                named_bar(14, NTHREADS);
            }
            const uint32_t src = sb + lane * 16 + q * SQ_ROW + (q < 6 ? SM_SQ + i * SQ_WG : sq_e ? SM_SQ + (NCONS - 1 + i) * SQ_WG : SM_RING + slot * SLOT_BYTES - SQ_WG);
            slot = slot == NSLOT - 1 ? 0 : slot + 1;
#pragma unroll
            for (int r = 0; r < 4; r++) {
                uint32_t u[4];
                ldsm4_t(u, src + r * 512);
#pragma unroll
                for (int k = 0; k < 2; k++)
                    asm volatile("mma.sync.aligned.m16n8k16.row.col.f32.f16.f16.f32 {%0, %1, %2, %3}, {%4, %5, %4, %5}, {%6, %7}, {%0, %1, %2, %3};"
                                 : "+f"(f[k][0]), "+f"(f[k][1]), "+f"(f[k][2]), "+f"(f[k][3]) : "r"(pick), "r"(0), "r"(u[2 * k]), "r"(u[2 * k + 1]));
            }
        }
        const float tot = g < 4 ? f[0][0] + f[1][0] : f[0][1] + f[1][1];
        atomicAdd(dst, __float2ull_rn(fminf((tot + helped) * to_fixed, 0x1p47f)) << 8 | 1);
    };
    const uint32_t s_fac = sb + SM_RING + (wk.rows + 1) % NSLOT * SLOT_BYTES + SQ_WG;
    if (warp_id < 4) {
        const bool prepares = gridDim.x - blockIdx.x <= W2_GROUPS / 2;
        const int q = (gridDim.x - 1 - blockIdx.x) * 2 + (w4 >> 1);
        conv_producer(wk, &tmap, sb, warp_id, [&](bool second) {
            if (!second) {
                if (blockIdx.x == 0) {
#pragma unroll 1
                    for (int e = tid; e < EX; e += 128) *sc->sum(e) = 0;
                    sc->bias[tid] = 0.f;
                    signal(&sc->early);
                }
                if (wk.lent) signal(&sc->early);
            } else if (prepares || helps) {
                spin_until(&sc->early, (ldsi(s_red + RED_LAUNCH) + 1) * 4 * (sp.lenders + 1));
                if (elect_one()) {
                    if (helps) prefetch_l2(reinterpret_cast<const char*>(out) + sp.lent_off[wk.index / 8] + w4 * WARP_BYTES, WARP_BYTES);
                    if (prepares) { prefetch_l2(w2 + 8 * q * CH, 8 * CH * 2); prefetch_l2(beta + 8 * q, 16); }
                }
            }
        });
        const int lane = opaque(tid & 31), g = lane >> 2, t = lane & 3;
        const unsigned epoch = ldsi(s_red + RED_LAUNCH);
        set_lane(lane);
        const int i0 = w4 * 32 + lane;
        float gam[3], rmax[3];
#pragma unroll
        for (int m = 0; m < 3; m++) {
            unsigned short v;
            asm volatile("ld.global.nc.u16 %0, [%1];" : "=h"(v) : "l"(gamma + i0 + 128 * m) : "memory");
            gam[m] = bf_lo(v);
        }
        if (prepares) {
            const int half = w4 & 1;
            uint32_t u[3][2], rmax = 0;
#pragma unroll
            for (int m = 0; m < 3; m++) {
                const uint4 w = ldg128_ordered(w2 + (8 * q + g) * CH + 32 * m + 8 * t);
                rmax = bf_absmax(bf_absmax(rmax, bf_absmax(w.x, w.y)), bf_absmax(w.z, w.w));
                u[m][0] = half ? w.z : w.x;
                u[m][1] = half ? w.w : w.y;
            }
            const float bt = __bfloat162float(beta[8 * q + g]);
            rmax = bf_absmax(rmax, __shfl_xor_sync(~0u, rmax, 1));
            rmax = bf_absmax(rmax, __shfl_xor_sync(~0u, rmax, 2));
            const float mx = fmaxf(fabsf(bf_lo(rmax)), fabsf(bf_hi(rmax))), rs = row_scale(mx);
            if (t == 0 && !half) sc->w2max[8 * q + g] = mx;
#pragma unroll
            for (int m = 0; m < 3; m++) {
                float f[4];
#pragma unroll
                for (int k = 0; k < 2; k++) {
                    const float lo = bf_lo(u[m][k]), hi = bf_hi(u[m][k]);
                    sc->w2h[(4 * m + 2 * half + k) * 1536 + q * 32 + lane] = transpose8x8(pack_h2(lo * rs, hi * rs));
                    f[2 * k] = lo * bt;
                    f[2 * k + 1] = hi * bt;
                }
                const float r0 = (g & 2 ? f[2] : f[0]) + __shfl_xor_sync(~0u, g & 2 ? f[0] : f[2], 8);
                const float r1 = (g & 2 ? f[3] : f[1]) + __shfl_xor_sync(~0u, g & 2 ? f[1] : f[3], 8);
                float r = (g & 1 ? r1 : r0) + __shfl_xor_sync(~0u, g & 1 ? r0 : r1, 4);
                r += __shfl_xor_sync(~0u, r, 16);
                if (g < 4) atomicAdd(&sc->bias[32 * m + 8 * t + 4 * half + g], r);
            }
            asm volatile("fence.proxy.async.global;" ::: "memory");
            signal(&sc->prep);
        }
        const int piece = wk.index;
        if (helps) {
            next_off = sp.lent_off[wk.index / 8];
            load_first();
            uint32_t d[12], gl[12];
            wg_fence();
#pragma unroll
            for (int s = 0; s < 6; s++) wgmma(d, a[s][0], a[s][1], a[s][2], a[s][3], ds.w1[0][s] + piece % 8 * (6 * 1536 / 16), s ? 1 : 0);
            wg_commit();
            wg_wait<0>();
            gelu_to(gl, d);
#pragma unroll
            for (int s = 0; s < 3; s++) sc->lent[(((piece / (8 * LENT) * 4 + w4) * (8 * LENT) + piece % (8 * LENT)) * 3 + s) * 32 + lane] = make_uint4(gl[4 * s], gl[4 * s + 1], gl[4 * s + 2], gl[4 * s + 3]);
            float f[6], r[3];
#pragma unroll
            for (int j = 0; j < 6; j++) {
                const float lo = fmaf(h_lo(gl[2 * j]), h_lo(gl[2 * j]), h_lo(gl[2 * j + 1]) * h_lo(gl[2 * j + 1]));
                const float hi = fmaf(h_hi(gl[2 * j]), h_hi(gl[2 * j]), h_hi(gl[2 * j + 1]) * h_hi(gl[2 * j + 1]));
                f[j] = (g & 1 ? hi : lo) + __shfl_xor_sync(~0u, g & 1 ? lo : hi, 4);
            }
            mbar_wait(sb + BAR_E + help_slot * 32 + 24, (wk.rows - 4) / NSLOT & 1);
#pragma unroll
            for (int j = 0; j < 3; j++) {
                r[j] = (g & 2 ? f[j + 3] : f[j]) + __shfl_xor_sync(~0u, g & 2 ? f[j] : f[j + 3], 8);
                r[j] += __shfl_xor_sync(~0u, r[j], 16);
                sts32(s_help + (8 * j + 12 * (g & 2) + 2 * t + (g & 1)) * 16 + w4 * 4, __float_as_uint(r[j]));
            }
        }
        const bool leader = warp_id == 0 && lane == 0;
        const float w1max = max_w1(lane), from_fixed = pow2i(-sum_exp(bound_exp(w1max)));
        const bool plain = plain_squares(bound_exp(w1max));
        auto load_upper = [&]() {
            bulk_load(sb + SM_W2 + NCONS * SQ_WG, reinterpret_cast<const char*>(sc->w2h) + NCONS * SQ_WG, EX * CH * 2 - NCONS * SQ_WG, sb + BAR_W);
        };
        if (leader) {
            spin_until(&sc->prep, (epoch + 1) * 2 * W2_GROUPS);
            asm volatile("fence.proxy.async.global;" ::: "memory");
            fence_async();
            mbar_expect_tx(sb + BAR_W, EX * CH * 2);
            if (plain) load_upper();
        }
        __syncwarp();
        named_bar(1, 128);
#pragma unroll
        for (int m = 0; m < 3; m++) rmax[m] = __ldcg(&sc->w2max[i0 + 128 * m]);
        float2 bpair = make_float2(0.f, 0.f);
        if (i0 < 96) bpair = __ldcg(reinterpret_cast<const float2*>(&sc->bias[32 * (i0 % 24 >> 3) + 8 * (i0 / 24) + (i0 % 24 & 6)]));
        const float gbound = fmaxf(2.f * KZ * 9.7979590f * 192.f * w1max, 1.f) * 19.5959180f * INV_2KZ;
        const unsigned fixed = __reduce_max_sync(~0u, __float_as_uint(fmaf(gbound, fmaxf(fmaxf(rmax[0], rmax[1]), rmax[2]), fmaxf(fabsf(bpair.x), fabsf(bpair.y)))));
        if (lane == 0) sts32(s_red + 96 + w4 * 4, fixed);
        reduce(4 * (NCONS - 1) + w4, lane, leader);
        PROF(2);
        named_bar(15, CONS_THREADS);
        if (leader) {
            fence_async();
            bulk_load(sb + SM_W2 + (NCONS - 1) * SQ_WG, reinterpret_cast<const char*>(sc->w2h) + (NCONS - 1) * SQ_WG, SQ_WG, sb + BAR_W);
            if (!plain) load_upper();
        }
        stage = sb + SM_RING + (wk.rows + 3 + (wk.lent + 2 * ntiles) % NCONS) % NSLOT * SLOT_BYTES + w4 * REGION_BYTES;
        auto grn = [&]() {
            auto peek = [&](int e) {
                unsigned long long v;
                asm volatile("ld.relaxed.gpu.global.u64 %0, [%1];" : "=l"(v) : "l"(sc->sum(e)) : "memory");
                return v;
            };
            unsigned n = 0;
            while (((unsigned)peek((blockIdx.x * 4 + w4) % (EX / 4) * 4) & 255u) != gridDim.x)
                if (++n > SPIN_LIMIT) __trap();
            unsigned long long sum[3];
            for (;;) {
                bool all = true;
#pragma unroll
                for (int m = 0; m < 3; m++) {
                    sum[m] = peek(i0 + 128 * m);
                    all &= ((unsigned)sum[m] & 255u) == gridDim.x;
                }
                if (__all_sync(~0u, all)) break;
                if (++n > SPIN_LIMIT) __trap();
            }
            PROF(3);
            if (blockIdx.x == 0 && leader) sc->launch = epoch + 1;
            float gx[3], tot = 0.f, vary = 0.f;
#pragma unroll
            for (int m = 0; m < 3; m++) {
                gx[m] = grn_norm(__ull2float_rn(sum[m] >> 8) * from_fixed);
                tot += gx[m];
                vary = fmaxf(vary, fabsf(gam[m]) * gx[m] * rmax[m]);
            }
#pragma unroll
            for (int o = 16; o >= 1; o >>= 1) tot += __shfl_xor_sync(~0u, tot, o);
            const unsigned vwarp = __reduce_max_sync(~0u, __float_as_uint(vary));
            if (lane == 0) { sts32(s_red + 64 + w4 * 4, __float_as_uint(tot)); sts32(s_red + 80 + w4 * 4, vwarp); }
            named_bar(1, 128);
            uint32_t u[4], v[4], w[4];
            lds128(u[0], u[1], u[2], u[3], s_red + 64);
            lds128(v[0], v[1], v[2], v[3], s_red + 80);
            lds128(w[0], w[1], w[2], w[3], s_red + 96);
            tot = (__uint_as_float(u[0]) + __uint_as_float(u[1])) + (__uint_as_float(u[2]) + __uint_as_float(u[3]));
            const float vmax = __uint_as_float(max(max(v[0], v[1]), max(v[2], v[3]))), fmax2 = __uint_as_float(max(max(w[0], w[1]), max(w[2], w[3])));
            const float inv_mean = __fdividef(1.f, tot * (1.f / EX) + 1e-6f);
            const float bound = fmaf(gbound * vmax, inv_mean, 2.f * fmax2);
            const int rho_e = bound > 0.f ? 14 - ilog2f(bound) : 0;
            const float rho = pow2i(rho_e), inv_rho = pow2i(-rho_e);
            inv_rho2 = pack_bf2(inv_rho, inv_rho);
#pragma unroll
            for (int m = 0; m < 3; m++) {
                const float f = __fdividef(fmaf(gam[m], gx[m] * inv_mean, 1.f) * INV_2KZ * rho, row_scale(rmax[m]));
                asm volatile("st.shared.u16 [%0], %1;" ::"r"(s_fac + (i0 + 128 * m) * 2), "h"((unsigned short)pack_h2(f, 0.f)) : "memory");
            }
            if (i0 < 96) sts32(sb + SM_BIASH + i0 * 4, pack_h2(bpair.x * rho, bpair.y * rho));
            if (i0 == 96) sts32(s_red + RED_INV_RHO, inv_rho2);
            named_arrive(12, NTHREADS);
        };
        lds32(next_off, sb + SM_TILES);
        next_off = __shfl_sync(~0u, next_off, 0);
        load_first();
        grn();
        if (wk.lent) spin_until(&sc->lent_out, (epoch + 1) * 8 * LENT * sp.lenders);
    } else {
        const int rank = (wgi + wk.lent + 2 * ntiles) % NCONS;
        const uint32_t a_addr = opaque(sb + SM_RING + w4 * REGION_BYTES + ((tid >> 3) & 1) * A_SBO + ((tid >> 4) & 1) * A_LBO + (tid & 7) * 16);
        const uint32_t bar_a = sb + BAR_A + w4 * 8, bar_e = sb + BAR_E + w4 * 8;
        const uint32_t sq = opaque(sb + SM_SQ + rank * SQ_WG + (tid & 127) * 16);
        const uint32_t sq_warp = sb + SM_SQ + rank * SQ_WG + w4 * 512;
        if (wgi == NCONS - 1) named_arrive(4, 256);
        const int pass_to = 4 + (wgi == NCONS - 1 ? 0 : wgi + 1);
        const uint32_t own_bar = opaque_uniform(4 + wgi), next_bar = opaque_uniform(pass_to);
        const uint32_t step = opaque_uniform(wk.dir * (NCONS * IMG_W * CH * 2));
        uint32_t turn, turn_end, so, so_sum, bo, bo_sum, off;
        auto set_run = [&](int j, int stop, int row) {
            const int slot = row % NSLOT, both = 2 * (row % 3) + 3;
            turn = opaque_uniform(row / 3);
            turn_end = opaque_uniform(row / 3 + max(stop - j + NCONS - 1, 0) / NCONS);
            so = opaque_uniform(slot * SLOT_BYTES);
            so_sum = opaque_uniform(both * SLOT_BYTES);
            bo = opaque_uniform(bar_a + slot * 32);
            bo_sum = opaque_uniform(2 * bar_a + both * 32);
            off = opaque_uniform(tile_offset(wk.tile(j)) + w4 * WARP_BYTES - sq_warp);
        };
        set_run(wk.lent + wgi, min(wk.nA, ntiles - NCONS), wk.lent + wgi + 2);
        int jt = wgi < wk.lent ? wgi : wk.lent + wgi;
        Cursor cur = {2, 0};
        cur.advance(jt + (jt >= wk.nA ? 2 : 0));
        {
            const int ct = tid - 128, lane = tid & 31;
            const unsigned epoch = *reinterpret_cast<volatile unsigned*>(&sc->launch);
            const int r = lane & 7, mi = lane >> 3;
            const uint32_t src = sb + SM_W2 + (cw >> 1) * (64 * CH * 2) + r * 128 + ((((cw & 1) * 4 + mi) ^ r) * 16);
            const uint32_t dst = sb + SM_W1 + (4 * cw + mi) * 1536 + r * 16;
            const int code = row_code(wk, PREFETCH_ROWS - 1 + wgi);
            named_bar(0, NTHREADS);
            auto request = [&](int pos) {
                if ((K_REQ >> 4 * wgi & 15) == pos && elect_one())
                    issue_region(&tmap, sb + SM_RING + (PREFETCH_ROWS - 1 + wgi) * SLOT_BYTES + w4 * REGION_BYTES, sb + BAR_X + (cw + 8) * 8, w4, code);
                __syncwarp();
            };
            request(0);
            mbar_wait(sb + BAR_W + (cw >> 1) * 8, 0);
            request(1);
            uint32_t wmax[2] = {}, wsum[4] = {};
#pragma unroll K_UNR
            for (int c = 0; c < 12; c++) {
                uint32_t u[4];
                ldsm4_t(u, src + c * 1024);
#pragma unroll
                for (int q = 0; q < 4; q++) {
                    wmax[q & 1] = bf_absmax(wmax[q & 1], u[q]);
                    wsum[q] = bf_fma(u[q], 0x3f803f80u, wsum[q]);
                    u[q] = pack_h2(K_IM ? __uint_as_float(u[q] * (65536 + zero)) : bf_lo(u[q]), bf_hi(u[q]));
                }
                stsm4(dst + c * 128, u[0], u[1], u[2], u[3]);
            }
            request(2);
            const float w1max = warp_absmax(bf_absmax(wmax[0], wmax[1]));
            if (lane == 0) sts32(s_red + RED_MAX + cw * 4, __float_as_uint(w1max));
            bool center = false;
#pragma unroll
            for (int q = 0; q < 4; q++) {
#pragma unroll
                for (int o = 1; o <= 2; o <<= 1) wsum[q] = bf_fma(__shfl_xor_sync(~0u, wsum[q], o), 0x3f803f80u, wsum[q]);
                center |= fabsf(bf_lo(wsum[q]) + bf_hi(wsum[q])) > (0.15f * CH) * w1max;
            }
            if (__builtin_expect(__any_sync(~0u, center), 0)) {
                float mean[4] = {};
#pragma unroll 1
                for (int pass = 0; pass < 2; pass++) {
                    float sum[4] = {};
#pragma unroll 1
                    for (int c = 0; c < 12; c++) {
                        uint32_t u[4];
                        ldsm4_t(u, src + c * 1024);
#pragma unroll
                        for (int q = 0; q < 4; q++) {
                            sum[q] += bf_lo(u[q]) + bf_hi(u[q]);
                            u[q] = pack_h2(bf_lo(u[q]) - mean[q], bf_hi(u[q]) - mean[q]);
                        }
                        stsm4(dst + c * 128, u[0], u[1], u[2], u[3]);
                    }
#pragma unroll
                    for (int q = 0; q < 4; q++) {
                        sum[q] += __shfl_xor_sync(~0u, sum[q], 1);
                        sum[q] += __shfl_xor_sync(~0u, sum[q], 2);
                        mean[q] = sum[q] * (1.f / CH);
                    }
                }
            }
            if (cw < 2 * NCONS) {
#pragma unroll
                for (int c = 0; c < 12; c++) sts128(src + c * 1024, 0, 0, 0, 0);
            }
            if (ct < 32) sts32(sb + SM_ONES + ct * 4, 0x3f803f80u);
            if (ct == 0) sts32(s_red + RED_LAUNCH, epoch);
            fence_async();
            named_bar(2, CONS_THREADS);
            request(3);
        }
        PROF(1);
        uint32_t k1[24], k2[24], k3[24];
        constexpr int SQC = 3 * SQ_ROW;
        auto store_at = [&](const uint32_t (&a)[6][4], uint32_t off) {
            char* ap = reinterpret_cast<char*>(out) + (off + sq);
#pragma unroll
            for (int s = 0; s < 6; s++) stg128(ap + s * 512, a[s]);
        };
        const bool plain = __all_sync(~0u, plain_squares(bound_exp(max_w1(sq >> 4 & 31))));
        if (!plain) {
#pragma unroll 1
            for (int q = 0; q < 6; q++) sts128(sq + NCONS * SQ_WG + q * SQ_ROW, 0, 0, 0, 0);
        }
        for (;;) {
            if (plain && jt >= wk.lent) {
                uint32_t hs2[12] = {}, hs3[12] = {};
                int second = wk.nB;
#pragma unroll 1
                for (;;) {
#pragma unroll 1
                while (turn != turn_end) {
                    uint32_t a[6][4], d0[24], d1[24], unused[24];
#define AT(pos) \
    if (K_WAIT == pos) named_bar(own_bar, 256); \
    if (K_PASS == pos) named_arrive(next_bar, 256); \
    if (K_STG == pos) store_at(a, off); \
    if (K_REL == pos) { if (elect_one()) mbar_arrive(bo + (BAR_E - BAR_A)); }
                    AT(20)
                    mbar_wait(bo, turn >> 1 & 1);
                    load_tile(a, a_addr + so);
                    AT(21)
                    const uint2 st = ln_stats(a, ds.ones);
                    AT(0)
                    ln_apply(a, st);
                    AT(1)
                    wg_fence();
                    gemm1_chunk<0>(d0, a, ds, 0);
                    wg_commit();
                    gemm1_chunk<96>(d1, a, ds, 0);
                    wg_commit();
                    AT(2)
                    wg_wait<1>();
                    AT(3)
                    gelu_sq<false, 0, 1>(d0, unused, sq, 0);
                    AT(4)
                    gelu_sq<false, 1, 2>(d0, unused, sq, 0);
                    AT(5)
                    gelu_sq<false, 2, 3>(d0, unused, sq, 0);
                    AT(6)
                    wg_fence();
                    gemm1_chunk<192>(d0, a, ds, zero);
                    wg_commit();
                    AT(7)
                    wg_wait<1>();
                    gelu_sq<false, 0, 1>(d1, unused, sq + SQC, 0);
                    AT(8)
                    gelu_sq<false, 1, 3>(d1, unused, sq + SQC, 0);
                    AT(9)
                    wg_fence();
                    gemm1_chunk<288>(d1, a, ds, zero);
                    wg_commit();
                    AT(10)
                    wg_wait<1>();
                    gelu_sq_reg(d0, hs2);
                    if (K_ANCH < 3) anchor(sq, hs2[4 * (K_ANCH % 3)], hs2[4 * (K_ANCH % 3) + 1], hs2[4 * (K_ANCH % 3) + 2], hs2[4 * (K_ANCH % 3) + 3]);
                    wg_wait<0>();
                    AT(11)
                    gelu_sq_reg(d1, hs3);
#undef AT
                    so = so_sum - so;
                    bo = bo_sum - bo;
                    off += step;
                    turn++;
                }
                if (!second) break;
                const int j = ntiles - second + (rank + second) % NCONS;
                second = 0;
                set_run(j, ntiles - NCONS, j + 4);
                }
                jt = ntiles - NCONS + rank;
                cur.slot = (bo - bar_a) >> 5;
                cur.par = turn >> 1 & 1;
                const uint32_t sq2 = sq - (SM_SQ + rank * SQ_WG) + SM_RING + (so_sum - so);
#pragma unroll
                for (int k = 0; k < 3; k++) {
                    sts128(sq2 + k * SQ_ROW, hs2[4 * k], hs2[4 * k + 1], hs2[4 * k + 2], hs2[4 * k + 3]);
                    sts128(sq2 + SQC + k * SQ_ROW, hs3[4 * k], hs3[4 * k + 1], hs3[4 * k + 2], hs3[4 * k + 3]);
                }
            }
            const bool last = jt + NCONS >= ntiles;
            if (last) {
                tile_off = tile_offset(wk.tile(jt));
                lds32(next_off, sb + SM_TILES + wg * 4);
                next_off = __shfl_sync(~0u, next_off, 0);
                if (elect_one()) {
                    prefetch_l2(reinterpret_cast<const char*>(x) + tile_off + w4 * WARP_BYTES, WARP_BYTES);
                    if (wg % ORDER_P >= ORDER_P - ORDER_Q) prefetch_l2(reinterpret_cast<const char*>(out) + next_off + w4 * WARP_BYTES, WARP_BYTES);
                }
            }
            uint32_t a[6][4], d0[24], d1[24], d3[24], k0[24];
#define AT(pos) \
    if (K_WAIT == pos && jt >= wk.lent) named_bar(4 + wgi, 256); \
    if ((K_LTOK ? K_LTOK : K_PASS) == pos && jt >= wk.lent && jt + 1 < ntiles) named_arrive(pass_to, 256);
            AT(20)
            mbar_wait(bar_a + cur.slot * 32, cur.par);
            load_tile(a, a_addr + cur.slot * SLOT_BYTES);
            AT(21)
            const uint2 st = ln_stats(a, ds.ones);
            AT(0)
            ln_apply(a, st);
            AT(1)
            if (!last) {
                store_at(a, tile_offset(wk.tile(jt)) + w4 * WARP_BYTES - sq_warp);
                __syncwarp();
                if (elect_one()) mbar_arrive(bar_e + cur.slot * 32);
                if (jt < wk.lent) {
                    jt += LENT;
                    cur.advance(LENT);
                    continue;
                }
            }
            wg_fence();
            gemm1_chunk<0>(d0, a, ds, 0);
            wg_commit();
            gemm1_chunk<96>(d1, a, ds, 0);
            wg_commit();
            const int sq_e = square_exp(bound_exp(max_w1(sq >> 4 & 31)));
            const uint32_t scale2 = pack_h2(pow2i(sq_e), pow2i(sq_e));
            AT(2)
            wg_wait<1>();
            AT(3)
            gelu_sq<true, 0, 1>(d0, k0, sq, scale2);
            AT(4)
            gelu_sq<true, 1, 2>(d0, k0, sq, scale2);
            AT(5)
            gelu_sq<true, 2, 3>(d0, k0, sq, scale2);
            AT(6)
            if (last) {
#pragma unroll
                for (int q = 0; q < 6; q++) sts128(sb + SM_RING + cur.slot * SLOT_BYTES + w4 * REGION_BYTES - sq_warp + sq + q * 512, k0[4 * q], k0[4 * q + 1], k0[4 * q + 2], k0[4 * q + 3]);
            }
            wg_fence();
            gemm1_chunk<192>(d0, a, ds, zero);
            wg_commit();
            AT(7)
            wg_wait<1>();
            gelu_sq<true, 0, 1>(d1, k1, sq + SQC, scale2);
            AT(8)
            gelu_sq<true, 1, 3>(d1, k1, sq + SQC, scale2);
            AT(9)
#undef AT
            wg_fence();
            gemm1_chunk<288>(d3, a, ds, 0);
            wg_commit();
            wg_wait<1>();
            const uint32_t sq2 = sq + (plain ? SM_RING + (cur.slot + 3) % NSLOT * SLOT_BYTES - (SM_SQ + rank * SQ_WG) : NCONS * SQ_WG);
            gelu_sq<true>(d0, k2, sq2, scale2);
            wg_wait<0>();
            gelu_sq<true>(d3, k3, sq2 + SQC, scale2);
            if (last) break;
            cur.advance(NCONS + ((jt < wk.nA && jt + NCONS >= wk.nA) ? 2 : 0));
            jt += NCONS;
        }
        {
            if (rank == NCONS - 1) {
                named_arrive(14, NTHREADS);
            } else {
                reduce(4 * rank + w4, (sq >> 4) & 31, false);
                named_arrive(15, CONS_THREADS);
                PROF(2);
                if (helps && rank == 0 && w4 == 0) signal(&sc->lent_out);
            }
        }
        {
            set_lane((sq >> 4) & 31);
            const uint32_t row = sb + SM_W2 + cw * 512 + lane16;
            uint32_t u[W2_EARLY][4], f2[4];
            mbar_wait(sb + BAR_W, 1);
#pragma unroll
            for (int nb = 0; nb < W2_EARLY; nb++) lds128(u[nb][0], u[nb][1], u[nb][2], u[nb][3], row + nb * 6144);
            named_bar(12, NTHREADS);
            PROF(3);
            stage = sb + SM_RING + (cur.slot + 3) % NSLOT * SLOT_BYTES + w4 * WARP_BYTES;
            if (K_XPOS == 0) stage_x();
            lds128(f2[0], f2[1], f2[2], f2[3], s_fac + cw * 64 + (lane16 >> 7) * 16);
            lds32(inv_rho2, s_red + RED_INV_RHO);
#pragma unroll
            for (int nb = 0; nb < 12; nb++) {
                uint32_t v[4];
                if (nb < W2_EARLY) { v[0] = u[nb % W2_EARLY][0]; v[1] = u[nb % W2_EARLY][1]; v[2] = u[nb % W2_EARLY][2]; v[3] = u[nb % W2_EARLY][3]; }
                else lds128(v[0], v[1], v[2], v[3], row + nb * 6144);
                sts128(row + nb * 6144, h_round8(h_mul(v[0], f2[0])), h_round8(h_mul(v[1], f2[1])), h_round8(h_mul(v[2], f2[2])), h_round8(h_mul(v[3], f2[3])));
            }
            fence_async();
            if (K_XPOS == 1) stage_x();
            named_bar(3, NTHREADS);
        }
        PROF(4);
        {
            load_bias(acc);
            if (wgi > 0) named_bar(8 + wgi, 256);
            pin(k1); pin(k2); pin(k3);
            wg_fence();
            gemm2_chunk<288>(acc, k3, ds);
            wg_commit();
            gemm2_chunk<(K_SWAP ? 192 : 96)>(acc, K_SWAP ? k2 : k1, ds);
            if (K_FINE) wg_commit();
            gemm2_chunk<(K_SWAP ? 96 : 192)>(acc, K_SWAP ? k1 : k2, ds);
            wg_commit();
            if (!K_LATE && wgi + 1 < NCONS) named_arrive(9 + wgi, 256);
            wg_wait<1 + K_FINE>();
            uint32_t k0[24];
#pragma unroll
            for (int q = 0; q < 6; q++)
                lds128(k0[4 * q], k0[4 * q + 1], k0[4 * q + 2], k0[4 * q + 3], sb + SM_RING + cur.slot * SLOT_BYTES + w4 * REGION_BYTES + lane16 + q * 512);
            pin(k0);
            wg_fence();
            gemm2_chunk<0>(acc, k0, ds);
            wg_commit();
            if (K_LATE && wgi + 1 < NCONS) named_arrive(9 + wgi, 256);
            if (wgi == 0) named_arrive(8, 256);
            wg_wait<1 + K_FINE>();
            load_first();
            if (lane16 == 0) mbar_arrive(sb + BAR_PIN);
            mbar_wait(bar_r, rpar);
            wg_wait<0>();
            first = wg - 4;
        }
    }
    {
        const int nrest = ntiles - NCONS;
        auto lent = [&](uint32_t entry) { return &sc->lent[((wk.index * 4 + w4) * LENT + (entry & 3) - 1) * (8 * 96)]; };
        for (int jt = first; jt < nrest; jt += 4) {
            if (jt >= 0) {
            tile_off = next_off;
            lds32(next_off, sb + SM_TILES + (jt + 4) * 4);
            if (tile_off & 3) {
                uint32_t gl[2][24];
                const uint4* src = lent(tile_off) + (lane16 >> 4);
                auto fetch = [&](uint32_t (&v)[24], int c) {
#pragma unroll
                    for (int s = 0; s < 6; s++) ldg128(reinterpret_cast<uint32_t (&)[4]>(v[4 * s]), src + (6 * c + s) * 32);
                };
                tile_off &= ~3u;
                next_off = __shfl_sync(~0u, next_off, 0);
                stage_x();
                if (elect_one()) prefetch_l2(reinterpret_cast<const char*>(out) + next_off + w4 * WARP_BYTES, WARP_BYTES);
                load_bias(acc);
#pragma unroll
                for (int half = 0; half < 2; half++) {
                    fetch(gl[0], 2 * half);
                    fetch(gl[1], 2 * half + 1);
                    if (!half) {
                        named_bar(4 + wg, 256);
                        named_arrive(4 + ((wg + 1) & 3), 256);
                    }
                    pin(gl[0]); pin(gl[1]);
                    wg_fence();
                    if (half) gemm2_chunk<192>(acc, gl[0], ds); else gemm2_chunk<0>(acc, gl[0], ds);
                    if (half) gemm2_chunk<288>(acc, gl[1], ds); else gemm2_chunk<96>(acc, gl[1], ds);
                    wg_commit();
                    wg_wait<0>();
                }
                load_first();
                mbar_wait(bar_r, rpar);
            } else {
            uint32_t d0[12], d1[12], g0[12], g1[12];
            if (jt >= S2_FIRST && jt < nrest - K_TAIL) named_bar(4 + wg, 256);
            wg_fence();
            gemm1_chunk<0>(d0, a, ds, 0);
            wg_commit();
            gemm1_chunk<48>(d1, a, ds, 0);
            wg_commit();
            load_bias(acc);
            next_off = __shfl_sync(~0u, next_off, 0);
            const bool more = jt + 4 < nrest && !(next_off & 3);
            wg_wait<1>();
#define CNX_PASS if (jt + 1 >= S2_FIRST && jt + 1 < nrest - K_TAIL) named_arrive(4 + ((wg + 1) & 3), 256);
#define CNX_STEP(C, D, G)                                              \
    gelu_to(G, D);                                                     \
    if (C == 0 && jt == 0) {                                           \
        named_bar(3, NTHREADS);                                        \
        load_bias(acc);                                                \
    }                                                                  \
    wg_fence();                                                        \
    if (C < 6) gemm1_chunk<48 * (C < 6 ? C + 2 : 0)>(D, a, ds, zero); \
    gemm2_chunk<48 * C>(acc, G, ds);                                  \
    wg_commit();                                                       \
    if (C == S2_PASS) { CNX_PASS }                                     \
    wg_wait<(C < 7 ? 1 : 0)>();
            CNX_STEP(0, d0, g0)
            CNX_STEP(1, d1, g1)
            if (jt == 0) named_bar(8, 256);
            stage_x();
            if (elect_one()) {
                if (more) prefetch_l2(reinterpret_cast<const char*>(out) + next_off + w4 * WARP_BYTES, WARP_BYTES);
                else if (next_off & 3) prefetch_l2(lent(next_off), 8 * 96 * 16);
            }
            CNX_STEP(2, d0, g0)
            CNX_STEP(3, d1, g1)
            CNX_STEP(4, d0, g0)
            CNX_STEP(5, d1, g1)
            CNX_STEP(6, d0, g0)
            load_frags(more);
            if (lane16 == 0) mbar_arrive(sb + BAR_PIN);
            mbar_wait(bar_r, rpar);
            CNX_STEP(7, d1, g1)
#undef CNX_STEP
            }
            }
            epilogue(acc);
        }
    }
    PROF(5);
}

}

typedef CUresult (*EncodeTiledFn)(CUtensorMap*, CUtensorMapDataType, cuuint32_t, void*, const cuuint64_t*, const cuuint64_t*,
                                  const cuuint32_t*, const cuuint32_t*, CUtensorMapInterleave, CUtensorMapSwizzle,
                                  CUtensorMapL2promotion, CUtensorMapFloatOOBfill);

extern "C" void kernel_launch(void* const* d_in, const int* in_sizes, int n_in, void* d_out, int out_size) {
    using namespace cnx;
    static EncodeTiledFn encode = nullptr;
    static int num_sms = 0;
    static Scratch* scratch = nullptr;
    if (!encode) {
        void* fn = nullptr;
        cudaDriverEntryPointQueryResult qr;
        cudaGetDriverEntryPoint("cuTensorMapEncodeTiled", &fn, cudaEnableDefault, &qr);
        encode = (EncodeTiledFn)fn;
        cudaGetSymbolAddress((void**)&scratch, g_scratch);
        int dev = 0;
        cudaGetDevice(&dev);
        cudaDeviceGetAttribute(&num_sms, cudaDevAttrMultiProcessorCount, dev);
        if (num_sms > MAX_CTAS) num_sms = MAX_CTAS;
        cudaFuncSetAttribute(block_kernel, cudaFuncAttributeMaxDynamicSharedMemorySize, SM_TOTAL);
    }
    CUtensorMap tm;
    cuuint64_t dims[3] = {(cuuint64_t)CH, (cuuint64_t)IMG_W, (cuuint64_t)IMG_H};
    cuuint64_t strides[2] = {(cuuint64_t)CH * 2, (cuuint64_t)CH * 2 * IMG_W};
    cuuint32_t box[3] = {(cuuint32_t)CH, (cuuint32_t)REGION_PX, 1};
    cuuint32_t estr[3] = {1, 1, 1};
    encode(&tm, CU_TENSOR_MAP_DATA_TYPE_BFLOAT16, 3, d_in[0], dims, strides, box, estr, CU_TENSOR_MAP_INTERLEAVE_NONE,
           CU_TENSOR_MAP_SWIZZLE_NONE, CU_TENSOR_MAP_L2_PROMOTION_L2_128B, CU_TENSOR_MAP_FLOAT_OOB_FILL_NONE);
    Params pm = {};
    Descs& ds = pm.ds;
    for (int c = 0; c < 8; c++)
        for (int k = 0; k < 6; k++) ds.w1[c][k] = make_desc(SB + SM_W1 + c * 6 * 1536 + k * 256, 128, 1536);
    for (int k = 0; k < 24; k++) ds.w2[k] = make_desc(SB + SM_W2 + k * 256, 128, 6144);
    ds.ones = make_desc(SB + SM_ONES, 0, 0);
    CUtensorMap tw;
    cuuint64_t wdims[2] = {(cuuint64_t)EX, (cuuint64_t)CH};
    cuuint64_t wstrides[1] = {(cuuint64_t)EX * 2};
    cuuint32_t wbox[2] = {64, (cuuint32_t)CH};
    encode(&tw, CU_TENSOR_MAP_DATA_TYPE_BFLOAT16, 2, d_in[2], wdims, wstrides, wbox, estr, CU_TENSOR_MAP_INTERLEAVE_NONE,
           CU_TENSOR_MAP_SWIZZLE_128B, CU_TENSOR_MAP_L2_PROMOTION_L2_128B, CU_TENSOR_MAP_FLOAT_OOB_FILL_NONE);
    Split& sp = pm.sp;
    sp = {NTILES / num_sms, NTILES % num_sms, 1, 1 << 16, 0, {}};
    if (sp.per_cta + 9 > MAX_ROWS) return;
    if (sp.extra && sp.extra * (8 * LENT + 1) <= num_sms && sp.per_cta >= 5 * LENT + 7) {
        sp.period = num_sms / sp.extra;
        sp.inv_period = 65535 / sp.period + 1;
        sp.lenders = sp.extra;
        for (int l = 0; l < sp.extra; l++) {
            const Work w = get_work((l + 1) * sp.period - sp.period / 2 - 1, sp);
            for (int e = 0; e < LENT; e++) sp.lent_off[l * LENT + e] = tile_offset(w.tile(e));
            if (w.nA < 2 * LENT) sp.lenders = 0;
        }
    }
    pm.x = (const __nv_bfloat16*)d_in[0];
    pm.dw = (const __nv_bfloat16*)d_in[1];
    pm.w2 = (const __nv_bfloat16*)d_in[3];
    pm.gamma = (const __nv_bfloat16*)d_in[4];
    pm.beta = (const __nv_bfloat16*)d_in[5];
    pm.out = (__nv_bfloat16*)d_out;
    pm.sc = scratch;
    block_kernel<<<num_sms, NTHREADS, SM_TOTAL>>>(tm, tw, pm);
}
```

```cpp
#include <cuda_runtime.h>
#include <cuda_bf16.h>
#include <cuda_fp16.h>
#include <cuda.h>
#include <stdint.h>

namespace cnx {

constexpr int IMG_H = 512, IMG_W = 512, CH = 96, EX = 384;
constexpr int TILE_W = 64;
constexpr int NTILES = (IMG_W / TILE_W) * IMG_H;
constexpr int NSLOT = 6;
constexpr int REGION_PX = 18;
constexpr int REGION_BYTES = REGION_PX * CH * 2;
constexpr int SLOT_BYTES = 4 * REGION_BYTES;
constexpr int A_LBO = 144, A_SBO = 12 * A_LBO;
constexpr int PREFETCH_ROWS = 3;
constexpr int NCONS = 3;
constexpr int CONS_THREADS = 128 * NCONS;
constexpr int NTHREADS = 128 + CONS_THREADS;
constexpr int MAX_ROWS = 52;
constexpr int TILE_BYTES = TILE_W * CH * 2, WARP_BYTES = TILE_BYTES / 4;
constexpr int S1_PASS = 1, S2_PASS = 1;
#define K_PASS 4
#define K_WAIT 20
#define K_STG 5
#define K_REL 6
#define K_ANCH 2
#define K_CVT 0
#define K_XPOS 3
#define K_CHAIN 3
#define K_OP 0
#define K_QS 0
#define K_GS 0
#define K_QR 0
#define K_GR 0
#define K_PD 0
#define K_PQ 0
#define K_PS 0
#define K_ROT 0
#define K_LTOK 0
#define K_REQ 0x310
#define K_INIT 0
#define K_IM 1
#define K_UNRV 6
constexpr int K_UNR = K_UNRV;
#define K_CUT 1
#define K_BPOS 2
#define K_BHALF 0
#define K_B0 1
#define K_P2 5
#define K_LATE 1
#define K_FINE 1
#define K_SWAP 0
#define K_TAIL 0
#define W2_EARLY 9
#define S2_FIRST 1
#define ORDER_P 3
#define ORDER_Q 1
static_assert(MAX_ROWS <= 128, "one table entry per producer thread");
static_assert(2 * A_SBO == REGION_BYTES && REGION_BYTES % 128 == 0, "region layout");

constexpr uint32_t SB = 1024;
constexpr int SM_W1 = 0;
constexpr int SM_W2 = SM_W1 + CH * EX * 2;
constexpr int SM_RING = SM_W2 + CH * EX * 2;
constexpr int SM_BIASH = SM_RING + NSLOT * SLOT_BYTES;
constexpr int SM_RED = SM_BIASH + 384;
constexpr int RED_MAX = 0, RED_LAUNCH = 48, RED_INV_RHO = 52;
constexpr int SM_TILES = SM_RED + 256;
constexpr int SM_ONES = SM_TILES + MAX_ROWS * 4;
constexpr int SM_BAR = SM_ONES + 128;
constexpr int BAR_X = SM_BAR;
constexpr int BAR_A = BAR_X + NSLOT * 4 * 8;
constexpr int BAR_E = BAR_A + NSLOT * 4 * 8;
constexpr int BAR_PIN = BAR_E + NSLOT * 4 * 8;
constexpr int BAR_W = BAR_PIN + 8;
constexpr int BAR_F = BAR_W + 6 * 8;
constexpr int BAR_R = BAR_F + 8;
constexpr int SM_TOTAL = BAR_R + 16 * 8;
constexpr int SM_FILTER = SM_RING + (NSLOT - 1) * SLOT_BYTES + 9 * 128;
constexpr int SM_SQ = SM_W2;
constexpr int SQ_ROW = 128 * 16, SQ_WG = 6 * SQ_ROW;
static_assert(SM_ONES % 16 == 0 && SM_TOTAL <= 232448, "shared memory budget");

constexpr float KZ = 0.3292034911525734f;
constexpr uint32_t GELU_C2 = 0x40d940d9u;
constexpr float INV_2KZ = 0.5f / KZ;
constexpr unsigned SPIN_LIMIT = 1u << 19;

constexpr int MAX_CTAS = 255;
constexpr int W2_GROUPS = EX / 8;
#define K_LENT 3
constexpr int LENT = K_LENT, MAX_LENDERS = MAX_CTAS / (8 * LENT + 1);
struct Scratch {
    uint32_t w2h[EX * CH / 2];
    float w2max[EX];
    float bias[CH + 32];
    unsigned long long sums[EX / 4][32];
    __device__ __forceinline__ unsigned long long* sum(int e) { return &sums[e >> 2][e & 3]; }
    uint4 lent[MAX_LENDERS * LENT * 8 * 4 * 3 * 32];
    unsigned launch, pad0[31], early, pad1[31], prep, pad2[31], lent_out, pad3[31];
};
__device__ __align__(128) Scratch g_scratch;

#define PROF(k)

__device__ __forceinline__ uint32_t smem_u32(const void* p) { return (uint32_t)__cvta_generic_to_shared(p); }
__device__ __forceinline__ void mbar_init(uint32_t bar, uint32_t cnt) {
    asm volatile("mbarrier.init.shared::cta.b64 [%0], %1;" ::"r"(bar), "r"(cnt) : "memory");
}
__device__ __forceinline__ void mbar_arrive(uint32_t bar) {
    asm volatile("mbarrier.arrive.shared::cta.b64 _, [%0];" ::"r"(bar) : "memory");
}
__device__ __forceinline__ void mbar_expect_tx(uint32_t bar, uint32_t bytes) {
    asm volatile("mbarrier.arrive.expect_tx.shared::cta.b64 _, [%0], %1;" ::"r"(bar), "r"(bytes) : "memory");
}
__device__ __forceinline__ bool mbar_try(uint32_t bar, uint32_t par) {
    uint32_t ok;
    asm volatile("{\n.reg .pred p;\nmbarrier.try_wait.parity.shared::cta.b64 p, [%1], %2;\nselp.u32 %0, 1, 0, p;\n}\n"
                 : "=r"(ok) : "r"(bar), "r"(par) : "memory");
    return ok != 0;
}
__device__ __forceinline__ void mbar_wait(uint32_t bar, uint32_t par) {
    unsigned n = 0;
    while (!mbar_try(bar, par)) {
        if (++n > SPIN_LIMIT) __trap();
    }
}
__device__ __forceinline__ bool mbar_test(uint32_t bar, uint32_t par) {
    uint32_t ok;
    asm volatile("{\n.reg .pred p;\nmbarrier.test_wait.parity.shared::cta.b64 p, [%1], %2;\nselp.u32 %0, 1, 0, p;\n}\n"
                 : "=r"(ok) : "r"(bar), "r"(par) : "memory");
    return ok != 0;
}
__device__ __forceinline__ bool elect_one() {
    uint32_t ok;
    asm volatile("{\n.reg .pred p;\nelect.sync _|p, 0xffffffff;\nselp.u32 %0, 1, 0, p;\n}\n" : "=r"(ok));
    return ok != 0;
}
__device__ __forceinline__ uint32_t opaque(uint32_t v) { return __shfl_sync(~0u, v, threadIdx.x & 31); }
__device__ __forceinline__ float opaque(float v) { return __uint_as_float(opaque(__float_as_uint(v))); }
__device__ __forceinline__ uint32_t opaque_uniform(uint32_t v) { return __shfl_sync(~0u, v, 0); }
__device__ __forceinline__ void named_bar(int id, int n) { asm volatile("bar.sync %0, %1;" ::"r"(id), "r"(n) : "memory"); }
__device__ __forceinline__ void named_arrive(int id, int n) { asm volatile("bar.arrive %0, %1;" ::"r"(id), "r"(n) : "memory"); }
__device__ __forceinline__ void fence_async() { asm volatile("fence.proxy.async.shared::cta;" ::: "memory"); }
__device__ __forceinline__ uint64_t evict_first() {
    uint64_t p;
    asm("createpolicy.fractional.L2::evict_first.b64 %0, 1.0;" : "=l"(p));
    return p;
}
__device__ __forceinline__ void tma_row(uint32_t dst, const CUtensorMap* tm, uint32_t bar, int x, int y) {
    asm volatile("cp.async.bulk.tensor.3d.shared::cluster.global.mbarrier::complete_tx::bytes.L2::cache_hint [%0], [%1, {%3, %4, %5}], [%2], %6;"
                 ::"r"(dst), "l"(tm), "r"(bar), "r"(0), "r"(x), "r"(y), "l"(evict_first()) : "memory");
}
__device__ __forceinline__ void bulk_load_stream(uint32_t dst, const void* src, uint32_t bytes, uint32_t bar) {
    asm volatile("cp.async.bulk.shared::cluster.global.mbarrier::complete_tx::bytes.L2::cache_hint [%0], [%1], %2, [%3], %4;"
                 ::"r"(dst), "l"(src), "r"(bytes), "r"(bar), "l"(evict_first()) : "memory");
}
__device__ __forceinline__ void prefetch_l2(const void* src, uint32_t bytes) {
    asm volatile("cp.async.bulk.prefetch.L2.global [%0], %1;" ::"l"(src), "r"(bytes) : "memory");
}
__device__ __forceinline__ void tma_2d(uint32_t dst, const CUtensorMap* tm, uint32_t bar, int x, int y) {
    asm volatile("cp.async.bulk.tensor.2d.shared::cluster.global.mbarrier::complete_tx::bytes [%0], [%1, {%3, %4}], [%2];"
                 ::"r"(dst), "l"(tm), "r"(bar), "r"(x), "r"(y) : "memory");
}
__device__ __forceinline__ void bulk_load(uint32_t dst, const void* src, uint32_t bytes, uint32_t bar) {
    asm volatile("cp.async.bulk.shared::cluster.global.mbarrier::complete_tx::bytes [%0], [%1], %2, [%3];"
                 ::"r"(dst), "l"(src), "r"(bytes), "r"(bar) : "memory");
}
__device__ __forceinline__ void wg_fence() { asm volatile("wgmma.fence.sync.aligned;" ::: "memory"); }
__device__ __forceinline__ void wg_commit() { asm volatile("wgmma.commit_group.sync.aligned;" ::: "memory"); }
template <int N> __device__ __forceinline__ void wg_wait() { asm volatile("wgmma.wait_group.sync.aligned %0;" ::"n"(N) : "memory"); }
template <int N> __device__ __forceinline__ void pin(uint32_t (&d)[N]) {
#pragma unroll
    for (int q = 0; q < N; q++) asm volatile("" : "+r"(d[q])::"memory");
}
__device__ __forceinline__ void stg128(void* p, const uint32_t (&v)[4]) {
    asm volatile("st.global.v4.u32 [%0], {%1, %2, %3, %4};" ::"l"(p), "r"(v[0]), "r"(v[1]), "r"(v[2]), "r"(v[3]) : "memory");
}
__device__ __forceinline__ void ldg128(uint32_t (&v)[4], const void* p) {
    asm volatile("ld.global.L1::no_allocate.v4.u32 {%0, %1, %2, %3}, [%4];" : "=r"(v[0]), "=r"(v[1]), "=r"(v[2]), "=r"(v[3]) : "l"(p) : "memory");
}
__device__ __forceinline__ void ldg128_if(bool on, uint32_t (&v)[4], const void* p) {
    asm volatile("{\n.reg .pred p;\nsetp.ne.b32 p, %5, 0;\n@p ld.global.L1::no_allocate.v4.u32 {%0, %1, %2, %3}, [%4];\n}\n"
                 : "+r"(v[0]), "+r"(v[1]), "+r"(v[2]), "+r"(v[3]) : "l"(p), "r"((int)on) : "memory");
}
__device__ __forceinline__ uint4 ldg128_ordered(const void* p) {
    uint4 v;
    asm volatile("ld.global.nc.v4.u32 {%0, %1, %2, %3}, [%4];" : "=r"(v.x), "=r"(v.y), "=r"(v.z), "=r"(v.w) : "l"(p) : "memory");
    return v;
}
__host__ __device__ constexpr uint64_t make_desc(uint32_t addr, uint32_t lbo, uint32_t sbo) {
    return (uint64_t)((addr & 0x3FFFF) >> 4) | ((uint64_t)(lbo >> 4) << 16) | ((uint64_t)(sbo >> 4) << 32);
}
__device__ __forceinline__ void wgmma(uint32_t (&d)[12], uint32_t a0, uint32_t a1, uint32_t a2, uint32_t a3, uint64_t db, int acc) {
    asm volatile("{\n.reg .pred p;\nsetp.ne.b32 p, %17, 0;\n"
                 "wgmma.mma_async.sync.aligned.m64n48k16.f16.f16.f16 "
                 "{%0, %1, %2, %3, %4, %5, %6, %7, %8, %9, %10, %11}, "
                 "{%12, %13, %14, %15}, %16, p, 1, 1, 0;\n}\n"
                 : "+r"(d[0]), "+r"(d[1]), "+r"(d[2]), "+r"(d[3]), "+r"(d[4]), "+r"(d[5]), "+r"(d[6]), "+r"(d[7]), "+r"(d[8]), "+r"(d[9]), "+r"(d[10]), "+r"(d[11])
                 : "r"(a0), "r"(a1), "r"(a2), "r"(a3), "l"(db), "r"(acc));
}
__device__ __forceinline__ void wgmma(uint32_t (&d)[24], uint32_t a0, uint32_t a1, uint32_t a2, uint32_t a3, uint64_t db, int acc) {
    asm volatile("{\n.reg .pred p;\nsetp.ne.b32 p, %29, 0;\n"
                 "wgmma.mma_async.sync.aligned.m64n96k16.f16.f16.f16 "
                 "{%0, %1, %2, %3, %4, %5, %6, %7, %8, %9, %10, %11, %12, %13, %14, %15, %16, %17, %18, %19, %20, %21, %22, %23}, "
                 "{%24, %25, %26, %27}, %28, p, 1, 1, 0;\n}\n"
                 : "+r"(d[0]), "+r"(d[1]), "+r"(d[2]), "+r"(d[3]), "+r"(d[4]), "+r"(d[5]), "+r"(d[6]), "+r"(d[7]), "+r"(d[8]), "+r"(d[9]), "+r"(d[10]), "+r"(d[11]), "+r"(d[12]), "+r"(d[13]), "+r"(d[14]), "+r"(d[15]), "+r"(d[16]), "+r"(d[17]), "+r"(d[18]), "+r"(d[19]), "+r"(d[20]), "+r"(d[21]), "+r"(d[22]), "+r"(d[23])
                 : "r"(a0), "r"(a1), "r"(a2), "r"(a3), "l"(db), "r"(acc));
}
template <int ACC>
__device__ __forceinline__ void wgmma_rowsum(float (&d)[4], const uint32_t (&a)[4], uint64_t ones) {
    asm volatile("{\n.reg .pred p;\nsetp.ne.b32 p, %9, 0;\n"
                 "wgmma.mma_async.sync.aligned.m64n8k16.f32.bf16.bf16 {%0, %1, %2, %3}, {%4, %5, %6, %7}, %8, p, 1, 1, 0;\n}\n"
                 : "+f"(d[0]), "+f"(d[1]), "+f"(d[2]), "+f"(d[3])
                 : "r"(a[0]), "r"(a[1]), "r"(a[2]), "r"(a[3]), "l"(ones), "n"(ACC));
}
__device__ __forceinline__ void ldsm4(uint32_t (&r)[4], uint32_t addr) {
    asm volatile("ldmatrix.sync.aligned.m8n8.x4.shared.b16 {%0, %1, %2, %3}, [%4];"
                 : "=r"(r[0]), "=r"(r[1]), "=r"(r[2]), "=r"(r[3]) : "r"(addr) : "memory");
}
__device__ __forceinline__ void ldsm4_t(uint32_t (&r)[4], uint32_t addr) {
    asm volatile("ldmatrix.sync.aligned.m8n8.x4.trans.shared.b16 {%0, %1, %2, %3}, [%4];"
                 : "=r"(r[0]), "=r"(r[1]), "=r"(r[2]), "=r"(r[3]) : "r"(addr) : "memory");
}
__device__ __forceinline__ void stsm4(uint32_t addr, uint32_t a, uint32_t b, uint32_t c, uint32_t d) {
    asm volatile("stmatrix.sync.aligned.m8n8.x4.shared.b16 [%0], {%1, %2, %3, %4};"
                 ::"r"(addr), "r"(a), "r"(b), "r"(c), "r"(d) : "memory");
}
__device__ __forceinline__ uint32_t transpose8x8(uint32_t v) {
    uint32_t d; asm volatile("movmatrix.sync.aligned.m8n8.trans.b16 %0, %1;" : "=r"(d) : "r"(v)); return d;
}
__device__ __forceinline__ void spin_until(const unsigned* counter, unsigned target) {
    unsigned n = 0, c;
    do {
        asm volatile("ld.acquire.gpu.global.u32 %0, [%1];" : "=r"(c) : "l"(counter) : "memory");
        if (++n > SPIN_LIMIT) __trap();
    } while ((int)(c - target) < 0);
}
__device__ __forceinline__ void signal(unsigned* counter) {
    __syncwarp();
    if (elect_one()) asm volatile("red.release.gpu.global.add.u32 [%0], 1;" ::"l"(counter) : "memory");
    __syncwarp();
}
__device__ __forceinline__ void lds128(uint32_t& a, uint32_t& b, uint32_t& c, uint32_t& d, uint32_t addr) {
    asm volatile("ld.shared.v4.u32 {%0, %1, %2, %3}, [%4];" : "=r"(a), "=r"(b), "=r"(c), "=r"(d) : "r"(addr) : "memory");
}
__device__ __forceinline__ void lds64(uint32_t& a, uint32_t& b, uint32_t addr) {
    asm volatile("ld.shared.v2.u32 {%0, %1}, [%2];" : "=r"(a), "=r"(b) : "r"(addr) : "memory");
}
__device__ __forceinline__ void lds32(uint32_t& a, uint32_t addr) {
    asm volatile("ld.shared.u32 %0, [%1];" : "=r"(a) : "r"(addr) : "memory");
}
__device__ __forceinline__ int ldsi(uint32_t addr) {
    uint32_t v;
    lds32(v, addr);
    return (int)v;
}
__device__ __forceinline__ float ldsf(uint32_t addr) {
    uint32_t v;
    lds32(v, addr);
    return __uint_as_float(v);
}
__device__ __forceinline__ void sts32(uint32_t addr, uint32_t a) {
    asm volatile("st.shared.u32 [%0], %1;" ::"r"(addr), "r"(a) : "memory");
}
__device__ __forceinline__ void sts128(uint32_t addr, uint32_t a, uint32_t b, uint32_t c, uint32_t d) {
    asm volatile("st.shared.v4.u32 [%0], {%1, %2, %3, %4};" ::"r"(addr), "r"(a), "r"(b), "r"(c), "r"(d) : "memory");
}
__device__ __forceinline__ void sts64(uint32_t addr, uint32_t a, uint32_t b) {
    asm volatile("st.shared.v2.u32 [%0], {%1, %2};" ::"r"(addr), "r"(a), "r"(b) : "memory");
}
__device__ __forceinline__ void anchor(uint32_t addr, uint32_t a, uint32_t b, uint32_t c, uint32_t d) {
    asm volatile("{\n.reg .pred p;\nsetp.eq.b32 p, %0, 0;\n@p st.shared.v4.u32 [%0], {%1, %2, %3, %4};\n}\n"
                 ::"r"(addr), "r"(a), "r"(b), "r"(c), "r"(d) : "memory");
}
__device__ __forceinline__ uint32_t bf_fma(uint32_t a, uint32_t b, uint32_t c) {
    uint32_t d; asm("fma.rn.bf16x2 %0, %1, %2, %3;" : "=r"(d) : "r"(a), "r"(b), "r"(c)); return d;
}
__device__ __forceinline__ uint32_t bf_mul(uint32_t a, uint32_t b) {
    uint32_t d; asm("mul.rn.bf16x2 %0, %1, %2;" : "=r"(d) : "r"(a), "r"(b)); return d;
}
__device__ __forceinline__ uint32_t bf_absmax(uint32_t a, uint32_t b) {
    uint32_t d; asm("max.xorsign.abs.bf16x2 %0, %1, %2;" : "=r"(d) : "r"(a), "r"(b)); return d;
}
__device__ __forceinline__ uint32_t h_fma(uint32_t a, uint32_t b, uint32_t c) {
    uint32_t d; asm("fma.rn.f16x2 %0, %1, %2, %3;" : "=r"(d) : "r"(a), "r"(b), "r"(c)); return d;
}
__device__ __forceinline__ uint32_t h_mul(uint32_t a, uint32_t b) {
    uint32_t d; asm("mul.rn.f16x2 %0, %1, %2;" : "=r"(d) : "r"(a), "r"(b)); return d;
}
__device__ __forceinline__ uint32_t h_round8(uint32_t v) { return K_CUT ? v & 0xfff8fff8u : (v + 0x00040004u) & 0xfff8fff8u; }
constexpr float CUT_GAIN = K_CUT ? 1.f + 0.4375f * 0.7213f / 128 : 1.f;
__device__ __forceinline__ uint32_t h_tanh(uint32_t a) {
    uint32_t d; asm("tanh.approx.f16x2 %0, %1;" : "=r"(d) : "r"(a)); return d;
}
__device__ __forceinline__ uint32_t pack_h2(float lo, float hi) {
    uint32_t d; asm("cvt.rn.f16x2.f32 %0, %1, %2;" : "=r"(d) : "f"(hi), "f"(lo)); return d;
}
__device__ __forceinline__ uint32_t pack_bf2(float lo, float hi) {
    uint32_t d; asm("cvt.rn.bf16x2.f32 %0, %1, %2;" : "=r"(d) : "f"(hi), "f"(lo)); return d;
}
__device__ __forceinline__ float bf_lo(uint32_t v) { return __uint_as_float(v << 16); }
__device__ __forceinline__ float bf_hi(uint32_t v) { return __uint_as_float(v & 0xffff0000u); }
__device__ __forceinline__ float h_lo(uint32_t v) { return __low2float(*reinterpret_cast<__half2*>(&v)); }
__device__ __forceinline__ float h_hi(uint32_t v) { return __high2float(*reinterpret_cast<__half2*>(&v)); }
__device__ __forceinline__ float warp_absmax(uint32_t v) {
    return __uint_as_float(__reduce_max_sync(~0u, max((v & 0x7fffu) << 16, v & 0x7fff0000u)));
}
__device__ __forceinline__ uint32_t gelu2(uint32_t z) {
    uint32_t p = h_fma(z, z, GELU_C2);
    uint32_t t = h_tanh(K_OP & 1 ? h_mul(p, z) : h_mul(z, p));
    return K_OP & 2 ? h_fma(t, z, z) : h_fma(z, t, z);
}
__device__ __forceinline__ float pow2i(int e) { return __uint_as_float((uint32_t)(e + 127) << 23); }
__device__ __forceinline__ int ilog2f(float v) {
    int e = (int)((__float_as_uint(v) >> 23) & 0xff) - 127;
    return max(-100, min(100, e));
}

__device__ __forceinline__ int bound_exp(float w1max) { return w1max > 0.f ? ilog2f(2.f * KZ * 96.f * w1max) : 0; }
__device__ __forceinline__ bool plain_squares(int e) { return (unsigned)(4 - e) <= 6; }
__device__ __forceinline__ int square_exp(int e) { return plain_squares(e) ? 0 : max(-14, min(4 - e, 14)); }
__device__ __forceinline__ int sum_exp(int e) { return max(-90, min(90, 33 - 2 * e)); }
__device__ __forceinline__ int row_exp(float m) { return 2 - ilog2f(m); }

struct Split {
    int per_cta, extra, period, inv_period, lenders;
    uint32_t lent_off[MAX_LENDERS * LENT];
    __host__ __device__ __forceinline__ int longer_before(int cta) const {
        const int n = (cta + period / 2) * inv_period >> 16;
        return n < extra ? n : extra;
    }
};
struct Work {
    int tA, tB, nA, nB, dir, rows, lent, index;
    __host__ __device__ __forceinline__ int tile(int j) const { return j < nA ? tA + dir * j : tB + dir * (j - nA); }
};
__host__ __device__ __forceinline__ Work get_work(int cta, const Split& sp) {
    Work w;
    const int before = sp.longer_before(cta), longer = sp.longer_before(cta + 1) - before;
    w.lent = longer && sp.lenders ? LENT : 0;
    w.index = longer ? before : cta - before;
    const int t0 = cta * sp.per_cta + before, t1 = t0 + sp.per_cta + longer;
    const int tm = t1 < (t0 | 511) + 1 ? t1 : (t0 | 511) + 1;
    const bool swap = t1 > tm && t1 - tm < tm - t0, down = cta & 1;
    w.nA = swap ? t1 - tm : tm - t0;
    w.nB = t1 - t0 - w.nA;
    w.tA = down ? (swap ? tm : t0) : (swap ? t1 : tm) - 1;
    w.tB = down ? (swap ? t0 : tm) : (swap ? tm : t1) - 1;
    w.dir = down ? 1 : -1;
    w.rows = w.nA + 2 + (w.nB ? w.nB + 2 : 0);
    return w;
}
__device__ __forceinline__ int row_code(const Work& w, int i) {
    const bool in_a = i < w.nA + 2;
    const int t = in_a ? w.tA : w.tB;
    return ((t & 511) + w.dir * ((in_a ? i : i - (w.nA + 2)) - 1)) << 16 | (t >> 9) * TILE_W;
}
__host__ __device__ __forceinline__ uint32_t tile_offset(int tile) { return ((tile & 511) * IMG_W + (tile >> 9) * TILE_W) * (CH * 2); }
__device__ __forceinline__ int tile_order(int j, int n) {
    const int olds = (j / ORDER_P) * ORDER_Q + max(0, j % ORDER_P - (ORDER_P - ORDER_Q));
    return (j % ORDER_P >= ORDER_P - ORDER_Q) ? olds : n - 1 - (j - olds);
}
__device__ __forceinline__ void issue_region(const CUtensorMap* tm, uint32_t dst, uint32_t bar, int warp, int code) {
    mbar_expect_tx(bar, REGION_BYTES);
    tma_row(dst, tm, bar, (code & 0xffff) + (16 * warp - 1), code >> 16);
}

template <class Event>
__device__ __forceinline__ void conv_producer(const Work& wk, const CUtensorMap* tm, uint32_t sb, int warp, Event event) {
    const int lane = threadIdx.x & 31;
    const int j = lane & 15, grp = lane >> 4;
    const uint32_t reg0 = sb + SM_RING + warp * REGION_BYTES;
    const uint32_t bars = sb + SM_BAR + warp * 8;
    if (warp * 32 + lane < MAX_ROWS) {
        const int i = warp * 32 + lane, before = min(i / 5, wk.lent);
        const bool back = i % 5 == 0 && i > 0 && i / 5 <= wk.lent;
        sts32(sb + SM_TILES + i * 4, back ? tile_offset(wk.tile(before - 1)) | before
                                          : tile_offset(wk.tile(wk.lent + tile_order(i - before, wk.nA + wk.nB - NCONS - wk.lent))));
    }
    const uint32_t ld64 = opaque(reg0 + grp * 8 * 192 + j * 8), ld32 = opaque(reg0 + grp * 8 * 192 + 128 + j * 4);
    const uint32_t st64 = opaque(reg0 + grp * A_SBO + (j >> 1) * A_LBO + (j & 1) * 8);
    const uint32_t st32 = opaque(reg0 + grp * A_SBO + (8 + (j >> 2)) * A_LBO + (j & 3) * 4);
    named_bar(0, NTHREADS);
    uint32_t w[3][3][3];
    mbar_wait(sb + BAR_F, 0);
#pragma unroll
    for (int tap = 0; tap < 9; tap++) {
        const uint32_t p = sb + SM_FILTER + (3 + wk.dir * 3 * (tap / 3 - 1) + tap % 3) * (CH * 2);
        lds64(w[tap / 3][tap % 3][0], w[tap / 3][tap % 3][1], p + 8 * j);
        lds32(w[tap / 3][tap % 3][2], p + 128 + 4 * j);
    }
#pragma unroll
    for (int tap = 0; tap < 9; tap++) sts64(reg0 + (NSLOT - 1) * SLOT_BYTES + tap * 128 + j * 8, w[tap / 3][tap % 3][1], w[tap / 3][tap % 3][0]);
    named_bar(1, 128);
#pragma unroll
    for (int tap = 0; tap < 9; tap++) lds64(w[tap / 3][tap % 3][1], w[tap / 3][tap % 3][0], reg0 + (NSLOT - 1) * SLOT_BYTES + tap * 128 + j * 8);
    static_assert(2 * PREFETCH_ROWS == NSLOT && SLOT_BYTES % 32 == 0, "slot arithmetic");
    uint32_t bo = 0, par = 0, pbo = PREFETCH_ROWS * 32, ppar = 1;
    int px, py;
    auto request = [&]() {
        mbar_wait(bars + (BAR_E - SM_BAR) + pbo, ppar);
        if (elect_one()) {
            mbar_expect_tx(bars + pbo, REGION_BYTES);
            tma_row(reg0 + pbo * (SLOT_BYTES / 32), tm, bars + pbo, px, py);
        }
    };
    auto advance = [&]() {
        bo += 32;
        if (bo == NSLOT * 32) { bo = 0; par ^= 1; }
        pbo += 32;
        if (pbo == NSLOT * 32) { pbo = 0; ppar ^= 1; }
    };
    auto aim = [&](int row) {
        const int code = row_code(wk, row);
        px = (code & 0xffff) + (16 * warp - 1);
        py = code >> 16;
    };
    uint32_t accB[8][3], accC[8][3];
    int r = 0;
#pragma unroll 1
    while (r < wk.rows) {
        if (r == 0 || r == wk.nA + 2) {
            const uint32_t bo0 = bo;
            uint32_t bo1;
#pragma unroll 1
            for (int k = 0; k < 2; k++, r++) {
                mbar_wait(bars + bo, par);
                bo1 = bo;
                if (r >= 2) {
                    aim(r + PREFETCH_ROWS);
                    request();
                }
                advance();
            }
            const uint32_t so0 = bo0 * (SLOT_BYTES / 32), so1 = bo1 * (SLOT_BYTES / 32);
#pragma unroll
            for (int p = 0; p < 10; p++) {
                uint32_t u[3], v[3];
                lds64(u[0], u[1], so0 + ld64 + p * 192);
                lds32(u[2], so0 + ld32 + p * 192);
                lds64(v[0], v[1], so1 + ld64 + p * 192);
                lds32(v[2], so1 + ld32 + p * 192);
#pragma unroll
                for (int dx = 0; dx < 3; dx++) {
                    const int o = p - dx;
                    if (o < 0 || o > 7) continue;
#pragma unroll
                    for (int q = 0; q < 3; q++) {
                        accB[o][q] = bf_fma(v[q], w[1][dx][q], dx == 0 ? bf_mul(u[q], w[0][dx][q]) : bf_fma(u[q], w[0][dx][q], accB[o][q]));
                        accC[o][q] = dx == 0 ? bf_mul(v[q], w[0][dx][q]) : bf_fma(v[q], w[0][dx][q], accC[o][q]);
                    }
                }
            }
            anchor(ld64, accB[7][0], accB[7][1], accB[7][2], 0);
            __syncwarp();
            if (elect_one()) {
                mbar_arrive(bars + (BAR_A - SM_BAR) + bo0);
                mbar_arrive(bars + (BAR_E - SM_BAR) + bo0);
                mbar_arrive(bars + (BAR_A - SM_BAR) + bo1);
                mbar_arrive(bars + (BAR_E - SM_BAR) + bo1);
            }
        }
        int end = wk.rows;
        const int marks[4] = {wk.rows - PREFETCH_ROWS, wk.rows - 11, wk.nA + 2, wk.nA + 2 - PREFETCH_ROWS};
#pragma unroll
        for (int k = 0; k < 4; k++) end = marks[k] > r ? min(end, marks[k]) : end;
        const bool fetch = r < wk.rows - PREFETCH_ROWS;
        aim(r + PREFETCH_ROWS);
        px = opaque_uniform(px);
        const int py_end = opaque_uniform(py + wk.dir * (end - r));
        r = end;
#pragma unroll 1
        do {
            mbar_wait(bars + bo, par);
            const uint32_t so = bo * (SLOT_BYTES / 32);
            uint32_t out[8][3];
#pragma unroll
            for (int p = 0; p < 10; p++) {
                uint32_t xv[3];
                lds64(xv[0], xv[1], so + ld64 + p * 192);
                lds32(xv[2], so + ld32 + p * 192);
#pragma unroll
                for (int dd = 0; dd < 3; dd++) {
                    const int dx = K_PD ? 2 - dd : dd, o = p - dx;
                    if (o < 0 || o > 7) continue;
#pragma unroll
                    for (int qq = 0; qq < 3; qq++) {
                        const int q = (qq + K_PQ) % 3;
                        out[o][q] = bf_fma(xv[q], w[2][dx][q], dx == 0 ? accB[o][q] : out[o][q]);
                        accB[o][q] = bf_fma(xv[q], w[1][dx][q], dx == 0 ? accC[o][q] : accB[o][q]);
                        accC[o][q] = dx == 0 ? bf_mul(xv[q], w[0][dx][q]) : bf_fma(xv[q], w[0][dx][q], accC[o][q]);
                    }
                }
            }
            __syncwarp();
#pragma unroll
            for (int oo = 0; oo < 8; oo++) {
                const int o = K_PS ? 7 - oo : oo;
                sts64(so + st64 + o * 16, out[o][0], out[o][1]);
                sts32(so + st32 + o * 16, out[o][2]);
            }
            __syncwarp();
            if (elect_one()) mbar_arrive(bars + (BAR_A - SM_BAR) + bo);
            if (fetch) request();
            advance();
            py += wk.dir;
        } while (py != py_end);
        if (((wk.rows - r) & ~8) == PREFETCH_ROWS) event(wk.rows - r == PREFETCH_ROWS);
    }
}

template <bool SCALED, int K0 = 0, int K1 = 3>
__device__ __forceinline__ void gelu_sq(uint32_t (&d)[24], uint32_t (&keep)[24], uint32_t sq_addr, uint32_t scale2) {
    pin(d);
#pragma unroll
    for (int k = K0; k < K1; k++) {
        uint32_t hs[4];
        lds128(hs[0], hs[1], hs[2], hs[3], sq_addr + k * SQ_ROW);
#pragma unroll
        for (int qq = 0; qq < 4; qq++) {
            const int q = K_QS == 0 ? qq : K_QS == 1 ? 3 - qq : K_QS == 2 ? (qq >> 1 | (qq & 1) << 1) : (qq + 1) & 3;
            uint32_t g0 = gelu2(d[8 * k + 2 * q]), g1 = gelu2(d[8 * k + 2 * q + 1]);
            keep[8 * k + 2 * q] = g0;
            keep[8 * k + 2 * q + 1] = g1;
            if (SCALED) { g0 = h_mul(g0, scale2); g1 = h_mul(g1, scale2); }
            hs[q] = (K_GS >> (q & 1) & 1) ? h_fma(g0, g0, h_fma(g1, g1, hs[q])) : h_fma(g1, g1, h_fma(g0, g0, hs[q]));
        }
        sts128(sq_addr + k * SQ_ROW, hs[0], hs[1], hs[2], hs[3]);
    }
}
__device__ __forceinline__ void gelu_sq_reg(uint32_t (&d)[24], uint32_t (&hs)[12]) {
    pin(d);
#pragma unroll
    for (int qq = 0; qq < 12; qq++) {
        const int q = K_QR == 0 ? qq : K_QR == 1 ? 11 - qq : K_QR == 2 ? qq ^ 1 : qq * 5 % 12;
        const uint32_t g0 = gelu2(d[2 * q]), g1 = gelu2(d[2 * q + 1]);
        hs[q] = (K_GR >> (q & 1) & 1) ? h_fma(g0, g0, h_fma(g1, g1, hs[q])) : h_fma(g1, g1, h_fma(g0, g0, hs[q]));
    }
}
__device__ __forceinline__ void gelu_to(uint32_t (&g)[12], uint32_t (&d)[12]) {
    pin(d);
#pragma unroll
    for (int q = 0; q < 12; q++) g[q] = gelu2(d[q]);
    pin(g);
}
__device__ __forceinline__ void load_tile(uint32_t (&raw)[6][4], uint32_t addr) {
#pragma unroll
    for (int s = 0; s < 6; s++) ldsm4(raw[s], addr + s * 2 * A_LBO);
}
__device__ __forceinline__ uint2 ln_stats(const uint32_t (&raw)[6][4], uint64_t ones) {
    constexpr int NS = 6 / K_CHAIN;
    uint32_t sq[NS][4];
#pragma unroll
    for (int s = 0; s < 6; s++)
#pragma unroll
        for (int q = 0; q < 4; q++) sq[s % NS][q] = s < NS ? bf_mul(raw[s][q], raw[s][q]) : bf_fma(raw[s][q], raw[s][q], sq[s % NS][q]);
    float sum[4], ssq[4];
    wg_fence();
    wgmma_rowsum<0>(sum, raw[0], ones);
#pragma unroll
    for (int s = 1; s < 6; s++) wgmma_rowsum<1>(sum, raw[s], ones);
    wgmma_rowsum<0>(ssq, sq[0], ones);
#pragma unroll
    for (int s = 1; s < NS; s++) wgmma_rowsum<1>(ssq, sq[s], ones);
    wg_commit();
    wg_wait<0>();
    uint32_t st[2];
#pragma unroll
    for (int h = 0; h < 2; h++) {
        asm volatile("" : "+f"(sum[2 * h]), "+f"(ssq[2 * h])::"memory");
        const float mean = sum[2 * h] * (1.f / CH);
        const float var = fmaxf(fmaf(ssq[2 * h], 1.f / CH, -mean * mean), 0.f);
        float rstd;
        asm("rsqrt.approx.ftz.f32 %0, %1;" : "=f"(rstd) : "f"(var + 1e-5f));
        rstd = bf_lo(pack_bf2(rstd * (K_CVT == 0 ? KZ : KZ * 0x1p-112f), 0.f));
        st[h] = pack_bf2(rstd, -mean * rstd);
    }
    return make_uint2(st[0], st[1]);
}
__device__ __forceinline__ void ln_apply(uint32_t (&a)[6][4], const uint2& st) {
    const uint32_t sc[2] = {__byte_perm(st.x, 0, 0x1010), __byte_perm(st.y, 0, 0x1010)};
    const uint32_t sh[2] = {__byte_perm(st.x, 0, 0x3232), __byte_perm(st.y, 0, 0x3232)};
#pragma unroll
    for (int s = 0; s < 6; s++)
#pragma unroll
        for (int q = 0; q < 4; q++) {
            const uint32_t v = bf_fma(a[s][q], sc[q & 1], sh[q & 1]);
            a[s][q] = K_CVT == 0 ? pack_h2(bf_lo(v), bf_hi(v)) : K_CVT == 1 ? (v & 0x7fff7fffu) * 7u + v : ((v << 3) & 0x7fff7fffu) | (v & 0x80008000u);
        }
}
struct Cursor {
    int slot;
    uint32_t par;
    __device__ __forceinline__ void advance(int n) {
        slot += n;
        if (slot >= NSLOT) { slot -= NSLOT; par ^= 1; }
    }
};
struct Descs {
    uint64_t w1[8][6];
    uint64_t w2[24];
    uint64_t ones;
};
template <int E0, int N>
__device__ __forceinline__ void gemm1_chunk(uint32_t (&d)[N], const uint32_t (&a)[6][4], const Descs& ds, int zero) {
#pragma unroll
    for (int s = 0; s < 6; s++) wgmma(d, a[s][0], a[s][1], a[s][2], a[s][3], ds.w1[E0 / 48][s], s ? 1 : zero);
}
template <int E0, int N>
__device__ __forceinline__ void gemm2_chunk(uint32_t (&acc)[24], const uint32_t (&g)[N], const Descs& ds) {
#pragma unroll
    for (int s = 0; s < N / 4; s++) wgmma(acc, g[4 * s], g[4 * s + 1], g[4 * s + 2], g[4 * s + 3], ds.w2[E0 / 16 + s], 1);
}

struct __align__(64) Params {
    Split sp;
    int zero;
    const __nv_bfloat16 *x, *dw, *w2, *gamma, *beta;
    __nv_bfloat16* out;
    Scratch* sc;
    Descs ds;
};

__global__ void __launch_bounds__(NTHREADS, 1)
block_kernel(const __grid_constant__ CUtensorMap tmap, const __grid_constant__ CUtensorMap tmap_w1, const __grid_constant__ Params pm) {
    const Split& sp = pm.sp;
    const Descs& ds = pm.ds;
    const int& zero = pm.zero;
    const __nv_bfloat16 *const &x = pm.x, *const &dw = pm.dw, *const &w2 = pm.w2, *const &gamma = pm.gamma, *const &beta = pm.beta;
    __nv_bfloat16* const& out = pm.out;
    Scratch* const& sc = pm.sc;
    extern __shared__ __align__(1024) uint8_t smem[];
    constexpr uint32_t sb = SB;
    const int tid = K_ROT < 4 ? (threadIdx.x + 128 * K_ROT) & (NTHREADS - 1) : threadIdx.x ^ 384;
    const Work wk = get_work(blockIdx.x, sp);
    constexpr uint32_t s_red = sb + SM_RED;
    if (smem_u32(smem) != SB) __trap();

    PROF(0);
    const int warp_id = __shfl_sync(~0u, tid >> 5, 0);
    const int cw = warp_id - 4, wgi = cw >> 2, w4 = warp_id & 3;
    if (elect_one()) {
        static_assert(3 * NSLOT * 4 == 8 + 4 * 16 && BAR_F == BAR_W + 48, "barrier shares");
        const int b = warp_id - 8;
        const uint32_t bar = b < 0 ? sb + BAR_X + warp_id * 8 : b < 7 ? sb + BAR_W + b * 8 : sb + BAR_PIN;
        mbar_init(bar, 1);
        if (!K_INIT) {
#pragma unroll
            for (int k = 0; k < 4; k++) mbar_init(sb + BAR_X + (8 + 4 * warp_id + k) * 8, 1);
            mbar_init(sb + BAR_R + warp_id * 8, 1);
        }
        fence_async();
        if (b < 0) {
            issue_region(&tmap, sb + SM_RING + warp_id * REGION_BYTES, bar, w4, ((wk.tA & 511) + wk.dir * wgi) << 16 | (wk.tA >> 9) * TILE_W);
        } else if (b < 6) {
            mbar_expect_tx(bar, 64 * CH * 2);
            tma_2d(sb + SM_W2 + b * (64 * CH * 2), &tmap_w1, bar, 64 * b, 0);
        } else if (b == 6) {
            mbar_expect_tx(bar, 9 * CH * 2);
            bulk_load(sb + SM_FILTER, dw, 9 * CH * 2, bar);
        }
        if (K_INIT) {
#pragma unroll
            for (int k = 0; k < 4; k++) mbar_init(sb + BAR_X + (8 + 4 * warp_id + k) * 8, 1);
            mbar_init(sb + BAR_R + warp_id * 8, 1);
            fence_async();
        }
    }
    __syncwarp();
    const int ntiles = wk.nA + wk.nB;
    const int wg = warp_id >> 2;
    int first = wg;
    uint32_t a[6][4], acc[24], tile_off, next_off, stage, inv_rho2 = 0, rpar = 0, bias_addr, lane16, lane_off;
    auto set_lane = [&](uint32_t lane) {
        bias_addr = sb + SM_BIASH + (lane & 3) * 96;
        lane16 = lane * 16;
        lane_off = ((lane >> 2) * CH + 8 * (lane & 3)) * 2;
    };
    const uint32_t bar_r = sb + BAR_R + warp_id * 8;
    auto load_bias = [&](uint32_t (&acc)[24]) {
        if (K_BHALF) {
#pragma unroll
            for (int q = 0; q < 3; q++) lds128(acc[8 * q], acc[8 * q + 2], acc[8 * q + 4], acc[8 * q + 6], bias_addr + q * 16);
#pragma unroll
            for (int q = 0; q < 12; q++) acc[2 * q + 1] = acc[2 * q];
        } else {
#pragma unroll
            for (int q = 0; q < 6; q++) lds128(acc[4 * q], acc[4 * q + 1], acc[4 * q + 2], acc[4 * q + 3], bias_addr + q * 16);
        }
    };
    auto load_frags = [&](bool on) {
#pragma unroll
        for (int s = 0; s < 6; s++) ldg128_if(on, a[s], reinterpret_cast<const char*>(out) + next_off + w4 * WARP_BYTES + lane16 + s * 512);
    };
    auto load_first = [&]() {
#pragma unroll
        for (int s = 0; s < 6; s++) ldg128(a[s], reinterpret_cast<const char*>(out) + next_off + w4 * WARP_BYTES + lane16 + s * 512);
    };
    auto stage_x = [&]() {
        if (elect_one()) {
            mbar_expect_tx(bar_r, WARP_BYTES);
            bulk_load_stream(stage, reinterpret_cast<const char*>(x) + tile_off + w4 * WARP_BYTES, WARP_BYTES, bar_r);
        }
    };
    auto epilogue = [&](uint32_t (&acc)[24]) {
        pin(acc);
        rpar ^= 1;
        uint4* op = reinterpret_cast<uint4*>(reinterpret_cast<char*>(out) + tile_off + w4 * WARP_BYTES + lane_off);
#pragma unroll
        for (int h = 0; h < 2; h++)
#pragma unroll
            for (int m = 0; m < 3; m++) {
                uint32_t xin[4], o[4];
                lds128(xin[0], xin[1], xin[2], xin[3], stage + lane_off + h * 1536 + m * 64);
#pragma unroll
                for (int q = 0; q < 4; q++) {
                    const uint32_t v = acc[2 * (4 * m + q) + h];
                    o[q] = bf_fma(pack_bf2(h_lo(v), h_hi(v)), inv_rho2, xin[q]);
                }
                __stcs(op + h * 96 + m * 4, make_uint4(o[0], o[1], o[2], o[3]));
            }
        __syncwarp();
    };
    auto max_w1 = [&](uint32_t lane) { return __uint_as_float(__reduce_max_sync(~0u, lane < 4 * NCONS ? ldsi(s_red + RED_MAX + lane * 4) : 0)); };
    const bool helps = !wk.lent && wk.index < 8 * LENT * sp.lenders;
    const int help_slot = (wk.rows + 2) % NSLOT;
    const uint32_t s_help = sb + SM_RING + help_slot * SLOT_BYTES + SQ_WG;
    auto reduce = [&](int q, uint32_t lane, bool leader) {
        const int g = lane >> 2, t = lane & 3, ch = 32 * q + 8 * t + 2 * (g & 3) + (g >> 2);
        const uint32_t pick = (g >> 1 & 1) == (t & 1) ? (g & 1 ? 0x3c000000u : 0x00003c00u) : 0;
        const int be = bound_exp(max_w1(lane)), sq_e = square_exp(be);
        const float to_fixed = pow2i(sum_exp(be) - 2 * sq_e);
        unsigned long long* dst = sc->sum(ch);
        named_bar(11, CONS_THREADS);
        const unsigned in_piece = ch - wk.index % 8 * 48;
        float helped = 0.f;
        if (helps && in_piece < 48) {
            uint32_t u[4];
            lds128(u[0], u[1], u[2], u[3], s_help + in_piece * 16);
            helped = ((__uint_as_float(u[0]) + __uint_as_float(u[1])) + (__uint_as_float(u[2]) + __uint_as_float(u[3]))) * pow2i(2 * sq_e);
        }
        float f[2][4] = {};
        int slot = wk.rows % NSLOT;
#pragma unroll 1
        for (int i = 0; i < NCONS; i++) {
            if (i == NCONS - 1) {
                named_bar(13, CONS_THREADS);
                if (leader) {
                    fence_async();
                    bulk_load(sb + SM_W2, sc->w2h, (NCONS - 1) * SQ_WG, sb + BAR_W);
                }
                __syncwarp();
                named_bar(14, NTHREADS);
            }
            const uint32_t src = sb + lane * 16 + q * SQ_ROW + (q < 6 ? SM_SQ + i * SQ_WG : sq_e ? SM_SQ + (NCONS - 1 + i) * SQ_WG : SM_RING + slot * SLOT_BYTES - SQ_WG);
            slot = slot == NSLOT - 1 ? 0 : slot + 1;
#pragma unroll
            for (int r = 0; r < 4; r++) {
                uint32_t u[4];
                ldsm4_t(u, src + r * 512);
#pragma unroll
                for (int k = 0; k < 2; k++)
                    asm volatile("mma.sync.aligned.m16n8k16.row.col.f32.f16.f16.f32 {%0, %1, %2, %3}, {%4, %5, %4, %5}, {%6, %7}, {%0, %1, %2, %3};"
                                 : "+f"(f[k][0]), "+f"(f[k][1]), "+f"(f[k][2]), "+f"(f[k][3]) : "r"(pick), "r"(0), "r"(u[2 * k]), "r"(u[2 * k + 1]));
            }
        }
        const float tot = g < 4 ? f[0][0] + f[1][0] : f[0][1] + f[1][1];
        atomicAdd(dst, __float2ull_rn(fminf((tot + helped) * to_fixed, 0x1p47f)) << 8 | 1);
    };
    const uint32_t s_fac = sb + SM_RING + (wk.rows + 1) % NSLOT * SLOT_BYTES + SQ_WG;
    if (warp_id < 4) {
        const bool prepares = gridDim.x - blockIdx.x <= W2_GROUPS / 2;
        const int q = (gridDim.x - 1 - blockIdx.x) * 2 + (w4 >> 1);
        conv_producer(wk, &tmap, sb, warp_id, [&](bool second) {
            if (!second) {
                if (blockIdx.x == 0) {
#pragma unroll 1
                    for (int e = tid; e < EX; e += 128) *sc->sum(e) = 0;
                    sc->bias[tid] = 0.f;
                    signal(&sc->early);
                }
                if (wk.lent) signal(&sc->early);
            } else if (prepares || helps) {
                spin_until(&sc->early, (ldsi(s_red + RED_LAUNCH) + 1) * 4 * (sp.lenders + 1));
                if (elect_one()) {
                    if (helps) prefetch_l2(reinterpret_cast<const char*>(out) + sp.lent_off[wk.index / 8] + w4 * WARP_BYTES, WARP_BYTES);
                    if (prepares) { prefetch_l2(w2 + 8 * q * CH, 8 * CH * 2); prefetch_l2(beta + 8 * q, 16); }
                }
            }
        });
        const int lane = opaque((uint32_t)tid & 31), g = lane >> 2, t = lane & 3;
        const unsigned epoch = ldsi(s_red + RED_LAUNCH);
        set_lane(lane);
        const int i0 = w4 * 32 + lane;
        float gam[3], rmax[3];
#pragma unroll
        for (int m = 0; m < 3; m++) {
            unsigned short v;
            asm volatile("ld.global.nc.u16 %0, [%1];" : "=h"(v) : "l"(gamma + i0 + 128 * m) : "memory");
            gam[m] = bf_lo(v);
        }
        if (prepares) {
            const int half = w4 & 1;
            uint32_t u[3][2], rmax = 0;
#pragma unroll
            for (int m = 0; m < 3; m++) {
                const uint4 w = ldg128_ordered(w2 + (8 * q + g) * CH + 32 * m + 8 * t);
                rmax = bf_absmax(bf_absmax(rmax, bf_absmax(w.x, w.y)), bf_absmax(w.z, w.w));
                u[m][0] = half ? w.z : w.x;
                u[m][1] = half ? w.w : w.y;
            }
            const float bt = __bfloat162float(beta[8 * q + g]);
            rmax = bf_absmax(rmax, __shfl_xor_sync(~0u, rmax, 1));
            rmax = bf_absmax(rmax, __shfl_xor_sync(~0u, rmax, 2));
            const float mx = fmaxf(fabsf(bf_lo(rmax)), fabsf(bf_hi(rmax))), rs = pow2i(row_exp(mx));
            if (t == 0 && !half) sc->w2max[8 * q + g] = mx;
#pragma unroll
            for (int m = 0; m < 3; m++) {
                float f[4];
#pragma unroll
                for (int k = 0; k < 2; k++) {
                    const float lo = bf_lo(u[m][k]), hi = bf_hi(u[m][k]);
                    sc->w2h[(4 * m + 2 * half + k) * 1536 + q * 32 + lane] = transpose8x8(pack_h2(lo * rs, hi * rs));
                    f[2 * k] = lo * bt;
                    f[2 * k + 1] = hi * bt;
                }
                const float r0 = (g & 2 ? f[2] : f[0]) + __shfl_xor_sync(~0u, g & 2 ? f[0] : f[2], 8);
                const float r1 = (g & 2 ? f[3] : f[1]) + __shfl_xor_sync(~0u, g & 2 ? f[1] : f[3], 8);
                float r = (g & 1 ? r1 : r0) + __shfl_xor_sync(~0u, g & 1 ? r0 : r1, 4);
                r += __shfl_xor_sync(~0u, r, 16);
                if (g < 4) atomicAdd(&sc->bias[32 * m + 8 * t + 4 * half + g], r);
            }
            asm volatile("fence.proxy.async.global;" ::: "memory");
            signal(&sc->prep);
        }
        const int piece = wk.index;
        if (helps) {
            next_off = sp.lent_off[wk.index / 8];
            load_first();
            uint32_t d[12], gl[12];
            wg_fence();
#pragma unroll
            for (int s = 0; s < 6; s++) wgmma(d, a[s][0], a[s][1], a[s][2], a[s][3], ds.w1[0][s] + piece % 8 * (6 * 1536 / 16), s ? 1 : 0);
            wg_commit();
            wg_wait<0>();
            gelu_to(gl, d);
#pragma unroll
            for (int s = 0; s < 3; s++) sc->lent[(((piece / (8 * LENT) * 4 + w4) * (8 * LENT) + piece % (8 * LENT)) * 3 + s) * 32 + lane] = make_uint4(gl[4 * s], gl[4 * s + 1], gl[4 * s + 2], gl[4 * s + 3]);
            float f[6], r[3];
#pragma unroll
            for (int j = 0; j < 6; j++) {
                const float lo = fmaf(h_lo(gl[2 * j]), h_lo(gl[2 * j]), h_lo(gl[2 * j + 1]) * h_lo(gl[2 * j + 1]));
                const float hi = fmaf(h_hi(gl[2 * j]), h_hi(gl[2 * j]), h_hi(gl[2 * j + 1]) * h_hi(gl[2 * j + 1]));
                f[j] = (g & 1 ? hi : lo) + __shfl_xor_sync(~0u, g & 1 ? lo : hi, 4);
            }
            mbar_wait(sb + BAR_E + help_slot * 32 + 24, (wk.rows - 4) / NSLOT & 1);
#pragma unroll
            for (int j = 0; j < 3; j++) {
                r[j] = (g & 2 ? f[j + 3] : f[j]) + __shfl_xor_sync(~0u, g & 2 ? f[j] : f[j + 3], 8);
                r[j] += __shfl_xor_sync(~0u, r[j], 16);
                sts32(s_help + (8 * j + 12 * (g & 2) + 2 * t + (g & 1)) * 16 + w4 * 4, __float_as_uint(r[j]));
            }
        }
        const bool leader = warp_id == 0 && lane == 0;
        const float w1max = max_w1(lane), from_fixed = pow2i(-sum_exp(bound_exp(w1max)));
        const bool plain = plain_squares(bound_exp(w1max));
        auto load_upper = [&]() {
            bulk_load(sb + SM_W2 + NCONS * SQ_WG, reinterpret_cast<const char*>(sc->w2h) + NCONS * SQ_WG, EX * CH * 2 - NCONS * SQ_WG, sb + BAR_W);
        };
        if (leader) {
            spin_until(&sc->prep, (epoch + 1) * 2 * W2_GROUPS);
            asm volatile("fence.proxy.async.global;" ::: "memory");
            fence_async();
            mbar_expect_tx(sb + BAR_W, EX * CH * 2);
            if (plain) load_upper();
        }
        __syncwarp();
        named_bar(1, 128);
#pragma unroll
        for (int m = 0; m < 3; m++) rmax[m] = __ldcg(&sc->w2max[i0 + 128 * m]);
        float2 bpair = make_float2(0.f, 0.f);
        if (i0 < 96) bpair = __ldcg(reinterpret_cast<const float2*>(&sc->bias[32 * (i0 % 24 >> 3) + 8 * (i0 / 24) + (i0 % 24 & 6)]));
        const float gbound = fmaxf(2.f * KZ * 9.7979590f * 192.f * w1max, 1.f) * 19.5959180f * INV_2KZ;
        const unsigned fixed = __reduce_max_sync(~0u, __float_as_uint(fmaf(gbound, fmaxf(fmaxf(rmax[0], rmax[1]), rmax[2]), fmaxf(fabsf(bpair.x), fabsf(bpair.y)))));
        if (lane == 0) sts32(s_red + 96 + w4 * 4, fixed);
        float base[3], slope[3], reach[3];
#pragma unroll
        for (int m = 0; m < 3; m++) {
            base[m] = opaque(rmax[m] > 0.f ? pow2i(-row_exp(rmax[m])) * (INV_2KZ * CUT_GAIN) : 0.f);
            slope[m] = opaque(base[m] * gam[m]);
            reach[m] = opaque(fabsf(gam[m]) * rmax[m] * gbound);
        }
        const float to_square = opaque(from_fixed * (INV_2KZ * INV_2KZ / 256));
        const uint32_t own_sum = opaque((uint32_t)(i0 >> 2) * 256 + (i0 & 3) * 8), own_fac = opaque(s_fac + i0 * 2);
        const uint32_t bias_slot = opaque(sb + SM_BIASH + (K_BHALF ? i0 / 24 * 96 + i0 % 24 / 2 * 4 : i0 * 4));
        reduce(4 * (NCONS - 1) + w4, lane, leader);
        PROF(2);
        named_bar(15, CONS_THREADS);
        if (leader) {
            fence_async();
            bulk_load(sb + SM_W2 + (NCONS - 1) * SQ_WG, reinterpret_cast<const char*>(sc->w2h) + (NCONS - 1) * SQ_WG, SQ_WG, sb + BAR_W);
            if (!plain) load_upper();
        }
        stage = sb + SM_RING + (wk.rows + 3 + (wk.lent + 2 * ntiles) % NCONS) % NSLOT * SLOT_BYTES + w4 * REGION_BYTES;
        auto grn = [&]() {
            auto peek = [&](const void* p) {
                unsigned long long v;
                asm volatile("ld.relaxed.gpu.global.u64 %0, [%1];" : "=l"(v) : "l"(p) : "memory");
                return v;
            };
            const char* mine = reinterpret_cast<const char*>(sc->sums) + own_sum;
            unsigned n = 0;
            while (((unsigned)peek(sc->sum((blockIdx.x * 4 + w4) % (EX / 4) * 4)) & 255u) != gridDim.x)
                if (++n > SPIN_LIMIT) __trap();
            unsigned long long sum[3];
            for (;;) {
                bool all = true;
#pragma unroll
                for (int m = 0; m < 3; m++) {
                    sum[m] = peek(mine + m * (32 * 256));
                    all &= ((unsigned)sum[m] & 255u) == gridDim.x;
                }
                if (__all_sync(~0u, all)) break;
                if (++n > SPIN_LIMIT) __trap();
            }
            PROF(3);
            float gx[3];
#pragma unroll
            for (int m = 0; m < 3; m++) asm("sqrt.approx.ftz.f32 %0, %1;" : "=f"(gx[m]) : "f"(fmaf(__ull2float_rn(sum[m]), to_square, 1e-6f)));
            float tot = gx[0] + gx[1] + gx[2];
#pragma unroll
            for (int o = 16; o >= 1; o >>= 1) tot += __shfl_xor_sync(~0u, tot, o);
            const unsigned vwarp = __reduce_max_sync(~0u, __float_as_uint(fmaxf(fmaxf(reach[0] * gx[0], reach[1] * gx[1]), reach[2] * gx[2])));
            if (lane == 0) { sts32(s_red + 64 + w4 * 4, __float_as_uint(tot)); sts32(s_red + 80 + w4 * 4, vwarp); }
            named_bar(1, 128);
            uint32_t u[4], v[4], w[4];
            lds128(u[0], u[1], u[2], u[3], s_red + 64);
            lds128(v[0], v[1], v[2], v[3], s_red + 80);
            lds128(w[0], w[1], w[2], w[3], s_red + 96);
            tot = (__uint_as_float(u[0]) + __uint_as_float(u[1])) + (__uint_as_float(u[2]) + __uint_as_float(u[3]));
            const float vmax = __uint_as_float(max(max(v[0], v[1]), max(v[2], v[3]))), fmax2 = __uint_as_float(max(max(w[0], w[1]), max(w[2], w[3])));
            float inv_mean;
            asm("rcp.approx.ftz.f32 %0, %1;" : "=f"(inv_mean) : "f"(fmaf(tot, 1.f / EX, 1e-6f)));
            const int rho_e = 14 - ilog2f(fmaf(vmax, inv_mean, 2.f * fmax2));
            const float rho = pow2i(rho_e), inv_rho = pow2i(-rho_e);
            inv_rho2 = pack_bf2(inv_rho, inv_rho);
#pragma unroll
            for (int m = 0; m < 3; m++) {
                const float f = fmaf(slope[m] * gx[m], inv_mean, base[m]) * rho;
                asm volatile("st.shared.u16 [%0], %1;" ::"r"(own_fac + 256 * m), "h"((unsigned short)pack_h2(f, 0.f)) : "memory");
            }
            if (i0 < 96) sts32(bias_slot, pack_h2(bpair.x * rho, bpair.y * rho));
            if (i0 == 96) sts32(s_red + RED_INV_RHO, inv_rho2);
            named_arrive(12, NTHREADS);
            if (blockIdx.x == 0 && leader) sc->launch = epoch + 1;
        };
        lds32(next_off, sb + SM_TILES);
        next_off = __shfl_sync(~0u, next_off, 0);
        load_first();
        grn();
        if (wk.lent) spin_until(&sc->lent_out, (epoch + 1) * 8 * LENT * sp.lenders);
    } else {
        const int rank = (wgi + wk.lent + 2 * ntiles) % NCONS;
        const uint32_t a_addr = opaque(sb + SM_RING + w4 * REGION_BYTES + ((tid >> 3) & 1) * A_SBO + ((tid >> 4) & 1) * A_LBO + (tid & 7) * 16);
        const uint32_t bar_a = sb + BAR_A + w4 * 8, bar_e = sb + BAR_E + w4 * 8;
        const uint32_t sq = opaque(sb + SM_SQ + rank * SQ_WG + (tid & 127) * 16);
        const uint32_t sq_warp = sb + SM_SQ + rank * SQ_WG + w4 * 512;
        if (wgi == NCONS - 1) named_arrive(4, 256);
        const int pass_to = 4 + (wgi == NCONS - 1 ? 0 : wgi + 1);
        const uint32_t own_bar = opaque_uniform(4 + wgi), next_bar = opaque_uniform(pass_to);
        const uint32_t step = opaque_uniform(wk.dir * (NCONS * IMG_W * CH * 2));
        uint32_t turn, turn_end, so, so_sum, bo, bo_sum, off;
        auto set_run = [&](int j, int stop, int row) {
            const int slot = row % NSLOT, both = 2 * (row % 3) + 3;
            turn = opaque_uniform(row / 3);
            turn_end = opaque_uniform(row / 3 + max(stop - j + NCONS - 1, 0) / NCONS);
            so = opaque_uniform(slot * SLOT_BYTES);
            so_sum = opaque_uniform(both * SLOT_BYTES);
            bo = opaque_uniform(bar_a + slot * 32);
            bo_sum = opaque_uniform(2 * bar_a + both * 32);
            off = opaque_uniform(tile_offset(wk.tile(j)) + w4 * WARP_BYTES - sq_warp);
        };
        set_run(wk.lent + wgi, min(wk.nA, ntiles - NCONS), wk.lent + wgi + 2);
        int jt = wgi < wk.lent ? wgi : wk.lent + wgi;
        Cursor cur = {2, 0};
        cur.advance(jt + (jt >= wk.nA ? 2 : 0));
        {
            const int ct = tid - 128, lane = tid & 31;
            const unsigned epoch = *reinterpret_cast<volatile unsigned*>(&sc->launch);
            const int r = lane & 7, mi = lane >> 3;
            const uint32_t src = sb + SM_W2 + (cw >> 1) * (64 * CH * 2) + r * 128 + ((((cw & 1) * 4 + mi) ^ r) * 16);
            const uint32_t dst = sb + SM_W1 + (4 * cw + mi) * 1536 + r * 16;
            const int code = row_code(wk, PREFETCH_ROWS - 1 + wgi);
            named_bar(0, NTHREADS);
            auto request = [&](int pos) {
                if ((K_REQ >> 4 * wgi & 15) == pos && elect_one())
                    issue_region(&tmap, sb + SM_RING + (PREFETCH_ROWS - 1 + wgi) * SLOT_BYTES + w4 * REGION_BYTES, sb + BAR_X + (cw + 8) * 8, w4, code);
                __syncwarp();
            };
            request(0);
            mbar_wait(sb + BAR_W + (cw >> 1) * 8, 0);
            request(1);
            uint32_t wmax[2] = {}, wsum[4] = {};
#pragma unroll K_UNR
            for (int c = 0; c < 12; c++) {
                uint32_t u[4];
                ldsm4_t(u, src + c * 1024);
#pragma unroll
                for (int q = 0; q < 4; q++) {
                    wmax[q & 1] = bf_absmax(wmax[q & 1], u[q]);
                    wsum[q] = bf_fma(u[q], 0x3f803f80u, wsum[q]);
                    u[q] = pack_h2(K_IM ? __uint_as_float(u[q] * (65536 + zero)) : bf_lo(u[q]), bf_hi(u[q]));
                }
                stsm4(dst + c * 128, u[0], u[1], u[2], u[3]);
            }
            request(2);
            const float w1max = warp_absmax(bf_absmax(wmax[0], wmax[1]));
            if (lane == 0) sts32(s_red + RED_MAX + cw * 4, __float_as_uint(w1max));
            bool center = false;
#pragma unroll
            for (int q = 0; q < 4; q++) {
#pragma unroll
                for (int o = 1; o <= 2; o <<= 1) wsum[q] = bf_fma(__shfl_xor_sync(~0u, wsum[q], o), 0x3f803f80u, wsum[q]);
                center |= fabsf(bf_lo(wsum[q]) + bf_hi(wsum[q])) > (0.15f * CH) * w1max;
            }
            if (__builtin_expect(__any_sync(~0u, center), 0)) {
                float mean[4] = {};
#pragma unroll 1
                for (int pass = 0; pass < 2; pass++) {
                    float sum[4] = {};
#pragma unroll 1
                    for (int c = 0; c < 12; c++) {
                        uint32_t u[4];
                        ldsm4_t(u, src + c * 1024);
#pragma unroll
                        for (int q = 0; q < 4; q++) {
                            sum[q] += bf_lo(u[q]) + bf_hi(u[q]);
                            u[q] = pack_h2(bf_lo(u[q]) - mean[q], bf_hi(u[q]) - mean[q]);
                        }
                        stsm4(dst + c * 128, u[0], u[1], u[2], u[3]);
                    }
#pragma unroll
                    for (int q = 0; q < 4; q++) {
                        sum[q] += __shfl_xor_sync(~0u, sum[q], 1);
                        sum[q] += __shfl_xor_sync(~0u, sum[q], 2);
                        mean[q] = sum[q] * (1.f / CH);
                    }
                }
            }
            if (cw < 2 * NCONS) {
#pragma unroll
                for (int c = 0; c < 12; c++) sts128(src + c * 1024, 0, 0, 0, 0);
            }
            if (ct < 32) sts32(sb + SM_ONES + ct * 4, 0x3f803f80u);
            if (ct == 0) sts32(s_red + RED_LAUNCH, epoch);
            fence_async();
            named_bar(2, CONS_THREADS);
            request(3);
        }
        PROF(1);
        uint32_t k1[24], k2[24], k3[24];
        constexpr int SQC = 3 * SQ_ROW;
        auto store_at = [&](const uint32_t (&a)[6][4], uint32_t off) {
            char* ap = reinterpret_cast<char*>(out) + (off + sq);
#pragma unroll
            for (int s = 0; s < 6; s++) stg128(ap + s * 512, a[s]);
        };
        const bool plain = __all_sync(~0u, plain_squares(bound_exp(max_w1(sq >> 4 & 31))));
        if (!plain) {
#pragma unroll 1
            for (int q = 0; q < 6; q++) sts128(sq + NCONS * SQ_WG + q * SQ_ROW, 0, 0, 0, 0);
        }
        for (;;) {
            if (plain && jt >= wk.lent) {
                uint32_t hs2[12] = {}, hs3[12] = {};
                int second = wk.nB;
#pragma unroll 1
                for (;;) {
#pragma unroll 1
                while (turn != turn_end) {
                    uint32_t a[6][4], d0[24], d1[24], unused[24];
#define AT(pos) \
    if (K_WAIT == pos) named_bar(own_bar, 256); \
    if (K_PASS == pos) named_arrive(next_bar, 256); \
    if (K_STG == pos) store_at(a, off); \
    if (K_REL == pos) { if (elect_one()) mbar_arrive(bo + (BAR_E - BAR_A)); }
                    AT(20)
                    mbar_wait(bo, turn >> 1 & 1);
                    load_tile(a, a_addr + so);
                    AT(21)
                    const uint2 st = ln_stats(a, ds.ones);
                    AT(0)
                    ln_apply(a, st);
                    AT(1)
                    wg_fence();
                    gemm1_chunk<0>(d0, a, ds, 0);
                    wg_commit();
                    gemm1_chunk<96>(d1, a, ds, 0);
                    wg_commit();
                    AT(2)
                    wg_wait<1>();
                    AT(3)
                    gelu_sq<false, 0, 1>(d0, unused, sq, 0);
                    AT(4)
                    gelu_sq<false, 1, 2>(d0, unused, sq, 0);
                    AT(5)
                    gelu_sq<false, 2, 3>(d0, unused, sq, 0);
                    AT(6)
                    wg_fence();
                    gemm1_chunk<192>(d0, a, ds, zero);
                    wg_commit();
                    AT(7)
                    wg_wait<1>();
                    gelu_sq<false, 0, 1>(d1, unused, sq + SQC, 0);
                    AT(8)
                    gelu_sq<false, 1, 3>(d1, unused, sq + SQC, 0);
                    AT(9)
                    wg_fence();
                    gemm1_chunk<288>(d1, a, ds, zero);
                    wg_commit();
                    AT(10)
                    wg_wait<1>();
                    gelu_sq_reg(d0, hs2);
                    if (K_ANCH < 3) anchor(sq, hs2[4 * (K_ANCH % 3)], hs2[4 * (K_ANCH % 3) + 1], hs2[4 * (K_ANCH % 3) + 2], hs2[4 * (K_ANCH % 3) + 3]);
                    wg_wait<0>();
                    AT(11)
                    gelu_sq_reg(d1, hs3);
#undef AT
                    so = so_sum - so;
                    bo = bo_sum - bo;
                    off += step;
                    turn++;
                }
                if (!second) break;
                const int j = ntiles - second + (rank + second) % NCONS;
                second = 0;
                set_run(j, ntiles - NCONS, j + 4);
                }
                jt = ntiles - NCONS + rank;
                cur.slot = (bo - bar_a) >> 5;
                cur.par = turn >> 1 & 1;
                const uint32_t sq2 = sq - (SM_SQ + rank * SQ_WG) + SM_RING + (so_sum - so);
#pragma unroll
                for (int k = 0; k < 3; k++) {
                    sts128(sq2 + k * SQ_ROW, hs2[4 * k], hs2[4 * k + 1], hs2[4 * k + 2], hs2[4 * k + 3]);
                    sts128(sq2 + SQC + k * SQ_ROW, hs3[4 * k], hs3[4 * k + 1], hs3[4 * k + 2], hs3[4 * k + 3]);
                }
            }
            const bool last = jt + NCONS >= ntiles;
            if (last) {
                tile_off = tile_offset(wk.tile(jt));
                lds32(next_off, sb + SM_TILES + wg * 4);
                next_off = __shfl_sync(~0u, next_off, 0);
                if (elect_one()) {
                    prefetch_l2(reinterpret_cast<const char*>(x) + tile_off + w4 * WARP_BYTES, WARP_BYTES);
                    if (wg % ORDER_P >= ORDER_P - ORDER_Q) prefetch_l2(reinterpret_cast<const char*>(out) + next_off + w4 * WARP_BYTES, WARP_BYTES);
                }
            }
            uint32_t a[6][4], d0[24], d1[24], d3[24], k0[24];
#define AT(pos) \
    if (K_WAIT == pos && jt >= wk.lent) named_bar(4 + wgi, 256); \
    if ((K_LTOK ? K_LTOK : K_PASS) == pos && jt >= wk.lent && jt + 1 < ntiles) named_arrive(pass_to, 256);
            AT(20)
            mbar_wait(bar_a + cur.slot * 32, cur.par);
            load_tile(a, a_addr + cur.slot * SLOT_BYTES);
            AT(21)
            const uint2 st = ln_stats(a, ds.ones);
            AT(0)
            ln_apply(a, st);
            AT(1)
            if (!last) {
                store_at(a, tile_offset(wk.tile(jt)) + w4 * WARP_BYTES - sq_warp);
                __syncwarp();
                if (elect_one()) mbar_arrive(bar_e + cur.slot * 32);
                if (jt < wk.lent) {
                    jt += LENT;
                    cur.advance(LENT);
                    continue;
                }
            }
            wg_fence();
            gemm1_chunk<0>(d0, a, ds, 0);
            wg_commit();
            gemm1_chunk<96>(d1, a, ds, 0);
            wg_commit();
            const int sq_e = square_exp(bound_exp(max_w1(sq >> 4 & 31)));
            const uint32_t scale2 = pack_h2(pow2i(sq_e), pow2i(sq_e));
            AT(2)
            wg_wait<1>();
            AT(3)
            gelu_sq<true, 0, 1>(d0, k0, sq, scale2);
            AT(4)
            gelu_sq<true, 1, 2>(d0, k0, sq, scale2);
            AT(5)
            gelu_sq<true, 2, 3>(d0, k0, sq, scale2);
            AT(6)
            if (last) {
#pragma unroll
                for (int q = 0; q < 6; q++) sts128(sb + SM_RING + cur.slot * SLOT_BYTES + w4 * REGION_BYTES - sq_warp + sq + q * 512, k0[4 * q], k0[4 * q + 1], k0[4 * q + 2], k0[4 * q + 3]);
            }
            wg_fence();
            gemm1_chunk<192>(d0, a, ds, zero);
            wg_commit();
            AT(7)
            wg_wait<1>();
            gelu_sq<true, 0, 1>(d1, k1, sq + SQC, scale2);
            AT(8)
            gelu_sq<true, 1, 3>(d1, k1, sq + SQC, scale2);
            AT(9)
#undef AT
            wg_fence();
            gemm1_chunk<288>(d3, a, ds, 0);
            wg_commit();
            wg_wait<1>();
            const uint32_t sq2 = sq + (plain ? SM_RING + (cur.slot + 3) % NSLOT * SLOT_BYTES - (SM_SQ + rank * SQ_WG) : NCONS * SQ_WG);
            gelu_sq<true>(d0, k2, sq2, scale2);
            wg_wait<0>();
            gelu_sq<true>(d3, k3, sq2 + SQC, scale2);
            if (last) break;
            cur.advance(NCONS + ((jt < wk.nA && jt + NCONS >= wk.nA) ? 2 : 0));
            jt += NCONS;
        }
        {
            if (rank == NCONS - 1) {
                named_arrive(14, NTHREADS);
            } else {
                reduce(4 * rank + w4, (sq >> 4) & 31, false);
                named_arrive(15, CONS_THREADS);
                PROF(2);
                if (helps && rank == 0 && w4 == 0) signal(&sc->lent_out);
            }
        }
        {
            set_lane((sq >> 4) & 31);
            const uint32_t row = sb + SM_W2 + cw * 512 + lane16;
            uint32_t u[W2_EARLY][4], f2[4];
            mbar_wait(sb + BAR_W, 1);
#pragma unroll
            for (int nb = 0; nb < W2_EARLY; nb++) lds128(u[nb][0], u[nb][1], u[nb][2], u[nb][3], row + nb * 6144);
            named_bar(12, NTHREADS);
            PROF(3);
            stage = sb + SM_RING + (cur.slot + 3) % NSLOT * SLOT_BYTES + w4 * WARP_BYTES;
            if (K_XPOS == 0) stage_x();
            lds128(f2[0], f2[1], f2[2], f2[3], s_fac + cw * 64 + (lane16 >> 7) * 16);
            lds32(inv_rho2, s_red + RED_INV_RHO);
#pragma unroll
            for (int nb = 0; nb < 12; nb++) {
                uint32_t v[4];
                if (nb < W2_EARLY) { v[0] = u[nb % W2_EARLY][0]; v[1] = u[nb % W2_EARLY][1]; v[2] = u[nb % W2_EARLY][2]; v[3] = u[nb % W2_EARLY][3]; }
                else lds128(v[0], v[1], v[2], v[3], row + nb * 6144);
                sts128(row + nb * 6144, h_round8(h_mul(v[0], f2[0])), h_round8(h_mul(v[1], f2[1])), h_round8(h_mul(v[2], f2[2])), h_round8(h_mul(v[3], f2[3])));
            }
            if (K_BPOS == 1) load_bias(acc);
            fence_async();
            if (K_XPOS == 1) stage_x();
            named_arrive(3, NTHREADS);
            named_bar(2, CONS_THREADS);
        }
        PROF(4);
        {
            if (!K_BPOS) load_bias(acc);
            if (wgi > 0) {
                if (K_XPOS == 2) stage_x();
                named_bar(8 + wgi, 256);
            }
            if (K_BPOS == 2) load_bias(acc);
            pin(k1); pin(k2); pin(k3);
            wg_fence();
            gemm2_chunk<288>(acc, k3, ds);
            wg_commit();
            gemm2_chunk<(K_SWAP ? 192 : 96)>(acc, K_SWAP ? k2 : k1, ds);
            if (K_FINE) wg_commit();
            gemm2_chunk<(K_SWAP ? 96 : 192)>(acc, K_SWAP ? k1 : k2, ds);
            wg_commit();
            if (!K_LATE && wgi + 1 < NCONS) named_arrive(9 + wgi, 256);
            if ((K_XPOS == 2 && wgi == 0) || K_XPOS == 3) stage_x();
            wg_wait<1 + K_FINE>();
            uint32_t k0[24];
#pragma unroll
            for (int q = 0; q < 6; q++)
                lds128(k0[4 * q], k0[4 * q + 1], k0[4 * q + 2], k0[4 * q + 3], sb + SM_RING + cur.slot * SLOT_BYTES + w4 * REGION_BYTES + lane16 + q * 512);
            pin(k0);
            wg_fence();
            gemm2_chunk<0>(acc, k0, ds);
            wg_commit();
            if (K_LATE && wgi + 1 < NCONS) named_arrive(9 + wgi, 256);
            if (wgi == 0) named_arrive(8, 256);
            wg_wait<1 + K_FINE>();
            load_first();
            if (lane16 == 0) mbar_arrive(sb + BAR_PIN);
            mbar_wait(bar_r, rpar);
            wg_wait<0>();
            first = wg - 4;
        }
    }
    {
        const int nrest = ntiles - NCONS;
        auto lent = [&](uint32_t entry) { return &sc->lent[((wk.index * 4 + w4) * LENT + (entry & 3) - 1) * (8 * 96)]; };
        for (int jt = first; jt < nrest; jt += 4) {
            if (jt >= 0) {
            tile_off = next_off;
            lds32(next_off, sb + SM_TILES + (jt + 4) * 4);
            if (tile_off & 3) {
                uint32_t gl[2][24];
                const uint4* src = lent(tile_off) + (lane16 >> 4);
                auto fetch = [&](uint32_t (&v)[24], int c) {
#pragma unroll
                    for (int s = 0; s < 6; s++) ldg128(reinterpret_cast<uint32_t (&)[4]>(v[4 * s]), src + (6 * c + s) * 32);
                };
                tile_off &= ~3u;
                next_off = __shfl_sync(~0u, next_off, 0);
                stage_x();
                if (elect_one()) prefetch_l2(reinterpret_cast<const char*>(out) + next_off + w4 * WARP_BYTES, WARP_BYTES);
                load_bias(acc);
#pragma unroll
                for (int half = 0; half < 2; half++) {
                    fetch(gl[0], 2 * half);
                    fetch(gl[1], 2 * half + 1);
                    if (!half) {
                        named_bar(4 + wg, 256);
                        named_arrive(4 + ((wg + 1) & 3), 256);
                    }
                    pin(gl[0]); pin(gl[1]);
                    wg_fence();
                    if (half) gemm2_chunk<192>(acc, gl[0], ds); else gemm2_chunk<0>(acc, gl[0], ds);
                    if (half) gemm2_chunk<288>(acc, gl[1], ds); else gemm2_chunk<96>(acc, gl[1], ds);
                    wg_commit();
                    wg_wait<0>();
                }
                load_first();
                mbar_wait(bar_r, rpar);
            } else {
            uint32_t d0[12], d1[12], g0[12], g1[12];
            if (jt >= S2_FIRST && jt < nrest - K_TAIL) named_bar(4 + wg, 256);
            wg_fence();
            gemm1_chunk<0>(d0, a, ds, 0);
            wg_commit();
            gemm1_chunk<48>(d1, a, ds, 0);
            wg_commit();
            if (!K_B0 || jt) load_bias(acc);
            next_off = __shfl_sync(~0u, next_off, 0);
            const bool more = jt + 4 < nrest && !(next_off & 3);
            wg_wait<1>();
#define CNX_PASS if (jt + 1 >= S2_FIRST && jt + 1 < nrest - K_TAIL) named_arrive(4 + ((wg + 1) & 3), 256);
#define CNX_STEP(C, D, G)                                              \
    gelu_to(G, D);                                                     \
    if (C == 0 && jt == 0) {                                           \
        named_bar(3, NTHREADS);                                        \
        load_bias(acc);                                                \
    }                                                                  \
    if (3 * C == K_P2) { CNX_PASS }                                    \
    wg_fence();                                                        \
    if (C < 6) gemm1_chunk<48 * (C < 6 ? C + 2 : 0)>(D, a, ds, zero); \
    gemm2_chunk<48 * C>(acc, G, ds);                                  \
    wg_commit();                                                       \
    if (3 * C + 1 == K_P2) { CNX_PASS }                                \
    wg_wait<(C < 7 ? 1 : 0)>();                                        \
    if (3 * C + 2 == K_P2) { CNX_PASS }
            CNX_STEP(0, d0, g0)
            CNX_STEP(1, d1, g1)
            if (jt == 0) named_bar(8, 256);
            stage_x();
            if (elect_one()) {
                if (more) prefetch_l2(reinterpret_cast<const char*>(out) + next_off + w4 * WARP_BYTES, WARP_BYTES);
                else if (next_off & 3) prefetch_l2(lent(next_off), 8 * 96 * 16);
            }
            CNX_STEP(2, d0, g0)
            CNX_STEP(3, d1, g1)
            CNX_STEP(4, d0, g0)
            CNX_STEP(5, d1, g1)
            CNX_STEP(6, d0, g0)
            load_frags(more);
            if (lane16 == 0) mbar_arrive(sb + BAR_PIN);
            mbar_wait(bar_r, rpar);
            CNX_STEP(7, d1, g1)
#undef CNX_STEP
            }
            }
            epilogue(acc);
        }
    }
    PROF(5);
}

}

typedef CUresult (*EncodeTiledFn)(CUtensorMap*, CUtensorMapDataType, cuuint32_t, void*, const cuuint64_t*, const cuuint64_t*,
                                  const cuuint32_t*, const cuuint32_t*, CUtensorMapInterleave, CUtensorMapSwizzle,
                                  CUtensorMapL2promotion, CUtensorMapFloatOOBfill);

extern "C" void kernel_launch(void* const* d_in, const int* in_sizes, int n_in, void* d_out, int out_size) {
    using namespace cnx;
    static EncodeTiledFn encode = nullptr;
    static int num_sms = 0;
    static Scratch* scratch = nullptr;
    if (!encode) {
        void* fn = nullptr;
        cudaDriverEntryPointQueryResult qr;
        cudaGetDriverEntryPoint("cuTensorMapEncodeTiled", &fn, cudaEnableDefault, &qr);
        encode = (EncodeTiledFn)fn;
        cudaGetSymbolAddress((void**)&scratch, g_scratch);
        int dev = 0;
        cudaGetDevice(&dev);
        cudaDeviceGetAttribute(&num_sms, cudaDevAttrMultiProcessorCount, dev);
        if (num_sms > MAX_CTAS) num_sms = MAX_CTAS;
        cudaFuncSetAttribute(block_kernel, cudaFuncAttributeMaxDynamicSharedMemorySize, SM_TOTAL);
    }
    CUtensorMap tm;
    cuuint64_t dims[3] = {(cuuint64_t)CH, (cuuint64_t)IMG_W, (cuuint64_t)IMG_H};
    cuuint64_t strides[2] = {(cuuint64_t)CH * 2, (cuuint64_t)CH * 2 * IMG_W};
    cuuint32_t box[3] = {(cuuint32_t)CH, (cuuint32_t)REGION_PX, 1};
    cuuint32_t estr[3] = {1, 1, 1};
    encode(&tm, CU_TENSOR_MAP_DATA_TYPE_BFLOAT16, 3, d_in[0], dims, strides, box, estr, CU_TENSOR_MAP_INTERLEAVE_NONE,
           CU_TENSOR_MAP_SWIZZLE_NONE, CU_TENSOR_MAP_L2_PROMOTION_L2_128B, CU_TENSOR_MAP_FLOAT_OOB_FILL_NONE);
    Params pm = {};
    Descs& ds = pm.ds;
    for (int c = 0; c < 8; c++)
        for (int k = 0; k < 6; k++) ds.w1[c][k] = make_desc(SB + SM_W1 + c * 6 * 1536 + k * 256, 128, 1536);
    for (int k = 0; k < 24; k++) ds.w2[k] = make_desc(SB + SM_W2 + k * 256, 128, 6144);
    ds.ones = make_desc(SB + SM_ONES, 0, 0);
    CUtensorMap tw;
    cuuint64_t wdims[2] = {(cuuint64_t)EX, (cuuint64_t)CH};
    cuuint64_t wstrides[1] = {(cuuint64_t)EX * 2};
    cuuint32_t wbox[2] = {64, (cuuint32_t)CH};
    encode(&tw, CU_TENSOR_MAP_DATA_TYPE_BFLOAT16, 2, d_in[2], wdims, wstrides, wbox, estr, CU_TENSOR_MAP_INTERLEAVE_NONE,
           CU_TENSOR_MAP_SWIZZLE_128B, CU_TENSOR_MAP_L2_PROMOTION_L2_128B, CU_TENSOR_MAP_FLOAT_OOB_FILL_NONE);
    Split& sp = pm.sp;
    sp = {NTILES / num_sms, NTILES % num_sms, 1, 1 << 16, 0, {}};
    if (sp.per_cta + 9 > MAX_ROWS) return;
    if (sp.extra && sp.extra * (8 * LENT + 1) <= num_sms && sp.per_cta >= 5 * LENT + 7) {
        sp.period = num_sms / sp.extra;
        sp.inv_period = 65535 / sp.period + 1;
        sp.lenders = sp.extra;
        for (int l = 0; l < sp.extra; l++) {
            const Work w = get_work((l + 1) * sp.period - sp.period / 2 - 1, sp);
            for (int e = 0; e < LENT; e++) sp.lent_off[l * LENT + e] = tile_offset(w.tile(e));
            if (w.nA < 2 * LENT) sp.lenders = 0;
        }
    }
    pm.x = (const __nv_bfloat16*)d_in[0];
    pm.dw = (const __nv_bfloat16*)d_in[1];
    pm.w2 = (const __nv_bfloat16*)d_in[3];
    pm.gamma = (const __nv_bfloat16*)d_in[4];
    pm.beta = (const __nv_bfloat16*)d_in[5];
    pm.out = (__nv_bfloat16*)d_out;
    pm.sc = scratch;
    block_kernel<<<num_sms, NTHREADS, SM_TOTAL>>>(tm, tw, pm);
}
```

```cpp
#include <cuda_runtime.h>
#include <cuda_bf16.h>
#include <cuda_fp16.h>
#include <cuda.h>
#include <stdint.h>

namespace cnx {

constexpr int IMG_H = 512, IMG_W = 512, CH = 96, EX = 384;
constexpr int TILE_W = 64;
constexpr int NTILES = (IMG_W / TILE_W) * IMG_H;
constexpr int NSLOT = 6;
constexpr int REGION_PX = 18;
constexpr int REGION_BYTES = REGION_PX * CH * 2;
constexpr int SLOT_BYTES = 4 * REGION_BYTES;
constexpr int A_LBO = 144, A_SBO = 12 * A_LBO;
constexpr int PREFETCH_ROWS = 3;
constexpr int NCONS = 3;
constexpr int CONS_THREADS = 128 * NCONS;
constexpr int NTHREADS = 128 + CONS_THREADS;
constexpr int MAX_ROWS = 52;
constexpr int TILE_BYTES = TILE_W * CH * 2, WARP_BYTES = TILE_BYTES / 4;
#define K_PASS 4
#define K_WAIT 20
#define K_STG 5
#define K_REL 6
#define K_ANCH 2
#define K_CVT 0
#define K_CHAIN 3
#define K_OP 0
#define K_QS 0
#define K_GS 0
#define K_QR 0
#define K_GR 0
#define K_PD 0
#define K_PQ 0
#define K_PS 0
#define K_REQ 0x310
#define K_UNRV 6
constexpr int K_UNR = K_UNRV;
#define K_P0 4
#define K_R0 1
#define K_ORD 1
#define KA 288
#define KB 96
#define KC 192
#define KX(e) (e == 96 ? k1 : e == 192 ? k2 : k3)
#define W2_EARLY 9
#define S2_FIRST 1
#define ORDER_P 3
#define ORDER_Q 1
static_assert(MAX_ROWS <= 128, "one table entry per producer thread");
static_assert(2 * A_SBO == REGION_BYTES && REGION_BYTES % 128 == 0, "region layout");

constexpr uint32_t SB = 1024;
constexpr int SM_W1 = 0;
constexpr int SM_W2 = SM_W1 + CH * EX * 2;
constexpr int SM_RING = SM_W2 + CH * EX * 2;
constexpr int SM_BIASH = SM_RING + NSLOT * SLOT_BYTES;
constexpr int SM_RED = SM_BIASH + 384;
constexpr int RED_MAX = 0, RED_LAUNCH = 48, RED_INV_RHO = 52;
constexpr int SM_TILES = SM_RED + 256;
constexpr int SM_ONES = SM_TILES + MAX_ROWS * 4;
constexpr int SM_BAR = SM_ONES + 128;
constexpr int BAR_X = SM_BAR;
constexpr int BAR_A = BAR_X + NSLOT * 4 * 8;
constexpr int BAR_E = BAR_A + NSLOT * 4 * 8;
constexpr int BAR_PIN = BAR_E + NSLOT * 4 * 8;
constexpr int BAR_W = BAR_PIN + 8;
constexpr int BAR_F = BAR_W + 6 * 8;
constexpr int BAR_R = BAR_F + 8;
constexpr int SM_TOTAL = BAR_R + 16 * 8;
constexpr int SM_FILTER = SM_RING + (NSLOT - 1) * SLOT_BYTES + 9 * 128;
constexpr int SM_SQ = SM_W2;
constexpr int SQ_ROW = 128 * 16, SQ_HALF = 6 * SQ_ROW;
static_assert(SM_ONES % 16 == 0 && SM_TOTAL <= 232448, "shared memory budget");

constexpr float KZ = 0.3292034911525734f;
constexpr uint32_t GELU_C2 = 0x40d940d9u;
constexpr float INV_2KZ = 0.5f / KZ;
constexpr unsigned SPIN_LIMIT = 1u << 19;

constexpr int MAX_CTAS = 255;
constexpr int W2_GROUPS = EX / 8;
#define K_LENT 3
constexpr int LENT = K_LENT, MAX_LENDERS = MAX_CTAS / (8 * LENT + 1);
struct Scratch {
    uint32_t w2h[EX * CH / 2];
    float w2max[EX];
    float bias[CH + 32];
    unsigned long long sums[EX / 4][32];
    __device__ __forceinline__ unsigned long long* sum(int e) { return &sums[e >> 2][e & 3]; }
    uint4 lent[MAX_LENDERS * LENT * 8 * 4 * 3 * 32];
    unsigned launch, pad0[31], early, pad1[31], prep, pad2[31], lent_out, pad3[31];
};
__device__ __align__(128) Scratch g_scratch;

#define PROF(k)

__device__ __forceinline__ uint32_t smem_u32(const void* p) { return (uint32_t)__cvta_generic_to_shared(p); }
__device__ __forceinline__ void mbar_init(uint32_t bar, uint32_t cnt) {
    asm volatile("mbarrier.init.shared::cta.b64 [%0], %1;" ::"r"(bar), "r"(cnt) : "memory");
}
__device__ __forceinline__ void mbar_arrive(uint32_t bar) {
    asm volatile("mbarrier.arrive.shared::cta.b64 _, [%0];" ::"r"(bar) : "memory");
}
__device__ __forceinline__ void mbar_expect_tx(uint32_t bar, uint32_t bytes) {
    asm volatile("mbarrier.arrive.expect_tx.shared::cta.b64 _, [%0], %1;" ::"r"(bar), "r"(bytes) : "memory");
}
__device__ __forceinline__ bool mbar_try(uint32_t bar, uint32_t par) {
    uint32_t ok;
    asm volatile("{\n.reg .pred p;\nmbarrier.try_wait.parity.shared::cta.b64 p, [%1], %2;\nselp.u32 %0, 1, 0, p;\n}\n"
                 : "=r"(ok) : "r"(bar), "r"(par) : "memory");
    return ok != 0;
}
__device__ __forceinline__ void mbar_wait(uint32_t bar, uint32_t par) {
    unsigned n = 0;
    while (!mbar_try(bar, par)) {
        if (++n > SPIN_LIMIT) __trap();
    }
}
__device__ __forceinline__ bool mbar_test(uint32_t bar, uint32_t par) {
    uint32_t ok;
    asm volatile("{\n.reg .pred p;\nmbarrier.test_wait.parity.shared::cta.b64 p, [%1], %2;\nselp.u32 %0, 1, 0, p;\n}\n"
                 : "=r"(ok) : "r"(bar), "r"(par) : "memory");
    return ok != 0;
}
__device__ __forceinline__ bool elect_one() {
    uint32_t ok;
    asm volatile("{\n.reg .pred p;\nelect.sync _|p, 0xffffffff;\nselp.u32 %0, 1, 0, p;\n}\n" : "=r"(ok));
    return ok != 0;
}
__device__ __forceinline__ uint32_t opaque(uint32_t v) { return __shfl_sync(~0u, v, threadIdx.x & 31); }
__device__ __forceinline__ float opaque(float v) { return __uint_as_float(opaque(__float_as_uint(v))); }
__device__ __forceinline__ uint32_t opaque_uniform(uint32_t v) { return __shfl_sync(~0u, v, 0); }
__device__ __forceinline__ void named_bar(int id, int n) { asm volatile("bar.sync %0, %1;" ::"r"(id), "r"(n) : "memory"); }
__device__ __forceinline__ void named_arrive(int id, int n) { asm volatile("bar.arrive %0, %1;" ::"r"(id), "r"(n) : "memory"); }
__device__ __forceinline__ void fence_async() { asm volatile("fence.proxy.async.shared::cta;" ::: "memory"); }
__device__ __forceinline__ uint64_t evict_first() {
    uint64_t p;
    asm("createpolicy.fractional.L2::evict_first.b64 %0, 1.0;" : "=l"(p));
    return p;
}
__device__ __forceinline__ void tma_row(uint32_t dst, const CUtensorMap* tm, uint32_t bar, int x, int y) {
    asm volatile("cp.async.bulk.tensor.3d.shared::cluster.global.mbarrier::complete_tx::bytes.L2::cache_hint [%0], [%1, {%3, %4, %5}], [%2], %6;"
                 ::"r"(dst), "l"(tm), "r"(bar), "r"(0), "r"(x), "r"(y), "l"(evict_first()) : "memory");
}
__device__ __forceinline__ void bulk_load_stream(uint32_t dst, const void* src, uint32_t bytes, uint32_t bar) {
    asm volatile("cp.async.bulk.shared::cluster.global.mbarrier::complete_tx::bytes.L2::cache_hint [%0], [%1], %2, [%3], %4;"
                 ::"r"(dst), "l"(src), "r"(bytes), "r"(bar), "l"(evict_first()) : "memory");
}
__device__ __forceinline__ void prefetch_l2(const void* src, uint32_t bytes) {
    asm volatile("cp.async.bulk.prefetch.L2.global [%0], %1;" ::"l"(src), "r"(bytes) : "memory");
}
__device__ __forceinline__ void tma_2d(uint32_t dst, const CUtensorMap* tm, uint32_t bar, int x, int y) {
    asm volatile("cp.async.bulk.tensor.2d.shared::cluster.global.mbarrier::complete_tx::bytes [%0], [%1, {%3, %4}], [%2];"
                 ::"r"(dst), "l"(tm), "r"(bar), "r"(x), "r"(y) : "memory");
}
__device__ __forceinline__ void bulk_load(uint32_t dst, const void* src, uint32_t bytes, uint32_t bar) {
    asm volatile("cp.async.bulk.shared::cluster.global.mbarrier::complete_tx::bytes [%0], [%1], %2, [%3];"
                 ::"r"(dst), "l"(src), "r"(bytes), "r"(bar) : "memory");
}
__device__ __forceinline__ void wg_fence() { asm volatile("wgmma.fence.sync.aligned;" ::: "memory"); }
__device__ __forceinline__ void wg_commit() { asm volatile("wgmma.commit_group.sync.aligned;" ::: "memory"); }
template <int N> __device__ __forceinline__ void wg_wait() { asm volatile("wgmma.wait_group.sync.aligned %0;" ::"n"(N) : "memory"); }
template <int N> __device__ __forceinline__ void pin(uint32_t (&d)[N]) {
#pragma unroll
    for (int q = 0; q < N; q++) asm volatile("" : "+r"(d[q])::"memory");
}
__device__ __forceinline__ void stg128(void* p, const uint32_t (&v)[4]) {
    asm volatile("st.global.v4.u32 [%0], {%1, %2, %3, %4};" ::"l"(p), "r"(v[0]), "r"(v[1]), "r"(v[2]), "r"(v[3]) : "memory");
}
__device__ __forceinline__ void ldg128(uint32_t (&v)[4], const void* p) {
    asm volatile("ld.global.L1::no_allocate.v4.u32 {%0, %1, %2, %3}, [%4];" : "=r"(v[0]), "=r"(v[1]), "=r"(v[2]), "=r"(v[3]) : "l"(p) : "memory");
}
__device__ __forceinline__ void ldg128_if(bool on, uint32_t (&v)[4], const void* p) {
    asm volatile("{\n.reg .pred p;\nsetp.ne.b32 p, %5, 0;\n@p ld.global.L1::no_allocate.v4.u32 {%0, %1, %2, %3}, [%4];\n}\n"
                 : "+r"(v[0]), "+r"(v[1]), "+r"(v[2]), "+r"(v[3]) : "l"(p), "r"((int)on) : "memory");
}
__device__ __forceinline__ uint4 ldg128_ordered(const void* p) {
    uint4 v;
    asm volatile("ld.global.nc.v4.u32 {%0, %1, %2, %3}, [%4];" : "=r"(v.x), "=r"(v.y), "=r"(v.z), "=r"(v.w) : "l"(p) : "memory");
    return v;
}
__host__ __device__ constexpr uint64_t make_desc(uint32_t addr, uint32_t lbo, uint32_t sbo) {
    return (uint64_t)((addr & 0x3FFFF) >> 4) | ((uint64_t)(lbo >> 4) << 16) | ((uint64_t)(sbo >> 4) << 32);
}
__device__ __forceinline__ void wgmma(uint32_t (&d)[12], uint32_t a0, uint32_t a1, uint32_t a2, uint32_t a3, uint64_t db, int acc) {
    asm volatile("{\n.reg .pred p;\nsetp.ne.b32 p, %17, 0;\n"
                 "wgmma.mma_async.sync.aligned.m64n48k16.f16.f16.f16 "
                 "{%0, %1, %2, %3, %4, %5, %6, %7, %8, %9, %10, %11}, "
                 "{%12, %13, %14, %15}, %16, p, 1, 1, 0;\n}\n"
                 : "+r"(d[0]), "+r"(d[1]), "+r"(d[2]), "+r"(d[3]), "+r"(d[4]), "+r"(d[5]), "+r"(d[6]), "+r"(d[7]), "+r"(d[8]), "+r"(d[9]), "+r"(d[10]), "+r"(d[11])
                 : "r"(a0), "r"(a1), "r"(a2), "r"(a3), "l"(db), "r"(acc));
}
__device__ __forceinline__ void wgmma(uint32_t (&d)[24], uint32_t a0, uint32_t a1, uint32_t a2, uint32_t a3, uint64_t db, int acc) {
    asm volatile("{\n.reg .pred p;\nsetp.ne.b32 p, %29, 0;\n"
                 "wgmma.mma_async.sync.aligned.m64n96k16.f16.f16.f16 "
                 "{%0, %1, %2, %3, %4, %5, %6, %7, %8, %9, %10, %11, %12, %13, %14, %15, %16, %17, %18, %19, %20, %21, %22, %23}, "
                 "{%24, %25, %26, %27}, %28, p, 1, 1, 0;\n}\n"
                 : "+r"(d[0]), "+r"(d[1]), "+r"(d[2]), "+r"(d[3]), "+r"(d[4]), "+r"(d[5]), "+r"(d[6]), "+r"(d[7]), "+r"(d[8]), "+r"(d[9]), "+r"(d[10]), "+r"(d[11]), "+r"(d[12]), "+r"(d[13]), "+r"(d[14]), "+r"(d[15]), "+r"(d[16]), "+r"(d[17]), "+r"(d[18]), "+r"(d[19]), "+r"(d[20]), "+r"(d[21]), "+r"(d[22]), "+r"(d[23])
                 : "r"(a0), "r"(a1), "r"(a2), "r"(a3), "l"(db), "r"(acc));
}
template <int ACC>
__device__ __forceinline__ void wgmma_rowsum(float (&d)[4], const uint32_t (&a)[4], uint64_t ones) {
    asm volatile("{\n.reg .pred p;\nsetp.ne.b32 p, %9, 0;\n"
                 "wgmma.mma_async.sync.aligned.m64n8k16.f32.bf16.bf16 {%0, %1, %2, %3}, {%4, %5, %6, %7}, %8, p, 1, 1, 0;\n}\n"
                 : "+f"(d[0]), "+f"(d[1]), "+f"(d[2]), "+f"(d[3])
                 : "r"(a[0]), "r"(a[1]), "r"(a[2]), "r"(a[3]), "l"(ones), "n"(ACC));
}
__device__ __forceinline__ void ldsm4(uint32_t (&r)[4], uint32_t addr) {
    asm volatile("ldmatrix.sync.aligned.m8n8.x4.shared.b16 {%0, %1, %2, %3}, [%4];"
                 : "=r"(r[0]), "=r"(r[1]), "=r"(r[2]), "=r"(r[3]) : "r"(addr) : "memory");
}
__device__ __forceinline__ void ldsm4_t(uint32_t (&r)[4], uint32_t addr) {
    asm volatile("ldmatrix.sync.aligned.m8n8.x4.trans.shared.b16 {%0, %1, %2, %3}, [%4];"
                 : "=r"(r[0]), "=r"(r[1]), "=r"(r[2]), "=r"(r[3]) : "r"(addr) : "memory");
}
__device__ __forceinline__ void stsm4(uint32_t addr, uint32_t a, uint32_t b, uint32_t c, uint32_t d) {
    asm volatile("stmatrix.sync.aligned.m8n8.x4.shared.b16 [%0], {%1, %2, %3, %4};"
                 ::"r"(addr), "r"(a), "r"(b), "r"(c), "r"(d) : "memory");
}
__device__ __forceinline__ uint32_t transpose8x8(uint32_t v) {
    uint32_t d; asm volatile("movmatrix.sync.aligned.m8n8.trans.b16 %0, %1;" : "=r"(d) : "r"(v)); return d;
}
__device__ __forceinline__ void spin_until(const unsigned* counter, unsigned target) {
    unsigned n = 0, c;
    do {
        asm volatile("ld.acquire.gpu.global.u32 %0, [%1];" : "=r"(c) : "l"(counter) : "memory");
        if (++n > SPIN_LIMIT) __trap();
    } while ((int)(c - target) < 0);
}
__device__ __forceinline__ void signal(unsigned* counter) {
    __syncwarp();
    if (elect_one()) asm volatile("red.release.gpu.global.add.u32 [%0], 1;" ::"l"(counter) : "memory");
    __syncwarp();
}
__device__ __forceinline__ void lds128(uint32_t& a, uint32_t& b, uint32_t& c, uint32_t& d, uint32_t addr) {
    asm volatile("ld.shared.v4.u32 {%0, %1, %2, %3}, [%4];" : "=r"(a), "=r"(b), "=r"(c), "=r"(d) : "r"(addr) : "memory");
}
__device__ __forceinline__ void lds64(uint32_t& a, uint32_t& b, uint32_t addr) {
    asm volatile("ld.shared.v2.u32 {%0, %1}, [%2];" : "=r"(a), "=r"(b) : "r"(addr) : "memory");
}
__device__ __forceinline__ void lds32(uint32_t& a, uint32_t addr) {
    asm volatile("ld.shared.u32 %0, [%1];" : "=r"(a) : "r"(addr) : "memory");
}
__device__ __forceinline__ int ldsi(uint32_t addr) {
    uint32_t v;
    lds32(v, addr);
    return (int)v;
}
__device__ __forceinline__ float ldsf(uint32_t addr) {
    uint32_t v;
    lds32(v, addr);
    return __uint_as_float(v);
}
__device__ __forceinline__ void sts32(uint32_t addr, uint32_t a) {
    asm volatile("st.shared.u32 [%0], %1;" ::"r"(addr), "r"(a) : "memory");
}
__device__ __forceinline__ void sts128(uint32_t addr, uint32_t a, uint32_t b, uint32_t c, uint32_t d) {
    asm volatile("st.shared.v4.u32 [%0], {%1, %2, %3, %4};" ::"r"(addr), "r"(a), "r"(b), "r"(c), "r"(d) : "memory");
}
__device__ __forceinline__ void sts64(uint32_t addr, uint32_t a, uint32_t b) {
    asm volatile("st.shared.v2.u32 [%0], {%1, %2};" ::"r"(addr), "r"(a), "r"(b) : "memory");
}
__device__ __forceinline__ void anchor(uint32_t addr, uint32_t a, uint32_t b, uint32_t c, uint32_t d) {
    asm volatile("{\n.reg .pred p;\nsetp.eq.b32 p, %0, 0;\n@p st.shared.v4.u32 [%0], {%1, %2, %3, %4};\n}\n"
                 ::"r"(addr), "r"(a), "r"(b), "r"(c), "r"(d) : "memory");
}
__device__ __forceinline__ uint32_t bf_fma(uint32_t a, uint32_t b, uint32_t c) {
    uint32_t d; asm("fma.rn.bf16x2 %0, %1, %2, %3;" : "=r"(d) : "r"(a), "r"(b), "r"(c)); return d;
}
__device__ __forceinline__ uint32_t bf_mul(uint32_t a, uint32_t b) {
    uint32_t d; asm("mul.rn.bf16x2 %0, %1, %2;" : "=r"(d) : "r"(a), "r"(b)); return d;
}
__device__ __forceinline__ uint32_t bf_absmax(uint32_t a, uint32_t b) {
    uint32_t d; asm("max.xorsign.abs.bf16x2 %0, %1, %2;" : "=r"(d) : "r"(a), "r"(b)); return d;
}
__device__ __forceinline__ uint32_t h_fma(uint32_t a, uint32_t b, uint32_t c) {
    uint32_t d; asm("fma.rn.f16x2 %0, %1, %2, %3;" : "=r"(d) : "r"(a), "r"(b), "r"(c)); return d;
}
__device__ __forceinline__ uint32_t h_mul(uint32_t a, uint32_t b) {
    uint32_t d; asm("mul.rn.f16x2 %0, %1, %2;" : "=r"(d) : "r"(a), "r"(b)); return d;
}
__device__ __forceinline__ uint32_t h_cut8(uint32_t v) { return v & 0xfff8fff8u; }
constexpr float CUT_GAIN = 1.f + 0.4375f * 0.7213f / 128;
__device__ __forceinline__ uint32_t h_tanh(uint32_t a) {
    uint32_t d; asm("tanh.approx.f16x2 %0, %1;" : "=r"(d) : "r"(a)); return d;
}
__device__ __forceinline__ uint32_t pack_h2(float lo, float hi) {
    uint32_t d; asm("cvt.rn.f16x2.f32 %0, %1, %2;" : "=r"(d) : "f"(hi), "f"(lo)); return d;
}
__device__ __forceinline__ uint32_t pack_bf2(float lo, float hi) {
    uint32_t d; asm("cvt.rn.bf16x2.f32 %0, %1, %2;" : "=r"(d) : "f"(hi), "f"(lo)); return d;
}
__device__ __forceinline__ float bf_lo(uint32_t v) { return __uint_as_float(v << 16); }
__device__ __forceinline__ float bf_hi(uint32_t v) { return __uint_as_float(v & 0xffff0000u); }
__device__ __forceinline__ float h_lo(uint32_t v) { return __low2float(*reinterpret_cast<__half2*>(&v)); }
__device__ __forceinline__ float h_hi(uint32_t v) { return __high2float(*reinterpret_cast<__half2*>(&v)); }
__device__ __forceinline__ float warp_absmax(uint32_t v) {
    return __uint_as_float(__reduce_max_sync(~0u, max((v & 0x7fffu) << 16, v & 0x7fff0000u)));
}
__device__ __forceinline__ uint32_t gelu2(uint32_t z) {
    uint32_t p = h_fma(z, z, GELU_C2);
    uint32_t t = h_tanh(K_OP & 1 ? h_mul(p, z) : h_mul(z, p));
    return K_OP & 2 ? h_fma(t, z, z) : h_fma(z, t, z);
}
__device__ __forceinline__ float pow2i(int e) { return __uint_as_float((uint32_t)(e + 127) << 23); }
__device__ __forceinline__ int ilog2f(float v) {
    int e = (int)((__float_as_uint(v) >> 23) & 0xff) - 127;
    return max(-100, min(100, e));
}

__device__ __forceinline__ int bound_exp(float w1max) { return w1max > 0.f ? ilog2f(2.f * KZ * 96.f * w1max) : 0; }
__device__ __forceinline__ bool plain_squares(int e) { return (unsigned)(4 - e) <= 6; }
__device__ __forceinline__ int square_exp(int e) { return plain_squares(e) ? 0 : max(-14, min(4 - e, 14)); }
__device__ __forceinline__ int sum_exp(int e) { return max(-90, min(90, 33 - 2 * e)); }
__device__ __forceinline__ int row_exp(float m) { return 2 - ilog2f(m); }

struct Split {
    int per_cta, extra, period, inv_period, lenders;
    uint32_t lent_off[MAX_LENDERS * LENT];
    __host__ __device__ __forceinline__ int longer_before(int cta) const {
        const int n = (cta + period / 2) * inv_period >> 16;
        return n < extra ? n : extra;
    }
};
struct Work {
    int tA, tB, nA, nB, dir, rows, lent, index;
    __host__ __device__ __forceinline__ int tile(int j) const { return j < nA ? tA + dir * j : tB + dir * (j - nA); }
};
__host__ __device__ __forceinline__ Work get_work(int cta, const Split& sp) {
    Work w;
    const int before = sp.longer_before(cta), longer = sp.longer_before(cta + 1) - before;
    w.lent = longer && sp.lenders ? LENT : 0;
    w.index = longer ? before : cta - before;
    const int t0 = cta * sp.per_cta + before, t1 = t0 + sp.per_cta + longer;
    const int tm = t1 < (t0 | 511) + 1 ? t1 : (t0 | 511) + 1;
    const bool swap = t1 > tm && t1 - tm < tm - t0, down = cta & 1;
    w.nA = swap ? t1 - tm : tm - t0;
    w.nB = t1 - t0 - w.nA;
    w.tA = down ? (swap ? tm : t0) : (swap ? t1 : tm) - 1;
    w.tB = down ? (swap ? t0 : tm) : (swap ? tm : t1) - 1;
    w.dir = down ? 1 : -1;
    w.rows = w.nA + 2 + (w.nB ? w.nB + 2 : 0);
    return w;
}
__device__ __forceinline__ int row_code(const Work& w, int i) {
    const bool in_a = i < w.nA + 2;
    const int t = in_a ? w.tA : w.tB;
    return ((t & 511) + w.dir * ((in_a ? i : i - (w.nA + 2)) - 1)) << 16 | (t >> 9) * TILE_W;
}
__host__ __device__ __forceinline__ uint32_t tile_offset(int tile) { return ((tile & 511) * IMG_W + (tile >> 9) * TILE_W) * (CH * 2); }
__device__ __forceinline__ int tile_order(int j, int n) {
    const int olds = (j / ORDER_P) * ORDER_Q + max(0, j % ORDER_P - (ORDER_P - ORDER_Q));
    return (j % ORDER_P >= ORDER_P - ORDER_Q) ? olds : n - 1 - (j - olds);
}
__device__ __forceinline__ void issue_region(const CUtensorMap* tm, uint32_t dst, uint32_t bar, int warp, int code) {
    mbar_expect_tx(bar, REGION_BYTES);
    tma_row(dst, tm, bar, (code & 0xffff) + (16 * warp - 1), code >> 16);
}

template <class Event>
__device__ __forceinline__ void conv_producer(const Work& wk, const CUtensorMap* tm, uint32_t sb, int warp, Event event) {
    const int lane = threadIdx.x & 31;
    const int j = lane & 15, grp = lane >> 4;
    const uint32_t reg0 = sb + SM_RING + warp * REGION_BYTES;
    const uint32_t bars = sb + SM_BAR + warp * 8;
    if (warp * 32 + lane < MAX_ROWS) {
        const int i = warp * 32 + lane, before = min(i / 5, wk.lent);
        const bool back = i % 5 == 0 && i > 0 && i / 5 <= wk.lent;
        sts32(sb + SM_TILES + i * 4, back ? tile_offset(wk.tile(before - 1)) | before
                                          : tile_offset(wk.tile(wk.lent + tile_order(i - before, wk.nA + wk.nB - 4 - wk.lent))));
    }
    const uint32_t ld64 = opaque(reg0 + grp * 8 * 192 + j * 8), ld32 = opaque(reg0 + grp * 8 * 192 + 128 + j * 4);
    const uint32_t st64 = opaque(reg0 + grp * A_SBO + (j >> 1) * A_LBO + (j & 1) * 8);
    const uint32_t st32 = opaque(reg0 + grp * A_SBO + (8 + (j >> 2)) * A_LBO + (j & 3) * 4);
    named_bar(0, NTHREADS);
    uint32_t w[3][3][3];
    mbar_wait(sb + BAR_F, 0);
#pragma unroll
    for (int tap = 0; tap < 9; tap++) {
        const uint32_t p = sb + SM_FILTER + (3 + wk.dir * 3 * (tap / 3 - 1) + tap % 3) * (CH * 2);
        lds64(w[tap / 3][tap % 3][0], w[tap / 3][tap % 3][1], p + 8 * j);
        lds32(w[tap / 3][tap % 3][2], p + 128 + 4 * j);
    }
#pragma unroll
    for (int tap = 0; tap < 9; tap++) sts64(reg0 + (NSLOT - 1) * SLOT_BYTES + tap * 128 + j * 8, w[tap / 3][tap % 3][1], w[tap / 3][tap % 3][0]);
    named_bar(1, 128);
#pragma unroll
    for (int tap = 0; tap < 9; tap++) lds64(w[tap / 3][tap % 3][1], w[tap / 3][tap % 3][0], reg0 + (NSLOT - 1) * SLOT_BYTES + tap * 128 + j * 8);
    static_assert(2 * PREFETCH_ROWS == NSLOT && SLOT_BYTES % 32 == 0, "slot arithmetic");
    uint32_t bo = 0, par = 0, pbo = PREFETCH_ROWS * 32, ppar = 1;
    int px, py;
    auto request = [&]() {
        mbar_wait(bars + (BAR_E - SM_BAR) + pbo, ppar);
        if (elect_one()) {
            mbar_expect_tx(bars + pbo, REGION_BYTES);
            tma_row(reg0 + pbo * (SLOT_BYTES / 32), tm, bars + pbo, px, py);
        }
    };
    auto advance = [&]() {
        bo += 32;
        if (bo == NSLOT * 32) { bo = 0; par ^= 1; }
        pbo += 32;
        if (pbo == NSLOT * 32) { pbo = 0; ppar ^= 1; }
    };
    auto aim = [&](int row) {
        const int code = row_code(wk, row);
        px = (code & 0xffff) + (16 * warp - 1);
        py = code >> 16;
    };
    uint32_t accB[8][3], accC[8][3];
    int r = 0;
#pragma unroll 1
    while (r < wk.rows) {
        if (r == 0 || r == wk.nA + 2) {
            const uint32_t bo0 = bo;
            uint32_t bo1;
#pragma unroll 1
            for (int k = 0; k < 2; k++, r++) {
                mbar_wait(bars + bo, par);
                bo1 = bo;
                if (r >= 2) {
                    aim(r + PREFETCH_ROWS);
                    request();
                }
                advance();
            }
            const uint32_t so0 = bo0 * (SLOT_BYTES / 32), so1 = bo1 * (SLOT_BYTES / 32);
#pragma unroll
            for (int p = 0; p < 10; p++) {
                uint32_t u[3], v[3];
                lds64(u[0], u[1], so0 + ld64 + p * 192);
                lds32(u[2], so0 + ld32 + p * 192);
                lds64(v[0], v[1], so1 + ld64 + p * 192);
                lds32(v[2], so1 + ld32 + p * 192);
#pragma unroll
                for (int dx = 0; dx < 3; dx++) {
                    const int o = p - dx;
                    if (o < 0 || o > 7) continue;
#pragma unroll
                    for (int q = 0; q < 3; q++) {
                        accB[o][q] = bf_fma(v[q], w[1][dx][q], dx == 0 ? bf_mul(u[q], w[0][dx][q]) : bf_fma(u[q], w[0][dx][q], accB[o][q]));
                        accC[o][q] = dx == 0 ? bf_mul(v[q], w[0][dx][q]) : bf_fma(v[q], w[0][dx][q], accC[o][q]);
                    }
                }
            }
            anchor(ld64, accB[7][0], accB[7][1], accB[7][2], 0);
            __syncwarp();
            if (elect_one()) {
                mbar_arrive(bars + (BAR_A - SM_BAR) + bo0);
                mbar_arrive(bars + (BAR_E - SM_BAR) + bo0);
                mbar_arrive(bars + (BAR_A - SM_BAR) + bo1);
                mbar_arrive(bars + (BAR_E - SM_BAR) + bo1);
            }
        }
        int end = wk.rows;
        const int marks[4] = {wk.rows - PREFETCH_ROWS, wk.rows - 11, wk.nA + 2, wk.nA + 2 - PREFETCH_ROWS};
#pragma unroll
        for (int k = 0; k < 4; k++) end = marks[k] > r ? min(end, marks[k]) : end;
        const bool fetch = r < wk.rows - PREFETCH_ROWS;
        aim(r + PREFETCH_ROWS);
        px = opaque_uniform(px);
        const int py_end = opaque_uniform(py + wk.dir * (end - r));
        r = end;
#pragma unroll 1
        do {
            mbar_wait(bars + bo, par);
            const uint32_t so = bo * (SLOT_BYTES / 32);
            uint32_t out[8][3];
#pragma unroll
            for (int p = 0; p < 10; p++) {
                uint32_t xv[3];
                lds64(xv[0], xv[1], so + ld64 + p * 192);
                lds32(xv[2], so + ld32 + p * 192);
#pragma unroll
                for (int dd = 0; dd < 3; dd++) {
                    const int dx = K_PD ? 2 - dd : dd, o = p - dx;
                    if (o < 0 || o > 7) continue;
#pragma unroll
                    for (int qq = 0; qq < 3; qq++) {
                        const int q = (qq + K_PQ) % 3;
                        out[o][q] = bf_fma(xv[q], w[2][dx][q], dx == 0 ? accB[o][q] : out[o][q]);
                        accB[o][q] = bf_fma(xv[q], w[1][dx][q], dx == 0 ? accC[o][q] : accB[o][q]);
                        accC[o][q] = dx == 0 ? bf_mul(xv[q], w[0][dx][q]) : bf_fma(xv[q], w[0][dx][q], accC[o][q]);
                    }
                }
            }
            __syncwarp();
#pragma unroll
            for (int oo = 0; oo < 8; oo++) {
                const int o = K_PS ? 7 - oo : oo;
                sts64(so + st64 + o * 16, out[o][0], out[o][1]);
                sts32(so + st32 + o * 16, out[o][2]);
            }
            __syncwarp();
            if (elect_one()) mbar_arrive(bars + (BAR_A - SM_BAR) + bo);
            if (fetch) request();
            advance();
            py += wk.dir;
        } while (py != py_end);
        if (((wk.rows - r) & ~8) == PREFETCH_ROWS) event(wk.rows - r == PREFETCH_ROWS);
    }
}

template <bool SCALED, int K0 = 0, int K1 = 3>
__device__ __forceinline__ void gelu_sq(uint32_t (&d)[24], uint32_t (&keep)[24], uint32_t sq_addr, uint32_t scale2) {
    pin(d);
#pragma unroll
    for (int k = K0; k < K1; k++) {
        uint32_t hs[4];
        lds128(hs[0], hs[1], hs[2], hs[3], sq_addr + k * SQ_ROW);
#pragma unroll
        for (int qq = 0; qq < 4; qq++) {
            const int q = K_QS == 0 ? qq : K_QS == 1 ? 3 - qq : K_QS == 2 ? (qq >> 1 | (qq & 1) << 1) : (qq + 1) & 3;
            uint32_t g0 = gelu2(d[8 * k + 2 * q]), g1 = gelu2(d[8 * k + 2 * q + 1]);
            keep[8 * k + 2 * q] = g0;
            keep[8 * k + 2 * q + 1] = g1;
            if (SCALED) { g0 = h_mul(g0, scale2); g1 = h_mul(g1, scale2); }
            hs[q] = (K_GS >> (q & 1) & 1) ? h_fma(g0, g0, h_fma(g1, g1, hs[q])) : h_fma(g1, g1, h_fma(g0, g0, hs[q]));
        }
        sts128(sq_addr + k * SQ_ROW, hs[0], hs[1], hs[2], hs[3]);
    }
}
__device__ __forceinline__ void gelu_sq_reg(uint32_t (&d)[24], uint32_t (&hs)[12]) {
    pin(d);
#pragma unroll
    for (int qq = 0; qq < 12; qq++) {
        const int q = K_QR == 0 ? qq : K_QR == 1 ? 11 - qq : K_QR == 2 ? qq ^ 1 : qq * 5 % 12;
        const uint32_t g0 = gelu2(d[2 * q]), g1 = gelu2(d[2 * q + 1]);
        hs[q] = (K_GR >> (q & 1) & 1) ? h_fma(g0, g0, h_fma(g1, g1, hs[q])) : h_fma(g1, g1, h_fma(g0, g0, hs[q]));
    }
}
__device__ __forceinline__ void gelu_to(uint32_t (&g)[12], uint32_t (&d)[12]) {
    pin(d);
#pragma unroll
    for (int q = 0; q < 12; q++) g[q] = gelu2(d[q]);
    pin(g);
}
__device__ __forceinline__ void load_tile(uint32_t (&raw)[6][4], uint32_t addr) {
#pragma unroll
    for (int s = 0; s < 6; s++) ldsm4(raw[s], addr + s * 2 * A_LBO);
}
__device__ __forceinline__ uint2 ln_stats(const uint32_t (&raw)[6][4], uint64_t ones) {
    constexpr int NS = 6 / K_CHAIN;
    uint32_t sq[NS][4];
#pragma unroll
    for (int s = 0; s < 6; s++)
#pragma unroll
        for (int q = 0; q < 4; q++) sq[s % NS][q] = s < NS ? bf_mul(raw[s][q], raw[s][q]) : bf_fma(raw[s][q], raw[s][q], sq[s % NS][q]);
    float sum[4], ssq[4];
    wg_fence();
    wgmma_rowsum<0>(sum, raw[0], ones);
#pragma unroll
    for (int s = 1; s < 6; s++) wgmma_rowsum<1>(sum, raw[s], ones);
    wgmma_rowsum<0>(ssq, sq[0], ones);
#pragma unroll
    for (int s = 1; s < NS; s++) wgmma_rowsum<1>(ssq, sq[s], ones);
    wg_commit();
    wg_wait<0>();
    uint32_t st[2];
#pragma unroll
    for (int h = 0; h < 2; h++) {
        asm volatile("" : "+f"(sum[2 * h]), "+f"(ssq[2 * h])::"memory");
        const float mean = sum[2 * h] * (1.f / CH);
        const float var = fmaxf(fmaf(ssq[2 * h], 1.f / CH, -mean * mean), 0.f);
        float rstd;
        asm("rsqrt.approx.ftz.f32 %0, %1;" : "=f"(rstd) : "f"(var + 1e-5f));
        rstd = bf_lo(pack_bf2(rstd * (K_CVT == 0 ? KZ : KZ * 0x1p-112f), 0.f));
        st[h] = pack_bf2(rstd, -mean * rstd);
    }
    return make_uint2(st[0], st[1]);
}
__device__ __forceinline__ void ln_apply(uint32_t (&a)[6][4], const uint2& st) {
    const uint32_t sc[2] = {__byte_perm(st.x, 0, 0x1010), __byte_perm(st.y, 0, 0x1010)};
    const uint32_t sh[2] = {__byte_perm(st.x, 0, 0x3232), __byte_perm(st.y, 0, 0x3232)};
#pragma unroll
    for (int s = 0; s < 6; s++)
#pragma unroll
        for (int q = 0; q < 4; q++) {
            const uint32_t v = bf_fma(a[s][q], sc[q & 1], sh[q & 1]);
            a[s][q] = K_CVT == 0 ? pack_h2(bf_lo(v), bf_hi(v)) : K_CVT == 1 ? (v & 0x7fff7fffu) * 7u + v : ((v << 3) & 0x7fff7fffu) | (v & 0x80008000u);
        }
}
struct Cursor {
    int slot;
    uint32_t par;
    __device__ __forceinline__ void advance(int n) {
        slot += n;
        if (slot >= NSLOT) { slot -= NSLOT; par ^= 1; }
    }
};
struct Descs {
    uint64_t w1[8][6];
    uint64_t w2[24];
    uint64_t ones;
};
template <int E0, int N>
__device__ __forceinline__ void gemm1_chunk(uint32_t (&d)[N], const uint32_t (&a)[6][4], const Descs& ds, int zero) {
#pragma unroll
    for (int s = 0; s < 6; s++) wgmma(d, a[s][0], a[s][1], a[s][2], a[s][3], ds.w1[E0 / 48][s], s ? 1 : zero);
}
template <int E0, int N>
__device__ __forceinline__ void gemm2_chunk(uint32_t (&acc)[24], const uint32_t (&g)[N], const Descs& ds) {
#pragma unroll
    for (int s = 0; s < N / 4; s++) wgmma(acc, g[4 * s], g[4 * s + 1], g[4 * s + 2], g[4 * s + 3], ds.w2[E0 / 16 + s], 1);
}

struct __align__(64) Params {
    Split sp;
    int zero;
    const __nv_bfloat16 *x, *dw, *w2, *gamma, *beta;
    __nv_bfloat16* out;
    Scratch* sc;
    Descs ds;
};

__global__ void __launch_bounds__(NTHREADS, 1)
block_kernel(const __grid_constant__ CUtensorMap tmap, const __grid_constant__ CUtensorMap tmap_w1, const __grid_constant__ Params pm) {
    const Split& sp = pm.sp;
    const Descs& ds = pm.ds;
    const int& zero = pm.zero;
    const __nv_bfloat16 *const &x = pm.x, *const &dw = pm.dw, *const &w2 = pm.w2, *const &gamma = pm.gamma, *const &beta = pm.beta;
    __nv_bfloat16* const& out = pm.out;
    Scratch* const& sc = pm.sc;
    extern __shared__ __align__(1024) uint8_t smem[];
    constexpr uint32_t sb = SB;
    const int tid = threadIdx.x;
    const Work wk = get_work(blockIdx.x, sp);
    constexpr uint32_t s_red = sb + SM_RED;
    if (smem_u32(smem) != SB) __trap();

    PROF(0);
    const int warp_id = __shfl_sync(~0u, tid >> 5, 0);
    const int cw = warp_id - 4, wgi = cw >> 2, w4 = warp_id & 3;
    if (elect_one()) {
        static_assert(3 * NSLOT * 4 == 8 + 4 * 16 && BAR_F == BAR_W + 48, "barrier shares");
        const int b = warp_id - 8;
        const uint32_t bar = b < 0 ? sb + BAR_X + warp_id * 8 : b < 7 ? sb + BAR_W + b * 8 : sb + BAR_PIN;
        mbar_init(bar, 1);
#pragma unroll
        for (int k = 0; k < 4; k++) mbar_init(sb + BAR_X + (8 + 4 * warp_id + k) * 8, 1);
        mbar_init(sb + BAR_R + warp_id * 8, 1);
        fence_async();
        if (b < 0) {
            issue_region(&tmap, sb + SM_RING + warp_id * REGION_BYTES, bar, w4, ((wk.tA & 511) + wk.dir * wgi) << 16 | (wk.tA >> 9) * TILE_W);
        } else if (b < 6) {
            mbar_expect_tx(bar, 64 * CH * 2);
            tma_2d(sb + SM_W2 + b * (64 * CH * 2), &tmap_w1, bar, 64 * b, 0);
        } else if (b == 6) {
            mbar_expect_tx(bar, 9 * CH * 2);
            bulk_load(sb + SM_FILTER, dw, 9 * CH * 2, bar);
        }
    }
    __syncwarp();
    const int ntiles = wk.nA + wk.nB;
    const int rank = wgi < 0 ? NCONS : (wgi + wk.lent + 2 * (ntiles - 1)) % NCONS;
    const int spare = wk.rows % NSLOT, spare2 = spare == NSLOT - 1 ? 0 : spare + 1;
    const uint32_t sq_base = sb + (wgi < 0 ? SM_RING + spare * SLOT_BYTES : SM_SQ + rank * 2 * SQ_HALF);
    const uint32_t sq_upper = wgi < 0 ? (spare2 - spare) * SLOT_BYTES : SQ_HALF;
    const uint32_t bar_a = sb + BAR_A + w4 * 8, bar_e = sb + BAR_E + w4 * 8;
    const bool helps = !wk.lent && wk.index < 8 * LENT * sp.lenders;
    auto max_w1 = [&](uint32_t lane) { return __uint_as_float(__reduce_max_sync(~0u, lane < 4 * NCONS ? ldsi(s_red + RED_MAX + lane * 4) : 0)); };
    auto square_scale = [&](uint32_t lane) {
        const float f = pow2i(square_exp(bound_exp(max_w1(lane))));
        return pack_h2(f, f);
    };
    uint32_t a_addr, sq;
    const uint32_t sq_warp = sq_base + w4 * 512;
    auto set_addresses = [&]() {
        a_addr = opaque(sb + SM_RING + w4 * REGION_BYTES + ((tid >> 3) & 1) * A_SBO + ((tid >> 4) & 1) * A_LBO + (tid & 7) * 16);
        sq = opaque(sq_base + (tid & 127) * 16);
    };
    uint32_t turn, turn_end, so, so_sum, bo, bo_sum, off;
    auto set_run = [&](int j, int stop, int row) {
        const int slot = row % NSLOT, both = 2 * (row % 3) + 3;
        turn = opaque_uniform(row / 3);
        turn_end = opaque_uniform(row / 3 + max(stop - j + NCONS - 1, 0) / NCONS);
        so = opaque_uniform(slot * SLOT_BYTES);
        so_sum = opaque_uniform(both * SLOT_BYTES);
        bo = opaque_uniform(bar_a + slot * 32);
        bo_sum = opaque_uniform(2 * bar_a + both * 32);
        off = opaque_uniform(tile_offset(wk.tile(j)) + w4 * WARP_BYTES - sq_warp);
    };
    const int nrest = ntiles - 4;
    int jt;
    Cursor cur;
    bool fast;
    if (warp_id < 4) {
        const bool prepares = gridDim.x - blockIdx.x <= W2_GROUPS / 2;
        const int q = (gridDim.x - 1 - blockIdx.x) * 2 + (w4 >> 1);
        conv_producer(wk, &tmap, sb, warp_id, [&](bool second) {
            if (!second) {
                if (blockIdx.x == 0) {
#pragma unroll 1
                    for (int e = tid; e < EX; e += 128) *sc->sum(e) = 0;
                    sc->bias[tid] = 0.f;
                    signal(&sc->early);
                }
                if (wk.lent) signal(&sc->early);
            } else if (prepares || helps) {
                spin_until(&sc->early, (ldsi(s_red + RED_LAUNCH) + 1) * 4 * (sp.lenders + 1));
                if (elect_one()) {
                    if (helps) prefetch_l2(reinterpret_cast<const char*>(out) + sp.lent_off[wk.index / 8] + w4 * WARP_BYTES, WARP_BYTES);
                    if (prepares) { prefetch_l2(w2 + 8 * q * CH, 8 * CH * 2); prefetch_l2(beta + 8 * q, 16); }
                }
            }
        });
        set_addresses();
        const int lane = sq >> 4 & 31, g = lane >> 2, t = lane & 3;
        if (prepares) {
            const int half = w4 & 1;
            uint32_t u[3][2], rmax = 0;
#pragma unroll
            for (int m = 0; m < 3; m++) {
                const uint4 w = ldg128_ordered(w2 + (8 * q + g) * CH + 32 * m + 8 * t);
                rmax = bf_absmax(bf_absmax(rmax, bf_absmax(w.x, w.y)), bf_absmax(w.z, w.w));
                u[m][0] = half ? w.z : w.x;
                u[m][1] = half ? w.w : w.y;
            }
            const float bt = __bfloat162float(beta[8 * q + g]);
            rmax = bf_absmax(rmax, __shfl_xor_sync(~0u, rmax, 1));
            rmax = bf_absmax(rmax, __shfl_xor_sync(~0u, rmax, 2));
            const float mx = fmaxf(fabsf(bf_lo(rmax)), fabsf(bf_hi(rmax))), rs = pow2i(row_exp(mx));
            if (t == 0 && !half) sc->w2max[8 * q + g] = mx;
#pragma unroll
            for (int m = 0; m < 3; m++) {
                float f[4];
#pragma unroll
                for (int k = 0; k < 2; k++) {
                    const float lo = bf_lo(u[m][k]), hi = bf_hi(u[m][k]);
                    sc->w2h[(4 * m + 2 * half + k) * 1536 + q * 32 + lane] = transpose8x8(pack_h2(lo * rs, hi * rs));
                    f[2 * k] = lo * bt;
                    f[2 * k + 1] = hi * bt;
                }
                const float r0 = (g & 2 ? f[2] : f[0]) + __shfl_xor_sync(~0u, g & 2 ? f[0] : f[2], 8);
                const float r1 = (g & 2 ? f[3] : f[1]) + __shfl_xor_sync(~0u, g & 2 ? f[1] : f[3], 8);
                float r = (g & 1 ? r1 : r0) + __shfl_xor_sync(~0u, g & 1 ? r0 : r1, 4);
                r += __shfl_xor_sync(~0u, r, 16);
                if (g < 4) atomicAdd(&sc->bias[32 * m + 8 * t + 4 * half + g], r);
            }
            asm volatile("fence.proxy.async.global;" ::: "memory");
            signal(&sc->prep);
        }
        mbar_wait(bar_e + spare * 32, (wk.rows - 6) / NSLOT & 1);
        mbar_wait(bar_e + spare2 * 32, (wk.rows - 5) / NSLOT & 1);
        named_bar(1, 128);
#pragma unroll
        for (int k = 0; k < 6; k++) { sts128(sq + k * SQ_ROW, 0, 0, 0, 0); sts128(sq + sq_upper + k * SQ_ROW, 0, 0, 0, 0); }
        if (helps) {
            const int piece = wk.index;
            uint32_t a[6][4], d[12], gl[12];
#pragma unroll
            for (int s = 0; s < 6; s++) ldg128(a[s], reinterpret_cast<const char*>(out) + sp.lent_off[piece / 8] + w4 * WARP_BYTES + lane * 16 + s * 512);
            const uint32_t scale2 = square_scale(lane);
            wg_fence();
#pragma unroll
            for (int s = 0; s < 6; s++) wgmma(d, a[s][0], a[s][1], a[s][2], a[s][3], ds.w1[0][s] + piece % 8 * (6 * 1536 / 16), s ? 1 : 0);
            wg_commit();
            wg_wait<0>();
            gelu_to(gl, d);
#pragma unroll
            for (int s = 0; s < 3; s++) {
                sc->lent[((piece / 8 * 4 + w4) * 24 + piece % 8 * 3 + s) * 32 + lane] = make_uint4(gl[4 * s], gl[4 * s + 1], gl[4 * s + 2], gl[4 * s + 3]);
                uint32_t hs[2];
#pragma unroll
                for (int k = 0; k < 2; k++) {
                    const uint32_t g0 = h_mul(gl[4 * s + 2 * k], scale2), g1 = h_mul(gl[4 * s + 2 * k + 1], scale2);
                    hs[k] = h_fma(g1, g1, h_mul(g0, g0));
                }
                const int pair = piece % 4 * 3 + s;
                sts64(sq + (piece & 4 ? sq_upper : 0) + (pair >> 1) * SQ_ROW + (pair & 1) * 8, hs[0], hs[1]);
            }
        }
        jt = ntiles - 1;
        cur.slot = spare ? spare - 1 : NSLOT - 1;
        cur.par = (wk.rows - 1) / NSLOT & 1;
        fast = false;
        turn = turn_end = so = so_sum = bo = bo_sum = off = 0;
    } else {
        set_addresses();
        if (wgi == NCONS - 1) named_arrive(4, 256);
        set_run(wk.lent + wgi, min(wk.nA, nrest), wk.lent + wgi + 2);
        jt = wgi < wk.lent ? wgi : wk.lent + wgi;
        cur = {2, 0};
        cur.advance(jt + (jt >= wk.nA ? 2 : 0));
        {
            const int ct = tid - 128, lane = tid & 31;
            const unsigned epoch = *reinterpret_cast<volatile unsigned*>(&sc->launch);
            const int r = lane & 7, mi = lane >> 3;
            const uint32_t src = sb + SM_W2 + (cw >> 1) * (64 * CH * 2) + r * 128 + ((((cw & 1) * 4 + mi) ^ r) * 16);
            const uint32_t dst = sb + SM_W1 + (4 * cw + mi) * 1536 + r * 16;
            const int code = row_code(wk, PREFETCH_ROWS - 1 + wgi);
            named_bar(0, NTHREADS);
            auto request = [&](int pos) {
                if ((K_REQ >> 4 * wgi & 15) == pos && elect_one())
                    issue_region(&tmap, sb + SM_RING + (PREFETCH_ROWS - 1 + wgi) * SLOT_BYTES + w4 * REGION_BYTES, sb + BAR_X + (cw + 8) * 8, w4, code);
                __syncwarp();
            };
            request(0);
            mbar_wait(sb + BAR_W + (cw >> 1) * 8, 0);
            request(1);
            uint32_t wmax[2] = {}, wsum[4] = {};
#pragma unroll K_UNR
            for (int c = 0; c < 12; c++) {
                uint32_t u[4];
                ldsm4_t(u, src + c * 1024);
#pragma unroll
                for (int q = 0; q < 4; q++) {
                    wmax[q & 1] = bf_absmax(wmax[q & 1], u[q]);
                    wsum[q] = bf_fma(u[q], 0x3f803f80u, wsum[q]);
                    u[q] = pack_h2(__uint_as_float(u[q] * (65536 + zero)), bf_hi(u[q]));
                }
                stsm4(dst + c * 128, u[0], u[1], u[2], u[3]);
            }
            request(2);
            const float w1max = warp_absmax(bf_absmax(wmax[0], wmax[1]));
            if (lane == 0) sts32(s_red + RED_MAX + cw * 4, __float_as_uint(w1max));
            bool center = false;
#pragma unroll
            for (int q = 0; q < 4; q++) {
#pragma unroll
                for (int o = 1; o <= 2; o <<= 1) wsum[q] = bf_fma(__shfl_xor_sync(~0u, wsum[q], o), 0x3f803f80u, wsum[q]);
                center |= fabsf(bf_lo(wsum[q]) + bf_hi(wsum[q])) > (0.15f * CH) * w1max;
            }
            if (__builtin_expect(__any_sync(~0u, center), 0)) {
                float mean[4] = {};
#pragma unroll 1
                for (int pass = 0; pass < 2; pass++) {
                    float sum[4] = {};
#pragma unroll 1
                    for (int c = 0; c < 12; c++) {
                        uint32_t u[4];
                        ldsm4_t(u, src + c * 1024);
#pragma unroll
                        for (int q = 0; q < 4; q++) {
                            sum[q] += bf_lo(u[q]) + bf_hi(u[q]);
                            u[q] = pack_h2(bf_lo(u[q]) - mean[q], bf_hi(u[q]) - mean[q]);
                        }
                        stsm4(dst + c * 128, u[0], u[1], u[2], u[3]);
                    }
#pragma unroll
                    for (int q = 0; q < 4; q++) {
                        sum[q] += __shfl_xor_sync(~0u, sum[q], 1);
                        sum[q] += __shfl_xor_sync(~0u, sum[q], 2);
                        mean[q] = sum[q] * (1.f / CH);
                    }
                }
            }
            if (!(cw & 2)) {
#pragma unroll
                for (int c = 0; c < 12; c++) sts128(src + c * 1024, 0, 0, 0, 0);
            }
            if (ct < 32) sts32(sb + SM_ONES + ct * 4, 0x3f803f80u);
            if (ct == 0) sts32(s_red + RED_LAUNCH, epoch);
            fence_async();
            named_bar(2, CONS_THREADS);
            request(3);
        }
        PROF(1);
        fast = __all_sync(~0u, plain_squares(bound_exp(max_w1(sq >> 4 & 31))));
        if (!fast) {
#pragma unroll 1
            for (int q = 0; q < 6; q++) sts128(sq + SQ_HALF + q * SQ_ROW, 0, 0, 0, 0);
        }
    }
    uint32_t k1[24], k2[24], k3[24], tile_off, next_off;
    constexpr int SQC = 3 * SQ_ROW;
    auto store_at = [&](const uint32_t (&a)[6][4], uint32_t off) {
        char* ap = reinterpret_cast<char*>(out) + (off + sq);
#pragma unroll
        for (int s = 0; s < 6; s++) stg128(ap + s * 512, a[s]);
    };
    const uint32_t own_bar = 4 + (wgi & 3), next_bar = 4 + (wgi == NCONS - 1 ? 0 : wgi + 1);
    for (;;) {
        if (fast && jt >= wk.lent) {
            uint32_t hs2[12] = {}, hs3[12] = {};
            const uint32_t step = wk.dir * (NCONS * IMG_W * CH * 2);
            int second = wk.nB;
#pragma unroll 1
            for (;;) {
#pragma unroll 1
                while (turn != turn_end) {
                    uint32_t a[6][4], d0[24], d1[24], unused[24];
#define AT(pos) \
    if (K_WAIT == pos) named_bar(own_bar, 256); \
    if (K_PASS == pos) named_arrive(next_bar, 256); \
    if (K_STG == pos) store_at(a, off); \
    if (K_REL == pos) { if (elect_one()) mbar_arrive(bo + (BAR_E - BAR_A)); }
                    AT(20)
                    mbar_wait(bo, turn >> 1 & 1);
                    load_tile(a, a_addr + so);
                    AT(21)
                    const uint2 st = ln_stats(a, ds.ones);
                    AT(0)
                    ln_apply(a, st);
                    AT(1)
                    wg_fence();
                    gemm1_chunk<0>(d0, a, ds, 0);
                    wg_commit();
                    gemm1_chunk<96>(d1, a, ds, 0);
                    wg_commit();
                    AT(2)
                    wg_wait<1>();
                    AT(3)
                    gelu_sq<false, 0, 1>(d0, unused, sq, 0);
                    AT(4)
                    gelu_sq<false, 1, 2>(d0, unused, sq, 0);
                    AT(5)
                    gelu_sq<false, 2, 3>(d0, unused, sq, 0);
                    AT(6)
                    wg_fence();
                    gemm1_chunk<192>(d0, a, ds, zero);
                    wg_commit();
                    AT(7)
                    wg_wait<1>();
                    gelu_sq<false, 0, 1>(d1, unused, sq + SQC, 0);
                    AT(8)
                    gelu_sq<false, 1, 3>(d1, unused, sq + SQC, 0);
                    AT(9)
                    wg_fence();
                    gemm1_chunk<288>(d1, a, ds, zero);
                    wg_commit();
                    AT(10)
                    wg_wait<1>();
                    gelu_sq_reg(d0, hs2);
                    if (K_ANCH < 3) anchor(sq, hs2[4 * (K_ANCH % 3)], hs2[4 * (K_ANCH % 3) + 1], hs2[4 * (K_ANCH % 3) + 2], hs2[4 * (K_ANCH % 3) + 3]);
                    wg_wait<0>();
                    AT(11)
                    gelu_sq_reg(d1, hs3);
#undef AT
                    so = so_sum - so;
                    bo = bo_sum - bo;
                    off += step;
                    turn++;
                }
                if (!second) break;
                const int j = ntiles - second + (rank + second + 2) % NCONS;
                second = 0;
                set_run(j, nrest, j + 4);
            }
            jt = nrest + rank;
            cur.slot = (bo - bar_a) >> 5;
            cur.par = turn >> 1 & 1;
#pragma unroll
            for (int k = 0; k < 3; k++) {
                sts128(sq + SQ_HALF + k * SQ_ROW, hs2[4 * k], hs2[4 * k + 1], hs2[4 * k + 2], hs2[4 * k + 3]);
                sts128(sq + SQ_HALF + SQC + k * SQ_ROW, hs3[4 * k], hs3[4 * k + 1], hs3[4 * k + 2], hs3[4 * k + 3]);
            }
        }
        const bool last = jt >= nrest;
        if (last) {
            tile_off = tile_offset(wk.tile(jt));
            lds32(next_off, sb + SM_TILES + rank * 4);
            next_off = __shfl_sync(~0u, next_off, 0);
            if (elect_one()) {
                prefetch_l2(reinterpret_cast<const char*>(x) + tile_off + w4 * WARP_BYTES, WARP_BYTES);
                if (rank % ORDER_P >= ORDER_P - ORDER_Q) prefetch_l2(reinterpret_cast<const char*>(out) + next_off + w4 * WARP_BYTES, WARP_BYTES);
            }
        }
        uint32_t a[6][4], d0[24], d1[24], d3[24], k0[24];
#define AT(pos) \
    if (K_WAIT == pos && jt >= wk.lent) named_bar(own_bar, 256); \
    if (K_PASS == pos && jt >= wk.lent && jt + 2 < ntiles) named_arrive(next_bar, 256); \
    if (K_P0 == pos && jt == nrest + K_R0) named_arrive(7, 256);
        AT(20)
        mbar_wait(bar_a + cur.slot * 32, cur.par);
        load_tile(a, a_addr + cur.slot * SLOT_BYTES);
        AT(21)
        const uint2 st = ln_stats(a, ds.ones);
        AT(0)
        ln_apply(a, st);
        AT(1)
        if (!last) {
            store_at(a, tile_offset(wk.tile(jt)) + w4 * WARP_BYTES - sq_warp);
            __syncwarp();
            if (elect_one()) mbar_arrive(bar_e + cur.slot * 32);
            if (jt < wk.lent) {
                jt += LENT;
                cur.advance(LENT);
                continue;
            }
        }
        wg_fence();
        gemm1_chunk<0>(d0, a, ds, 0);
        wg_commit();
        gemm1_chunk<96>(d1, a, ds, 0);
        wg_commit();
        const uint32_t scale2 = square_scale(sq >> 4 & 31);
        AT(2)
        wg_wait<1>();
        AT(3)
        gelu_sq<true, 0, 1>(d0, k0, sq, scale2);
        AT(4)
        gelu_sq<true, 1, 2>(d0, k0, sq, scale2);
        AT(5)
        gelu_sq<true, 2, 3>(d0, k0, sq, scale2);
        AT(6)
        if (last) {
#pragma unroll
            for (int q = 0; q < 6; q++)
                sts128(sb + SM_RING + cur.slot * SLOT_BYTES + w4 * REGION_BYTES - sq_warp + sq + q * 512, k0[4 * q], k0[4 * q + 1], k0[4 * q + 2], k0[4 * q + 3]);
        }
        wg_fence();
        gemm1_chunk<192>(d0, a, ds, zero);
        wg_commit();
        AT(7)
        wg_wait<1>();
        gelu_sq<true>(d1, k1, sq + SQC, scale2);
        AT(9)
#undef AT
        wg_fence();
        gemm1_chunk<288>(d3, a, ds, 0);
        wg_commit();
        wg_wait<1>();
        gelu_sq<true>(d0, k2, sq + sq_upper, scale2);
        wg_wait<0>();
        gelu_sq<true>(d3, k3, sq + sq_upper + SQC, scale2);
        if (last) break;
        cur.advance(NCONS + ((jt < wk.nA && jt + NCONS >= wk.nA) ? 2 : 0));
        jt += NCONS;
    }
    const uint32_t lane = sq >> 4 & 31;
    const uint32_t s_fac = sb + SM_RING + spare * SLOT_BYTES + SQ_HALF;
    uint32_t inv_rho2;
    {
        const bool leader = rank == 0 && w4 == 0 && lane == 0;
        const int i0 = w4 * 32 + lane;
        float base[3], slope[3], reach[3], to_square;
        float2 bpair = make_float2(0.f, 0.f);
        unsigned epoch;
        if (rank == 0) {
            float gam[3], rmax[3];
#pragma unroll
            for (int m = 0; m < 3; m++) {
                unsigned short v;
                asm volatile("ld.global.nc.u16 %0, [%1];" : "=h"(v) : "l"(gamma + i0 + 128 * m) : "memory");
                gam[m] = bf_lo(v);
            }
            epoch = ldsi(s_red + RED_LAUNCH);
            if (leader) {
                spin_until(&sc->prep, (epoch + 1) * 2 * W2_GROUPS);
                asm volatile("fence.proxy.async.global;" ::: "memory");
            }
            __syncwarp();
            named_bar(2, 128);
#pragma unroll
            for (int m = 0; m < 3; m++) rmax[m] = __ldcg(&sc->w2max[i0 + 128 * m]);
            if (i0 < 96) bpair = __ldcg(reinterpret_cast<const float2*>(&sc->bias[32 * (i0 % 24 >> 3) + 8 * (i0 / 24) + (i0 % 24 & 6)]));
            const float w1max = max_w1(lane);
            const float gbound = fmaxf(2.f * KZ * 9.7979590f * 192.f * w1max, 1.f) * 19.5959180f * INV_2KZ;
            const unsigned fixed = __reduce_max_sync(~0u, __float_as_uint(fmaf(gbound, fmaxf(fmaxf(rmax[0], rmax[1]), rmax[2]), fmaxf(fabsf(bpair.x), fabsf(bpair.y)))));
            if (lane == 0) sts32(s_red + 96 + w4 * 4, fixed);
#pragma unroll
            for (int m = 0; m < 3; m++) {
                base[m] = rmax[m] > 0.f ? pow2i(-row_exp(rmax[m])) * (INV_2KZ * CUT_GAIN) : 0.f;
                slope[m] = base[m] * gam[m];
                reach[m] = fabsf(gam[m]) * rmax[m] * gbound;
            }
            to_square = pow2i(-sum_exp(bound_exp(w1max))) * (INV_2KZ * INV_2KZ / 256);
        }
        if (rank >= 2) {
            named_arrive(12 + rank, CONS_THREADS);
        } else {
            const int rw = rank * 4 + w4, g = lane >> 2, t = lane & 3;
            const uint32_t pick = (g >> 1 & 1) == (t & 1) ? (g & 1 ? 0x3c000000u : 0x00003c00u) : 0;
            const int be = bound_exp(max_w1(lane));
            const float to_fixed = pow2i(sum_exp(be) - 2 * square_exp(be));
            unsigned long long* dst = sc->sum(64 * rw + 8 * t + 2 * (g & 3) + (g >> 2));
            float f[2][4] = {};
            named_bar(13, 256);
#pragma unroll 1
            for (int i = 0; i < 4; i++) {
                if (i == 2) {
                    named_bar(13, 256);
                    if (leader) {
                        fence_async();
                        mbar_expect_tx(sb + BAR_W, 4 * SQ_HALF);
                        bulk_load(sb + SM_W2, sc->w2h, 4 * SQ_HALF, sb + BAR_W);
                    }
                    __syncwarp();
                }
                const int from = i < 2 ? i : i ^ K_ORD;
                const uint32_t src = sb + lane * 16 + rw * 2 * SQ_ROW +
                                     (from < NCONS ? SM_SQ + from * 2 * SQ_HALF : rw < 3 ? SM_RING + spare * SLOT_BYTES : SM_RING + spare2 * SLOT_BYTES - SQ_HALF);
                if (i >= 2) named_bar(12 + from, CONS_THREADS);
                if (rw < 6) {
#pragma unroll
                    for (int r = 0; r < 8; r++) {
                        uint32_t u[4];
                        ldsm4_t(u, src + (r & 1) * SQ_ROW + (r >> 1) * 512);
#pragma unroll
                        for (int k = 0; k < 2; k++)
                            asm volatile("mma.sync.aligned.m16n8k16.row.col.f32.f16.f16.f32 {%0, %1, %2, %3}, {%4, %4, %4, %4}, {%5, %6}, {%0, %1, %2, %3};"
                                         : "+f"(f[r & 1][0]), "+f"(f[r & 1][1]), "+f"(f[r & 1][2]), "+f"(f[r & 1][3]) : "r"(pick), "r"(u[2 * k]), "r"(u[2 * k + 1]));
                    }
                }
            }
            if (rw < 6) {
#pragma unroll
                for (int r = 0; r < 2; r++)
                    atomicAdd(dst + r * (8 * 32), __float2ull_rn(fminf((g < 4 ? f[r][0] : f[r][1]) * to_fixed, 0x1p47f)) << 8 | 1);
            }
            PROF(2);
            named_bar(13, 256);
            if (leader) {
                fence_async();
                mbar_expect_tx(sb + BAR_W + 8, 2 * SQ_HALF);
                bulk_load(sb + SM_W2 + 4 * SQ_HALF, reinterpret_cast<const char*>(sc->w2h) + 4 * SQ_HALF, 2 * SQ_HALF, sb + BAR_W + 8);
            }
            if (helps && rw == 7) signal(&sc->lent_out);
        }
        if (rank == 0) {
            const uint32_t own_sum = (i0 >> 2) * 256 + (i0 & 3) * 8, own_fac = s_fac + i0 * 2;
            auto peek = [&](const void* p) {
                unsigned long long v;
                asm volatile("ld.relaxed.gpu.global.u64 %0, [%1];" : "=l"(v) : "l"(p) : "memory");
                return v;
            };
            const char* mine = reinterpret_cast<const char*>(sc->sums) + own_sum;
            unsigned n = 0;
            while (((unsigned)peek(sc->sum((blockIdx.x * 4 + w4) % (EX / 4) * 4)) & 255u) != gridDim.x)
                if (++n > SPIN_LIMIT) __trap();
            unsigned long long sum[3];
            for (;;) {
                bool all = true;
#pragma unroll
                for (int m = 0; m < 3; m++) {
                    sum[m] = peek(mine + m * (32 * 256));
                    all &= ((unsigned)sum[m] & 255u) == gridDim.x;
                }
                if (__all_sync(~0u, all)) break;
                if (++n > SPIN_LIMIT) __trap();
            }
            PROF(3);
            float gx[3];
#pragma unroll
            for (int m = 0; m < 3; m++) asm("sqrt.approx.ftz.f32 %0, %1;" : "=f"(gx[m]) : "f"(fmaf(__ull2float_rn(sum[m]), to_square, 1e-6f)));
            float tot = gx[0] + gx[1] + gx[2];
#pragma unroll
            for (int o = 16; o >= 1; o >>= 1) tot += __shfl_xor_sync(~0u, tot, o);
            const unsigned vwarp = __reduce_max_sync(~0u, __float_as_uint(fmaxf(fmaxf(reach[0] * gx[0], reach[1] * gx[1]), reach[2] * gx[2])));
            if (lane == 0) { sts32(s_red + 64 + w4 * 4, __float_as_uint(tot)); sts32(s_red + 80 + w4 * 4, vwarp); }
            named_bar(2, 128);
            uint32_t u[4], v[4], w[4];
            lds128(u[0], u[1], u[2], u[3], s_red + 64);
            lds128(v[0], v[1], v[2], v[3], s_red + 80);
            lds128(w[0], w[1], w[2], w[3], s_red + 96);
            tot = (__uint_as_float(u[0]) + __uint_as_float(u[1])) + (__uint_as_float(u[2]) + __uint_as_float(u[3]));
            const float vmax = __uint_as_float(max(max(v[0], v[1]), max(v[2], v[3]))), fmax2 = __uint_as_float(max(max(w[0], w[1]), max(w[2], w[3])));
            float inv_mean;
            asm("rcp.approx.ftz.f32 %0, %1;" : "=f"(inv_mean) : "f"(fmaf(tot, 1.f / EX, 1e-6f)));
            const int rho_e = 14 - ilog2f(fmaf(vmax, inv_mean, 2.f * fmax2));
            const float rho = pow2i(rho_e), inv_rho = pow2i(-rho_e);
            inv_rho2 = pack_bf2(inv_rho, inv_rho);
#pragma unroll
            for (int m = 0; m < 3; m++) {
                const float f = fmaf(slope[m] * gx[m], inv_mean, base[m]) * rho;
                asm volatile("st.shared.u16 [%0], %1;" ::"r"(own_fac + 256 * m), "h"((unsigned short)pack_h2(f, 0.f)) : "memory");
            }
            if (i0 < 96) sts32(sb + SM_BIASH + i0 * 4, pack_h2(bpair.x * rho, bpair.y * rho));
            if (i0 == 96) sts32(s_red + RED_INV_RHO, inv_rho2);
            named_arrive(12, NTHREADS);
            if (blockIdx.x == 0 && leader) sc->launch = epoch + 1;
            if (wk.lent) spin_until(&sc->lent_out, (epoch + 1) * 8 * LENT * sp.lenders);
        } else {
            const int rw = rank * 4 - 4 + w4;
            const uint32_t row = sb + SM_W2 + rw * 512 + lane * 16;
            uint32_t u[W2_EARLY][4], f2[4];
#pragma unroll
            for (int nb = 0; nb < W2_EARLY; nb++) {
                if (nb % 8 == 0) mbar_wait(sb + BAR_W + nb, 1);
                lds128(u[nb][0], u[nb][1], u[nb][2], u[nb][3], row + nb * 6144);
            }
            if (W2_EARLY <= 8) mbar_wait(sb + BAR_W + 8, 1);
            named_bar(12, NTHREADS);
            PROF(3);
            lds128(f2[0], f2[1], f2[2], f2[3], s_fac + rw * 64 + (lane >> 3) * 16);
            lds32(inv_rho2, s_red + RED_INV_RHO);
#pragma unroll
            for (int nb = 0; nb < 12; nb++) {
                uint32_t v[4];
                if (nb < W2_EARLY) { v[0] = u[nb % W2_EARLY][0]; v[1] = u[nb % W2_EARLY][1]; v[2] = u[nb % W2_EARLY][2]; v[3] = u[nb % W2_EARLY][3]; }
                else lds128(v[0], v[1], v[2], v[3], row + nb * 6144);
                sts128(row + nb * 6144, h_cut8(h_mul(v[0], f2[0])), h_cut8(h_mul(v[1], f2[1])), h_cut8(h_mul(v[2], f2[2])), h_cut8(h_mul(v[3], f2[3])));
            }
            fence_async();
            named_arrive(8, NTHREADS);
        }
    }
    uint32_t a[6][4], acc[24], rpar = 0;
    const uint32_t bias_addr = sb + SM_BIASH + (lane & 3) * 96, lane16 = lane * 16, lane_off = ((lane >> 2) * CH + 8 * (lane & 3)) * 2;
    const uint32_t stage = sb + SM_RING + (spare + rank) % NSLOT * SLOT_BYTES + w4 * WARP_BYTES, bar_r = sb + BAR_R + warp_id * 8;
    auto load_bias = [&]() {
#pragma unroll
        for (int q = 0; q < 6; q++) lds128(acc[4 * q], acc[4 * q + 1], acc[4 * q + 2], acc[4 * q + 3], bias_addr + q * 16);
    };
    auto load_frags = [&]() {
#pragma unroll
        for (int s = 0; s < 6; s++) ldg128(a[s], reinterpret_cast<const char*>(out) + next_off + w4 * WARP_BYTES + lane16 + s * 512);
    };
    auto stage_x = [&]() {
        if (elect_one()) {
            mbar_expect_tx(bar_r, WARP_BYTES);
            bulk_load_stream(stage, reinterpret_cast<const char*>(x) + tile_off + w4 * WARP_BYTES, WARP_BYTES, bar_r);
        }
    };
    {
        named_bar(8 + rank, rank ? 256 : NTHREADS);
        if (rank == 0) PROF(4);
        load_bias();
        pin(k1); pin(k2); pin(k3);
        wg_fence();
        gemm2_chunk<KA>(acc, KX(KA), ds);
        wg_commit();
        gemm2_chunk<KB>(acc, KX(KB), ds);
        wg_commit();
        gemm2_chunk<KC>(acc, KX(KC), ds);
        wg_commit();
        stage_x();
        wg_wait<2>();
        uint32_t k0[24];
#pragma unroll
        for (int q = 0; q < 6; q++)
            lds128(k0[4 * q], k0[4 * q + 1], k0[4 * q + 2], k0[4 * q + 3], sb + SM_RING + cur.slot * SLOT_BYTES + w4 * REGION_BYTES + lane16 + q * 512);
        pin(k0);
        wg_fence();
        gemm2_chunk<0>(acc, k0, ds);
        wg_commit();
        if (rank < NCONS) named_arrive(9 + rank, 256);
        wg_wait<2>();
        load_frags();
        if (lane16 == 0) mbar_arrive(sb + BAR_PIN);
        mbar_wait(bar_r, rpar);
        wg_wait<0>();
    }
    auto lent = [&](uint32_t entry) { return &sc->lent[((wk.index * LENT + (entry & 3) - 1) * 4 + w4) * (24 * 32)]; };
    for (jt = rank;; jt += 4) {
        {
            pin(acc);
            rpar ^= 1;
            uint4* op = reinterpret_cast<uint4*>(reinterpret_cast<char*>(out) + tile_off + w4 * WARP_BYTES + lane_off);
#pragma unroll
            for (int h = 0; h < 2; h++)
#pragma unroll
                for (int m = 0; m < 3; m++) {
                    uint32_t xin[4], o[4];
                    lds128(xin[0], xin[1], xin[2], xin[3], stage + lane_off + h * 1536 + m * 64);
#pragma unroll
                    for (int q = 0; q < 4; q++) {
                        const uint32_t v = acc[2 * (4 * m + q) + h];
                        o[q] = bf_fma(pack_bf2(h_lo(v), h_hi(v)), inv_rho2, xin[q]);
                    }
                    __stcs(op + h * 96 + m * 4, make_uint4(o[0], o[1], o[2], o[3]));
                }
            __syncwarp();
        }
        if (jt >= nrest) break;
        tile_off = next_off;
        lds32(next_off, sb + SM_TILES + (jt + 4) * 4);
        if (tile_off & 3) {
            uint32_t gl[2][24];
            const uint4* src = lent(tile_off) + lane;
            tile_off &= ~3u;
            next_off = __shfl_sync(~0u, next_off, 0);
            stage_x();
            if (elect_one()) prefetch_l2(reinterpret_cast<const char*>(out) + next_off + w4 * WARP_BYTES, WARP_BYTES);
            load_bias();
#pragma unroll
            for (int half = 0; half < 2; half++) {
#pragma unroll
                for (int s = 0; s < 12; s++) ldg128(reinterpret_cast<uint32_t (&)[4]>(gl[s / 6][4 * (s % 6)]), src + (12 * half + s) * 32);
                if (!half) {
                    named_bar(4 + rank, 256);
                    named_arrive(4 + ((rank + 1) & 3), 256);
                }
                pin(gl[0]); pin(gl[1]);
                wg_fence();
                if (half) gemm2_chunk<192>(acc, gl[0], ds); else gemm2_chunk<0>(acc, gl[0], ds);
                if (half) gemm2_chunk<288>(acc, gl[1], ds); else gemm2_chunk<96>(acc, gl[1], ds);
                wg_commit();
                wg_wait<0>();
            }
            load_frags();
            mbar_wait(bar_r, rpar);
        } else {
            uint32_t d0[12], d1[12], g0[12], g1[12];
            if (jt >= S2_FIRST) named_bar(4 + rank, 256);
            wg_fence();
            gemm1_chunk<0>(d0, a, ds, 0);
            wg_commit();
            gemm1_chunk<48>(d1, a, ds, 0);
            wg_commit();
            load_bias();
            next_off = __shfl_sync(~0u, next_off, 0);
            const bool more = jt + 4 < nrest && !(next_off & 3);
            wg_wait<1>();
#define CNX_STEP(C, D, G)                                              \
    gelu_to(G, D);                                                     \
    wg_fence();                                                        \
    if (C < 6) gemm1_chunk<48 * (C < 6 ? C + 2 : 0)>(D, a, ds, zero); \
    gemm2_chunk<48 * C>(acc, G, ds);                                  \
    wg_commit();                                                       \
    wg_wait<(C < 7 ? 1 : 0)>();
            CNX_STEP(0, d0, g0)
            CNX_STEP(1, d1, g1)
            if (jt + 1 >= S2_FIRST && jt + 1 < nrest) named_arrive(4 + ((rank + 1) & 3), 256);
            stage_x();
            if (elect_one()) {
                if (more) prefetch_l2(reinterpret_cast<const char*>(out) + next_off + w4 * WARP_BYTES, WARP_BYTES);
                else if (next_off & 3) prefetch_l2(lent(next_off), 24 * 32 * 16);
            }
            CNX_STEP(2, d0, g0)
            CNX_STEP(3, d1, g1)
            CNX_STEP(4, d0, g0)
            CNX_STEP(5, d1, g1)
            CNX_STEP(6, d0, g0)
#pragma unroll
            for (int s = 0; s < 6; s++) ldg128_if(more, a[s], reinterpret_cast<const char*>(out) + next_off + w4 * WARP_BYTES + lane16 + s * 512);
            if (lane16 == 0) mbar_arrive(sb + BAR_PIN);
            mbar_wait(bar_r, rpar);
            CNX_STEP(7, d1, g1)
#undef CNX_STEP
        }
    }
    PROF(5);
}

}

typedef CUresult (*EncodeTiledFn)(CUtensorMap*, CUtensorMapDataType, cuuint32_t, void*, const cuuint64_t*, const cuuint64_t*,
                                  const cuuint32_t*, const cuuint32_t*, CUtensorMapInterleave, CUtensorMapSwizzle,
                                  CUtensorMapL2promotion, CUtensorMapFloatOOBfill);

extern "C" void kernel_launch(void* const* d_in, const int* in_sizes, int n_in, void* d_out, int out_size) {
    using namespace cnx;
    static EncodeTiledFn encode = nullptr;
    static int num_sms = 0;
    static Scratch* scratch = nullptr;
    if (!encode) {
        void* fn = nullptr;
        cudaDriverEntryPointQueryResult qr;
        cudaGetDriverEntryPoint("cuTensorMapEncodeTiled", &fn, cudaEnableDefault, &qr);
        encode = (EncodeTiledFn)fn;
        cudaGetSymbolAddress((void**)&scratch, g_scratch);
        int dev = 0;
        cudaGetDevice(&dev);
        cudaDeviceGetAttribute(&num_sms, cudaDevAttrMultiProcessorCount, dev);
        if (num_sms > MAX_CTAS) num_sms = MAX_CTAS;
        cudaFuncSetAttribute(block_kernel, cudaFuncAttributeMaxDynamicSharedMemorySize, SM_TOTAL);
    }
    CUtensorMap tm;
    cuuint64_t dims[3] = {(cuuint64_t)CH, (cuuint64_t)IMG_W, (cuuint64_t)IMG_H};
    cuuint64_t strides[2] = {(cuuint64_t)CH * 2, (cuuint64_t)CH * 2 * IMG_W};
    cuuint32_t box[3] = {(cuuint32_t)CH, (cuuint32_t)REGION_PX, 1};
    cuuint32_t estr[3] = {1, 1, 1};
    encode(&tm, CU_TENSOR_MAP_DATA_TYPE_BFLOAT16, 3, d_in[0], dims, strides, box, estr, CU_TENSOR_MAP_INTERLEAVE_NONE,
           CU_TENSOR_MAP_SWIZZLE_NONE, CU_TENSOR_MAP_L2_PROMOTION_L2_128B, CU_TENSOR_MAP_FLOAT_OOB_FILL_NONE);
    Params pm = {};
    Descs& ds = pm.ds;
    for (int c = 0; c < 8; c++)
        for (int k = 0; k < 6; k++) ds.w1[c][k] = make_desc(SB + SM_W1 + c * 6 * 1536 + k * 256, 128, 1536);
    for (int k = 0; k < 24; k++) ds.w2[k] = make_desc(SB + SM_W2 + k * 256, 128, 6144);
    ds.ones = make_desc(SB + SM_ONES, 0, 0);
    CUtensorMap tw;
    cuuint64_t wdims[2] = {(cuuint64_t)EX, (cuuint64_t)CH};
    cuuint64_t wstrides[1] = {(cuuint64_t)EX * 2};
    cuuint32_t wbox[2] = {64, (cuuint32_t)CH};
    encode(&tw, CU_TENSOR_MAP_DATA_TYPE_BFLOAT16, 2, d_in[2], wdims, wstrides, wbox, estr, CU_TENSOR_MAP_INTERLEAVE_NONE,
           CU_TENSOR_MAP_SWIZZLE_128B, CU_TENSOR_MAP_L2_PROMOTION_L2_128B, CU_TENSOR_MAP_FLOAT_OOB_FILL_NONE);
    Split& sp = pm.sp;
    sp = {NTILES / num_sms, NTILES % num_sms, 1, 1 << 16, 0, {}};
    if (sp.per_cta + 9 > MAX_ROWS) return;
    if (sp.extra && sp.extra * (8 * LENT + 1) <= num_sms && sp.per_cta >= 5 * LENT + 8) {
        sp.period = num_sms / sp.extra;
        sp.inv_period = 65535 / sp.period + 1;
        sp.lenders = sp.extra;
        for (int l = 0; l < sp.extra; l++) {
            const Work w = get_work((l + 1) * sp.period - sp.period / 2 - 1, sp);
            for (int e = 0; e < LENT; e++) sp.lent_off[l * LENT + e] = tile_offset(w.tile(e));
            if (w.nA < 2 * LENT) sp.lenders = 0;
        }
    }
    pm.x = (const __nv_bfloat16*)d_in[0];
    pm.dw = (const __nv_bfloat16*)d_in[1];
    pm.w2 = (const __nv_bfloat16*)d_in[3];
    pm.gamma = (const __nv_bfloat16*)d_in[4];
    pm.beta = (const __nv_bfloat16*)d_in[5];
    pm.out = (__nv_bfloat16*)d_out;
    pm.sc = scratch;
    block_kernel<<<num_sms, NTHREADS, SM_TOTAL>>>(tm, tw, pm);
}
```

```cpp
#include <cuda_runtime.h>
#include <cuda_bf16.h>
#include <cuda_fp16.h>
#include <cuda.h>
#include <stdint.h>

namespace cnx {

constexpr int IMG_H = 512, IMG_W = 512, CH = 96, EX = 384;
constexpr int TILE_W = 64;
constexpr int NTILES = (IMG_W / TILE_W) * IMG_H;
constexpr int NSLOT = 6;
constexpr int REGION_PX = 18;
constexpr int REGION_BYTES = REGION_PX * CH * 2;
constexpr int SLOT_BYTES = 4 * REGION_BYTES;
constexpr int A_LBO = 144, A_SBO = 12 * A_LBO;
constexpr int PREFETCH_ROWS = 3;
constexpr int NCONS = 3;
constexpr int CONS_THREADS = 128 * NCONS;
constexpr int NTHREADS = 128 + CONS_THREADS;
constexpr int MAX_ROWS = 52;
constexpr int TILE_BYTES = TILE_W * CH * 2, WARP_BYTES = TILE_BYTES / 4;
#define K_PASS 4
#define K_WAIT 20
#define K_STG 5
#define K_REL 8
#define K_ANCH 2
#define K_CVT 0
#define K_CHAIN 3
#define K_OP 0
#define K_QS 0
#define K_GS 0
#define K_QR 0
#define K_GR 0
#define K_PD 0
#define K_PQ 0
#define K_PS 0
#define K_UNRV 3
constexpr int K_UNR = K_UNRV;
#define K_RW 0
#define K_P0 4
#define K_R0 1
#define K_ORD 0
#define KA 288
#define KB 96
#define KC 192
#define KX(e) (e == 96 ? k1 : e == 192 ? k2 : k3)
#define W2_EARLY 9
#define S2_FIRST 1
#define ORDER_P 3
#define ORDER_Q 1
static_assert(MAX_ROWS <= 128, "one table entry per producer thread");
static_assert(2 * A_SBO == REGION_BYTES && REGION_BYTES % 128 == 0, "region layout");

constexpr uint32_t SB = 1024;
constexpr int SM_W1 = 0;
constexpr int SM_W2 = SM_W1 + CH * EX * 2;
constexpr int SM_RING = SM_W2 + CH * EX * 2;
constexpr int SM_BIASH = SM_RING + NSLOT * SLOT_BYTES;
constexpr int SM_RED = SM_BIASH + 384;
constexpr int RED_MAX = 0, RED_LAUNCH = 48, RED_INV_RHO = 52;
constexpr int SM_TILES = SM_RED + 256;
constexpr int SM_ONES = SM_TILES + MAX_ROWS * 4;
constexpr int SM_BAR = SM_ONES + 128;
constexpr int BAR_X = SM_BAR;
constexpr int BAR_A = BAR_X + NSLOT * 4 * 8;
constexpr int BAR_E = BAR_A + NSLOT * 4 * 8;
constexpr int BAR_PIN = BAR_E + NSLOT * 4 * 8;
constexpr int BAR_W = BAR_PIN + 8;
constexpr int BAR_F = BAR_W + 6 * 8;
constexpr int BAR_R = BAR_F + 8;
constexpr int SM_TOTAL = BAR_R + 16 * 8;
constexpr int SM_FILTER = SM_RING + (NSLOT - 1) * SLOT_BYTES + 9 * 128;
constexpr int SM_SQ = SM_W2;
constexpr int SQ_ROW = 128 * 16, SQ_HALF = 6 * SQ_ROW;
static_assert(SM_ONES % 16 == 0 && SM_TOTAL <= 232448, "shared memory budget");

constexpr float KZ = 0.3292034911525734f;
constexpr uint32_t GELU_C2 = 0x40d940d9u;
constexpr float INV_2KZ = 0.5f / KZ;
constexpr unsigned SPIN_LIMIT = 1u << 19;

constexpr int MAX_CTAS = 255;
constexpr int W2_GROUPS = EX / 8;
#define K_LENT 3
constexpr int LENT = K_LENT, MAX_LENDERS = MAX_CTAS / (8 * LENT + 1);
struct Scratch {
    uint32_t w2h[EX * CH / 2];
    float w2max[EX];
    float bias[CH + 32];
    unsigned long long sums[EX / 4][32];
    __device__ __forceinline__ unsigned long long* sum(int e) { return &sums[e >> 2][e & 3]; }
    uint4 lent[MAX_LENDERS * LENT * 8 * 4 * 3 * 32];
    unsigned launch, pad0[31], early, pad1[31], prep, pad2[31], lent_out, pad3[31];
};
__device__ __align__(128) Scratch g_scratch;

#define PROF(k)

__device__ __forceinline__ uint32_t smem_u32(const void* p) { return (uint32_t)__cvta_generic_to_shared(p); }
__device__ __forceinline__ void mbar_init(uint32_t bar, uint32_t cnt) {
    asm volatile("mbarrier.init.shared::cta.b64 [%0], %1;" ::"r"(bar), "r"(cnt) : "memory");
}
__device__ __forceinline__ void mbar_arrive(uint32_t bar) {
    asm volatile("mbarrier.arrive.shared::cta.b64 _, [%0];" ::"r"(bar) : "memory");
}
__device__ __forceinline__ void mbar_expect_tx(uint32_t bar, uint32_t bytes) {
    asm volatile("mbarrier.arrive.expect_tx.shared::cta.b64 _, [%0], %1;" ::"r"(bar), "r"(bytes) : "memory");
}
__device__ __forceinline__ bool mbar_try(uint32_t bar, uint32_t par) {
    uint32_t ok;
    asm volatile("{\n.reg .pred p;\nmbarrier.try_wait.parity.shared::cta.b64 p, [%1], %2;\nselp.u32 %0, 1, 0, p;\n}\n"
                 : "=r"(ok) : "r"(bar), "r"(par) : "memory");
    return ok != 0;
}
__device__ __forceinline__ void mbar_wait(uint32_t bar, uint32_t par) {
    unsigned n = 0;
    while (!mbar_try(bar, par)) {
        if (++n > SPIN_LIMIT) __trap();
    }
}
__device__ __forceinline__ void mbar_wait_once(uint32_t bar, uint32_t par) {
    unsigned n = 0;
    bool ok;
#pragma unroll 1
    do {
        ok = mbar_try(bar, par);
        if (++n > SPIN_LIMIT) __trap();
    } while (!ok);
}
__device__ __forceinline__ bool elect_one() {
    uint32_t ok;
    asm volatile("{\n.reg .pred p;\nelect.sync _|p, 0xffffffff;\nselp.u32 %0, 1, 0, p;\n}\n" : "=r"(ok));
    return ok != 0;
}
__device__ __forceinline__ uint32_t opaque(uint32_t v) { return __shfl_sync(~0u, v, threadIdx.x & 31); }
__device__ __forceinline__ uint32_t lane_id() { uint32_t v; asm volatile("mov.u32 %0, %%laneid;" : "=r"(v)); return v; }
__device__ __forceinline__ uint32_t opaque_uniform(uint32_t v) { return __shfl_sync(~0u, v, 0); }
__device__ __forceinline__ void named_bar(int id, int n) { asm volatile("bar.sync %0, %1;" ::"r"(id), "r"(n) : "memory"); }
__device__ __forceinline__ void named_arrive(int id, int n) { asm volatile("bar.arrive %0, %1;" ::"r"(id), "r"(n) : "memory"); }
__device__ __forceinline__ void fence_async() { asm volatile("fence.proxy.async.shared::cta;" ::: "memory"); }
constexpr uint64_t EVICT_FIRST = 0x12F0000000000000ull;
__device__ __forceinline__ void tma_row(uint32_t dst, const CUtensorMap* tm, uint32_t bar, int x, int y) {
    asm volatile("cp.async.bulk.tensor.3d.shared::cluster.global.mbarrier::complete_tx::bytes.L2::cache_hint [%0], [%1, {%3, %4, %5}], [%2], %6;"
                 ::"r"(dst), "l"(tm), "r"(bar), "r"(0), "r"(x), "r"(y), "l"(EVICT_FIRST) : "memory");
}
__device__ __forceinline__ void bulk_load_stream(uint32_t dst, const void* src, uint32_t bytes, uint32_t bar) {
    asm volatile("cp.async.bulk.shared::cluster.global.mbarrier::complete_tx::bytes.L2::cache_hint [%0], [%1], %2, [%3], %4;"
                 ::"r"(dst), "l"(src), "r"(bytes), "r"(bar), "l"(EVICT_FIRST) : "memory");
}
__device__ __forceinline__ void prefetch_l2(const void* src, uint32_t bytes) {
    asm volatile("cp.async.bulk.prefetch.L2.global [%0], %1;" ::"l"(src), "r"(bytes) : "memory");
}
__device__ __forceinline__ void tma_2d(uint32_t dst, const CUtensorMap* tm, uint32_t bar, int x, int y) {
    asm volatile("cp.async.bulk.tensor.2d.shared::cluster.global.mbarrier::complete_tx::bytes [%0], [%1, {%3, %4}], [%2];"
                 ::"r"(dst), "l"(tm), "r"(bar), "r"(x), "r"(y) : "memory");
}
__device__ __forceinline__ void bulk_load(uint32_t dst, const void* src, uint32_t bytes, uint32_t bar) {
    asm volatile("cp.async.bulk.shared::cluster.global.mbarrier::complete_tx::bytes [%0], [%1], %2, [%3];"
                 ::"r"(dst), "l"(src), "r"(bytes), "r"(bar) : "memory");
}
__device__ __forceinline__ void wg_fence() { asm volatile("wgmma.fence.sync.aligned;" ::: "memory"); }
__device__ __forceinline__ void wg_commit() { asm volatile("wgmma.commit_group.sync.aligned;" ::: "memory"); }
template <int N> __device__ __forceinline__ void wg_wait() { asm volatile("wgmma.wait_group.sync.aligned %0;" ::"n"(N) : "memory"); }
template <int N> __device__ __forceinline__ void pin(uint32_t (&d)[N]) {
#pragma unroll
    for (int q = 0; q < N; q++) asm volatile("" : "+r"(d[q])::"memory");
}
__device__ __forceinline__ void stg128(void* p, const uint32_t (&v)[4]) {
    asm volatile("st.global.v4.u32 [%0], {%1, %2, %3, %4};" ::"l"(p), "r"(v[0]), "r"(v[1]), "r"(v[2]), "r"(v[3]) : "memory");
}
__device__ __forceinline__ void ldg128(uint32_t (&v)[4], const void* p) {
    asm volatile("ld.global.L1::no_allocate.v4.u32 {%0, %1, %2, %3}, [%4];" : "=r"(v[0]), "=r"(v[1]), "=r"(v[2]), "=r"(v[3]) : "l"(p) : "memory");
}
__device__ __forceinline__ void ldg128_if(bool on, uint32_t (&v)[4], const void* p) {
    asm volatile("{\n.reg .pred p;\nsetp.ne.b32 p, %5, 0;\n@p ld.global.L1::no_allocate.v4.u32 {%0, %1, %2, %3}, [%4];\n}\n"
                 : "+r"(v[0]), "+r"(v[1]), "+r"(v[2]), "+r"(v[3]) : "l"(p), "r"((int)on) : "memory");
}
__host__ __device__ constexpr uint64_t make_desc(uint32_t addr, uint32_t lbo, uint32_t sbo) {
    return (uint64_t)((addr & 0x3FFFF) >> 4) | ((uint64_t)(lbo >> 4) << 16) | ((uint64_t)(sbo >> 4) << 32);
}
__device__ __forceinline__ void wgmma(uint32_t (&d)[12], uint32_t a0, uint32_t a1, uint32_t a2, uint32_t a3, uint64_t db, int acc) {
    asm volatile("{\n.reg .pred p;\nsetp.ne.b32 p, %17, 0;\n"
                 "wgmma.mma_async.sync.aligned.m64n48k16.f16.f16.f16 "
                 "{%0, %1, %2, %3, %4, %5, %6, %7, %8, %9, %10, %11}, "
                 "{%12, %13, %14, %15}, %16, p, 1, 1, 0;\n}\n"
                 : "+r"(d[0]), "+r"(d[1]), "+r"(d[2]), "+r"(d[3]), "+r"(d[4]), "+r"(d[5]), "+r"(d[6]), "+r"(d[7]), "+r"(d[8]), "+r"(d[9]), "+r"(d[10]), "+r"(d[11])
                 : "r"(a0), "r"(a1), "r"(a2), "r"(a3), "l"(db), "r"(acc));
}
__device__ __forceinline__ void wgmma(uint32_t (&d)[24], uint32_t a0, uint32_t a1, uint32_t a2, uint32_t a3, uint64_t db, int acc) {
    asm volatile("{\n.reg .pred p;\nsetp.ne.b32 p, %29, 0;\n"
                 "wgmma.mma_async.sync.aligned.m64n96k16.f16.f16.f16 "
                 "{%0, %1, %2, %3, %4, %5, %6, %7, %8, %9, %10, %11, %12, %13, %14, %15, %16, %17, %18, %19, %20, %21, %22, %23}, "
                 "{%24, %25, %26, %27}, %28, p, 1, 1, 0;\n}\n"
                 : "+r"(d[0]), "+r"(d[1]), "+r"(d[2]), "+r"(d[3]), "+r"(d[4]), "+r"(d[5]), "+r"(d[6]), "+r"(d[7]), "+r"(d[8]), "+r"(d[9]), "+r"(d[10]), "+r"(d[11]), "+r"(d[12]), "+r"(d[13]), "+r"(d[14]), "+r"(d[15]), "+r"(d[16]), "+r"(d[17]), "+r"(d[18]), "+r"(d[19]), "+r"(d[20]), "+r"(d[21]), "+r"(d[22]), "+r"(d[23])
                 : "r"(a0), "r"(a1), "r"(a2), "r"(a3), "l"(db), "r"(acc));
}
template <int ACC>
__device__ __forceinline__ void wgmma_rowsum(float (&d)[4], const uint32_t (&a)[4], uint64_t ones) {
    asm volatile("{\n.reg .pred p;\nsetp.ne.b32 p, %9, 0;\n"
                 "wgmma.mma_async.sync.aligned.m64n8k16.f32.bf16.bf16 {%0, %1, %2, %3}, {%4, %5, %6, %7}, %8, p, 1, 1, 0;\n}\n"
                 : "+f"(d[0]), "+f"(d[1]), "+f"(d[2]), "+f"(d[3])
                 : "r"(a[0]), "r"(a[1]), "r"(a[2]), "r"(a[3]), "l"(ones), "n"(ACC));
}
__device__ __forceinline__ void ldsm4(uint32_t (&r)[4], uint32_t addr) {
    asm volatile("ldmatrix.sync.aligned.m8n8.x4.shared.b16 {%0, %1, %2, %3}, [%4];"
                 : "=r"(r[0]), "=r"(r[1]), "=r"(r[2]), "=r"(r[3]) : "r"(addr) : "memory");
}
__device__ __forceinline__ void ldsm4_t(uint32_t (&r)[4], uint32_t addr) {
    asm volatile("ldmatrix.sync.aligned.m8n8.x4.trans.shared.b16 {%0, %1, %2, %3}, [%4];"
                 : "=r"(r[0]), "=r"(r[1]), "=r"(r[2]), "=r"(r[3]) : "r"(addr) : "memory");
}
__device__ __forceinline__ void stsm4(uint32_t addr, uint32_t a, uint32_t b, uint32_t c, uint32_t d) {
    asm volatile("stmatrix.sync.aligned.m8n8.x4.shared.b16 [%0], {%1, %2, %3, %4};"
                 ::"r"(addr), "r"(a), "r"(b), "r"(c), "r"(d) : "memory");
}
__device__ __forceinline__ uint32_t transpose8x8(uint32_t v) {
    uint32_t d; asm volatile("movmatrix.sync.aligned.m8n8.trans.b16 %0, %1;" : "=r"(d) : "r"(v)); return d;
}
__device__ __forceinline__ void spin_until(const unsigned* counter, unsigned target) {
    unsigned n = 0, c;
    do {
        asm volatile("ld.acquire.gpu.global.u32 %0, [%1];" : "=r"(c) : "l"(counter) : "memory");
        if (++n > SPIN_LIMIT) __trap();
    } while ((int)(c - target) < 0);
}
__device__ __forceinline__ void signal(unsigned* counter) {
    __syncwarp();
    if (elect_one()) asm volatile("red.release.gpu.global.add.u32 [%0], 1;" ::"l"(counter) : "memory");
    __syncwarp();
}
__device__ __forceinline__ void lds128(uint32_t& a, uint32_t& b, uint32_t& c, uint32_t& d, uint32_t addr) {
    asm volatile("ld.shared.v4.u32 {%0, %1, %2, %3}, [%4];" : "=r"(a), "=r"(b), "=r"(c), "=r"(d) : "r"(addr) : "memory");
}
__device__ __forceinline__ void lds64(uint32_t& a, uint32_t& b, uint32_t addr) {
    asm volatile("ld.shared.v2.u32 {%0, %1}, [%2];" : "=r"(a), "=r"(b) : "r"(addr) : "memory");
}
__device__ __forceinline__ void lds32(uint32_t& a, uint32_t addr) {
    asm volatile("ld.shared.u32 %0, [%1];" : "=r"(a) : "r"(addr) : "memory");
}
__device__ __forceinline__ int ldsi(uint32_t addr) {
    uint32_t v;
    lds32(v, addr);
    return (int)v;
}
__device__ __forceinline__ float ldsf(uint32_t addr) {
    uint32_t v;
    lds32(v, addr);
    return __uint_as_float(v);
}
__device__ __forceinline__ void sts32(uint32_t addr, uint32_t a) {
    asm volatile("st.shared.u32 [%0], %1;" ::"r"(addr), "r"(a) : "memory");
}
__device__ __forceinline__ void sts128(uint32_t addr, uint32_t a, uint32_t b, uint32_t c, uint32_t d) {
    asm volatile("st.shared.v4.u32 [%0], {%1, %2, %3, %4};" ::"r"(addr), "r"(a), "r"(b), "r"(c), "r"(d) : "memory");
}
__device__ __forceinline__ void sts64(uint32_t addr, uint32_t a, uint32_t b) {
    asm volatile("st.shared.v2.u32 [%0], {%1, %2};" ::"r"(addr), "r"(a), "r"(b) : "memory");
}
__device__ __forceinline__ void anchor(uint32_t addr, uint32_t a, uint32_t b, uint32_t c, uint32_t d) {
    asm volatile("{\n.reg .pred p;\nsetp.eq.b32 p, %0, 0;\n@p st.shared.v4.u32 [%0], {%1, %2, %3, %4};\n}\n"
                 ::"r"(addr), "r"(a), "r"(b), "r"(c), "r"(d) : "memory");
}
__device__ __forceinline__ uint32_t bf_fma(uint32_t a, uint32_t b, uint32_t c) {
    uint32_t d; asm("fma.rn.bf16x2 %0, %1, %2, %3;" : "=r"(d) : "r"(a), "r"(b), "r"(c)); return d;
}
__device__ __forceinline__ uint32_t bf_mul(uint32_t a, uint32_t b) {
    uint32_t d; asm("mul.rn.bf16x2 %0, %1, %2;" : "=r"(d) : "r"(a), "r"(b)); return d;
}
__device__ __forceinline__ uint32_t bf_absmax(uint32_t a, uint32_t b) {
    uint32_t d; asm("max.xorsign.abs.bf16x2 %0, %1, %2;" : "=r"(d) : "r"(a), "r"(b)); return d;
}
__device__ __forceinline__ uint32_t h_fma(uint32_t a, uint32_t b, uint32_t c) {
    uint32_t d; asm("fma.rn.f16x2 %0, %1, %2, %3;" : "=r"(d) : "r"(a), "r"(b), "r"(c)); return d;
}
__device__ __forceinline__ uint32_t h_mul(uint32_t a, uint32_t b) {
    uint32_t d; asm("mul.rn.f16x2 %0, %1, %2;" : "=r"(d) : "r"(a), "r"(b)); return d;
}
__device__ __forceinline__ uint32_t h_cut8(uint32_t v) { return v & 0xfff8fff8u; }
constexpr float CUT_GAIN = 1.f + 0.4375f * 0.7213f / 128;
__device__ __forceinline__ uint32_t h_tanh(uint32_t a) {
    uint32_t d; asm("tanh.approx.f16x2 %0, %1;" : "=r"(d) : "r"(a)); return d;
}
__device__ __forceinline__ uint32_t pack_h2(float lo, float hi) {
    uint32_t d; asm("cvt.rn.f16x2.f32 %0, %1, %2;" : "=r"(d) : "f"(hi), "f"(lo)); return d;
}
__device__ __forceinline__ uint32_t pack_bf2(float lo, float hi) {
    uint32_t d; asm("cvt.rn.bf16x2.f32 %0, %1, %2;" : "=r"(d) : "f"(hi), "f"(lo)); return d;
}
__device__ __forceinline__ float bf_lo(uint32_t v) { return __uint_as_float(v << 16); }
__device__ __forceinline__ float bf_hi(uint32_t v) { return __uint_as_float(v & 0xffff0000u); }
__device__ __forceinline__ float h_lo(uint32_t v) { return __low2float(*reinterpret_cast<__half2*>(&v)); }
__device__ __forceinline__ float h_hi(uint32_t v) { return __high2float(*reinterpret_cast<__half2*>(&v)); }
__device__ __forceinline__ float warp_absmax(uint32_t v) {
    return __uint_as_float(__reduce_max_sync(~0u, max((v & 0x7fffu) << 16, v & 0x7fff0000u)));
}
__device__ __forceinline__ uint32_t gelu2(uint32_t z) {
    uint32_t p = h_fma(z, z, GELU_C2);
    uint32_t t = h_tanh(K_OP & 1 ? h_mul(p, z) : h_mul(z, p));
    return K_OP & 2 ? h_fma(t, z, z) : h_fma(z, t, z);
}
__device__ __forceinline__ float pow2i(int e) { return __uint_as_float((uint32_t)(e + 127) << 23); }
__device__ __forceinline__ int ilog2f(float v) {
    int e = (int)((__float_as_uint(v) >> 23) & 0xff) - 127;
    return max(-100, min(100, e));
}

__device__ __forceinline__ int bound_exp(float w1max) { return w1max > 0.f ? ilog2f(2.f * KZ * 96.f * w1max) : 0; }
__device__ __forceinline__ bool plain_squares(int e) { return (unsigned)(4 - e) <= 6; }
__device__ __forceinline__ int square_exp(int e) { return plain_squares(e) ? 0 : max(-14, min(4 - e, 14)); }
__device__ __forceinline__ int sum_exp(int e) { return max(-90, min(90, 33 - 2 * e)); }
__device__ __forceinline__ int row_exp(float m) { return 2 - ilog2f(m); }

struct Split {
    int per_cta, extra, period, inv_period, lenders;
    uint32_t lent_off[MAX_LENDERS * LENT];
    __host__ __device__ __forceinline__ int longer_before(int cta) const {
        const int n = (cta + period / 2) * inv_period >> 16;
        return n < extra ? n : extra;
    }
};
struct Work {
    int tA, tB, nA, nB, dir, rows, lent, index;
    __host__ __device__ __forceinline__ int tile(int j) const { return j < nA ? tA + dir * j : tB + dir * (j - nA); }
};
__host__ __device__ __forceinline__ Work get_work(int cta, const Split& sp) {
    Work w;
    const int before = sp.longer_before(cta), longer = sp.longer_before(cta + 1) - before;
    w.lent = longer && sp.lenders ? LENT : 0;
    w.index = longer ? before : cta - before;
    const int t0 = cta * sp.per_cta + before, t1 = t0 + sp.per_cta + longer;
    const int tm = t1 < (t0 | 511) + 1 ? t1 : (t0 | 511) + 1;
    const bool swap = t1 > tm && t1 - tm < tm - t0, down = cta & 1;
    w.nA = swap ? t1 - tm : tm - t0;
    w.nB = t1 - t0 - w.nA;
    w.tA = down ? (swap ? tm : t0) : (swap ? t1 : tm) - 1;
    w.tB = down ? (swap ? t0 : tm) : (swap ? tm : t1) - 1;
    w.dir = down ? 1 : -1;
    w.rows = w.nA + 2 + (w.nB ? w.nB + 2 : 0);
    return w;
}
__device__ __forceinline__ int row_code(const Work& w, int i) {
    const bool in_a = i < w.nA + 2;
    const int t = in_a ? w.tA : w.tB;
    return ((t & 511) + w.dir * ((in_a ? i : i - (w.nA + 2)) - 1)) << 16 | (t >> 9) * TILE_W;
}
__host__ __device__ __forceinline__ uint32_t tile_offset(int tile) { return ((tile & 511) * IMG_W + (tile >> 9) * TILE_W) * (CH * 2); }
__device__ __forceinline__ int tile_order(int j, int n) {
    const int olds = (j / ORDER_P) * ORDER_Q + max(0, j % ORDER_P - (ORDER_P - ORDER_Q));
    return (j % ORDER_P >= ORDER_P - ORDER_Q) ? olds : n - 1 - (j - olds);
}
__device__ __forceinline__ void issue_region(const CUtensorMap* tm, uint32_t dst, uint32_t bar, int warp, int code) {
    mbar_expect_tx(bar, REGION_BYTES);
    tma_row(dst, tm, bar, (code & 0xffff) + (16 * warp - 1), code >> 16);
}

template <class Event>
__device__ __forceinline__ void conv_producer(const Work& wk, const CUtensorMap* tm, uint32_t sb, int warp, Event event) {
    const int lane = threadIdx.x & 31;
    const int j = lane & 15, grp = lane >> 4;
    const uint32_t reg0 = sb + SM_RING + warp * REGION_BYTES;
    const uint32_t bars = sb + SM_BAR + warp * 8;
    if (warp * 32 + lane < MAX_ROWS) {
        const int i = warp * 32 + lane, before = min(i / 5, wk.lent);
        const bool back = i % 5 == 0 && i > 0 && i / 5 <= wk.lent;
        sts32(sb + SM_TILES + i * 4, back ? tile_offset(wk.tile(before - 1)) | before
                                          : tile_offset(wk.tile(wk.lent + tile_order(i - before, wk.nA + wk.nB - 4 - wk.lent))));
    }
    const uint32_t ld64 = opaque(reg0 + grp * 8 * 192 + j * 8), ld32 = opaque(reg0 + grp * 8 * 192 + 128 + j * 4);
    const uint32_t st64 = opaque(reg0 + grp * A_SBO + (j >> 1) * A_LBO + (j & 1) * 8);
    const uint32_t st32 = opaque(reg0 + grp * A_SBO + (8 + (j >> 2)) * A_LBO + (j & 3) * 4);
    named_bar(0, NTHREADS);
    uint32_t w[3][3][3];
    mbar_wait_once(sb + BAR_F, 0);
#pragma unroll
    for (int tap = 0; tap < 9; tap++) {
        const uint32_t p = sb + SM_FILTER + (3 + wk.dir * 3 * (tap / 3 - 1) + tap % 3) * (CH * 2);
        lds64(w[tap / 3][tap % 3][0], w[tap / 3][tap % 3][1], p + 8 * j);
        lds32(w[tap / 3][tap % 3][2], p + 128 + 4 * j);
    }
#pragma unroll
    for (int tap = 0; tap < 9; tap++) sts64(reg0 + (NSLOT - 1) * SLOT_BYTES + tap * 128 + j * 8, w[tap / 3][tap % 3][1], w[tap / 3][tap % 3][0]);
    named_bar(1, 128);
#pragma unroll
    for (int tap = 0; tap < 9; tap++) lds64(w[tap / 3][tap % 3][1], w[tap / 3][tap % 3][0], reg0 + (NSLOT - 1) * SLOT_BYTES + tap * 128 + j * 8);
    static_assert(2 * PREFETCH_ROWS == NSLOT && SLOT_BYTES % 32 == 0, "slot arithmetic");
    uint32_t bo = 0, par = 0, pbo = PREFETCH_ROWS * 32, ppar = 1;
    int px, py;
    auto request = [&]() {
        mbar_wait_once(bars + (BAR_E - SM_BAR) + pbo, ppar);
        if (elect_one()) {
            mbar_expect_tx(bars + pbo, REGION_BYTES);
            tma_row(reg0 + pbo * (SLOT_BYTES / 32), tm, bars + pbo, px, py);
        }
    };
    auto advance = [&]() {
        bo += 32;
        if (bo == NSLOT * 32) { bo = 0; par ^= 1; }
        pbo += 32;
        if (pbo == NSLOT * 32) { pbo = 0; ppar ^= 1; }
    };
    auto aim = [&](int row) {
        const int code = row_code(wk, row);
        px = (code & 0xffff) + (16 * warp - 1);
        py = code >> 16;
    };
    uint32_t accB[8][3], accC[8][3];
    int r = 0;
#pragma unroll 1
    while (r < wk.rows) {
        if (r == 0 || r == wk.nA + 2) {
            const uint32_t bo0 = bo;
            uint32_t bo1;
#pragma unroll 1
            for (int k = 0; k < 2; k++, r++) {
                mbar_wait_once(bars + bo, par);
                bo1 = bo;
                if (r >= 2) {
                    aim(r + PREFETCH_ROWS);
                    request();
                }
                advance();
            }
            const uint32_t so0 = bo0 * (SLOT_BYTES / 32), so1 = bo1 * (SLOT_BYTES / 32);
#pragma unroll
            for (int p = 0; p < 10; p++) {
                uint32_t u[3], v[3];
                lds64(u[0], u[1], so0 + ld64 + p * 192);
                lds32(u[2], so0 + ld32 + p * 192);
                lds64(v[0], v[1], so1 + ld64 + p * 192);
                lds32(v[2], so1 + ld32 + p * 192);
#pragma unroll
                for (int dx = 0; dx < 3; dx++) {
                    const int o = p - dx;
                    if (o < 0 || o > 7) continue;
#pragma unroll
                    for (int q = 0; q < 3; q++) {
                        accB[o][q] = bf_fma(v[q], w[1][dx][q], dx == 0 ? bf_mul(u[q], w[0][dx][q]) : bf_fma(u[q], w[0][dx][q], accB[o][q]));
                        accC[o][q] = dx == 0 ? bf_mul(v[q], w[0][dx][q]) : bf_fma(v[q], w[0][dx][q], accC[o][q]);
                    }
                }
            }
            anchor(ld64, accB[7][0], accB[7][1], accB[7][2], 0);
            __syncwarp();
            if (elect_one()) {
                mbar_arrive(bars + (BAR_A - SM_BAR) + bo0);
                mbar_arrive(bars + (BAR_E - SM_BAR) + bo0);
                mbar_arrive(bars + (BAR_A - SM_BAR) + bo1);
                mbar_arrive(bars + (BAR_E - SM_BAR) + bo1);
            }
        }
        int end = wk.rows;
        const int marks[4] = {wk.rows - PREFETCH_ROWS, wk.rows - 11, wk.nA + 2, wk.nA + 2 - PREFETCH_ROWS};
#pragma unroll
        for (int k = 0; k < 4; k++) end = marks[k] > r ? min(end, marks[k]) : end;
        const bool fetch = r < wk.rows - PREFETCH_ROWS;
        aim(r + PREFETCH_ROWS);
        px = opaque_uniform(px);
        const int py_end = opaque_uniform(py + wk.dir * (end - r));
        r = end;
#pragma unroll 1
        do {
            mbar_wait(bars + bo, par);
            const uint32_t so = bo * (SLOT_BYTES / 32);
            uint32_t out[8][3];
#pragma unroll
            for (int p = 0; p < 10; p++) {
                uint32_t xv[3];
                lds64(xv[0], xv[1], so + ld64 + p * 192);
                lds32(xv[2], so + ld32 + p * 192);
#pragma unroll
                for (int dd = 0; dd < 3; dd++) {
                    const int dx = K_PD ? 2 - dd : dd, o = p - dx;
                    if (o < 0 || o > 7) continue;
#pragma unroll
                    for (int qq = 0; qq < 3; qq++) {
                        const int q = (qq + K_PQ) % 3;
                        out[o][q] = bf_fma(xv[q], w[2][dx][q], dx == 0 ? accB[o][q] : out[o][q]);
                        accB[o][q] = bf_fma(xv[q], w[1][dx][q], dx == 0 ? accC[o][q] : accB[o][q]);
                        accC[o][q] = dx == 0 ? bf_mul(xv[q], w[0][dx][q]) : bf_fma(xv[q], w[0][dx][q], accC[o][q]);
                    }
                }
            }
            __syncwarp();
#pragma unroll
            for (int oo = 0; oo < 8; oo++) {
                const int o = K_PS ? 7 - oo : oo;
                sts64(so + st64 + o * 16, out[o][0], out[o][1]);
                sts32(so + st32 + o * 16, out[o][2]);
            }
            __syncwarp();
            if (elect_one()) mbar_arrive(bars + (BAR_A - SM_BAR) + bo);
            if (fetch) request();
            advance();
            py += wk.dir;
        } while (py != py_end);
        if (((wk.rows - r) & ~8) == PREFETCH_ROWS) event(wk.rows - r == PREFETCH_ROWS);
    }
}

template <bool SCALED, int K0 = 0, int K1 = 3>
__device__ __forceinline__ void gelu_sq(uint32_t (&d)[24], uint32_t (&keep)[24], uint32_t sq_addr, uint32_t scale2) {
    pin(d);
#pragma unroll
    for (int k = K0; k < K1; k++) {
        uint32_t hs[4];
        lds128(hs[0], hs[1], hs[2], hs[3], sq_addr + k * SQ_ROW);
#pragma unroll
        for (int qq = 0; qq < 4; qq++) {
            const int q = K_QS == 0 ? qq : K_QS == 1 ? 3 - qq : K_QS == 2 ? (qq >> 1 | (qq & 1) << 1) : (qq + 1) & 3;
            uint32_t g0 = gelu2(d[8 * k + 2 * q]), g1 = gelu2(d[8 * k + 2 * q + 1]);
            keep[8 * k + 2 * q] = g0;
            keep[8 * k + 2 * q + 1] = g1;
            if (SCALED) { g0 = h_mul(g0, scale2); g1 = h_mul(g1, scale2); }
            hs[q] = (K_GS >> (q & 1) & 1) ? h_fma(g0, g0, h_fma(g1, g1, hs[q])) : h_fma(g1, g1, h_fma(g0, g0, hs[q]));
        }
        sts128(sq_addr + k * SQ_ROW, hs[0], hs[1], hs[2], hs[3]);
    }
}
__device__ __forceinline__ void gelu_sq_reg(uint32_t (&d)[24], uint32_t (&hs)[12]) {
    pin(d);
#pragma unroll
    for (int qq = 0; qq < 12; qq++) {
        const int q = K_QR == 0 ? qq : K_QR == 1 ? 11 - qq : K_QR == 2 ? qq ^ 1 : qq * 5 % 12;
        const uint32_t g0 = gelu2(d[2 * q]), g1 = gelu2(d[2 * q + 1]);
        hs[q] = (K_GR >> (q & 1) & 1) ? h_fma(g0, g0, h_fma(g1, g1, hs[q])) : h_fma(g1, g1, h_fma(g0, g0, hs[q]));
    }
}
__device__ __forceinline__ void gelu_to(uint32_t (&g)[12], uint32_t (&d)[12]) {
    pin(d);
#pragma unroll
    for (int q = 0; q < 12; q++) g[q] = gelu2(d[q]);
    pin(g);
}
__device__ __forceinline__ void load_tile(uint32_t (&raw)[6][4], uint32_t addr) {
#pragma unroll
    for (int s = 0; s < 6; s++) ldsm4(raw[s], addr + s * 2 * A_LBO);
}
__device__ __forceinline__ uint2 ln_stats(const uint32_t (&raw)[6][4], uint64_t ones) {
    constexpr int NS = 6 / K_CHAIN;
    uint32_t sq[NS][4];
#pragma unroll
    for (int s = 0; s < 6; s++)
#pragma unroll
        for (int q = 0; q < 4; q++) sq[s % NS][q] = s < NS ? bf_mul(raw[s][q], raw[s][q]) : bf_fma(raw[s][q], raw[s][q], sq[s % NS][q]);
    float sum[4], ssq[4];
    wg_fence();
    wgmma_rowsum<0>(sum, raw[0], ones);
#pragma unroll
    for (int s = 1; s < 6; s++) wgmma_rowsum<1>(sum, raw[s], ones);
    wgmma_rowsum<0>(ssq, sq[0], ones);
#pragma unroll
    for (int s = 1; s < NS; s++) wgmma_rowsum<1>(ssq, sq[s], ones);
    wg_commit();
    wg_wait<0>();
    uint32_t st[2];
#pragma unroll
    for (int h = 0; h < 2; h++) {
        asm volatile("" : "+f"(sum[2 * h]), "+f"(ssq[2 * h])::"memory");
        const float mean = sum[2 * h] * (1.f / CH);
        const float var = fmaxf(fmaf(ssq[2 * h], 1.f / CH, -mean * mean), 0.f);
        float rstd;
        asm("rsqrt.approx.ftz.f32 %0, %1;" : "=f"(rstd) : "f"(var + 1e-5f));
        rstd = bf_lo(pack_bf2(rstd * (K_CVT == 0 ? KZ : KZ * 0x1p-112f), 0.f));
        st[h] = pack_bf2(rstd, -mean * rstd);
    }
    return make_uint2(st[0], st[1]);
}
__device__ __forceinline__ void ln_apply(uint32_t (&a)[6][4], const uint2& st) {
    const uint32_t sc[2] = {__byte_perm(st.x, 0, 0x1010), __byte_perm(st.y, 0, 0x1010)};
    const uint32_t sh[2] = {__byte_perm(st.x, 0, 0x3232), __byte_perm(st.y, 0, 0x3232)};
#pragma unroll
    for (int s = 0; s < 6; s++)
#pragma unroll
        for (int q = 0; q < 4; q++) {
            const uint32_t v = bf_fma(a[s][q], sc[q & 1], sh[q & 1]);
            a[s][q] = K_CVT == 0 ? pack_h2(bf_lo(v), bf_hi(v)) : K_CVT == 1 ? (v & 0x7fff7fffu) * 7u + v : ((v << 3) & 0x7fff7fffu) | (v & 0x80008000u);
        }
}
struct Cursor {
    int slot;
    uint32_t par;
    __device__ __forceinline__ void advance(int n) {
        slot += n;
        if (slot >= NSLOT) { slot -= NSLOT; par ^= 1; }
    }
};
struct Descs {
    uint64_t w1[8][6];
    uint64_t w2[24];
    uint64_t ones;
};
template <int E0, int N>
__device__ __forceinline__ void gemm1_chunk(uint32_t (&d)[N], const uint32_t (&a)[6][4], const Descs& ds, int zero) {
#pragma unroll
    for (int s = 0; s < 6; s++) wgmma(d, a[s][0], a[s][1], a[s][2], a[s][3], ds.w1[E0 / 48][s], s ? 1 : zero);
}
template <int E0, int N>
__device__ __forceinline__ void gemm2_chunk(uint32_t (&acc)[24], const uint32_t (&g)[N], const Descs& ds) {
#pragma unroll
    for (int s = 0; s < N / 4; s++) wgmma(acc, g[4 * s], g[4 * s + 1], g[4 * s + 2], g[4 * s + 3], ds.w2[E0 / 16 + s], 1);
}

struct __align__(64) Params {
    Split sp;
    int zero;
    const __nv_bfloat16 *x, *dw, *w2, *gamma, *beta;
    __nv_bfloat16* out;
    Scratch* sc;
    Descs ds;
};

__global__ void __launch_bounds__(NTHREADS, 1)
block_kernel(const __grid_constant__ CUtensorMap tmap, const __grid_constant__ CUtensorMap tmap_w1, const __grid_constant__ Params pm) {
    const Split& sp = pm.sp;
    const Descs& ds = pm.ds;
    const int& zero = pm.zero;
    const __nv_bfloat16 *const &x = pm.x, *const &dw = pm.dw, *const &w2 = pm.w2, *const &gamma = pm.gamma, *const &beta = pm.beta;
    __nv_bfloat16* const& out = pm.out;
    Scratch* const& sc = pm.sc;
    extern __shared__ __align__(1024) uint8_t smem[];
    constexpr uint32_t sb = SB;
    const int tid = threadIdx.x;
    const Work wk = get_work(blockIdx.x, sp);
    constexpr uint32_t s_red = sb + SM_RED;
    if (smem_u32(smem) != SB) __trap();

    const int warp_id = __shfl_sync(~0u, tid >> 5, 0);
    PROF(0);
    const int cw = warp_id - 4, wgi = cw >> 2, w4 = warp_id & 3;
    if (elect_one()) {
        static_assert(3 * NSLOT * 4 == 8 + 4 * 16 && BAR_F == BAR_W + 48, "barrier shares");
        const int b = warp_id - 8;
        const uint32_t bar = b < 0 ? sb + BAR_X + warp_id * 8 : b < 7 ? sb + BAR_W + b * 8 : sb + BAR_PIN;
        mbar_init(bar, 1);
#pragma unroll
        for (int k = 0; k < 4; k++) mbar_init(sb + BAR_X + (8 + 4 * warp_id + k) * 8, 1);
        mbar_init(sb + BAR_R + warp_id * 8, 1);
        fence_async();
        if (b < 0) {
            issue_region(&tmap, sb + SM_RING + warp_id * REGION_BYTES, bar, w4, ((wk.tA & 511) + wk.dir * wgi) << 16 | (wk.tA >> 9) * TILE_W);
        } else if (b < 6) {
            mbar_expect_tx(bar, 64 * CH * 2);
            tma_2d(sb + SM_W2 + b * (64 * CH * 2), &tmap_w1, bar, 64 * b, 0);
        } else if (b == 6) {
            mbar_expect_tx(bar, 9 * CH * 2);
            bulk_load(sb + SM_FILTER, dw, 9 * CH * 2, bar);
        }
    }
    __syncwarp();
    const int ntiles = wk.nA + wk.nB;
    const int rank = (wgi + wk.lent + 2 * (ntiles - 1)) % NCONS | (wgi >> 2 & 3);
    const int spare = wk.rows % NSLOT, spare2 = spare == NSLOT - 1 ? 0 : spare + 1;
    const uint32_t sq_base = sb + (wgi < 0 ? SM_RING + spare * SLOT_BYTES : SM_SQ + rank * 2 * SQ_HALF);
    const uint32_t sq_upper = wgi < 0 ? (spare2 - spare) * SLOT_BYTES : SQ_HALF;
    const uint32_t bar_a = sb + BAR_A + w4 * 8, bar_e = sb + BAR_E + w4 * 8;
    const bool helps = !wk.lent && wk.index < 8 * LENT * sp.lenders;
    auto max_w1 = [&](uint32_t lane) { return __uint_as_float(__reduce_max_sync(~0u, lane < 4 * NCONS ? ldsi(s_red + RED_MAX + lane * 4) : 0)); };
    auto square_scale = [&](uint32_t lane) {
        const float f = pow2i(square_exp(bound_exp(max_w1(lane))));
        return pack_h2(f, f);
    };
    uint32_t a_addr, sq;
    const uint32_t sq_warp = sq_base + w4 * 512;
    auto set_addresses = [&]() {
        a_addr = opaque(sb + SM_RING + w4 * REGION_BYTES + ((tid >> 3) & 1) * A_SBO + ((tid >> 4) & 1) * A_LBO + (tid & 7) * 16);
        sq = opaque(sq_base + (tid & 127) * 16);
    };
    uint32_t turn, turn_end, so, so_sum, bo, bo_sum, off;
    auto set_run = [&](int j, int stop, int row) {
        const int slot = row % NSLOT, both = 2 * (row % 3) + 3;
        turn = opaque_uniform(row / 3);
        turn_end = opaque_uniform(row / 3 + max(stop - j + NCONS - 1, 0) / NCONS);
        so = opaque_uniform(slot * SLOT_BYTES);
        so_sum = opaque_uniform(both * SLOT_BYTES);
        bo = opaque_uniform(bar_a + slot * 32);
        bo_sum = opaque_uniform(2 * bar_a + both * 32);
        off = opaque_uniform(tile_offset(wk.tile(j)) + w4 * WARP_BYTES - sq_warp);
    };
    const int nrest = ntiles - 4;
    int jt;
    Cursor cur;
    int fast_from;
    if (warp_id < 4) {
        const bool prepares = gridDim.x - blockIdx.x <= W2_GROUPS / 2;
        const int q = (gridDim.x - 1 - blockIdx.x) * 2 + (w4 >> 1);
        conv_producer(wk, &tmap, sb, warp_id, [&](bool second) {
            if (!second) {
                if (blockIdx.x == 0) {
#pragma unroll 1
                    for (int e = tid; e < EX; e += 128) *sc->sum(e) = 0;
                    sc->bias[tid] = 0.f;
                }
                if (blockIdx.x == 0 || wk.lent) signal(&sc->early);
            } else if (prepares || helps) {
                spin_until(&sc->early, (ldsi(s_red + RED_LAUNCH) + 1) * 4 * (sp.lenders + 1));
                if (elect_one()) {
                    if (helps) prefetch_l2(reinterpret_cast<const char*>(out) + sp.lent_off[wk.index / 8] + w4 * WARP_BYTES, WARP_BYTES);
                    if (prepares) { prefetch_l2(w2 + 8 * q * CH, 8 * CH * 2); prefetch_l2(beta + 8 * q, 16); }
                }
            }
        });
        set_addresses();
        const int lane = lane_id(), g = lane >> 2, t = lane & 3;
        if (prepares) {
            const int half = w4 & 1;
            const __nv_bfloat16* row = w2 + (8 * q + g) * CH + 8 * t;
            uint32_t rmax = 0;
#pragma unroll
            for (int m = 0; m < 3; m++) {
                const uint4 w = __ldg(reinterpret_cast<const uint4*>(row + 32 * m));
                rmax = bf_absmax(bf_absmax(rmax, bf_absmax(w.x, w.y)), bf_absmax(w.z, w.w));
            }
            uint2 u = __ldg(reinterpret_cast<const uint2*>(row + 4 * half)), u1 = __ldg(reinterpret_cast<const uint2*>(row + 32 + 4 * half));
            const uint2 u2 = __ldg(reinterpret_cast<const uint2*>(row + 64 + 4 * half));
            const float bt = __bfloat162float(beta[8 * q + g]);
            rmax = bf_absmax(rmax, __shfl_xor_sync(~0u, rmax, 1));
            rmax = bf_absmax(rmax, __shfl_xor_sync(~0u, rmax, 2));
            const float mx = fmaxf(fabsf(bf_lo(rmax)), fabsf(bf_hi(rmax))), rs = pow2i(row_exp(mx));
            if (t == 0 && !half) sc->w2max[8 * q + g] = mx;
#pragma unroll 1
            for (int m = 0; m < 3; m++, u = u1, u1 = u2) {
                float f[4];
#pragma unroll
                for (int k = 0; k < 2; k++) {
                    const float lo = bf_lo(k ? u.y : u.x), hi = bf_hi(k ? u.y : u.x);
                    sc->w2h[(4 * m + 2 * half + k) * 1536 + q * 32 + lane] = transpose8x8(pack_h2(lo * rs, hi * rs));
                    f[2 * k] = lo * bt;
                    f[2 * k + 1] = hi * bt;
                }
                const float r0 = (g & 2 ? f[2] : f[0]) + __shfl_xor_sync(~0u, g & 2 ? f[0] : f[2], 8);
                const float r1 = (g & 2 ? f[3] : f[1]) + __shfl_xor_sync(~0u, g & 2 ? f[1] : f[3], 8);
                float r = (g & 1 ? r1 : r0) + __shfl_xor_sync(~0u, g & 1 ? r0 : r1, 4);
                r += __shfl_xor_sync(~0u, r, 16);
                if (g < 4) atomicAdd(&sc->bias[32 * m + 8 * t + 4 * half + g], r);
            }
            asm volatile("fence.proxy.async.global;" ::: "memory");
            signal(&sc->prep);
        }
        const int piece = wk.index;
        uint32_t a[6][4];
        if (helps) {
#pragma unroll
            for (int s = 0; s < 6; s++) ldg128(a[s], reinterpret_cast<const char*>(out) + sp.lent_off[piece / 8] + w4 * WARP_BYTES + lane * 16 + s * 512);
        }
        mbar_wait_once(bar_e + spare2 * 32, (wk.rows - 5) / NSLOT & 1);
        mbar_wait_once(bar_e + spare * 32, (wk.rows - 6) / NSLOT & 1);
        named_bar(1, 128);
#pragma unroll
        for (int k = 0; k < 6; k++) { sts128(sq + k * SQ_ROW, 0, 0, 0, 0); sts128(sq + sq_upper + k * SQ_ROW, 0, 0, 0, 0); }
        if (helps) {
            uint32_t d[12], gl[12];
            const uint32_t scale2 = square_scale(lane);
            wg_fence();
#pragma unroll
            for (int s = 0; s < 6; s++) wgmma(d, a[s][0], a[s][1], a[s][2], a[s][3], ds.w1[0][s] + piece % 8 * (6 * 1536 / 16), s ? 1 : 0);
            wg_commit();
            wg_wait<0>();
            gelu_to(gl, d);
#pragma unroll
            for (int s = 0; s < 3; s++) {
                sc->lent[((piece / 8 * 4 + w4) * 24 + piece % 8 * 3 + s) * 32 + lane] = make_uint4(gl[4 * s], gl[4 * s + 1], gl[4 * s + 2], gl[4 * s + 3]);
                uint32_t hs[2];
#pragma unroll
                for (int k = 0; k < 2; k++) {
                    const uint32_t g0 = h_mul(gl[4 * s + 2 * k], scale2), g1 = h_mul(gl[4 * s + 2 * k + 1], scale2);
                    hs[k] = h_fma(g1, g1, h_mul(g0, g0));
                }
                const int pair = piece % 4 * 3 + s;
                sts64(sq + (piece & 4 ? sq_upper : 0) + (pair >> 1) * SQ_ROW + (pair & 1) * 8, hs[0], hs[1]);
            }
        }
        jt = ntiles - 1;
        cur.slot = spare ? spare - 1 : NSLOT - 1;
        cur.par = (wk.rows - 1) / NSLOT & 1;
        fast_from = ntiles;
        turn = turn_end = so = so_sum = bo = bo_sum = off = rank;
    } else {
        set_addresses();
        if (wgi == NCONS - 1) named_arrive(4, 256);
        set_run(wk.lent + wgi, min(wk.nA, nrest), wk.lent + wgi + 2);
        jt = wgi < wk.lent ? wgi : wk.lent + wgi;
        cur = {2, 0};
        cur.advance(jt + (jt >= wk.nA ? 2 : 0));
        {
            const int ct = tid - 128, lane = tid & 31;
            const unsigned epoch = *reinterpret_cast<volatile unsigned*>(&sc->launch);
            const int r = lane & 7, mi = lane >> 3;
            const uint32_t src = sb + SM_W2 + (cw >> 1) * (64 * CH * 2) + r * 128 + ((((cw & 1) * 4 + mi) ^ r) * 16);
            const uint32_t dst = sb + SM_W1 + (4 * cw + mi) * 1536 + r * 16;
            const int code = row_code(wk, PREFETCH_ROWS - 1 + wgi);
            named_bar(0, NTHREADS);
            auto request = [&]() {
                if (elect_one())
                    issue_region(&tmap, sb + SM_RING + (PREFETCH_ROWS - 1 + wgi) * SLOT_BYTES + w4 * REGION_BYTES, sb + BAR_X + (cw + 8) * 8, w4, code);
                __syncwarp();
            };
#pragma unroll 1
            for (int k = 0; k < 2; k++) {
                if (wgi == k) request();
                mbar_wait_once(sb + BAR_W + (cw >> 1) * 8, 0);
            }
            uint32_t wmax[2] = {}, wsum[4] = {};
#pragma unroll K_UNR
            for (int c = 0; c < 12; c++) {
                uint32_t u[4];
                ldsm4_t(u, src + c * 1024);
#pragma unroll
                for (int q = 0; q < 4; q++) {
                    wmax[q & 1] = bf_absmax(wmax[q & 1], u[q]);
                    wsum[q] = bf_fma(u[q], 0x3f803f80u, wsum[q]);
                    u[q] = pack_h2(__uint_as_float(u[q] * (65536 + zero)), bf_hi(u[q]));
                }
                stsm4(dst + c * 128, u[0], u[1], u[2], u[3]);
            }
            const float w1max = warp_absmax(bf_absmax(wmax[0], wmax[1]));
            if (lane == 0) sts32(s_red + RED_MAX + cw * 4, __float_as_uint(w1max));
            bool center = false;
#pragma unroll
            for (int q = 0; q < 4; q++) {
#pragma unroll
                for (int o = 1; o <= 2; o <<= 1) wsum[q] = bf_fma(__shfl_xor_sync(~0u, wsum[q], o), 0x3f803f80u, wsum[q]);
                center |= fabsf(bf_lo(wsum[q]) + bf_hi(wsum[q])) > (0.15f * CH) * w1max;
            }
            if (__builtin_expect(__any_sync(~0u, center), 0)) {
                float mean[4] = {};
#pragma unroll 1
                for (int pass = 0; pass < 2; pass++) {
                    float sum[4] = {};
#pragma unroll 1
                    for (int c = 0; c < 12; c++) {
                        uint32_t u[4];
                        ldsm4_t(u, src + c * 1024);
#pragma unroll
                        for (int q = 0; q < 4; q++) {
                            sum[q] += bf_lo(u[q]) + bf_hi(u[q]);
                            u[q] = pack_h2(bf_lo(u[q]) - mean[q], bf_hi(u[q]) - mean[q]);
                        }
                        stsm4(dst + c * 128, u[0], u[1], u[2], u[3]);
                    }
#pragma unroll
                    for (int q = 0; q < 4; q++) {
                        sum[q] += __shfl_xor_sync(~0u, sum[q], 1);
                        sum[q] += __shfl_xor_sync(~0u, sum[q], 2);
                        mean[q] = sum[q] * (1.f / CH);
                    }
                }
            }
            if (!(cw & 2)) {
#pragma unroll
                for (int c = 0; c < 12; c++) sts128(src + c * 1024, 0, 0, 0, 0);
            }
            if (ct < 32) sts32(sb + SM_ONES + ct * 4, 0x3f803f80u);
            if (ct == 0) sts32(s_red + RED_LAUNCH, epoch);
            fence_async();
            named_bar(2, CONS_THREADS);
            if (wgi == 2) request();
        }
        PROF(1);
        fast_from = wk.lent;
        if (!__all_sync(~0u, plain_squares(bound_exp(max_w1(lane_id()))))) {
            fast_from = ntiles;
#pragma unroll 1
            for (int q = 0; q < 6; q++) sts128(sq + SQ_HALF + q * SQ_ROW, 0, 0, 0, 0);
        }
    }
    uint32_t k1[24], k2[24], k3[24], tile_off, next_off;
    constexpr int SQC = 3 * SQ_ROW;
    auto store_at = [&](const uint32_t (&a)[6][4], uint32_t off) {
        char* ap = reinterpret_cast<char*>(out) + (off + sq);
#pragma unroll
        for (int s = 0; s < 6; s++) stg128(ap + s * 512, a[s]);
    };
    const uint32_t own_bar = 4 + (wgi & 3), next_bar = 4 + (wgi == NCONS - 1 ? 0 : wgi + 1);
    for (;;) {
        if (jt >= fast_from) {
            uint32_t hs2[12] = {}, hs3[12] = {};
            const uint32_t step = wk.dir * (NCONS * IMG_W * CH * 2);
            int second = wk.nB;
#pragma unroll 1
            for (;;) {
#pragma unroll 1
                while (turn != turn_end) {
                    uint32_t a[6][4], d0[24], d1[24], unused[24];
#define AT(pos) \
    if (K_WAIT == pos) named_bar(own_bar, 256); \
    if (K_PASS == pos) named_arrive(next_bar, 256); \
    if (K_STG == pos) store_at(a, off); \
    if (K_REL == pos) { if (elect_one()) mbar_arrive(bo + (BAR_E - BAR_A)); }
                    AT(20)
                    mbar_wait(bo, turn >> 1 & 1);
                    load_tile(a, a_addr + so);
                    AT(21)
                    const uint2 st = ln_stats(a, ds.ones);
                    AT(0)
                    ln_apply(a, st);
                    AT(1)
                    wg_fence();
                    gemm1_chunk<0>(d0, a, ds, 0);
                    wg_commit();
                    gemm1_chunk<96>(d1, a, ds, 0);
                    wg_commit();
                    AT(2)
                    wg_wait<1>();
                    AT(3)
                    gelu_sq<false, 0, 1>(d0, unused, sq, 0);
                    AT(4)
                    gelu_sq<false, 1, 2>(d0, unused, sq, 0);
                    AT(5)
                    gelu_sq<false, 2, 3>(d0, unused, sq, 0);
                    AT(6)
                    wg_fence();
                    gemm1_chunk<192>(d0, a, ds, zero);
                    wg_commit();
                    AT(7)
                    wg_wait<1>();
                    gelu_sq<false, 0, 1>(d1, unused, sq + SQC, 0);
                    AT(8)
                    gelu_sq<false, 1, 3>(d1, unused, sq + SQC, 0);
                    AT(9)
                    wg_fence();
                    gemm1_chunk<288>(d1, a, ds, zero);
                    wg_commit();
                    AT(10)
                    wg_wait<1>();
                    gelu_sq_reg(d0, hs2);
                    if (K_ANCH < 3) anchor(sq, hs2[4 * (K_ANCH % 3)], hs2[4 * (K_ANCH % 3) + 1], hs2[4 * (K_ANCH % 3) + 2], hs2[4 * (K_ANCH % 3) + 3]);
                    wg_wait<0>();
                    AT(11)
                    gelu_sq_reg(d1, hs3);
#undef AT
                    so = so_sum - so;
                    bo = bo_sum - bo;
                    off += step;
                    turn++;
                }
                if (!second) break;
                const int j = ntiles - second + (rank + second + 2) % NCONS;
                second = 0;
                set_run(j, nrest, j + 4);
            }
            jt = nrest + rank;
            cur.slot = (bo - bar_a) >> 5;
            cur.par = turn >> 1 & 1;
#pragma unroll
            for (int k = 0; k < 3; k++) {
                sts128(sq + SQ_HALF + k * SQ_ROW, hs2[4 * k], hs2[4 * k + 1], hs2[4 * k + 2], hs2[4 * k + 3]);
                sts128(sq + SQ_HALF + SQC + k * SQ_ROW, hs3[4 * k], hs3[4 * k + 1], hs3[4 * k + 2], hs3[4 * k + 3]);
            }
        }
        const bool last = jt >= nrest;
        if (last) {
            tile_off = tile_offset(wk.tile(jt));
            lds32(next_off, sb + SM_TILES + rank * 4);
            next_off = __shfl_sync(~0u, next_off, 0);
            if (elect_one()) {
                prefetch_l2(reinterpret_cast<const char*>(x) + tile_off + w4 * WARP_BYTES, WARP_BYTES);
                if (rank % ORDER_P >= ORDER_P - ORDER_Q) prefetch_l2(reinterpret_cast<const char*>(out) + next_off + w4 * WARP_BYTES, WARP_BYTES);
            }
        }
        uint32_t a[6][4], d0[24], d1[24], d3[24], k0[24];
#define AT(pos) \
    if (K_WAIT == pos && jt >= wk.lent) named_bar(own_bar, 256); \
    if (K_PASS == pos && jt >= wk.lent && jt + 2 < ntiles) named_arrive(next_bar, 256); \
    if (K_P0 == pos && jt == nrest + K_R0) named_arrive(7, 256);
        AT(20)
        mbar_wait_once(bar_a + cur.slot * 32, cur.par);
        load_tile(a, a_addr + cur.slot * SLOT_BYTES);
        AT(21)
        const uint2 st = ln_stats(a, ds.ones);
        AT(0)
        ln_apply(a, st);
        AT(1)
        if (!last) {
            store_at(a, tile_offset(wk.tile(jt)) + w4 * WARP_BYTES - sq_warp);
            __syncwarp();
            if (elect_one()) mbar_arrive(bar_e + cur.slot * 32);
            if (jt < wk.lent) {
                jt += LENT;
                cur.advance(LENT);
                continue;
            }
        }
        wg_fence();
        gemm1_chunk<0>(d0, a, ds, 0);
        wg_commit();
        gemm1_chunk<96>(d1, a, ds, 0);
        wg_commit();
        const uint32_t scale2 = square_scale(lane_id());
        AT(2)
        wg_wait<1>();
        AT(3)
        gelu_sq<true, 0, 1>(d0, k0, sq, scale2);
        AT(4)
        gelu_sq<true, 1, 2>(d0, k0, sq, scale2);
        AT(5)
        gelu_sq<true, 2, 3>(d0, k0, sq, scale2);
        AT(6)
        if (last) {
#pragma unroll
            for (int q = 0; q < 6; q++)
                sts128(sb + SM_RING + cur.slot * SLOT_BYTES + w4 * REGION_BYTES - sq_warp + sq + q * 512, k0[4 * q], k0[4 * q + 1], k0[4 * q + 2], k0[4 * q + 3]);
        }
        wg_fence();
        gemm1_chunk<192>(d0, a, ds, zero);
        wg_commit();
        AT(7)
        wg_wait<1>();
        gelu_sq<true>(d1, k1, sq + SQC, scale2);
        AT(9)
#undef AT
        wg_fence();
        gemm1_chunk<288>(d3, a, ds, 0);
        wg_commit();
        wg_wait<1>();
        gelu_sq<true>(d0, k2, sq + sq_upper, scale2);
        wg_wait<0>();
        gelu_sq<true>(d3, k3, sq + sq_upper + SQC, scale2);
        if (last) break;
        cur.advance(NCONS + ((jt < wk.nA && jt + NCONS >= wk.nA) ? 2 : 0));
        jt += NCONS;
    }
    const uint32_t lane = lane_id();
    const uint32_t s_fac = sb + SM_RING + spare * SLOT_BYTES + SQ_HALF;
    uint32_t inv_rho2;
    {
        const bool leader = rank == 0 && w4 == 0 && lane == 0;
        const int i0 = w4 * 32 + lane;
        float base[3], slope[3], reach[3], to_square;
        float2 bpair = make_float2(0.f, 0.f);
        unsigned epoch;
        if (rank == 0) {
            float gam[3], rmax[3];
#pragma unroll
            for (int m = 0; m < 3; m++) {
                unsigned short v;
                asm volatile("ld.global.nc.u16 %0, [%1];" : "=h"(v) : "l"(gamma + i0 + 128 * m) : "memory");
                gam[m] = bf_lo(v);
            }
            epoch = ldsi(s_red + RED_LAUNCH);
            if (leader) {
                spin_until(&sc->prep, (epoch + 1) * 2 * W2_GROUPS);
                asm volatile("fence.proxy.async.global;" ::: "memory");
            }
            __syncwarp();
            named_bar(2, 128);
#pragma unroll
            for (int m = 0; m < 3; m++) rmax[m] = __ldcg(&sc->w2max[i0 + 128 * m]);
            if (i0 < 96) bpair = __ldcg(reinterpret_cast<const float2*>(&sc->bias[32 * (i0 % 24 >> 3) + 8 * (i0 / 24) + (i0 % 24 & 6)]));
            const float w1max = max_w1(lane);
            const float gbound = fmaxf(2.f * KZ * 9.7979590f * 192.f * w1max, 1.f) * 19.5959180f * INV_2KZ;
            const unsigned fixed = __reduce_max_sync(~0u, __float_as_uint(fmaf(gbound, fmaxf(fmaxf(rmax[0], rmax[1]), rmax[2]), fmaxf(fabsf(bpair.x), fabsf(bpair.y)))));
            if (lane == 0) sts32(s_red + 96 + w4 * 4, fixed);
#pragma unroll
            for (int m = 0; m < 3; m++) {
                base[m] = rmax[m] > 0.f ? pow2i(-row_exp(rmax[m])) * (INV_2KZ * CUT_GAIN) : 0.f;
                slope[m] = base[m] * gam[m];
                reach[m] = fabsf(gam[m]) * rmax[m] * gbound;
            }
            to_square = pow2i(-sum_exp(bound_exp(w1max))) * (INV_2KZ * INV_2KZ / 256);
        }
        if (rank >= 2) {
            named_arrive(12 + rank, CONS_THREADS);
        } else {
            const int rw = rank * 4 + w4, g = lane >> 2, t = lane & 3;
            const uint32_t pick = (g & 1) == (t & 1) ? (g & 2 ? 0x3c000000u : 0x00003c00u) : 0;
            const int be = bound_exp(max_w1(lane));
            const float to_fixed = pow2i(sum_exp(be) - 2 * square_exp(be));
            unsigned long long* dst = sc->sum(64 * rw + 32 * (t >> 1) + 8 * (g >> 1) + 2 * (t & 1) + (g & 1));
            const uint32_t rows = sb + (rw * 2 + (lane >> 3 & 1)) * SQ_ROW + ((lane >> 4) * 8 + (lane & 7)) * 16;
            float f[2][4] = {};
            named_bar(13, 256);
#pragma unroll 1
            for (int i = 0; i < 4; i++) {
                if (i == 2) {
                    named_bar(13, 256);
                    if (leader) {
                        fence_async();
                        mbar_expect_tx(sb + BAR_W, 4 * SQ_HALF);
                        bulk_load(sb + SM_W2, sc->w2h, 4 * SQ_HALF, sb + BAR_W);
                    }
                    __syncwarp();
                }
                const int from = i < 2 ? i : i ^ K_ORD;
                const uint32_t src = rows + (from < NCONS ? SM_SQ + from * 2 * SQ_HALF : rw < 3 ? SM_RING + spare * SLOT_BYTES : SM_RING + spare2 * SLOT_BYTES - SQ_HALF);
                if (i >= 2) named_bar(12 + from, CONS_THREADS);
                if (rw < 6) {
#pragma unroll
                    for (int r = 0; r < 8; r++) {
                        uint32_t u[4];
                        ldsm4_t(u, src + r * 256);
                        asm volatile("mma.sync.aligned.m16n8k16.row.col.f32.f16.f16.f32 {%0, %1, %2, %3}, {%4, %5, %6, %7}, {%8, %8}, {%0, %1, %2, %3};"
                                     : "+f"(f[r & 1][0]), "+f"(f[r & 1][1]), "+f"(f[r & 1][2]), "+f"(f[r & 1][3])
                                     : "r"(u[0]), "r"(u[1]), "r"(u[2]), "r"(u[3]), "r"(pick));
                    }
                }
            }
            if (rw < 6) {
#pragma unroll
                for (int r = 0; r < 2; r++)
                    atomicAdd(dst + r * 32, __float2ull_rn(fminf((t < 2 ? f[0][r] + f[1][r] : f[0][r + 2] + f[1][r + 2]) * to_fixed, 0x1p47f)) << 8 | 1);
            }
            PROF(2);
            named_bar(13, 256);
            if (leader) {
                fence_async();
                mbar_expect_tx(sb + BAR_W + 8, 2 * SQ_HALF);
                bulk_load(sb + SM_W2 + 4 * SQ_HALF, reinterpret_cast<const char*>(sc->w2h) + 4 * SQ_HALF, 2 * SQ_HALF, sb + BAR_W + 8);
            }
            if (helps && rw == 7) signal(&sc->lent_out);
        }
        if (rank == 0) {
            const uint32_t own_sum = (i0 >> 2) * 256 + (i0 & 3) * 8, own_fac = s_fac + i0 * 2;
            auto peek = [&](const void* p) {
                unsigned long long v;
                asm volatile("ld.relaxed.gpu.global.u64 %0, [%1];" : "=l"(v) : "l"(p) : "memory");
                return v;
            };
            const char* mine = reinterpret_cast<const char*>(sc->sums) + own_sum;
            unsigned n = 0;
            while (((unsigned)peek(sc->sum((blockIdx.x * 4 + w4) % (EX / 4) * 4)) & 255u) != gridDim.x)
                if (++n > SPIN_LIMIT) __trap();
            unsigned long long sum[3];
            for (;;) {
                bool all = true;
#pragma unroll
                for (int m = 0; m < 3; m++) {
                    sum[m] = peek(mine + m * (32 * 256));
                    all &= ((unsigned)sum[m] & 255u) == gridDim.x;
                }
                if (__all_sync(~0u, all)) break;
                if (++n > SPIN_LIMIT) __trap();
            }
            PROF(3);
            float gx[3];
#pragma unroll
            for (int m = 0; m < 3; m++) asm("sqrt.approx.ftz.f32 %0, %1;" : "=f"(gx[m]) : "f"(fmaf(__ull2float_rn(sum[m]), to_square, 1e-6f)));
            float tot = gx[0] + gx[1] + gx[2];
#pragma unroll
            for (int o = 16; o >= 1; o >>= 1) tot += __shfl_xor_sync(~0u, tot, o);
            const unsigned vwarp = __reduce_max_sync(~0u, __float_as_uint(fmaxf(fmaxf(reach[0] * gx[0], reach[1] * gx[1]), reach[2] * gx[2])));
            if (lane == 0) { sts32(s_red + 64 + w4 * 4, __float_as_uint(tot)); sts32(s_red + 80 + w4 * 4, vwarp); }
            named_bar(2, 128);
            uint32_t u[4], v[4], w[4];
            lds128(u[0], u[1], u[2], u[3], s_red + 64);
            lds128(v[0], v[1], v[2], v[3], s_red + 80);
            lds128(w[0], w[1], w[2], w[3], s_red + 96);
            tot = (__uint_as_float(u[0]) + __uint_as_float(u[1])) + (__uint_as_float(u[2]) + __uint_as_float(u[3]));
            const float vmax = __uint_as_float(max(max(v[0], v[1]), max(v[2], v[3]))), fmax2 = __uint_as_float(max(max(w[0], w[1]), max(w[2], w[3])));
            float inv_mean;
            asm("rcp.approx.ftz.f32 %0, %1;" : "=f"(inv_mean) : "f"(fmaf(tot, 1.f / EX, 1e-6f)));
            const int rho_e = 14 - ilog2f(fmaf(vmax, inv_mean, 2.f * fmax2));
            const float rho = pow2i(rho_e), inv_rho = pow2i(-rho_e);
            inv_rho2 = pack_bf2(inv_rho, inv_rho);
#pragma unroll
            for (int m = 0; m < 3; m++) {
                const float f = fmaf(slope[m] * gx[m], inv_mean, base[m]) * rho;
                asm volatile("st.shared.u16 [%0], %1;" ::"r"(own_fac + 256 * m), "h"((unsigned short)pack_h2(f, 0.f)) : "memory");
            }
            if (i0 < 96) sts32(sb + SM_BIASH + i0 * 4, pack_h2(bpair.x * rho, bpair.y * rho));
            if (i0 == 96) sts32(s_red + RED_INV_RHO, inv_rho2);
            named_arrive(12, NTHREADS);
            if (blockIdx.x == 0 && leader) sc->launch = epoch + 1;
            if (wk.lent) spin_until(&sc->lent_out, (epoch + 1) * 8 * LENT * sp.lenders);
        } else {
            const int rw = rank * 4 - 4 + w4;
            const uint32_t row = sb + SM_W2 + rw * 512 + lane * 16;
            uint32_t u[W2_EARLY][4], f2[4];
#pragma unroll
            for (int nb = 0; nb < W2_EARLY; nb++) {
                if (nb % 8 == 0) mbar_wait_once(sb + BAR_W + nb, 1);
                lds128(u[nb][0], u[nb][1], u[nb][2], u[nb][3], row + nb * 6144);
            }
            if (W2_EARLY <= 8) mbar_wait_once(sb + BAR_W + 8, 1);
            named_bar(12, NTHREADS);
            PROF(3);
            lds128(f2[0], f2[1], f2[2], f2[3], s_fac + rw * 64 + (lane >> 3) * 16);
            lds32(inv_rho2, s_red + RED_INV_RHO);
#pragma unroll
            for (int nb = 0; nb < 12; nb++) {
                uint32_t v[4];
                if (nb < W2_EARLY) { v[0] = u[nb % W2_EARLY][0]; v[1] = u[nb % W2_EARLY][1]; v[2] = u[nb % W2_EARLY][2]; v[3] = u[nb % W2_EARLY][3]; }
                else lds128(v[0], v[1], v[2], v[3], row + nb * 6144);
                sts128(row + nb * 6144, h_cut8(h_mul(v[0], f2[0])), h_cut8(h_mul(v[1], f2[1])), h_cut8(h_mul(v[2], f2[2])), h_cut8(h_mul(v[3], f2[3])));
            }
            fence_async();
            named_arrive(8, NTHREADS);
        }
    }
    uint32_t a[6][4], acc[24], rpar = 0;
    const uint32_t bias_addr = sb + SM_BIASH + (lane & 3) * 96, lane16 = lane * 16, lane_off = ((lane >> 2) * CH + 8 * (lane & 3)) * 2;
    const uint32_t stage = sb + SM_RING + (spare + rank) % NSLOT * SLOT_BYTES + w4 * WARP_BYTES, bar_r = sb + BAR_R + warp_id * 8;
    auto load_bias = [&]() {
#pragma unroll
        for (int q = 0; q < 6; q++) lds128(acc[4 * q], acc[4 * q + 1], acc[4 * q + 2], acc[4 * q + 3], bias_addr + q * 16);
    };
    auto load_frags = [&]() {
#pragma unroll
        for (int s = 0; s < 6; s++) ldg128(a[s], reinterpret_cast<const char*>(out) + next_off + w4 * WARP_BYTES + lane16 + s * 512);
    };
    auto stage_x = [&]() {
        if (elect_one()) {
            mbar_expect_tx(bar_r, WARP_BYTES);
            bulk_load_stream(stage, reinterpret_cast<const char*>(x) + tile_off + w4 * WARP_BYTES, WARP_BYTES, bar_r);
        }
    };
    {
        named_bar(8 + rank, rank ? 256 : NTHREADS);
        if (rank == 0) PROF(4);
        load_bias();
        pin(k1); pin(k2); pin(k3);
        wg_fence();
        gemm2_chunk<KA>(acc, KX(KA), ds);
        wg_commit();
        gemm2_chunk<KB>(acc, KX(KB), ds);
        wg_commit();
        gemm2_chunk<KC>(acc, KX(KC), ds);
        wg_commit();
        stage_x();
        wg_wait<2>();
        uint32_t k0[24];
#pragma unroll
        for (int q = 0; q < 6; q++)
            lds128(k0[4 * q], k0[4 * q + 1], k0[4 * q + 2], k0[4 * q + 3], sb + SM_RING + cur.slot * SLOT_BYTES + w4 * REGION_BYTES + lane16 + q * 512);
        pin(k0);
        wg_fence();
        gemm2_chunk<0>(acc, k0, ds);
        wg_commit();
        if (rank < NCONS) named_arrive(9 + rank, 256);
        wg_wait<2>();
        load_frags();
        if (lane16 == 0) mbar_arrive(sb + BAR_PIN);
        if (!K_RW) mbar_wait(bar_r, rpar);
        wg_wait<0>();
    }
    auto lent = [&](uint32_t entry) { return &sc->lent[((wk.index * LENT + (entry & 3) - 1) * 4 + w4) * (24 * 32)]; };
    for (jt = rank - 4; jt < nrest; jt += 4) {
        if (jt >= zero) {
        tile_off = next_off;
        lds32(next_off, sb + SM_TILES + (jt + 4) * 4);
        if (tile_off & 3) {
            const uint4* src = lent(tile_off) + lane;
            tile_off &= ~3u;
            next_off = __shfl_sync(~0u, next_off, 0);
            stage_x();
            if (elect_one()) prefetch_l2(reinterpret_cast<const char*>(out) + next_off + w4 * WARP_BYTES, WARP_BYTES);
            load_bias();
#pragma unroll 1
            for (int half = 0; half < 2; half++, src += 12 * 32) {
                uint32_t gl[48];
#pragma unroll
                for (int s = 0; s < 12; s++) ldg128(reinterpret_cast<uint32_t (&)[4]>(gl[4 * s]), src + s * 32);
                if (!half) {
                    named_bar(4 + rank, 256);
                    named_arrive(4 + ((rank + 1) & 3), 256);
                }
                pin(gl);
                wg_fence();
#pragma unroll
                for (int s = 0; s < 12; s++) wgmma(acc, gl[4 * s], gl[4 * s + 1], gl[4 * s + 2], gl[4 * s + 3], ds.w2[12 * half + s], 1);
                wg_commit();
                wg_wait<0>();
            }
            load_frags();
            if (!K_RW) mbar_wait(bar_r, rpar);
        } else {
            uint32_t d0[12], d1[12], g0[12], g1[12];
            if (jt >= S2_FIRST) named_bar(4 + rank, 256);
            wg_fence();
            gemm1_chunk<0>(d0, a, ds, 0);
            wg_commit();
            gemm1_chunk<48>(d1, a, ds, 0);
            wg_commit();
            load_bias();
            next_off = __shfl_sync(~0u, next_off, 0);
            const bool more = jt + 4 < nrest && !(next_off & 3);
            wg_wait<1>();
#define CNX_STEP(C, D, G)                                              \
    gelu_to(G, D);                                                     \
    wg_fence();                                                        \
    if (C < 6) gemm1_chunk<48 * (C < 6 ? C + 2 : 0)>(D, a, ds, zero); \
    gemm2_chunk<48 * C>(acc, G, ds);                                  \
    wg_commit();                                                       \
    wg_wait<(C < 7 ? 1 : 0)>();
            CNX_STEP(0, d0, g0)
            CNX_STEP(1, d1, g1)
            if (jt + 1 >= S2_FIRST && jt + 1 < nrest) named_arrive(4 + ((rank + 1) & 3), 256);
            stage_x();
            if (elect_one()) {
                if (more) prefetch_l2(reinterpret_cast<const char*>(out) + next_off + w4 * WARP_BYTES, WARP_BYTES);
                else if (next_off & 3) prefetch_l2(lent(next_off), 24 * 32 * 16);
            }
            CNX_STEP(2, d0, g0)
            CNX_STEP(3, d1, g1)
            CNX_STEP(4, d0, g0)
            CNX_STEP(5, d1, g1)
            CNX_STEP(6, d0, g0)
#pragma unroll
            for (int s = 0; s < 6; s++) ldg128_if(more, a[s], reinterpret_cast<const char*>(out) + next_off + w4 * WARP_BYTES + lane16 + s * 512);
            if (lane16 == 0) mbar_arrive(sb + BAR_PIN);
            if (!K_RW) mbar_wait(bar_r, rpar);
            CNX_STEP(7, d1, g1)
#undef CNX_STEP
        }
        }
        {
            if (K_RW) mbar_wait(bar_r, rpar);
            pin(acc);
            rpar ^= 1;
            uint4* op = reinterpret_cast<uint4*>(reinterpret_cast<char*>(out) + tile_off + w4 * WARP_BYTES + lane_off);
#pragma unroll
            for (int h = 0; h < 2; h++)
#pragma unroll
                for (int m = 0; m < 3; m++) {
                    uint32_t xin[4], o[4];
                    lds128(xin[0], xin[1], xin[2], xin[3], stage + lane_off + h * 1536 + m * 64);
#pragma unroll
                    for (int q = 0; q < 4; q++) {
                        const uint32_t v = acc[2 * (4 * m + q) + h];
                        o[q] = bf_fma(pack_bf2(h_lo(v), h_hi(v)), inv_rho2, xin[q]);
                    }
                    __stcs(op + h * 96 + m * 4, make_uint4(o[0], o[1], o[2], o[3]));
                }
            __syncwarp();
        }
    }
    PROF(5);
}

}

typedef CUresult (*EncodeTiledFn)(CUtensorMap*, CUtensorMapDataType, cuuint32_t, void*, const cuuint64_t*, const cuuint64_t*,
                                  const cuuint32_t*, const cuuint32_t*, CUtensorMapInterleave, CUtensorMapSwizzle,
                                  CUtensorMapL2promotion, CUtensorMapFloatOOBfill);

extern "C" void kernel_launch(void* const* d_in, const int* in_sizes, int n_in, void* d_out, int out_size) {
    using namespace cnx;
    static EncodeTiledFn encode = nullptr;
    static int num_sms = 0;
    static Scratch* scratch = nullptr;
    if (!encode) {
        void* fn = nullptr;
        cudaDriverEntryPointQueryResult qr;
        cudaGetDriverEntryPoint("cuTensorMapEncodeTiled", &fn, cudaEnableDefault, &qr);
        encode = (EncodeTiledFn)fn;
        cudaGetSymbolAddress((void**)&scratch, g_scratch);
        int dev = 0;
        cudaGetDevice(&dev);
        cudaDeviceGetAttribute(&num_sms, cudaDevAttrMultiProcessorCount, dev);
        if (num_sms > MAX_CTAS) num_sms = MAX_CTAS;
        cudaFuncSetAttribute(block_kernel, cudaFuncAttributeMaxDynamicSharedMemorySize, SM_TOTAL);
    }
    CUtensorMap tm;
    cuuint64_t dims[3] = {(cuuint64_t)CH, (cuuint64_t)IMG_W, (cuuint64_t)IMG_H};
    cuuint64_t strides[2] = {(cuuint64_t)CH * 2, (cuuint64_t)CH * 2 * IMG_W};
    cuuint32_t box[3] = {(cuuint32_t)CH, (cuuint32_t)REGION_PX, 1};
    cuuint32_t estr[3] = {1, 1, 1};
    encode(&tm, CU_TENSOR_MAP_DATA_TYPE_BFLOAT16, 3, d_in[0], dims, strides, box, estr, CU_TENSOR_MAP_INTERLEAVE_NONE,
           CU_TENSOR_MAP_SWIZZLE_NONE, CU_TENSOR_MAP_L2_PROMOTION_L2_128B, CU_TENSOR_MAP_FLOAT_OOB_FILL_NONE);
    Params pm = {};
    Descs& ds = pm.ds;
    for (int c = 0; c < 8; c++)
        for (int k = 0; k < 6; k++) ds.w1[c][k] = make_desc(SB + SM_W1 + c * 6 * 1536 + k * 256, 128, 1536);
    for (int k = 0; k < 24; k++) ds.w2[k] = make_desc(SB + SM_W2 + k * 256, 128, 6144);
    ds.ones = make_desc(SB + SM_ONES, 0, 0);
    CUtensorMap tw;
    cuuint64_t wdims[2] = {(cuuint64_t)EX, (cuuint64_t)CH};
    cuuint64_t wstrides[1] = {(cuuint64_t)EX * 2};
    cuuint32_t wbox[2] = {64, (cuuint32_t)CH};
    encode(&tw, CU_TENSOR_MAP_DATA_TYPE_BFLOAT16, 2, d_in[2], wdims, wstrides, wbox, estr, CU_TENSOR_MAP_INTERLEAVE_NONE,
           CU_TENSOR_MAP_SWIZZLE_128B, CU_TENSOR_MAP_L2_PROMOTION_L2_128B, CU_TENSOR_MAP_FLOAT_OOB_FILL_NONE);
    Split& sp = pm.sp;
    sp = {NTILES / num_sms, NTILES % num_sms, 1, 1 << 16, 0, {}};
    if (sp.per_cta + 9 > MAX_ROWS) return;
    if (sp.extra && sp.extra * (8 * LENT + 1) <= num_sms && sp.per_cta >= 5 * LENT + 8) {
        sp.period = num_sms / sp.extra;
        sp.inv_period = 65535 / sp.period + 1;
        sp.lenders = sp.extra;
        for (int l = 0; l < sp.extra; l++) {
            const Work w = get_work((l + 1) * sp.period - sp.period / 2 - 1, sp);
            for (int e = 0; e < LENT; e++) sp.lent_off[l * LENT + e] = tile_offset(w.tile(e));
            if (w.nA < 2 * LENT) sp.lenders = 0;
        }
    }
    pm.x = (const __nv_bfloat16*)d_in[0];
    pm.dw = (const __nv_bfloat16*)d_in[1];
    pm.w2 = (const __nv_bfloat16*)d_in[3];
    pm.gamma = (const __nv_bfloat16*)d_in[4];
    pm.beta = (const __nv_bfloat16*)d_in[5];
    pm.out = (__nv_bfloat16*)d_out;
    pm.sc = scratch;
    block_kernel<<<num_sms, NTHREADS, SM_TOTAL>>>(tm, tw, pm);
}
```

```cpp
#include <cuda_runtime.h>
#include <cuda_bf16.h>
#include <cuda_fp16.h>
#include <cuda.h>
#include <stdint.h>

namespace cnx {

constexpr int IMG_H = 512, IMG_W = 512, CH = 96, EX = 384;
constexpr int TILE_W = 64;
constexpr int NTILES = (IMG_W / TILE_W) * IMG_H;
constexpr int NSLOT = 6;
constexpr int REGION_PX = 18;
constexpr int REGION_BYTES = REGION_PX * CH * 2;
constexpr int SLOT_BYTES = 4 * REGION_BYTES;
constexpr int A_LBO = 144, A_SBO = 12 * A_LBO;
constexpr int PREFETCH_ROWS = 3;
constexpr int NCONS = 3;
constexpr int CONS_THREADS = 128 * NCONS;
constexpr int NTHREADS = 128 + CONS_THREADS;
constexpr int MAX_ROWS = 52;
constexpr int TILE_BYTES = TILE_W * CH * 2, WARP_BYTES = TILE_BYTES / 4;
#define K_PASS 4
#define K_WAIT 20
#define K_STG 5
#define K_REL 8
#define K_ANCH 2
#define K_CVT 0
#define K_CHAIN 3
#define K_OP 0
#define K_QS 0
#define K_GS 0
#define K_QR 0
#define K_GR 0
#define K_PD 0
#define K_PQ 0
#define K_PS 0
#define K_UNRV 3
constexpr int K_UNR = K_UNRV;
#define K_RW 0
#define K_P0 20
#define K_R0 0
#define K_ORD 0
#define KA 288
#define KB 96
#define KC 192
#define KX(e) (e == 96 ? k1 : e == 192 ? k2 : k3)
#define W2_EARLY 9
#define S2_FIRST 1
#define ORDER_P 3
#define ORDER_Q 1
static_assert(MAX_ROWS <= 128, "one table entry per producer thread");
static_assert(2 * A_SBO == REGION_BYTES && REGION_BYTES % 128 == 0, "region layout");

constexpr uint32_t SB = 1024;
constexpr int SM_W1 = 0;
constexpr int SM_W2 = SM_W1 + CH * EX * 2;
constexpr int SM_RING = SM_W2 + CH * EX * 2;
constexpr int SM_BIASH = SM_RING + NSLOT * SLOT_BYTES;
constexpr int SM_RED = SM_BIASH + 384;
constexpr int RED_MAX = 0, RED_LAUNCH = 48, RED_INV_RHO = 52;
constexpr int SM_TILES = SM_RED + 256;
constexpr int SM_ONES = SM_TILES + MAX_ROWS * 4;
constexpr int SM_BAR = SM_ONES + 128;
constexpr int BAR_X = SM_BAR;
constexpr int BAR_A = BAR_X + NSLOT * 4 * 8;
constexpr int BAR_E = BAR_A + NSLOT * 4 * 8;
constexpr int BAR_PIN = BAR_E + NSLOT * 4 * 8;
constexpr int BAR_W = BAR_PIN + 8;
constexpr int BAR_F = BAR_W + 6 * 8;
constexpr int BAR_R = BAR_F + 8;
constexpr int SM_TOTAL = BAR_R + 16 * 8;
constexpr int SM_FILTER = SM_RING + (NSLOT - 1) * SLOT_BYTES + 9 * 128;
constexpr int SM_SQ = SM_W2;
constexpr int SQ_ROW = 128 * 16, SQ_HALF = 6 * SQ_ROW;
static_assert(SM_ONES % 16 == 0 && SM_TOTAL <= 232448, "shared memory budget");

constexpr float KZ = 0.3292034911525734f;
constexpr uint32_t GELU_C2 = 0x40d940d9u;
constexpr float INV_2KZ = 0.5f / KZ;
constexpr unsigned SPIN_LIMIT = 1u << 19;

constexpr int MAX_CTAS = 255;
constexpr int W2_GROUPS = EX / 8;
#define K_LENT 3
constexpr int LENT = K_LENT, MAX_LENDERS = MAX_CTAS / (8 * LENT + 1);
struct Scratch {
    uint32_t w2h[EX * CH / 2];
    float w2max[EX];
    float bias[CH + 32];
    unsigned long long sums[EX / 4][32];
    __device__ __forceinline__ unsigned long long* sum(int e) { return &sums[e >> 2][e & 3]; }
    uint4 lent[MAX_LENDERS * LENT * 8 * 4 * 3 * 32];
    unsigned launch, pad0[31], early, pad1[31], prep, pad2[31], lent_out, pad3[31];
};
__device__ __align__(128) Scratch g_scratch;

#define PROF(k)

__device__ __forceinline__ uint32_t smem_u32(const void* p) { return (uint32_t)__cvta_generic_to_shared(p); }
__device__ __forceinline__ void mbar_init(uint32_t bar, uint32_t cnt) {
    asm volatile("mbarrier.init.shared::cta.b64 [%0], %1;" ::"r"(bar), "r"(cnt) : "memory");
}
__device__ __forceinline__ void mbar_arrive(uint32_t bar) {
    asm volatile("mbarrier.arrive.shared::cta.b64 _, [%0];" ::"r"(bar) : "memory");
}
__device__ __forceinline__ void mbar_expect_tx(uint32_t bar, uint32_t bytes) {
    asm volatile("mbarrier.arrive.expect_tx.shared::cta.b64 _, [%0], %1;" ::"r"(bar), "r"(bytes) : "memory");
}
__device__ __forceinline__ bool mbar_try(uint32_t bar, uint32_t par) {
    uint32_t ok;
    asm volatile("{\n.reg .pred p;\nmbarrier.try_wait.parity.shared::cta.b64 p, [%1], %2;\nselp.u32 %0, 1, 0, p;\n}\n"
                 : "=r"(ok) : "r"(bar), "r"(par) : "memory");
    return ok != 0;
}
__device__ __forceinline__ void mbar_wait(uint32_t bar, uint32_t par) {
    unsigned n = 0;
    while (!mbar_try(bar, par)) {
        if (++n > SPIN_LIMIT) __trap();
    }
}
__device__ __forceinline__ void mbar_wait_once(uint32_t bar, uint32_t par) {
    unsigned n = 0;
    bool ok;
#pragma unroll 1
    do {
        ok = mbar_try(bar, par);
        if (++n > SPIN_LIMIT) __trap();
    } while (!ok);
}
__device__ __forceinline__ bool elect_one() {
    uint32_t ok;
    asm volatile("{\n.reg .pred p;\nelect.sync _|p, 0xffffffff;\nselp.u32 %0, 1, 0, p;\n}\n" : "=r"(ok));
    return ok != 0;
}
__device__ __forceinline__ uint32_t opaque(uint32_t v) { return __shfl_sync(~0u, v, threadIdx.x & 31); }
__device__ __forceinline__ uint32_t lane_id() { uint32_t v; asm volatile("mov.u32 %0, %%laneid;" : "=r"(v)); return v; }
__device__ __forceinline__ uint32_t opaque_uniform(uint32_t v) { return __shfl_sync(~0u, v, 0); }
__device__ __forceinline__ void named_bar(int id, int n) { asm volatile("bar.sync %0, %1;" ::"r"(id), "r"(n) : "memory"); }
__device__ __forceinline__ void named_arrive(int id, int n) { asm volatile("bar.arrive %0, %1;" ::"r"(id), "r"(n) : "memory"); }
__device__ __forceinline__ void fence_async() { asm volatile("fence.proxy.async.shared::cta;" ::: "memory"); }
constexpr uint64_t EVICT_FIRST = 0x12F0000000000000ull;
__device__ __forceinline__ void tma_row(uint32_t dst, const CUtensorMap* tm, uint32_t bar, int x, int y) {
    asm volatile("cp.async.bulk.tensor.3d.shared::cluster.global.mbarrier::complete_tx::bytes.L2::cache_hint [%0], [%1, {%3, %4, %5}], [%2], %6;"
                 ::"r"(dst), "l"(tm), "r"(bar), "r"(0), "r"(x), "r"(y), "l"(EVICT_FIRST) : "memory");
}
__device__ __forceinline__ void bulk_load_stream(uint32_t dst, const void* src, uint32_t bytes, uint32_t bar) {
    asm volatile("cp.async.bulk.shared::cluster.global.mbarrier::complete_tx::bytes.L2::cache_hint [%0], [%1], %2, [%3], %4;"
                 ::"r"(dst), "l"(src), "r"(bytes), "r"(bar), "l"(EVICT_FIRST) : "memory");
}
__device__ __forceinline__ void prefetch_l2(const void* src, uint32_t bytes) {
    asm volatile("cp.async.bulk.prefetch.L2.global [%0], %1;" ::"l"(src), "r"(bytes) : "memory");
}
__device__ __forceinline__ void tma_2d(uint32_t dst, const CUtensorMap* tm, uint32_t bar, int x, int y) {
    asm volatile("cp.async.bulk.tensor.2d.shared::cluster.global.mbarrier::complete_tx::bytes [%0], [%1, {%3, %4}], [%2];"
                 ::"r"(dst), "l"(tm), "r"(bar), "r"(x), "r"(y) : "memory");
}
__device__ __forceinline__ void bulk_load(uint32_t dst, const void* src, uint32_t bytes, uint32_t bar) {
    asm volatile("cp.async.bulk.shared::cluster.global.mbarrier::complete_tx::bytes [%0], [%1], %2, [%3];"
                 ::"r"(dst), "l"(src), "r"(bytes), "r"(bar) : "memory");
}
__device__ __forceinline__ void wg_fence() { asm volatile("wgmma.fence.sync.aligned;" ::: "memory"); }
__device__ __forceinline__ void wg_commit() { asm volatile("wgmma.commit_group.sync.aligned;" ::: "memory"); }
template <int N> __device__ __forceinline__ void wg_wait() { asm volatile("wgmma.wait_group.sync.aligned %0;" ::"n"(N) : "memory"); }
template <int N> __device__ __forceinline__ void pin(uint32_t (&d)[N]) {
#pragma unroll
    for (int q = 0; q < N; q++) asm volatile("" : "+r"(d[q])::"memory");
}
__device__ __forceinline__ void stg128(void* p, const uint32_t (&v)[4]) {
    asm volatile("st.global.v4.u32 [%0], {%1, %2, %3, %4};" ::"l"(p), "r"(v[0]), "r"(v[1]), "r"(v[2]), "r"(v[3]) : "memory");
}
__device__ __forceinline__ void ldg128(uint32_t (&v)[4], const void* p) {
    asm volatile("ld.global.L1::no_allocate.v4.u32 {%0, %1, %2, %3}, [%4];" : "=r"(v[0]), "=r"(v[1]), "=r"(v[2]), "=r"(v[3]) : "l"(p) : "memory");
}
__device__ __forceinline__ void ldg128_if(bool on, uint32_t (&v)[4], const void* p) {
    asm volatile("{\n.reg .pred p;\nsetp.ne.b32 p, %5, 0;\n@p ld.global.L1::no_allocate.v4.u32 {%0, %1, %2, %3}, [%4];\n}\n"
                 : "+r"(v[0]), "+r"(v[1]), "+r"(v[2]), "+r"(v[3]) : "l"(p), "r"((int)on) : "memory");
}
__host__ __device__ constexpr uint64_t make_desc(uint32_t addr, uint32_t lbo, uint32_t sbo) {
    return (uint64_t)((addr & 0x3FFFF) >> 4) | ((uint64_t)(lbo >> 4) << 16) | ((uint64_t)(sbo >> 4) << 32);
}
__device__ __forceinline__ void wgmma(uint32_t (&d)[12], uint32_t a0, uint32_t a1, uint32_t a2, uint32_t a3, uint64_t db, int acc) {
    asm volatile("{\n.reg .pred p;\nsetp.ne.b32 p, %17, 0;\n"
                 "wgmma.mma_async.sync.aligned.m64n48k16.f16.f16.f16 "
                 "{%0, %1, %2, %3, %4, %5, %6, %7, %8, %9, %10, %11}, "
                 "{%12, %13, %14, %15}, %16, p, 1, 1, 0;\n}\n"
                 : "+r"(d[0]), "+r"(d[1]), "+r"(d[2]), "+r"(d[3]), "+r"(d[4]), "+r"(d[5]), "+r"(d[6]), "+r"(d[7]), "+r"(d[8]), "+r"(d[9]), "+r"(d[10]), "+r"(d[11])
                 : "r"(a0), "r"(a1), "r"(a2), "r"(a3), "l"(db), "r"(acc));
}
__device__ __forceinline__ void wgmma(uint32_t (&d)[24], uint32_t a0, uint32_t a1, uint32_t a2, uint32_t a3, uint64_t db, int acc) {
    asm volatile("{\n.reg .pred p;\nsetp.ne.b32 p, %29, 0;\n"
                 "wgmma.mma_async.sync.aligned.m64n96k16.f16.f16.f16 "
                 "{%0, %1, %2, %3, %4, %5, %6, %7, %8, %9, %10, %11, %12, %13, %14, %15, %16, %17, %18, %19, %20, %21, %22, %23}, "
                 "{%24, %25, %26, %27}, %28, p, 1, 1, 0;\n}\n"
                 : "+r"(d[0]), "+r"(d[1]), "+r"(d[2]), "+r"(d[3]), "+r"(d[4]), "+r"(d[5]), "+r"(d[6]), "+r"(d[7]), "+r"(d[8]), "+r"(d[9]), "+r"(d[10]), "+r"(d[11]), "+r"(d[12]), "+r"(d[13]), "+r"(d[14]), "+r"(d[15]), "+r"(d[16]), "+r"(d[17]), "+r"(d[18]), "+r"(d[19]), "+r"(d[20]), "+r"(d[21]), "+r"(d[22]), "+r"(d[23])
                 : "r"(a0), "r"(a1), "r"(a2), "r"(a3), "l"(db), "r"(acc));
}
template <int ACC>
__device__ __forceinline__ void wgmma_rowsum(float (&d)[4], const uint32_t (&a)[4], uint64_t ones) {
    asm volatile("{\n.reg .pred p;\nsetp.ne.b32 p, %9, 0;\n"
                 "wgmma.mma_async.sync.aligned.m64n8k16.f32.bf16.bf16 {%0, %1, %2, %3}, {%4, %5, %6, %7}, %8, p, 1, 1, 0;\n}\n"
                 : "+f"(d[0]), "+f"(d[1]), "+f"(d[2]), "+f"(d[3])
                 : "r"(a[0]), "r"(a[1]), "r"(a[2]), "r"(a[3]), "l"(ones), "n"(ACC));
}
__device__ __forceinline__ void ldsm4(uint32_t (&r)[4], uint32_t addr) {
    asm volatile("ldmatrix.sync.aligned.m8n8.x4.shared.b16 {%0, %1, %2, %3}, [%4];"
                 : "=r"(r[0]), "=r"(r[1]), "=r"(r[2]), "=r"(r[3]) : "r"(addr) : "memory");
}
__device__ __forceinline__ void ldsm4_t(uint32_t (&r)[4], uint32_t addr) {
    asm volatile("ldmatrix.sync.aligned.m8n8.x4.trans.shared.b16 {%0, %1, %2, %3}, [%4];"
                 : "=r"(r[0]), "=r"(r[1]), "=r"(r[2]), "=r"(r[3]) : "r"(addr) : "memory");
}
__device__ __forceinline__ void stsm4(uint32_t addr, uint32_t a, uint32_t b, uint32_t c, uint32_t d) {
    asm volatile("stmatrix.sync.aligned.m8n8.x4.shared.b16 [%0], {%1, %2, %3, %4};"
                 ::"r"(addr), "r"(a), "r"(b), "r"(c), "r"(d) : "memory");
}
__device__ __forceinline__ uint32_t transpose8x8(uint32_t v) {
    uint32_t d; asm volatile("movmatrix.sync.aligned.m8n8.trans.b16 %0, %1;" : "=r"(d) : "r"(v)); return d;
}
__device__ __forceinline__ void spin_until(const unsigned* counter, unsigned target) {
    unsigned n = 0, c;
    do {
        asm volatile("ld.acquire.gpu.global.u32 %0, [%1];" : "=r"(c) : "l"(counter) : "memory");
        if (++n > SPIN_LIMIT) __trap();
    } while ((int)(c - target) < 0);
}
__device__ __forceinline__ void signal(unsigned* counter) {
    __syncwarp();
    if (elect_one()) asm volatile("red.release.gpu.global.add.u32 [%0], 1;" ::"l"(counter) : "memory");
    __syncwarp();
}
__device__ __forceinline__ void lds128(uint32_t& a, uint32_t& b, uint32_t& c, uint32_t& d, uint32_t addr) {
    asm volatile("ld.shared.v4.u32 {%0, %1, %2, %3}, [%4];" : "=r"(a), "=r"(b), "=r"(c), "=r"(d) : "r"(addr) : "memory");
}
__device__ __forceinline__ void lds64(uint32_t& a, uint32_t& b, uint32_t addr) {
    asm volatile("ld.shared.v2.u32 {%0, %1}, [%2];" : "=r"(a), "=r"(b) : "r"(addr) : "memory");
}
__device__ __forceinline__ void lds32(uint32_t& a, uint32_t addr) {
    asm volatile("ld.shared.u32 %0, [%1];" : "=r"(a) : "r"(addr) : "memory");
}
__device__ __forceinline__ int ldsi(uint32_t addr) {
    uint32_t v;
    lds32(v, addr);
    return (int)v;
}
__device__ __forceinline__ float ldsf(uint32_t addr) {
    uint32_t v;
    lds32(v, addr);
    return __uint_as_float(v);
}
__device__ __forceinline__ void sts32(uint32_t addr, uint32_t a) {
    asm volatile("st.shared.u32 [%0], %1;" ::"r"(addr), "r"(a) : "memory");
}
__device__ __forceinline__ void sts128(uint32_t addr, uint32_t a, uint32_t b, uint32_t c, uint32_t d) {
    asm volatile("st.shared.v4.u32 [%0], {%1, %2, %3, %4};" ::"r"(addr), "r"(a), "r"(b), "r"(c), "r"(d) : "memory");
}
__device__ __forceinline__ void sts64(uint32_t addr, uint32_t a, uint32_t b) {
    asm volatile("st.shared.v2.u32 [%0], {%1, %2};" ::"r"(addr), "r"(a), "r"(b) : "memory");
}
__device__ __forceinline__ void anchor(uint32_t addr, uint32_t a, uint32_t b, uint32_t c, uint32_t d) {
    asm volatile("{\n.reg .pred p;\nsetp.eq.b32 p, %0, 0;\n@p st.shared.v4.u32 [%0], {%1, %2, %3, %4};\n}\n"
                 ::"r"(addr), "r"(a), "r"(b), "r"(c), "r"(d) : "memory");
}
__device__ __forceinline__ uint32_t bf_fma(uint32_t a, uint32_t b, uint32_t c) {
    uint32_t d; asm("fma.rn.bf16x2 %0, %1, %2, %3;" : "=r"(d) : "r"(a), "r"(b), "r"(c)); return d;
}
__device__ __forceinline__ uint32_t bf_mul(uint32_t a, uint32_t b) {
    uint32_t d; asm("mul.rn.bf16x2 %0, %1, %2;" : "=r"(d) : "r"(a), "r"(b)); return d;
}
__device__ __forceinline__ uint32_t bf_absmax(uint32_t a, uint32_t b) {
    uint32_t d; asm("max.xorsign.abs.bf16x2 %0, %1, %2;" : "=r"(d) : "r"(a), "r"(b)); return d;
}
__device__ __forceinline__ uint32_t h_fma(uint32_t a, uint32_t b, uint32_t c) {
    uint32_t d; asm("fma.rn.f16x2 %0, %1, %2, %3;" : "=r"(d) : "r"(a), "r"(b), "r"(c)); return d;
}
__device__ __forceinline__ uint32_t h_mul(uint32_t a, uint32_t b) {
    uint32_t d; asm("mul.rn.f16x2 %0, %1, %2;" : "=r"(d) : "r"(a), "r"(b)); return d;
}
__device__ __forceinline__ uint32_t h_cut8(uint32_t v) { return v & 0xfff8fff8u; }
constexpr float CUT_GAIN = 1.f + 0.4375f * 0.7213f / 128;
__device__ __forceinline__ uint32_t h_tanh(uint32_t a) {
    uint32_t d; asm("tanh.approx.f16x2 %0, %1;" : "=r"(d) : "r"(a)); return d;
}
__device__ __forceinline__ uint32_t pack_h2(float lo, float hi) {
    uint32_t d; asm("cvt.rn.f16x2.f32 %0, %1, %2;" : "=r"(d) : "f"(hi), "f"(lo)); return d;
}
__device__ __forceinline__ uint32_t pack_bf2(float lo, float hi) {
    uint32_t d; asm("cvt.rn.bf16x2.f32 %0, %1, %2;" : "=r"(d) : "f"(hi), "f"(lo)); return d;
}
__device__ __forceinline__ float bf_lo(uint32_t v) { return __uint_as_float(v << 16); }
__device__ __forceinline__ float bf_hi(uint32_t v) { return __uint_as_float(v & 0xffff0000u); }
__device__ __forceinline__ float h_lo(uint32_t v) { return __low2float(*reinterpret_cast<__half2*>(&v)); }
__device__ __forceinline__ float h_hi(uint32_t v) { return __high2float(*reinterpret_cast<__half2*>(&v)); }
__device__ __forceinline__ float warp_absmax(uint32_t v) {
    return __uint_as_float(__reduce_max_sync(~0u, max((v & 0x7fffu) << 16, v & 0x7fff0000u)));
}
__device__ __forceinline__ uint32_t gelu2(uint32_t z) {
    uint32_t p = h_fma(z, z, GELU_C2);
    uint32_t t = h_tanh(K_OP & 1 ? h_mul(p, z) : h_mul(z, p));
    return K_OP & 2 ? h_fma(t, z, z) : h_fma(z, t, z);
}
__device__ __forceinline__ float pow2i(int e) { return __uint_as_float((uint32_t)(e + 127) << 23); }
__device__ __forceinline__ int ilog2f(float v) {
    int e = (int)((__float_as_uint(v) >> 23) & 0xff) - 127;
    return max(-100, min(100, e));
}

__device__ __forceinline__ int bound_exp(float w1max) { return w1max > 0.f ? ilog2f(2.f * KZ * 96.f * w1max) : 0; }
__device__ __forceinline__ bool plain_squares(int e) { return (unsigned)(4 - e) <= 6; }
__device__ __forceinline__ int square_exp(int e) { return plain_squares(e) ? 0 : max(-14, min(4 - e, 14)); }
__device__ __forceinline__ int sum_exp(int e) { return max(-90, min(90, 33 - 2 * e)); }
__device__ __forceinline__ int row_exp(float m) { return 2 - ilog2f(m); }

struct Split {
    int per_cta, extra, period, inv_period, lenders;
    uint32_t lent_off[MAX_LENDERS * LENT];
    __host__ __device__ __forceinline__ int longer_before(int cta) const {
        const int n = (cta + period / 2) * inv_period >> 16;
        return n < extra ? n : extra;
    }
};
struct Work {
    int tA, tB, nA, nB, dir, rows, lent, index;
    __host__ __device__ __forceinline__ int tile(int j) const { return j < nA ? tA + dir * j : tB + dir * (j - nA); }
};
__host__ __device__ __forceinline__ Work get_work(int cta, const Split& sp) {
    Work w;
    const int before = sp.longer_before(cta), longer = sp.longer_before(cta + 1) - before;
    w.lent = longer && sp.lenders ? LENT : 0;
    w.index = longer ? before : cta - before;
    const int t0 = cta * sp.per_cta + before, t1 = t0 + sp.per_cta + longer;
    const int tm = t1 < (t0 | 511) + 1 ? t1 : (t0 | 511) + 1;
    const bool swap = t1 > tm && t1 - tm < tm - t0, down = cta & 1;
    w.nA = swap ? t1 - tm : tm - t0;
    w.nB = t1 - t0 - w.nA;
    w.tA = down ? (swap ? tm : t0) : (swap ? t1 : tm) - 1;
    w.tB = down ? (swap ? t0 : tm) : (swap ? tm : t1) - 1;
    w.dir = down ? 1 : -1;
    w.rows = w.nA + 2 + (w.nB ? w.nB + 2 : 0);
    return w;
}
__device__ __forceinline__ int row_code(const Work& w, int i) {
    const bool in_a = i < w.nA + 2;
    const int t = in_a ? w.tA : w.tB;
    return ((t & 511) + w.dir * ((in_a ? i : i - (w.nA + 2)) - 1)) << 16 | (t >> 9) * TILE_W;
}
__host__ __device__ __forceinline__ uint32_t tile_offset(int tile) { return ((tile & 511) * IMG_W + (tile >> 9) * TILE_W) * (CH * 2); }
__device__ __forceinline__ int tile_order(int j, int n) {
    const int olds = (j / ORDER_P) * ORDER_Q + max(0, j % ORDER_P - (ORDER_P - ORDER_Q));
    return (j % ORDER_P >= ORDER_P - ORDER_Q) ? olds : n - 1 - (j - olds);
}
__device__ __forceinline__ void issue_region(const CUtensorMap* tm, uint32_t dst, uint32_t bar, int warp, int code) {
    mbar_expect_tx(bar, REGION_BYTES);
    tma_row(dst, tm, bar, (code & 0xffff) + (16 * warp - 1), code >> 16);
}

template <class Event>
__device__ __forceinline__ void conv_producer(const Work& wk, const CUtensorMap* tm, uint32_t sb, int warp, Event event) {
    const int lane = threadIdx.x & 31;
    const int j = lane & 15, grp = lane >> 4;
    const uint32_t reg0 = sb + SM_RING + warp * REGION_BYTES;
    const uint32_t bars = sb + SM_BAR + warp * 8;
    if (warp * 32 + lane < MAX_ROWS) {
        const int i = warp * 32 + lane, before = min(i / 5, wk.lent);
        const bool back = i % 5 == 0 && i > 0 && i / 5 <= wk.lent;
        sts32(sb + SM_TILES + i * 4, back ? tile_offset(wk.tile(before - 1)) | before
                                          : tile_offset(wk.tile(wk.lent + tile_order(i - before, wk.nA + wk.nB - 4 - wk.lent))));
    }
    const uint32_t ld64 = opaque(reg0 + grp * 8 * 192 + j * 8), ld32 = opaque(reg0 + grp * 8 * 192 + 128 + j * 4);
    const uint32_t st64 = opaque(reg0 + grp * A_SBO + (j >> 1) * A_LBO + (j & 1) * 8);
    const uint32_t st32 = opaque(reg0 + grp * A_SBO + (8 + (j >> 2)) * A_LBO + (j & 3) * 4);
    named_bar(0, NTHREADS);
    uint32_t w[3][3][3];
    mbar_wait_once(sb + BAR_F, 0);
#pragma unroll
    for (int tap = 0; tap < 9; tap++) {
        const uint32_t p = sb + SM_FILTER + (3 + wk.dir * 3 * (tap / 3 - 1) + tap % 3) * (CH * 2);
        lds64(w[tap / 3][tap % 3][0], w[tap / 3][tap % 3][1], p + 8 * j);
        lds32(w[tap / 3][tap % 3][2], p + 128 + 4 * j);
    }
#pragma unroll
    for (int tap = 0; tap < 9; tap++) sts64(reg0 + (NSLOT - 1) * SLOT_BYTES + tap * 128 + j * 8, w[tap / 3][tap % 3][1], w[tap / 3][tap % 3][0]);
    named_bar(1, 128);
#pragma unroll
    for (int tap = 0; tap < 9; tap++) lds64(w[tap / 3][tap % 3][1], w[tap / 3][tap % 3][0], reg0 + (NSLOT - 1) * SLOT_BYTES + tap * 128 + j * 8);
    static_assert(2 * PREFETCH_ROWS == NSLOT && SLOT_BYTES % 32 == 0, "slot arithmetic");
    uint32_t bo = 0, par = 0, pbo = PREFETCH_ROWS * 32, ppar = 1;
    int px, py;
    auto request = [&]() {
        mbar_wait_once(bars + (BAR_E - SM_BAR) + pbo, ppar);
        if (elect_one()) {
            mbar_expect_tx(bars + pbo, REGION_BYTES);
            tma_row(reg0 + pbo * (SLOT_BYTES / 32), tm, bars + pbo, px, py);
        }
    };
    auto advance = [&]() {
        bo += 32;
        if (bo == NSLOT * 32) { bo = 0; par ^= 1; }
        pbo += 32;
        if (pbo == NSLOT * 32) { pbo = 0; ppar ^= 1; }
    };
    auto aim = [&](int row) {
        const int code = row_code(wk, row);
        px = (code & 0xffff) + (16 * warp - 1);
        py = code >> 16;
    };
    uint32_t accB[8][3], accC[8][3];
    int r = 0;
#pragma unroll 1
    while (r < wk.rows) {
        if (r == 0 || r == wk.nA + 2) {
            const uint32_t bo0 = bo;
            uint32_t bo1;
#pragma unroll 1
            for (int k = 0; k < 2; k++, r++) {
                mbar_wait_once(bars + bo, par);
                bo1 = bo;
                if (r >= 2) {
                    aim(r + PREFETCH_ROWS);
                    request();
                }
                advance();
            }
            const uint32_t so0 = bo0 * (SLOT_BYTES / 32), so1 = bo1 * (SLOT_BYTES / 32);
#pragma unroll
            for (int p = 0; p < 10; p++) {
                uint32_t u[3], v[3];
                lds64(u[0], u[1], so0 + ld64 + p * 192);
                lds32(u[2], so0 + ld32 + p * 192);
                lds64(v[0], v[1], so1 + ld64 + p * 192);
                lds32(v[2], so1 + ld32 + p * 192);
#pragma unroll
                for (int dx = 0; dx < 3; dx++) {
                    const int o = p - dx;
                    if (o < 0 || o > 7) continue;
#pragma unroll
                    for (int q = 0; q < 3; q++) {
                        accB[o][q] = bf_fma(v[q], w[1][dx][q], dx == 0 ? bf_mul(u[q], w[0][dx][q]) : bf_fma(u[q], w[0][dx][q], accB[o][q]));
                        accC[o][q] = dx == 0 ? bf_mul(v[q], w[0][dx][q]) : bf_fma(v[q], w[0][dx][q], accC[o][q]);
                    }
                }
            }
            anchor(ld64, accB[7][0], accB[7][1], accB[7][2], 0);
            __syncwarp();
            if (elect_one()) {
                mbar_arrive(bars + (BAR_A - SM_BAR) + bo0);
                mbar_arrive(bars + (BAR_E - SM_BAR) + bo0);
                mbar_arrive(bars + (BAR_A - SM_BAR) + bo1);
                mbar_arrive(bars + (BAR_E - SM_BAR) + bo1);
            }
        }
        int end = wk.rows;
        const int marks[4] = {wk.rows - PREFETCH_ROWS, wk.rows - 11, wk.nA + 2, wk.nA + 2 - PREFETCH_ROWS};
#pragma unroll
        for (int k = 0; k < 4; k++) end = marks[k] > r ? min(end, marks[k]) : end;
        const bool fetch = r < wk.rows - PREFETCH_ROWS;
        aim(r + PREFETCH_ROWS);
        px = opaque_uniform(px);
        const int py_end = opaque_uniform(py + wk.dir * (end - r));
        r = end;
#pragma unroll 1
        do {
            mbar_wait(bars + bo, par);
            const uint32_t so = bo * (SLOT_BYTES / 32);
            uint32_t out[8][3];
#pragma unroll
            for (int p = 0; p < 10; p++) {
                uint32_t xv[3];
                lds64(xv[0], xv[1], so + ld64 + p * 192);
                lds32(xv[2], so + ld32 + p * 192);
#pragma unroll
                for (int dd = 0; dd < 3; dd++) {
                    const int dx = K_PD ? 2 - dd : dd, o = p - dx;
                    if (o < 0 || o > 7) continue;
#pragma unroll
                    for (int qq = 0; qq < 3; qq++) {
                        const int q = (qq + K_PQ) % 3;
                        out[o][q] = bf_fma(xv[q], w[2][dx][q], dx == 0 ? accB[o][q] : out[o][q]);
                        accB[o][q] = bf_fma(xv[q], w[1][dx][q], dx == 0 ? accC[o][q] : accB[o][q]);
                        accC[o][q] = dx == 0 ? bf_mul(xv[q], w[0][dx][q]) : bf_fma(xv[q], w[0][dx][q], accC[o][q]);
                    }
                }
            }
            __syncwarp();
#pragma unroll
            for (int oo = 0; oo < 8; oo++) {
                const int o = K_PS ? 7 - oo : oo;
                sts64(so + st64 + o * 16, out[o][0], out[o][1]);
                sts32(so + st32 + o * 16, out[o][2]);
            }
            __syncwarp();
            if (elect_one()) mbar_arrive(bars + (BAR_A - SM_BAR) + bo);
            if (fetch) request();
            advance();
            py += wk.dir;
        } while (py != py_end);
        if (((wk.rows - r) & ~8) == PREFETCH_ROWS) event(wk.rows - r == PREFETCH_ROWS);
    }
}

template <bool SCALED, int K0 = 0, int K1 = 3>
__device__ __forceinline__ void gelu_sq(uint32_t (&d)[24], uint32_t (&keep)[24], uint32_t sq_addr, uint32_t scale2) {
    pin(d);
#pragma unroll
    for (int k = K0; k < K1; k++) {
        uint32_t hs[4];
        lds128(hs[0], hs[1], hs[2], hs[3], sq_addr + k * SQ_ROW);
#pragma unroll
        for (int qq = 0; qq < 4; qq++) {
            const int q = K_QS == 0 ? qq : K_QS == 1 ? 3 - qq : K_QS == 2 ? (qq >> 1 | (qq & 1) << 1) : (qq + 1) & 3;
            uint32_t g0 = gelu2(d[8 * k + 2 * q]), g1 = gelu2(d[8 * k + 2 * q + 1]);
            keep[8 * k + 2 * q] = g0;
            keep[8 * k + 2 * q + 1] = g1;
            if (SCALED) { g0 = h_mul(g0, scale2); g1 = h_mul(g1, scale2); }
            hs[q] = (K_GS >> (q & 1) & 1) ? h_fma(g0, g0, h_fma(g1, g1, hs[q])) : h_fma(g1, g1, h_fma(g0, g0, hs[q]));
        }
        sts128(sq_addr + k * SQ_ROW, hs[0], hs[1], hs[2], hs[3]);
    }
}
__device__ __forceinline__ void gelu_sq_reg(uint32_t (&d)[24], uint32_t (&hs)[12]) {
    pin(d);
#pragma unroll
    for (int qq = 0; qq < 12; qq++) {
        const int q = K_QR == 0 ? qq : K_QR == 1 ? 11 - qq : K_QR == 2 ? qq ^ 1 : qq * 5 % 12;
        const uint32_t g0 = gelu2(d[2 * q]), g1 = gelu2(d[2 * q + 1]);
        hs[q] = (K_GR >> (q & 1) & 1) ? h_fma(g0, g0, h_fma(g1, g1, hs[q])) : h_fma(g1, g1, h_fma(g0, g0, hs[q]));
    }
}
__device__ __forceinline__ void gelu_to(uint32_t (&g)[12], uint32_t (&d)[12]) {
    pin(d);
#pragma unroll
    for (int q = 0; q < 12; q++) g[q] = gelu2(d[q]);
    pin(g);
}
__device__ __forceinline__ void load_tile(uint32_t (&raw)[6][4], uint32_t addr) {
#pragma unroll
    for (int s = 0; s < 6; s++) ldsm4(raw[s], addr + s * 2 * A_LBO);
}
__device__ __forceinline__ uint2 ln_stats(const uint32_t (&raw)[6][4], uint64_t ones) {
    constexpr int NS = 6 / K_CHAIN;
    uint32_t sq[NS][4];
#pragma unroll
    for (int s = 0; s < 6; s++)
#pragma unroll
        for (int q = 0; q < 4; q++) sq[s % NS][q] = s < NS ? bf_mul(raw[s][q], raw[s][q]) : bf_fma(raw[s][q], raw[s][q], sq[s % NS][q]);
    float sum[4], ssq[4];
    wg_fence();
    wgmma_rowsum<0>(sum, raw[0], ones);
#pragma unroll
    for (int s = 1; s < 6; s++) wgmma_rowsum<1>(sum, raw[s], ones);
    wgmma_rowsum<0>(ssq, sq[0], ones);
#pragma unroll
    for (int s = 1; s < NS; s++) wgmma_rowsum<1>(ssq, sq[s], ones);
    wg_commit();
    wg_wait<0>();
    uint32_t st[2];
#pragma unroll
    for (int h = 0; h < 2; h++) {
        asm volatile("" : "+f"(sum[2 * h]), "+f"(ssq[2 * h])::"memory");
        const float mean = sum[2 * h] * (1.f / CH);
        const float var = fmaxf(fmaf(ssq[2 * h], 1.f / CH, -mean * mean), 0.f);
        float rstd;
        asm("rsqrt.approx.ftz.f32 %0, %1;" : "=f"(rstd) : "f"(var + 1e-5f));
        rstd = bf_lo(pack_bf2(rstd * (K_CVT == 0 ? KZ : KZ * 0x1p-112f), 0.f));
        st[h] = pack_bf2(rstd, -mean * rstd);
    }
    return make_uint2(st[0], st[1]);
}
__device__ __forceinline__ void ln_apply(uint32_t (&a)[6][4], const uint2& st) {
    const uint32_t sc[2] = {__byte_perm(st.x, 0, 0x1010), __byte_perm(st.y, 0, 0x1010)};
    const uint32_t sh[2] = {__byte_perm(st.x, 0, 0x3232), __byte_perm(st.y, 0, 0x3232)};
#pragma unroll
    for (int s = 0; s < 6; s++)
#pragma unroll
        for (int q = 0; q < 4; q++) {
            const uint32_t v = bf_fma(a[s][q], sc[q & 1], sh[q & 1]);
            a[s][q] = K_CVT == 0 ? pack_h2(bf_lo(v), bf_hi(v)) : K_CVT == 1 ? (v & 0x7fff7fffu) * 7u + v : ((v << 3) & 0x7fff7fffu) | (v & 0x80008000u);
        }
}
struct Cursor {
    int slot;
    uint32_t par;
    __device__ __forceinline__ void advance(int n) {
        slot += n;
        if (slot >= NSLOT) { slot -= NSLOT; par ^= 1; }
    }
};
struct Descs {
    uint64_t w1[8][6];
    uint64_t w2[24];
    uint64_t ones;
};
template <int E0, int N>
__device__ __forceinline__ void gemm1_chunk(uint32_t (&d)[N], const uint32_t (&a)[6][4], const Descs& ds, int zero) {
#pragma unroll
    for (int s = 0; s < 6; s++) wgmma(d, a[s][0], a[s][1], a[s][2], a[s][3], ds.w1[E0 / 48][s], s ? 1 : zero);
}
template <int E0, int N>
__device__ __forceinline__ void gemm2_chunk(uint32_t (&acc)[24], const uint32_t (&g)[N], const Descs& ds) {
#pragma unroll
    for (int s = 0; s < N / 4; s++) wgmma(acc, g[4 * s], g[4 * s + 1], g[4 * s + 2], g[4 * s + 3], ds.w2[E0 / 16 + s], 1);
}

struct __align__(64) Params {
    Split sp;
    int zero;
    const __nv_bfloat16 *x, *dw, *w2, *gamma, *beta;
    __nv_bfloat16* out;
    Scratch* sc;
    Descs ds;
};

__global__ void __launch_bounds__(NTHREADS, 1)
block_kernel(const __grid_constant__ CUtensorMap tmap, const __grid_constant__ CUtensorMap tmap_w1, const __grid_constant__ Params pm) {
    const Split& sp = pm.sp;
    const Descs& ds = pm.ds;
    const int& zero = pm.zero;
    const __nv_bfloat16 *const &x = pm.x, *const &dw = pm.dw, *const &w2 = pm.w2, *const &gamma = pm.gamma, *const &beta = pm.beta;
    __nv_bfloat16* const& out = pm.out;
    Scratch* const& sc = pm.sc;
    extern __shared__ __align__(1024) uint8_t smem[];
    constexpr uint32_t sb = SB;
    const int tid = threadIdx.x;
    const Work wk = get_work(blockIdx.x, sp);
    constexpr uint32_t s_red = sb + SM_RED;
    if (smem_u32(smem) != SB) __trap();

    const int warp_id = __shfl_sync(~0u, tid >> 5, 0);
    PROF(0);
    const int cw = warp_id - 4, wgi = cw >> 2, w4 = warp_id & 3;
    if (elect_one()) {
        static_assert(3 * NSLOT * 4 == 8 + 4 * 16 && BAR_F == BAR_W + 48, "barrier shares");
        const int b = warp_id - 8;
        const uint32_t bar = b < 0 ? sb + BAR_X + warp_id * 8 : b < 7 ? sb + BAR_W + b * 8 : sb + BAR_PIN;
        mbar_init(bar, 1);
#pragma unroll
        for (int k = 0; k < 4; k++) mbar_init(sb + BAR_X + (8 + 4 * warp_id + k) * 8, 1);
        mbar_init(sb + BAR_R + warp_id * 8, 1);
        fence_async();
        if (b < 0) {
            issue_region(&tmap, sb + SM_RING + warp_id * REGION_BYTES, bar, w4, ((wk.tA & 511) + wk.dir * wgi) << 16 | (wk.tA >> 9) * TILE_W);
        } else if (b < 6) {
            mbar_expect_tx(bar, 64 * CH * 2);
            tma_2d(sb + SM_W2 + b * (64 * CH * 2), &tmap_w1, bar, 64 * b, 0);
        } else if (b == 6) {
            mbar_expect_tx(bar, 9 * CH * 2);
            bulk_load(sb + SM_FILTER, dw, 9 * CH * 2, bar);
        }
    }
    __syncwarp();
    const int ntiles = wk.nA + wk.nB;
    const int rank = (wgi + wk.lent + 2 * (ntiles - 1)) % NCONS | (wgi >> 2 & 3);
    const int spare = wk.rows % NSLOT, spare2 = spare == NSLOT - 1 ? 0 : spare + 1;
    const uint32_t sq_base = sb + (wgi < 0 ? SM_RING + spare * SLOT_BYTES : SM_SQ + rank * 2 * SQ_HALF);
    const uint32_t sq_upper = wgi < 0 ? (spare2 - spare) * SLOT_BYTES : SQ_HALF;
    const uint32_t bar_a = sb + BAR_A + w4 * 8, bar_e = sb + BAR_E + w4 * 8;
    const bool prepares = gridDim.x - blockIdx.x <= W2_GROUPS / 2, helps = !wk.lent && wk.index < 8 * LENT * sp.lenders;
    auto max_w1 = [&](uint32_t lane) { return __uint_as_float(__reduce_max_sync(~0u, lane < 4 * NCONS ? ldsi(s_red + RED_MAX + lane * 4) : 0)); };
    auto square_scale = [&](uint32_t lane) {
        const float f = pow2i(square_exp(bound_exp(max_w1(lane))));
        return pack_h2(f, f);
    };
    uint32_t a_addr, sq;
    const uint32_t sq_warp = sq_base + w4 * 512;
    auto set_addresses = [&]() {
        a_addr = opaque(sb + SM_RING + w4 * REGION_BYTES + ((tid >> 3) & 1) * A_SBO + ((tid >> 4) & 1) * A_LBO + (tid & 7) * 16);
        sq = opaque(sq_base + (tid & 127) * 16);
    };
    uint32_t turn, turn_end, so, so_sum, bo, bo_sum, off;
    auto set_run = [&](int j, int stop, int row) {
        const int slot = row % NSLOT, both = 2 * (row % 3) + 3;
        turn = opaque_uniform(row / 3);
        turn_end = opaque_uniform(row / 3 + max(stop - j + NCONS - 1, 0) / NCONS);
        so = opaque_uniform(slot * SLOT_BYTES);
        so_sum = opaque_uniform(both * SLOT_BYTES);
        bo = opaque_uniform(bar_a + slot * 32);
        bo_sum = opaque_uniform(2 * bar_a + both * 32);
        off = opaque_uniform(tile_offset(wk.tile(j)) + w4 * WARP_BYTES - sq_warp);
    };
    const int nrest = ntiles - 4;
    int jt;
    Cursor cur;
    int fast_from;
    if (warp_id < 4) {
        const int q = (gridDim.x - 1 - blockIdx.x) * 2 + (w4 >> 1);
        conv_producer(wk, &tmap, sb, warp_id, [&](bool second) {
            if (!second) {
                if (blockIdx.x == 0) {
#pragma unroll 1
                    for (int e = tid; e < EX; e += 128) *sc->sum(e) = 0;
                    sc->bias[tid] = 0.f;
                }
                if (blockIdx.x == 0 || wk.lent) signal(&sc->early);
            } else if (prepares || helps) {
                spin_until(&sc->early, (ldsi(s_red + RED_LAUNCH) + 1) * 4 * (sp.lenders + 1));
                if (elect_one()) {
                    if (helps) prefetch_l2(reinterpret_cast<const char*>(out) + sp.lent_off[wk.index / 8] + w4 * WARP_BYTES, WARP_BYTES);
                    if (prepares) { prefetch_l2(w2 + 8 * q * CH, 8 * CH * 2); prefetch_l2(beta + 8 * q, 16); }
                }
            }
        });
        set_addresses();
        const int lane = lane_id(), g = lane >> 2, t = lane & 3;
        const int piece = wk.index;
        uint32_t a[6][4];
        unsigned short bt_raw;
        if (prepares) {
#pragma unroll
            for (int m = 0; m < 3; m++) ldg128(a[m], w2 + (8 * q + g) * CH + 32 * m + 8 * t);
            asm volatile("ld.global.nc.u16 %0, [%1];" : "=h"(bt_raw) : "l"(beta + 8 * q + g) : "memory");
        } else if (helps) {
#pragma unroll
            for (int s = 0; s < 6; s++) ldg128(a[s], reinterpret_cast<const char*>(out) + sp.lent_off[piece / 8] + w4 * WARP_BYTES + lane * 16 + s * 512);
        }
        mbar_wait_once(bar_e + spare2 * 32, (wk.rows - 5) / NSLOT & 1);
        mbar_wait_once(bar_e + spare * 32, (wk.rows - 6) / NSLOT & 1);
        named_bar(1, 128);
#pragma unroll
        for (int k = 0; k < 6; k++) { sts128(sq + k * SQ_ROW, 0, 0, 0, 0); sts128(sq + sq_upper + k * SQ_ROW, 0, 0, 0, 0); }
        if (prepares) {
            const int half = w4 & 1;
            uint32_t rmax = 0;
#pragma unroll
            for (int m = 0; m < 3; m++) rmax = bf_absmax(bf_absmax(rmax, bf_absmax(a[m][0], a[m][1])), bf_absmax(a[m][2], a[m][3]));
            uint2 u = half ? make_uint2(a[0][2], a[0][3]) : make_uint2(a[0][0], a[0][1]), u1 = half ? make_uint2(a[1][2], a[1][3]) : make_uint2(a[1][0], a[1][1]);
            const uint2 u2 = half ? make_uint2(a[2][2], a[2][3]) : make_uint2(a[2][0], a[2][1]);
            const float bt = bf_lo(bt_raw);
            rmax = bf_absmax(rmax, __shfl_xor_sync(~0u, rmax, 1));
            rmax = bf_absmax(rmax, __shfl_xor_sync(~0u, rmax, 2));
            const float mx = fmaxf(fabsf(bf_lo(rmax)), fabsf(bf_hi(rmax))), rs = pow2i(row_exp(mx));
            if (t == 0 && !half) sc->w2max[8 * q + g] = mx;
#pragma unroll 1
            for (int m = 0; m < 3; m++, u = u1, u1 = u2) {
                float f[4];
#pragma unroll
                for (int k = 0; k < 2; k++) {
                    const float lo = bf_lo(k ? u.y : u.x), hi = bf_hi(k ? u.y : u.x);
                    sc->w2h[(4 * m + 2 * half + k) * 1536 + q * 32 + lane] = transpose8x8(pack_h2(lo * rs, hi * rs));
                    f[2 * k] = lo * bt;
                    f[2 * k + 1] = hi * bt;
                }
                const float r0 = (g & 2 ? f[2] : f[0]) + __shfl_xor_sync(~0u, g & 2 ? f[0] : f[2], 8);
                const float r1 = (g & 2 ? f[3] : f[1]) + __shfl_xor_sync(~0u, g & 2 ? f[1] : f[3], 8);
                float r = (g & 1 ? r1 : r0) + __shfl_xor_sync(~0u, g & 1 ? r0 : r1, 4);
                r += __shfl_xor_sync(~0u, r, 16);
                if (g < 4) atomicAdd(&sc->bias[32 * m + 8 * t + 4 * half + g], r);
            }
            asm volatile("fence.proxy.async.global;" ::: "memory");
            __syncwarp();
            named_arrive(3, 256);
        } else
        if (helps) {
            uint32_t d[12], gl[12];
            const uint32_t scale2 = square_scale(lane);
            wg_fence();
#pragma unroll
            for (int s = 0; s < 6; s++) wgmma(d, a[s][0], a[s][1], a[s][2], a[s][3], ds.w1[0][s] + piece % 8 * (6 * 1536 / 16), s ? 1 : 0);
            wg_commit();
            wg_wait<0>();
            gelu_to(gl, d);
#pragma unroll
            for (int s = 0; s < 3; s++) {
                sc->lent[((piece / 8 * 4 + w4) * 24 + piece % 8 * 3 + s) * 32 + lane] = make_uint4(gl[4 * s], gl[4 * s + 1], gl[4 * s + 2], gl[4 * s + 3]);
                uint32_t hs[2];
#pragma unroll
                for (int k = 0; k < 2; k++) {
                    const uint32_t g0 = h_mul(gl[4 * s + 2 * k], scale2), g1 = h_mul(gl[4 * s + 2 * k + 1], scale2);
                    hs[k] = h_fma(g1, g1, h_mul(g0, g0));
                }
                const int pair = piece % 4 * 3 + s;
                sts64(sq + (piece & 4 ? sq_upper : 0) + (pair >> 1) * SQ_ROW + (pair & 1) * 8, hs[0], hs[1]);
            }
        }
        jt = ntiles - 1;
        cur.slot = spare ? spare - 1 : NSLOT - 1;
        cur.par = (wk.rows - 1) / NSLOT & 1;
        fast_from = ntiles;
        turn = turn_end = so = so_sum = bo = bo_sum = off = rank;
    } else {
        set_addresses();
        if (wgi == NCONS - 1) named_arrive(4, 256);
        set_run(wk.lent + wgi, min(wk.nA, nrest), wk.lent + wgi + 2);
        jt = wgi < wk.lent ? wgi : wk.lent + wgi;
        cur = {2, 0};
        cur.advance(jt + (jt >= wk.nA ? 2 : 0));
        {
            const int ct = tid - 128, lane = tid & 31;
            const unsigned epoch = *reinterpret_cast<volatile unsigned*>(&sc->launch);
            const int r = lane & 7, mi = lane >> 3;
            const uint32_t src = sb + SM_W2 + (cw >> 1) * (64 * CH * 2) + r * 128 + ((((cw & 1) * 4 + mi) ^ r) * 16);
            const uint32_t dst = sb + SM_W1 + (4 * cw + mi) * 1536 + r * 16;
            const int code = row_code(wk, PREFETCH_ROWS - 1 + wgi);
            named_bar(0, NTHREADS);
            auto request = [&]() {
                if (elect_one())
                    issue_region(&tmap, sb + SM_RING + (PREFETCH_ROWS - 1 + wgi) * SLOT_BYTES + w4 * REGION_BYTES, sb + BAR_X + (cw + 8) * 8, w4, code);
                __syncwarp();
            };
#pragma unroll 1
            for (int k = 0; k < 2; k++) {
                if (wgi == k) request();
                mbar_wait_once(sb + BAR_W + (cw >> 1) * 8, 0);
            }
            uint32_t wmax[2] = {}, wsum[4] = {};
#pragma unroll K_UNR
            for (int c = 0; c < 12; c++) {
                uint32_t u[4];
                ldsm4_t(u, src + c * 1024);
#pragma unroll
                for (int q = 0; q < 4; q++) {
                    wmax[q & 1] = bf_absmax(wmax[q & 1], u[q]);
                    wsum[q] = bf_fma(u[q], 0x3f803f80u, wsum[q]);
                    u[q] = pack_h2(__uint_as_float(u[q] * (65536 + zero)), bf_hi(u[q]));
                }
                stsm4(dst + c * 128, u[0], u[1], u[2], u[3]);
            }
            const float w1max = warp_absmax(bf_absmax(wmax[0], wmax[1]));
            if (lane == 0) sts32(s_red + RED_MAX + cw * 4, __float_as_uint(w1max));
            bool center = false;
#pragma unroll
            for (int q = 0; q < 4; q++) {
#pragma unroll
                for (int o = 1; o <= 2; o <<= 1) wsum[q] = bf_fma(__shfl_xor_sync(~0u, wsum[q], o), 0x3f803f80u, wsum[q]);
                center |= fabsf(bf_lo(wsum[q]) + bf_hi(wsum[q])) > (0.15f * CH) * w1max;
            }
            if (__builtin_expect(__any_sync(~0u, center), 0)) {
                float mean[4] = {};
#pragma unroll 1
                for (int pass = 0; pass < 2; pass++) {
                    float sum[4] = {};
#pragma unroll 1
                    for (int c = 0; c < 12; c++) {
                        uint32_t u[4];
                        ldsm4_t(u, src + c * 1024);
#pragma unroll
                        for (int q = 0; q < 4; q++) {
                            sum[q] += bf_lo(u[q]) + bf_hi(u[q]);
                            u[q] = pack_h2(bf_lo(u[q]) - mean[q], bf_hi(u[q]) - mean[q]);
                        }
                        stsm4(dst + c * 128, u[0], u[1], u[2], u[3]);
                    }
#pragma unroll
                    for (int q = 0; q < 4; q++) {
                        sum[q] += __shfl_xor_sync(~0u, sum[q], 1);
                        sum[q] += __shfl_xor_sync(~0u, sum[q], 2);
                        mean[q] = sum[q] * (1.f / CH);
                    }
                }
            }
            if (!(cw & 2)) {
#pragma unroll
                for (int c = 0; c < 12; c++) sts128(src + c * 1024, 0, 0, 0, 0);
            }
            if (ct < 32) sts32(sb + SM_ONES + ct * 4, 0x3f803f80u);
            if (ct == 0) sts32(s_red + RED_LAUNCH, epoch);
            fence_async();
            named_bar(2, CONS_THREADS);
            if (wgi == 2) request();
        }
        PROF(1);
        fast_from = wk.lent;
        if (!__all_sync(~0u, plain_squares(bound_exp(max_w1(lane_id()))))) {
            fast_from = ntiles;
#pragma unroll 1
            for (int q = 0; q < 6; q++) sts128(sq + SQ_HALF + q * SQ_ROW, 0, 0, 0, 0);
        }
    }
    uint32_t k1[24], k2[24], k3[24], tile_off, next_off;
    constexpr int SQC = 3 * SQ_ROW;
    auto store_at = [&](const uint32_t (&a)[6][4], uint32_t off) {
        char* ap = reinterpret_cast<char*>(out) + (off + sq);
#pragma unroll
        for (int s = 0; s < 6; s++) stg128(ap + s * 512, a[s]);
    };
    const uint32_t own_bar = 4 + (wgi & 3), next_bar = 4 + (wgi == NCONS - 1 ? 0 : wgi + 1);
    for (;;) {
        if (jt >= fast_from) {
            uint32_t hs2[12] = {}, hs3[12] = {};
            const uint32_t step = wk.dir * (NCONS * IMG_W * CH * 2);
            int second = wk.nB;
#pragma unroll 1
            for (;;) {
#pragma unroll 1
                while (turn != turn_end) {
                    uint32_t a[6][4], d0[24], d1[24], unused[24];
#define AT(pos) \
    if (K_WAIT == pos) named_bar(own_bar, 256); \
    if (K_PASS == pos) named_arrive(next_bar, 256); \
    if (K_STG == pos) store_at(a, off); \
    if (K_REL == pos) { if (elect_one()) mbar_arrive(bo + (BAR_E - BAR_A)); }
                    AT(20)
                    mbar_wait(bo, turn >> 1 & 1);
                    load_tile(a, a_addr + so);
                    AT(21)
                    const uint2 st = ln_stats(a, ds.ones);
                    AT(0)
                    ln_apply(a, st);
                    AT(1)
                    wg_fence();
                    gemm1_chunk<0>(d0, a, ds, 0);
                    wg_commit();
                    gemm1_chunk<96>(d1, a, ds, 0);
                    wg_commit();
                    AT(2)
                    wg_wait<1>();
                    AT(3)
                    gelu_sq<false, 0, 1>(d0, unused, sq, 0);
                    AT(4)
                    gelu_sq<false, 1, 2>(d0, unused, sq, 0);
                    AT(5)
                    gelu_sq<false, 2, 3>(d0, unused, sq, 0);
                    AT(6)
                    wg_fence();
                    gemm1_chunk<192>(d0, a, ds, zero);
                    wg_commit();
                    AT(7)
                    wg_wait<1>();
                    gelu_sq<false, 0, 1>(d1, unused, sq + SQC, 0);
                    AT(8)
                    gelu_sq<false, 1, 3>(d1, unused, sq + SQC, 0);
                    AT(9)
                    wg_fence();
                    gemm1_chunk<288>(d1, a, ds, zero);
                    wg_commit();
                    AT(10)
                    wg_wait<1>();
                    gelu_sq_reg(d0, hs2);
                    if (K_ANCH < 3) anchor(sq, hs2[4 * (K_ANCH % 3)], hs2[4 * (K_ANCH % 3) + 1], hs2[4 * (K_ANCH % 3) + 2], hs2[4 * (K_ANCH % 3) + 3]);
                    wg_wait<0>();
                    AT(11)
                    gelu_sq_reg(d1, hs3);
#undef AT
                    so = so_sum - so;
                    bo = bo_sum - bo;
                    off += step;
                    turn++;
                }
                if (!second) break;
                const int j = ntiles - second + (rank + second + 2) % NCONS;
                second = 0;
                set_run(j, nrest, j + 4);
            }
            jt = nrest + rank;
            cur.slot = (bo - bar_a) >> 5;
            cur.par = turn >> 1 & 1;
#pragma unroll
            for (int k = 0; k < 3; k++) {
                sts128(sq + SQ_HALF + k * SQ_ROW, hs2[4 * k], hs2[4 * k + 1], hs2[4 * k + 2], hs2[4 * k + 3]);
                sts128(sq + SQ_HALF + SQC + k * SQ_ROW, hs3[4 * k], hs3[4 * k + 1], hs3[4 * k + 2], hs3[4 * k + 3]);
            }
        }
        const bool last = jt >= nrest;
        if (last) {
            tile_off = tile_offset(wk.tile(jt));
            lds32(next_off, sb + SM_TILES + rank * 4);
            next_off = __shfl_sync(~0u, next_off, 0);
            if (elect_one()) {
                prefetch_l2(reinterpret_cast<const char*>(x) + tile_off + w4 * WARP_BYTES, WARP_BYTES);
                if (rank % ORDER_P >= ORDER_P - ORDER_Q) prefetch_l2(reinterpret_cast<const char*>(out) + next_off + w4 * WARP_BYTES, WARP_BYTES);
            }
        }
        uint32_t a[6][4], d0[24], d1[24], d3[24], k0[24];
#define AT(pos) \
    if (K_WAIT == pos && jt >= wk.lent) named_bar(own_bar, 256); \
    if (K_PASS == pos && jt >= wk.lent && jt + 2 < ntiles) named_arrive(next_bar, 256); \
    if (K_P0 == pos && jt == nrest + K_R0) named_arrive(7, 256);
        AT(20)
        mbar_wait_once(bar_a + cur.slot * 32, cur.par);
        load_tile(a, a_addr + cur.slot * SLOT_BYTES);
        AT(21)
        const uint2 st = ln_stats(a, ds.ones);
        AT(0)
        ln_apply(a, st);
        AT(1)
        if (!last) {
            store_at(a, tile_offset(wk.tile(jt)) + w4 * WARP_BYTES - sq_warp);
            __syncwarp();
            if (elect_one()) mbar_arrive(bar_e + cur.slot * 32);
            if (jt < wk.lent) {
                jt += LENT;
                cur.advance(LENT);
                continue;
            }
        }
        wg_fence();
        gemm1_chunk<0>(d0, a, ds, 0);
        wg_commit();
        gemm1_chunk<96>(d1, a, ds, 0);
        wg_commit();
        const uint32_t scale2 = square_scale(lane_id());
        AT(2)
        wg_wait<1>();
        AT(3)
        gelu_sq<true, 0, 1>(d0, k0, sq, scale2);
        AT(4)
        gelu_sq<true, 1, 2>(d0, k0, sq, scale2);
        AT(5)
        gelu_sq<true, 2, 3>(d0, k0, sq, scale2);
        AT(6)
        if (last) {
#pragma unroll
            for (int q = 0; q < 6; q++)
                sts128(sb + SM_RING + cur.slot * SLOT_BYTES + w4 * REGION_BYTES - sq_warp + sq + q * 512, k0[4 * q], k0[4 * q + 1], k0[4 * q + 2], k0[4 * q + 3]);
        }
        wg_fence();
        gemm1_chunk<192>(d0, a, ds, zero);
        wg_commit();
        AT(7)
        wg_wait<1>();
        gelu_sq<true>(d1, k1, sq + SQC, scale2);
        AT(9)
#undef AT
        wg_fence();
        gemm1_chunk<288>(d3, a, ds, 0);
        wg_commit();
        wg_wait<1>();
        gelu_sq<true>(d0, k2, sq + sq_upper, scale2);
        wg_wait<0>();
        gelu_sq<true>(d3, k3, sq + sq_upper + SQC, scale2);
        if (last) break;
        cur.advance(NCONS + ((jt < wk.nA && jt + NCONS >= wk.nA) ? 2 : 0));
        jt += NCONS;
    }
    const uint32_t lane = lane_id();
    const uint32_t s_fac = sb + SM_RING + spare * SLOT_BYTES + SQ_HALF;
    uint32_t inv_rho2;
    {
        const bool leader = rank == 0 && w4 == 0 && lane == 0;
        const int i0 = w4 * 32 + lane;
        float base[3], slope[3], reach[3], to_square;
        float2 bpair = make_float2(0.f, 0.f);
        unsigned epoch;
        if (rank == 0) {
            float gam[3], rmax[3];
#pragma unroll
            for (int m = 0; m < 3; m++) {
                unsigned short v;
                asm volatile("ld.global.nc.u16 %0, [%1];" : "=h"(v) : "l"(gamma + i0 + 128 * m) : "memory");
                gam[m] = bf_lo(v);
            }
            epoch = ldsi(s_red + RED_LAUNCH);
            if (prepares) {
                named_bar(3, 256);
                if (w4 == 1) signal(&sc->prep);
            }
            if (leader) {
                spin_until(&sc->prep, (epoch + 1) * (W2_GROUPS / 2));
                asm volatile("fence.proxy.async.global;" ::: "memory");
            }
            __syncwarp();
            named_bar(2, 128);
#pragma unroll
            for (int m = 0; m < 3; m++) rmax[m] = __ldcg(&sc->w2max[i0 + 128 * m]);
            if (i0 < 96) bpair = __ldcg(reinterpret_cast<const float2*>(&sc->bias[32 * (i0 % 24 >> 3) + 8 * (i0 / 24) + (i0 % 24 & 6)]));
            const float w1max = max_w1(lane);
            const float gbound = fmaxf(2.f * KZ * 9.7979590f * 192.f * w1max, 1.f) * 19.5959180f * INV_2KZ;
            const unsigned fixed = __reduce_max_sync(~0u, __float_as_uint(fmaf(gbound, fmaxf(fmaxf(rmax[0], rmax[1]), rmax[2]), fmaxf(fabsf(bpair.x), fabsf(bpair.y)))));
            if (lane == 0) sts32(s_red + 96 + w4 * 4, fixed);
#pragma unroll
            for (int m = 0; m < 3; m++) {
                base[m] = rmax[m] > 0.f ? pow2i(-row_exp(rmax[m])) * (INV_2KZ * CUT_GAIN) : 0.f;
                slope[m] = base[m] * gam[m];
                reach[m] = fabsf(gam[m]) * rmax[m] * gbound;
            }
            to_square = pow2i(-sum_exp(bound_exp(w1max))) * (INV_2KZ * INV_2KZ / 256);
        }
        if (rank >= 2) {
            named_arrive(12 + rank, CONS_THREADS);
        } else {
            const int rw = rank * 4 + w4, g = lane >> 2, t = lane & 3;
            const uint32_t pick = (g & 1) == (t & 1) ? (g & 2 ? 0x3c000000u : 0x00003c00u) : 0;
            const int be = bound_exp(max_w1(lane));
            const float to_fixed = pow2i(sum_exp(be) - 2 * square_exp(be));
            unsigned long long* dst = sc->sum(64 * rw + 32 * (t >> 1) + 8 * (g >> 1) + 2 * (t & 1) + (g & 1));
            const uint32_t rows = sb + (rw * 2 + (lane >> 3 & 1)) * SQ_ROW + ((lane >> 4) * 8 + (lane & 7)) * 16;
            float f[2][4] = {};
            named_bar(13, 256);
#pragma unroll 1
            for (int i = 0; i < 4; i++) {
                if (i == 2) {
                    named_bar(13, 256);
                    if (leader) {
                        fence_async();
                        mbar_expect_tx(sb + BAR_W, 4 * SQ_HALF);
                        bulk_load(sb + SM_W2, sc->w2h, 4 * SQ_HALF, sb + BAR_W);
                    }
                    __syncwarp();
                }
                const int from = i < 2 ? i : i ^ K_ORD;
                const uint32_t src = rows + (from < NCONS ? SM_SQ + from * 2 * SQ_HALF : rw < 3 ? SM_RING + spare * SLOT_BYTES : SM_RING + spare2 * SLOT_BYTES - SQ_HALF);
                if (i >= 2) named_bar(12 + from, CONS_THREADS);
                if (rw < 6) {
#pragma unroll
                    for (int r = 0; r < 8; r++) {
                        uint32_t u[4];
                        ldsm4_t(u, src + r * 256);
                        asm volatile("mma.sync.aligned.m16n8k16.row.col.f32.f16.f16.f32 {%0, %1, %2, %3}, {%4, %5, %6, %7}, {%8, %8}, {%0, %1, %2, %3};"
                                     : "+f"(f[r & 1][0]), "+f"(f[r & 1][1]), "+f"(f[r & 1][2]), "+f"(f[r & 1][3])
                                     : "r"(u[0]), "r"(u[1]), "r"(u[2]), "r"(u[3]), "r"(pick));
                    }
                }
            }
            if (rw < 6) {
#pragma unroll
                for (int r = 0; r < 2; r++)
                    atomicAdd(dst + r * 32, __float2ull_rn(fminf((t < 2 ? f[0][r] + f[1][r] : f[0][r + 2] + f[1][r + 2]) * to_fixed, 0x1p47f)) << 8 | 1);
            }
            PROF(2);
            named_bar(13, 256);
            if (leader) {
                fence_async();
                mbar_expect_tx(sb + BAR_W + 8, 2 * SQ_HALF);
                bulk_load(sb + SM_W2 + 4 * SQ_HALF, reinterpret_cast<const char*>(sc->w2h) + 4 * SQ_HALF, 2 * SQ_HALF, sb + BAR_W + 8);
            }
            if (helps && rw == 7) signal(&sc->lent_out);
        }
        if (rank == 0) {
            const uint32_t own_sum = (i0 >> 2) * 256 + (i0 & 3) * 8, own_fac = s_fac + i0 * 2;
            auto peek = [&](const void* p) {
                unsigned long long v;
                asm volatile("ld.relaxed.gpu.global.u64 %0, [%1];" : "=l"(v) : "l"(p) : "memory");
                return v;
            };
            const char* mine = reinterpret_cast<const char*>(sc->sums) + own_sum;
            unsigned n = 0;
            while (((unsigned)peek(sc->sum((blockIdx.x * 4 + w4) % (EX / 4) * 4)) & 255u) != gridDim.x)
                if (++n > SPIN_LIMIT) __trap();
            unsigned long long sum[3];
            for (;;) {
                bool all = true;
#pragma unroll
                for (int m = 0; m < 3; m++) {
                    sum[m] = peek(mine + m * (32 * 256));
                    all &= ((unsigned)sum[m] & 255u) == gridDim.x;
                }
                if (__all_sync(~0u, all)) break;
                if (++n > SPIN_LIMIT) __trap();
            }
            PROF(3);
            float gx[3];
#pragma unroll
            for (int m = 0; m < 3; m++) asm("sqrt.approx.ftz.f32 %0, %1;" : "=f"(gx[m]) : "f"(fmaf(__ull2float_rn(sum[m]), to_square, 1e-6f)));
            float tot = gx[0] + gx[1] + gx[2];
#pragma unroll
            for (int o = 16; o >= 1; o >>= 1) tot += __shfl_xor_sync(~0u, tot, o);
            const unsigned vwarp = __reduce_max_sync(~0u, __float_as_uint(fmaxf(fmaxf(reach[0] * gx[0], reach[1] * gx[1]), reach[2] * gx[2])));
            if (lane == 0) { sts32(s_red + 64 + w4 * 4, __float_as_uint(tot)); sts32(s_red + 80 + w4 * 4, vwarp); }
            named_bar(2, 128);
            uint32_t u[4], v[4], w[4];
            lds128(u[0], u[1], u[2], u[3], s_red + 64);
            lds128(v[0], v[1], v[2], v[3], s_red + 80);
            lds128(w[0], w[1], w[2], w[3], s_red + 96);
            tot = (__uint_as_float(u[0]) + __uint_as_float(u[1])) + (__uint_as_float(u[2]) + __uint_as_float(u[3]));
            const float vmax = __uint_as_float(max(max(v[0], v[1]), max(v[2], v[3]))), fmax2 = __uint_as_float(max(max(w[0], w[1]), max(w[2], w[3])));
            float inv_mean;
            asm("rcp.approx.ftz.f32 %0, %1;" : "=f"(inv_mean) : "f"(fmaf(tot, 1.f / EX, 1e-6f)));
            const int rho_e = 14 - ilog2f(fmaf(vmax, inv_mean, 2.f * fmax2));
            const float rho = pow2i(rho_e), inv_rho = pow2i(-rho_e);
            inv_rho2 = pack_bf2(inv_rho, inv_rho);
#pragma unroll
            for (int m = 0; m < 3; m++) {
                const float f = fmaf(slope[m] * gx[m], inv_mean, base[m]) * rho;
                asm volatile("st.shared.u16 [%0], %1;" ::"r"(own_fac + 256 * m), "h"((unsigned short)pack_h2(f, 0.f)) : "memory");
            }
            if (i0 < 96) sts32(sb + SM_BIASH + i0 * 4, pack_h2(bpair.x * rho, bpair.y * rho));
            if (i0 == 96) sts32(s_red + RED_INV_RHO, inv_rho2);
            named_arrive(12, NTHREADS);
            if (blockIdx.x == 0 && leader) sc->launch = epoch + 1;
            if (wk.lent) spin_until(&sc->lent_out, (epoch + 1) * 8 * LENT * sp.lenders);
        } else {
            const int rw = rank * 4 - 4 + w4;
            const uint32_t row = sb + SM_W2 + rw * 512 + lane * 16;
            uint32_t u[W2_EARLY][4], f2[4];
#pragma unroll
            for (int nb = 0; nb < W2_EARLY; nb++) {
                if (nb % 8 == 0) mbar_wait_once(sb + BAR_W + nb, 1);
                lds128(u[nb][0], u[nb][1], u[nb][2], u[nb][3], row + nb * 6144);
            }
            if (W2_EARLY <= 8) mbar_wait_once(sb + BAR_W + 8, 1);
            named_bar(12, NTHREADS);
            PROF(3);
            lds128(f2[0], f2[1], f2[2], f2[3], s_fac + rw * 64 + (lane >> 3) * 16);
            lds32(inv_rho2, s_red + RED_INV_RHO);
#pragma unroll
            for (int nb = 0; nb < 12; nb++) {
                uint32_t v[4];
                if (nb < W2_EARLY) { v[0] = u[nb % W2_EARLY][0]; v[1] = u[nb % W2_EARLY][1]; v[2] = u[nb % W2_EARLY][2]; v[3] = u[nb % W2_EARLY][3]; }
                else lds128(v[0], v[1], v[2], v[3], row + nb * 6144);
                sts128(row + nb * 6144, h_cut8(h_mul(v[0], f2[0])), h_cut8(h_mul(v[1], f2[1])), h_cut8(h_mul(v[2], f2[2])), h_cut8(h_mul(v[3], f2[3])));
            }
            fence_async();
            named_arrive(8, NTHREADS);
        }
    }
    uint32_t a[6][4], acc[24], rpar = 0;
    const uint32_t bias_addr = sb + SM_BIASH + (lane & 3) * 96, lane16 = lane * 16, lane_off = ((lane >> 2) * CH + 8 * (lane & 3)) * 2;
    const uint32_t stage = sb + SM_RING + (spare + rank) % NSLOT * SLOT_BYTES + w4 * WARP_BYTES, bar_r = sb + BAR_R + warp_id * 8;
    auto load_bias = [&]() {
#pragma unroll
        for (int q = 0; q < 6; q++) lds128(acc[4 * q], acc[4 * q + 1], acc[4 * q + 2], acc[4 * q + 3], bias_addr + q * 16);
    };
    auto load_frags = [&]() {
#pragma unroll
        for (int s = 0; s < 6; s++) ldg128(a[s], reinterpret_cast<const char*>(out) + next_off + w4 * WARP_BYTES + lane16 + s * 512);
    };
    auto stage_x = [&]() {
        if (elect_one()) {
            mbar_expect_tx(bar_r, WARP_BYTES);
            bulk_load_stream(stage, reinterpret_cast<const char*>(x) + tile_off + w4 * WARP_BYTES, WARP_BYTES, bar_r);
        }
    };
    {
        named_bar(8 + rank, rank ? 256 : NTHREADS);
        if (rank == 0) PROF(4);
        load_bias();
        pin(k1); pin(k2); pin(k3);
        wg_fence();
        gemm2_chunk<KA>(acc, KX(KA), ds);
        wg_commit();
        gemm2_chunk<KB>(acc, KX(KB), ds);
        wg_commit();
        gemm2_chunk<KC>(acc, KX(KC), ds);
        wg_commit();
        stage_x();
        wg_wait<2>();
        uint32_t k0[24];
#pragma unroll
        for (int q = 0; q < 6; q++)
            lds128(k0[4 * q], k0[4 * q + 1], k0[4 * q + 2], k0[4 * q + 3], sb + SM_RING + cur.slot * SLOT_BYTES + w4 * REGION_BYTES + lane16 + q * 512);
        pin(k0);
        wg_fence();
        gemm2_chunk<0>(acc, k0, ds);
        wg_commit();
        if (rank < NCONS) named_arrive(9 + rank, 256);
        wg_wait<2>();
        load_frags();
        if (lane16 == 0) mbar_arrive(sb + BAR_PIN);
        if (!K_RW) mbar_wait(bar_r, rpar);
        wg_wait<0>();
    }
    auto lent = [&](uint32_t entry) { return &sc->lent[((wk.index * LENT + (entry & 3) - 1) * 4 + w4) * (24 * 32)]; };
    for (jt = rank - 4; jt < nrest; jt += 4) {
        if (jt >= zero) {
        tile_off = next_off;
        lds32(next_off, sb + SM_TILES + (jt + 4) * 4);
        if (tile_off & 3) {
            const uint4* src = lent(tile_off) + lane;
            tile_off &= ~3u;
            next_off = __shfl_sync(~0u, next_off, 0);
            stage_x();
            if (elect_one()) prefetch_l2(reinterpret_cast<const char*>(out) + next_off + w4 * WARP_BYTES, WARP_BYTES);
            load_bias();
#pragma unroll 1
            for (int half = 0; half < 2; half++, src += 12 * 32) {
                uint32_t gl[48];
#pragma unroll
                for (int s = 0; s < 12; s++) ldg128(reinterpret_cast<uint32_t (&)[4]>(gl[4 * s]), src + s * 32);
                if (!half) {
                    named_bar(4 + rank, 256);
                    named_arrive(4 + ((rank + 1) & 3), 256);
                }
                pin(gl);
                wg_fence();
#pragma unroll
                for (int s = 0; s < 12; s++) wgmma(acc, gl[4 * s], gl[4 * s + 1], gl[4 * s + 2], gl[4 * s + 3], ds.w2[12 * half + s], 1);
                wg_commit();
                wg_wait<0>();
            }
            load_frags();
            if (!K_RW) mbar_wait(bar_r, rpar);
        } else {
            uint32_t d0[12], d1[12], g0[12], g1[12];
            if (jt >= S2_FIRST) named_bar(4 + rank, 256);
            wg_fence();
            gemm1_chunk<0>(d0, a, ds, 0);
            wg_commit();
            gemm1_chunk<48>(d1, a, ds, 0);
            wg_commit();
            load_bias();
            next_off = __shfl_sync(~0u, next_off, 0);
            const bool more = jt + 4 < nrest && !(next_off & 3);
            wg_wait<1>();
#define CNX_STEP(C, D, G)                                              \
    gelu_to(G, D);                                                     \
    wg_fence();                                                        \
    if (C < 6) gemm1_chunk<48 * (C < 6 ? C + 2 : 0)>(D, a, ds, zero); \
    gemm2_chunk<48 * C>(acc, G, ds);                                  \
    wg_commit();                                                       \
    wg_wait<(C < 7 ? 1 : 0)>();
            CNX_STEP(0, d0, g0)
            CNX_STEP(1, d1, g1)
            if (jt + 1 >= S2_FIRST && jt + 1 < nrest) named_arrive(4 + ((rank + 1) & 3), 256);
            stage_x();
            if (elect_one()) {
                if (more) prefetch_l2(reinterpret_cast<const char*>(out) + next_off + w4 * WARP_BYTES, WARP_BYTES);
                else if (next_off & 3) prefetch_l2(lent(next_off), 24 * 32 * 16);
            }
            CNX_STEP(2, d0, g0)
            CNX_STEP(3, d1, g1)
            CNX_STEP(4, d0, g0)
            CNX_STEP(5, d1, g1)
            CNX_STEP(6, d0, g0)
#pragma unroll
            for (int s = 0; s < 6; s++) ldg128_if(more, a[s], reinterpret_cast<const char*>(out) + next_off + w4 * WARP_BYTES + lane16 + s * 512);
            if (lane16 == 0) mbar_arrive(sb + BAR_PIN);
            if (!K_RW) mbar_wait(bar_r, rpar);
            CNX_STEP(7, d1, g1)
#undef CNX_STEP
        }
        }
        {
            if (K_RW) mbar_wait(bar_r, rpar);
            pin(acc);
            rpar ^= 1;
            uint4* op = reinterpret_cast<uint4*>(reinterpret_cast<char*>(out) + tile_off + w4 * WARP_BYTES + lane_off);
#pragma unroll
            for (int h = 0; h < 2; h++)
#pragma unroll
                for (int m = 0; m < 3; m++) {
                    uint32_t xin[4], o[4];
                    lds128(xin[0], xin[1], xin[2], xin[3], stage + lane_off + h * 1536 + m * 64);
#pragma unroll
                    for (int q = 0; q < 4; q++) {
                        const uint32_t v = acc[2 * (4 * m + q) + h];
                        o[q] = bf_fma(pack_bf2(h_lo(v), h_hi(v)), inv_rho2, xin[q]);
                    }
                    __stcs(op + h * 96 + m * 4, make_uint4(o[0], o[1], o[2], o[3]));
                }
            __syncwarp();
        }
    }
    PROF(5);
}

}

typedef CUresult (*EncodeTiledFn)(CUtensorMap*, CUtensorMapDataType, cuuint32_t, void*, const cuuint64_t*, const cuuint64_t*,
                                  const cuuint32_t*, const cuuint32_t*, CUtensorMapInterleave, CUtensorMapSwizzle,
                                  CUtensorMapL2promotion, CUtensorMapFloatOOBfill);

extern "C" void kernel_launch(void* const* d_in, const int* in_sizes, int n_in, void* d_out, int out_size) {
    using namespace cnx;
    static EncodeTiledFn encode = nullptr;
    static int num_sms = 0;
    static Scratch* scratch = nullptr;
    if (!encode) {
        void* fn = nullptr;
        cudaDriverEntryPointQueryResult qr;
        cudaGetDriverEntryPoint("cuTensorMapEncodeTiled", &fn, cudaEnableDefault, &qr);
        encode = (EncodeTiledFn)fn;
        cudaGetSymbolAddress((void**)&scratch, g_scratch);
        int dev = 0;
        cudaGetDevice(&dev);
        cudaDeviceGetAttribute(&num_sms, cudaDevAttrMultiProcessorCount, dev);
        if (num_sms > MAX_CTAS) num_sms = MAX_CTAS;
        cudaFuncSetAttribute(block_kernel, cudaFuncAttributeMaxDynamicSharedMemorySize, SM_TOTAL);
    }
    CUtensorMap tm;
    cuuint64_t dims[3] = {(cuuint64_t)CH, (cuuint64_t)IMG_W, (cuuint64_t)IMG_H};
    cuuint64_t strides[2] = {(cuuint64_t)CH * 2, (cuuint64_t)CH * 2 * IMG_W};
    cuuint32_t box[3] = {(cuuint32_t)CH, (cuuint32_t)REGION_PX, 1};
    cuuint32_t estr[3] = {1, 1, 1};
    encode(&tm, CU_TENSOR_MAP_DATA_TYPE_BFLOAT16, 3, d_in[0], dims, strides, box, estr, CU_TENSOR_MAP_INTERLEAVE_NONE,
           CU_TENSOR_MAP_SWIZZLE_NONE, CU_TENSOR_MAP_L2_PROMOTION_L2_128B, CU_TENSOR_MAP_FLOAT_OOB_FILL_NONE);
    Params pm = {};
    Descs& ds = pm.ds;
    for (int c = 0; c < 8; c++)
        for (int k = 0; k < 6; k++) ds.w1[c][k] = make_desc(SB + SM_W1 + c * 6 * 1536 + k * 256, 128, 1536);
    for (int k = 0; k < 24; k++) ds.w2[k] = make_desc(SB + SM_W2 + k * 256, 128, 6144);
    ds.ones = make_desc(SB + SM_ONES, 0, 0);
    CUtensorMap tw;
    cuuint64_t wdims[2] = {(cuuint64_t)EX, (cuuint64_t)CH};
    cuuint64_t wstrides[1] = {(cuuint64_t)EX * 2};
    cuuint32_t wbox[2] = {64, (cuuint32_t)CH};
    encode(&tw, CU_TENSOR_MAP_DATA_TYPE_BFLOAT16, 2, d_in[2], wdims, wstrides, wbox, estr, CU_TENSOR_MAP_INTERLEAVE_NONE,
           CU_TENSOR_MAP_SWIZZLE_128B, CU_TENSOR_MAP_L2_PROMOTION_L2_128B, CU_TENSOR_MAP_FLOAT_OOB_FILL_NONE);
    Split& sp = pm.sp;
    sp = {NTILES / num_sms, NTILES % num_sms, 1, 1 << 16, 0, {}};
    if (sp.per_cta + 9 > MAX_ROWS) return;
    if (sp.extra && sp.extra * (8 * LENT + 1) + W2_GROUPS / 2 <= num_sms && sp.per_cta >= 5 * LENT + 8) {
        sp.period = num_sms / sp.extra;
        sp.inv_period = 65535 / sp.period + 1;
        sp.lenders = sp.extra;
        for (int l = 0; l < sp.extra; l++) {
            const Work w = get_work((l + 1) * sp.period - sp.period / 2 - 1, sp);
            for (int e = 0; e < LENT; e++) sp.lent_off[l * LENT + e] = tile_offset(w.tile(e));
            if (w.nA < 2 * LENT) sp.lenders = 0;
        }
    }
    pm.x = (const __nv_bfloat16*)d_in[0];
    pm.dw = (const __nv_bfloat16*)d_in[1];
    pm.w2 = (const __nv_bfloat16*)d_in[3];
    pm.gamma = (const __nv_bfloat16*)d_in[4];
    pm.beta = (const __nv_bfloat16*)d_in[5];
    pm.out = (__nv_bfloat16*)d_out;
    pm.sc = scratch;
    block_kernel<<<num_sms, NTHREADS, SM_TOTAL>>>(tm, tw, pm);
}
```

```cpp
#include <cuda_runtime.h>
#include <cuda_bf16.h>
#include <cuda_fp16.h>
#include <cuda.h>
#include <stdint.h>

namespace cnx {

constexpr int IMG_H = 512, IMG_W = 512, CH = 96, EX = 384;
constexpr int TILE_W = 64;
constexpr int NTILES = (IMG_W / TILE_W) * IMG_H;
constexpr int NSLOT = 6;
constexpr int REGION_PX = 18;
constexpr int REGION_BYTES = REGION_PX * CH * 2;
constexpr int SLOT_BYTES = 4 * REGION_BYTES;
constexpr int A_LBO = 144, A_SBO = 12 * A_LBO;
constexpr int PREFETCH_ROWS = 3;
constexpr int NCONS = 3;
constexpr int CONS_THREADS = 128 * NCONS;
constexpr int NTHREADS = 128 + CONS_THREADS;
constexpr int MAX_ROWS = 52;
constexpr int TILE_BYTES = TILE_W * CH * 2, WARP_BYTES = TILE_BYTES / 4;
#define K_PASS 7
#define K_WAIT 22
#define K_STG 5
#define K_REL 6
#define K_ANCH 2
#define K_CHAIN 3
#define K_OP 0
#define K_QS 0
#define K_GS 0
#define K_QR 0
#define K_GR 0
#define K_PD 0
#define K_PQ 0
#define K_PS 0
#define K_UNRV 3
constexpr int K_UNR = K_UNRV;
#define K_RW 0
#define K_P0 20
#define K_R0 0
#define K_ORD 0
#define KA 288
#define KB 96
#define KC 192
#define KX(e) (e == 96 ? k1 : e == 192 ? k2 : k3)
#define W2_EARLY 9
#define S2_FIRST 1
#define ORDER_P 3
#define ORDER_Q 1
static_assert(MAX_ROWS <= 128, "one table entry per producer thread");
static_assert(2 * A_SBO == REGION_BYTES && REGION_BYTES % 128 == 0, "region layout");

constexpr uint32_t SB = 1024;
constexpr int SM_W1 = 0;
constexpr int SM_W2 = SM_W1 + CH * EX * 2;
constexpr int SM_RING = SM_W2 + CH * EX * 2;
constexpr int SM_BIASH = SM_RING + NSLOT * SLOT_BYTES;
constexpr int SM_RED = SM_BIASH + 384;
constexpr int RED_MAX = 0, RED_LAUNCH = 48, RED_INV_RHO = 52;
constexpr int SM_TILES = SM_RED + 256;
constexpr int SM_ONES = SM_TILES + MAX_ROWS * 4;
constexpr int SM_BAR = SM_ONES + 128;
constexpr int BAR_X = SM_BAR;
constexpr int BAR_A = BAR_X + NSLOT * 4 * 8;
constexpr int BAR_E = BAR_A + NSLOT * 4 * 8;
constexpr int BAR_PIN = BAR_E + NSLOT * 4 * 8;
constexpr int BAR_W = BAR_PIN + 8;
constexpr int BAR_F = BAR_W + 6 * 8;
constexpr int BAR_R = BAR_F + 8;
constexpr int SM_TOTAL = BAR_R + 16 * 8;
constexpr int SM_FILTER = SM_RING + (NSLOT - 1) * SLOT_BYTES + 9 * 128;
constexpr int SM_SQ = SM_W2;
constexpr int SQ_ROW = 128 * 16, SQ_HALF = 6 * SQ_ROW;
static_assert(SM_ONES % 16 == 0 && SM_TOTAL <= 232448, "shared memory budget");

constexpr float KZ = 0.3292034911525734f;
constexpr uint32_t GELU_C2 = 0x40d940d9u;
constexpr float INV_2KZ = 0.5f / KZ;
constexpr unsigned SPIN_LIMIT = 1u << 19;

constexpr int MAX_CTAS = 255;
constexpr int W2_GROUPS = EX / 8;
#define K_LENT 3
constexpr int LENT = K_LENT, MAX_LENDERS = MAX_CTAS / (8 * LENT + 1);
struct Scratch {
    uint32_t w2h[EX * CH / 2];
    float w2max[EX];
    float bias[CH + 32];
    unsigned long long sums[EX / 4][32];
    __device__ __forceinline__ unsigned long long* sum(int e) { return &sums[e >> 2][e & 3]; }
    uint4 lent[MAX_LENDERS * LENT * 8 * 4 * 3 * 32];
    unsigned launch, pad0[31], early, pad1[31], prep, pad2[31], lent_out, pad3[31];
};
__device__ __align__(128) Scratch g_scratch;

#define PROF(k)

__device__ __forceinline__ uint32_t smem_u32(const void* p) { return (uint32_t)__cvta_generic_to_shared(p); }
__device__ __forceinline__ void mbar_init(uint32_t bar, uint32_t cnt) {
    asm volatile("mbarrier.init.shared::cta.b64 [%0], %1;" ::"r"(bar), "r"(cnt) : "memory");
}
__device__ __forceinline__ void mbar_arrive(uint32_t bar) {
    asm volatile("mbarrier.arrive.shared::cta.b64 _, [%0];" ::"r"(bar) : "memory");
}
__device__ __forceinline__ void mbar_expect_tx(uint32_t bar, uint32_t bytes) {
    asm volatile("mbarrier.arrive.expect_tx.shared::cta.b64 _, [%0], %1;" ::"r"(bar), "r"(bytes) : "memory");
}
__device__ __forceinline__ bool mbar_try(uint32_t bar, uint32_t par) {
    uint32_t ok;
    asm volatile("{\n.reg .pred p;\nmbarrier.try_wait.parity.shared::cta.b64 p, [%1], %2;\nselp.u32 %0, 1, 0, p;\n}\n"
                 : "=r"(ok) : "r"(bar), "r"(par) : "memory");
    return ok != 0;
}
__device__ __forceinline__ void mbar_wait(uint32_t bar, uint32_t par) {
    unsigned n = 0;
    while (!mbar_try(bar, par)) {
        if (++n > SPIN_LIMIT) __trap();
    }
}
__device__ __forceinline__ void mbar_wait_once(uint32_t bar, uint32_t par) {
    unsigned n = 0;
    bool ok;
#pragma unroll 1
    do {
        ok = mbar_try(bar, par);
        if (++n > SPIN_LIMIT) __trap();
    } while (!ok);
}
__device__ __forceinline__ bool elect_one() {
    uint32_t ok;
    asm volatile("{\n.reg .pred p;\nelect.sync _|p, 0xffffffff;\nselp.u32 %0, 1, 0, p;\n}\n" : "=r"(ok));
    return ok != 0;
}
__device__ __forceinline__ uint32_t opaque(uint32_t v) { return __shfl_sync(~0u, v, threadIdx.x & 31); }
__device__ __forceinline__ uint32_t lane_id() { uint32_t v; asm volatile("mov.u32 %0, %%laneid;" : "=r"(v)); return v; }
__device__ __forceinline__ uint32_t opaque_uniform(uint32_t v) { return __shfl_sync(~0u, v, 0); }
__device__ __forceinline__ void named_bar(int id, int n) { asm volatile("bar.sync %0, %1;" ::"r"(id), "r"(n) : "memory"); }
__device__ __forceinline__ void named_arrive(int id, int n) { asm volatile("bar.arrive %0, %1;" ::"r"(id), "r"(n) : "memory"); }
__device__ __forceinline__ void fence_async() { asm volatile("fence.proxy.async.shared::cta;" ::: "memory"); }
constexpr uint64_t EVICT_FIRST = 0x12F0000000000000ull;
__device__ __forceinline__ void tma_row(uint32_t dst, const CUtensorMap* tm, uint32_t bar, int x, int y) {
    asm volatile("cp.async.bulk.tensor.3d.shared::cluster.global.mbarrier::complete_tx::bytes.L2::cache_hint [%0], [%1, {%3, %4, %5}], [%2], %6;"
                 ::"r"(dst), "l"(tm), "r"(bar), "r"(0), "r"(x), "r"(y), "l"(EVICT_FIRST) : "memory");
}
__device__ __forceinline__ void bulk_load_stream(uint32_t dst, const void* src, uint32_t bytes, uint32_t bar) {
    asm volatile("cp.async.bulk.shared::cluster.global.mbarrier::complete_tx::bytes.L2::cache_hint [%0], [%1], %2, [%3], %4;"
                 ::"r"(dst), "l"(src), "r"(bytes), "r"(bar), "l"(EVICT_FIRST) : "memory");
}
__device__ __forceinline__ void prefetch_l2(const void* src, uint32_t bytes) {
    asm volatile("cp.async.bulk.prefetch.L2.global [%0], %1;" ::"l"(src), "r"(bytes) : "memory");
}
__device__ __forceinline__ void tma_2d(uint32_t dst, const CUtensorMap* tm, uint32_t bar, int x, int y) {
    asm volatile("cp.async.bulk.tensor.2d.shared::cluster.global.mbarrier::complete_tx::bytes [%0], [%1, {%3, %4}], [%2];"
                 ::"r"(dst), "l"(tm), "r"(bar), "r"(x), "r"(y) : "memory");
}
__device__ __forceinline__ void bulk_load(uint32_t dst, const void* src, uint32_t bytes, uint32_t bar) {
    asm volatile("cp.async.bulk.shared::cluster.global.mbarrier::complete_tx::bytes [%0], [%1], %2, [%3];"
                 ::"r"(dst), "l"(src), "r"(bytes), "r"(bar) : "memory");
}
__device__ __forceinline__ void wg_fence() { asm volatile("wgmma.fence.sync.aligned;" ::: "memory"); }
__device__ __forceinline__ void wg_commit() { asm volatile("wgmma.commit_group.sync.aligned;" ::: "memory"); }
template <int N> __device__ __forceinline__ void wg_wait() { asm volatile("wgmma.wait_group.sync.aligned %0;" ::"n"(N) : "memory"); }
template <int N> __device__ __forceinline__ void pin(uint32_t (&d)[N]) {
#pragma unroll
    for (int q = 0; q < N; q++) asm volatile("" : "+r"(d[q])::"memory");
}
__device__ __forceinline__ void stg128(void* p, const uint32_t (&v)[4]) {
    asm volatile("st.global.v4.u32 [%0], {%1, %2, %3, %4};" ::"l"(p), "r"(v[0]), "r"(v[1]), "r"(v[2]), "r"(v[3]) : "memory");
}
__device__ __forceinline__ void ldg128(uint32_t (&v)[4], const void* p) {
    asm volatile("ld.global.L1::no_allocate.v4.u32 {%0, %1, %2, %3}, [%4];" : "=r"(v[0]), "=r"(v[1]), "=r"(v[2]), "=r"(v[3]) : "l"(p) : "memory");
}
__device__ __forceinline__ void ldg128_if(bool on, uint32_t (&v)[4], const void* p) {
    asm volatile("{\n.reg .pred p;\nsetp.ne.b32 p, %5, 0;\n@p ld.global.L1::no_allocate.v4.u32 {%0, %1, %2, %3}, [%4];\n}\n"
                 : "+r"(v[0]), "+r"(v[1]), "+r"(v[2]), "+r"(v[3]) : "l"(p), "r"((int)on) : "memory");
}
__host__ __device__ constexpr uint64_t make_desc(uint32_t addr, uint32_t lbo, uint32_t sbo) {
    return (uint64_t)((addr & 0x3FFFF) >> 4) | ((uint64_t)(lbo >> 4) << 16) | ((uint64_t)(sbo >> 4) << 32);
}
__device__ __forceinline__ void wgmma(uint32_t (&d)[12], uint32_t a0, uint32_t a1, uint32_t a2, uint32_t a3, uint64_t db, int acc) {
    asm volatile("{\n.reg .pred p;\nsetp.ne.b32 p, %17, 0;\n"
                 "wgmma.mma_async.sync.aligned.m64n48k16.f16.f16.f16 "
                 "{%0, %1, %2, %3, %4, %5, %6, %7, %8, %9, %10, %11}, "
                 "{%12, %13, %14, %15}, %16, p, 1, 1, 0;\n}\n"
                 : "+r"(d[0]), "+r"(d[1]), "+r"(d[2]), "+r"(d[3]), "+r"(d[4]), "+r"(d[5]), "+r"(d[6]), "+r"(d[7]), "+r"(d[8]), "+r"(d[9]), "+r"(d[10]), "+r"(d[11])
                 : "r"(a0), "r"(a1), "r"(a2), "r"(a3), "l"(db), "r"(acc));
}
__device__ __forceinline__ void wgmma(uint32_t (&d)[24], uint32_t a0, uint32_t a1, uint32_t a2, uint32_t a3, uint64_t db, int acc) {
    asm volatile("{\n.reg .pred p;\nsetp.ne.b32 p, %29, 0;\n"
                 "wgmma.mma_async.sync.aligned.m64n96k16.f16.f16.f16 "
                 "{%0, %1, %2, %3, %4, %5, %6, %7, %8, %9, %10, %11, %12, %13, %14, %15, %16, %17, %18, %19, %20, %21, %22, %23}, "
                 "{%24, %25, %26, %27}, %28, p, 1, 1, 0;\n}\n"
                 : "+r"(d[0]), "+r"(d[1]), "+r"(d[2]), "+r"(d[3]), "+r"(d[4]), "+r"(d[5]), "+r"(d[6]), "+r"(d[7]), "+r"(d[8]), "+r"(d[9]), "+r"(d[10]), "+r"(d[11]), "+r"(d[12]), "+r"(d[13]), "+r"(d[14]), "+r"(d[15]), "+r"(d[16]), "+r"(d[17]), "+r"(d[18]), "+r"(d[19]), "+r"(d[20]), "+r"(d[21]), "+r"(d[22]), "+r"(d[23])
                 : "r"(a0), "r"(a1), "r"(a2), "r"(a3), "l"(db), "r"(acc));
}
template <int ACC>
__device__ __forceinline__ void wgmma_rowsum(float (&d)[4], const uint32_t (&a)[4], uint64_t ones) {
    asm volatile("{\n.reg .pred p;\nsetp.ne.b32 p, %9, 0;\n"
                 "wgmma.mma_async.sync.aligned.m64n8k16.f32.bf16.bf16 {%0, %1, %2, %3}, {%4, %5, %6, %7}, %8, p, 1, 1, 0;\n}\n"
                 : "+f"(d[0]), "+f"(d[1]), "+f"(d[2]), "+f"(d[3])
                 : "r"(a[0]), "r"(a[1]), "r"(a[2]), "r"(a[3]), "l"(ones), "n"(ACC));
}
__device__ __forceinline__ void ldsm4(uint32_t (&r)[4], uint32_t addr) {
    asm volatile("ldmatrix.sync.aligned.m8n8.x4.shared.b16 {%0, %1, %2, %3}, [%4];"
                 : "=r"(r[0]), "=r"(r[1]), "=r"(r[2]), "=r"(r[3]) : "r"(addr) : "memory");
}
__device__ __forceinline__ void ldsm4_t(uint32_t (&r)[4], uint32_t addr) {
    asm volatile("ldmatrix.sync.aligned.m8n8.x4.trans.shared.b16 {%0, %1, %2, %3}, [%4];"
                 : "=r"(r[0]), "=r"(r[1]), "=r"(r[2]), "=r"(r[3]) : "r"(addr) : "memory");
}
__device__ __forceinline__ void stsm4(uint32_t addr, uint32_t a, uint32_t b, uint32_t c, uint32_t d) {
    asm volatile("stmatrix.sync.aligned.m8n8.x4.shared.b16 [%0], {%1, %2, %3, %4};"
                 ::"r"(addr), "r"(a), "r"(b), "r"(c), "r"(d) : "memory");
}
__device__ __forceinline__ uint32_t transpose8x8(uint32_t v) {
    uint32_t d; asm volatile("movmatrix.sync.aligned.m8n8.trans.b16 %0, %1;" : "=r"(d) : "r"(v)); return d;
}
__device__ __forceinline__ void spin_until(const unsigned* counter, unsigned target) {
    unsigned n = 0, c;
    do {
        asm volatile("ld.acquire.gpu.global.u32 %0, [%1];" : "=r"(c) : "l"(counter) : "memory");
        if (++n > SPIN_LIMIT) __trap();
    } while ((int)(c - target) < 0);
}
__device__ __forceinline__ void signal(unsigned* counter) {
    __syncwarp();
    if (elect_one()) asm volatile("red.release.gpu.global.add.u32 [%0], 1;" ::"l"(counter) : "memory");
    __syncwarp();
}
__device__ __forceinline__ void lds128(uint32_t& a, uint32_t& b, uint32_t& c, uint32_t& d, uint32_t addr) {
    asm volatile("ld.shared.v4.u32 {%0, %1, %2, %3}, [%4];" : "=r"(a), "=r"(b), "=r"(c), "=r"(d) : "r"(addr) : "memory");
}
__device__ __forceinline__ void lds64(uint32_t& a, uint32_t& b, uint32_t addr) {
    asm volatile("ld.shared.v2.u32 {%0, %1}, [%2];" : "=r"(a), "=r"(b) : "r"(addr) : "memory");
}
__device__ __forceinline__ void lds32(uint32_t& a, uint32_t addr) {
    asm volatile("ld.shared.u32 %0, [%1];" : "=r"(a) : "r"(addr) : "memory");
}
__device__ __forceinline__ int ldsi(uint32_t addr) {
    uint32_t v;
    lds32(v, addr);
    return (int)v;
}
__device__ __forceinline__ float ldsf(uint32_t addr) {
    uint32_t v;
    lds32(v, addr);
    return __uint_as_float(v);
}
__device__ __forceinline__ void sts32(uint32_t addr, uint32_t a) {
    asm volatile("st.shared.u32 [%0], %1;" ::"r"(addr), "r"(a) : "memory");
}
__device__ __forceinline__ void sts128(uint32_t addr, uint32_t a, uint32_t b, uint32_t c, uint32_t d) {
    asm volatile("st.shared.v4.u32 [%0], {%1, %2, %3, %4};" ::"r"(addr), "r"(a), "r"(b), "r"(c), "r"(d) : "memory");
}
__device__ __forceinline__ void sts64(uint32_t addr, uint32_t a, uint32_t b) {
    asm volatile("st.shared.v2.u32 [%0], {%1, %2};" ::"r"(addr), "r"(a), "r"(b) : "memory");
}
__device__ __forceinline__ void anchor(uint32_t addr, uint32_t a, uint32_t b, uint32_t c, uint32_t d) {
    asm volatile("{\n.reg .pred p;\nsetp.eq.b32 p, %0, 0;\n@p st.shared.v4.u32 [%0], {%1, %2, %3, %4};\n}\n"
                 ::"r"(addr), "r"(a), "r"(b), "r"(c), "r"(d) : "memory");
}
__device__ __forceinline__ uint32_t bf_fma(uint32_t a, uint32_t b, uint32_t c) {
    uint32_t d; asm("fma.rn.bf16x2 %0, %1, %2, %3;" : "=r"(d) : "r"(a), "r"(b), "r"(c)); return d;
}
__device__ __forceinline__ uint32_t bf_mul(uint32_t a, uint32_t b) {
    uint32_t d; asm("mul.rn.bf16x2 %0, %1, %2;" : "=r"(d) : "r"(a), "r"(b)); return d;
}
__device__ __forceinline__ uint32_t bf_absmax(uint32_t a, uint32_t b) {
    uint32_t d; asm("max.xorsign.abs.bf16x2 %0, %1, %2;" : "=r"(d) : "r"(a), "r"(b)); return d;
}
__device__ __forceinline__ uint32_t h_fma(uint32_t a, uint32_t b, uint32_t c) {
    uint32_t d; asm("fma.rn.f16x2 %0, %1, %2, %3;" : "=r"(d) : "r"(a), "r"(b), "r"(c)); return d;
}
__device__ __forceinline__ uint32_t h_mul(uint32_t a, uint32_t b) {
    uint32_t d; asm("mul.rn.f16x2 %0, %1, %2;" : "=r"(d) : "r"(a), "r"(b)); return d;
}
__device__ __forceinline__ uint32_t h_cut8(uint32_t v) { return v & 0xfff8fff8u; }
constexpr float CUT_GAIN = 1.f + 0.4375f * 0.7213f / 128;
__device__ __forceinline__ uint32_t h_tanh(uint32_t a) {
    uint32_t d; asm("tanh.approx.f16x2 %0, %1;" : "=r"(d) : "r"(a)); return d;
}
__device__ __forceinline__ uint32_t pack_h2(float lo, float hi) {
    uint32_t d; asm("cvt.rn.f16x2.f32 %0, %1, %2;" : "=r"(d) : "f"(hi), "f"(lo)); return d;
}
__device__ __forceinline__ uint32_t pack_bf2(float lo, float hi) {
    uint32_t d; asm("cvt.rn.bf16x2.f32 %0, %1, %2;" : "=r"(d) : "f"(hi), "f"(lo)); return d;
}
__device__ __forceinline__ float bf_lo(uint32_t v) { return __uint_as_float(v << 16); }
__device__ __forceinline__ float bf_hi(uint32_t v) { return __uint_as_float(v & 0xffff0000u); }
__device__ __forceinline__ float h_lo(uint32_t v) { return __low2float(*reinterpret_cast<__half2*>(&v)); }
__device__ __forceinline__ float h_hi(uint32_t v) { return __high2float(*reinterpret_cast<__half2*>(&v)); }
__device__ __forceinline__ float warp_absmax(uint32_t v) {
    return __uint_as_float(__reduce_max_sync(~0u, max((v & 0x7fffu) << 16, v & 0x7fff0000u)));
}
__device__ __forceinline__ uint32_t gelu2(uint32_t z) {
    uint32_t p = h_fma(z, z, GELU_C2);
    uint32_t t = h_tanh(K_OP & 1 ? h_mul(p, z) : h_mul(z, p));
    return K_OP & 2 ? h_fma(t, z, z) : h_fma(z, t, z);
}
__device__ __forceinline__ float pow2i(int e) { return __uint_as_float((uint32_t)(e + 127) << 23); }
__device__ __forceinline__ int ilog2f(float v) {
    int e = (int)((__float_as_uint(v) >> 23) & 0xff) - 127;
    return max(-100, min(100, e));
}

__device__ __forceinline__ int bound_exp(float w1max) { return w1max > 0.f ? ilog2f(2.f * KZ * 96.f * w1max) : 0; }
__device__ __forceinline__ bool plain_squares(int e) { return (unsigned)(4 - e) <= 6; }
__device__ __forceinline__ int square_exp(int e) { return plain_squares(e) ? 0 : max(-14, min(4 - e, 14)); }
__device__ __forceinline__ int sum_exp(int e) { return max(-90, min(90, 33 - 2 * e)); }
__device__ __forceinline__ int row_exp(float m) { return 2 - ilog2f(m); }

struct Split {
    int per_cta, extra, period, inv_period, lenders;
    uint32_t lent_off[MAX_LENDERS * LENT];
    __host__ __device__ __forceinline__ int longer_before(int cta) const {
        const int n = (cta + period / 2) * inv_period >> 16;
        return n < extra ? n : extra;
    }
};
struct Work {
    int tA, tB, nA, nB, dir, rows, lent, index;
    __host__ __device__ __forceinline__ int tile(int j) const { return j < nA ? tA + dir * j : tB + dir * (j - nA); }
};
__host__ __device__ __forceinline__ Work get_work(int cta, const Split& sp) {
    Work w;
    const int before = sp.longer_before(cta), longer = sp.longer_before(cta + 1) - before;
    w.lent = longer && sp.lenders ? LENT : 0;
    w.index = longer ? before : cta - before;
    const int t0 = cta * sp.per_cta + before, t1 = t0 + sp.per_cta + longer;
    const int tm = t1 < (t0 | 511) + 1 ? t1 : (t0 | 511) + 1;
    const bool swap = t1 > tm && t1 - tm < tm - t0, down = cta & 1;
    w.nA = swap ? t1 - tm : tm - t0;
    w.nB = t1 - t0 - w.nA;
    w.tA = down ? (swap ? tm : t0) : (swap ? t1 : tm) - 1;
    w.tB = down ? (swap ? t0 : tm) : (swap ? tm : t1) - 1;
    w.dir = down ? 1 : -1;
    w.rows = w.nA + 2 + (w.nB ? w.nB + 2 : 0);
    return w;
}
__device__ __forceinline__ int row_code(const Work& w, int i) {
    const bool in_a = i < w.nA + 2;
    const int t = in_a ? w.tA : w.tB;
    return ((t & 511) + w.dir * ((in_a ? i : i - (w.nA + 2)) - 1)) << 16 | (t >> 9) * TILE_W;
}
__host__ __device__ __forceinline__ uint32_t tile_offset(int tile) { return ((tile & 511) * IMG_W + (tile >> 9) * TILE_W) * (CH * 2); }
__device__ __forceinline__ int tile_order(int j, int n) {
    const int olds = (j / ORDER_P) * ORDER_Q + max(0, j % ORDER_P - (ORDER_P - ORDER_Q));
    return (j % ORDER_P >= ORDER_P - ORDER_Q) ? olds : n - 1 - (j - olds);
}
__device__ __forceinline__ void issue_region(const CUtensorMap* tm, uint32_t dst, uint32_t bar, int warp, int code) {
    mbar_expect_tx(bar, REGION_BYTES);
    tma_row(dst, tm, bar, (code & 0xffff) + (16 * warp - 1), code >> 16);
}

template <class Event>
__device__ __forceinline__ void conv_producer(const Work& wk, const CUtensorMap* tm, uint32_t sb, int warp, Event event) {
    const int lane = threadIdx.x & 31;
    const int j = lane & 15, grp = lane >> 4;
    const uint32_t reg0 = sb + SM_RING + warp * REGION_BYTES;
    const uint32_t bars = sb + SM_BAR + warp * 8;
    if (warp * 32 + lane < MAX_ROWS) {
        const int i = warp * 32 + lane, before = min(i / 5, wk.lent);
        const bool back = i % 5 == 0 && i > 0 && i / 5 <= wk.lent;
        sts32(sb + SM_TILES + i * 4, back ? tile_offset(wk.tile(before - 1)) | before
                                          : tile_offset(wk.tile(wk.lent + tile_order(i - before, wk.nA + wk.nB - 4 - wk.lent))));
    }
    const uint32_t ld64 = opaque(reg0 + grp * 8 * 192 + j * 8), ld32 = opaque(reg0 + grp * 8 * 192 + 128 + j * 4);
    const uint32_t st64 = opaque(reg0 + grp * A_SBO + (j >> 1) * A_LBO + (j & 1) * 8);
    const uint32_t st32 = opaque(reg0 + grp * A_SBO + (8 + (j >> 2)) * A_LBO + (j & 3) * 4);
    named_bar(0, NTHREADS);
    uint32_t w[3][3][3];
    mbar_wait_once(sb + BAR_F, 0);
#pragma unroll
    for (int tap = 0; tap < 9; tap++) {
        const uint32_t p = sb + SM_FILTER + (3 + wk.dir * 3 * (tap / 3 - 1) + tap % 3) * (CH * 2);
        lds64(w[tap / 3][tap % 3][0], w[tap / 3][tap % 3][1], p + 8 * j);
        lds32(w[tap / 3][tap % 3][2], p + 128 + 4 * j);
    }
#pragma unroll
    for (int tap = 0; tap < 9; tap++) sts64(reg0 + (NSLOT - 1) * SLOT_BYTES + tap * 128 + j * 8, w[tap / 3][tap % 3][1], w[tap / 3][tap % 3][0]);
    named_bar(1, 128);
#pragma unroll
    for (int tap = 0; tap < 9; tap++) lds64(w[tap / 3][tap % 3][1], w[tap / 3][tap % 3][0], reg0 + (NSLOT - 1) * SLOT_BYTES + tap * 128 + j * 8);
    static_assert(2 * PREFETCH_ROWS == NSLOT && SLOT_BYTES % 32 == 0, "slot arithmetic");
    uint32_t bo = 0, par = 0, pbo = PREFETCH_ROWS * 32, ppar = 1;
    int px, py;
    auto request = [&]() {
        mbar_wait_once(bars + (BAR_E - SM_BAR) + pbo, ppar);
        if (elect_one()) {
            mbar_expect_tx(bars + pbo, REGION_BYTES);
            tma_row(reg0 + pbo * (SLOT_BYTES / 32), tm, bars + pbo, px, py);
        }
    };
    auto advance = [&]() {
        bo += 32;
        if (bo == NSLOT * 32) { bo = 0; par ^= 1; }
        pbo += 32;
        if (pbo == NSLOT * 32) { pbo = 0; ppar ^= 1; }
    };
    auto aim = [&](int row) {
        const int code = row_code(wk, row);
        px = (code & 0xffff) + (16 * warp - 1);
        py = code >> 16;
    };
    uint32_t accB[8][3], accC[8][3];
    int r = 0;
#pragma unroll 1
    while (r < wk.rows) {
        if (r == 0 || r == wk.nA + 2) {
            const uint32_t bo0 = bo;
            uint32_t bo1;
#pragma unroll 1
            for (int k = 0; k < 2; k++, r++) {
                mbar_wait_once(bars + bo, par);
                bo1 = bo;
                if (r >= 2) {
                    aim(r + PREFETCH_ROWS);
                    request();
                }
                advance();
            }
            const uint32_t so0 = bo0 * (SLOT_BYTES / 32), so1 = bo1 * (SLOT_BYTES / 32);
#pragma unroll
            for (int p = 0; p < 10; p++) {
                uint32_t u[3], v[3];
                lds64(u[0], u[1], so0 + ld64 + p * 192);
                lds32(u[2], so0 + ld32 + p * 192);
                lds64(v[0], v[1], so1 + ld64 + p * 192);
                lds32(v[2], so1 + ld32 + p * 192);
#pragma unroll
                for (int dx = 0; dx < 3; dx++) {
                    const int o = p - dx;
                    if (o < 0 || o > 7) continue;
#pragma unroll
                    for (int q = 0; q < 3; q++) {
                        accB[o][q] = bf_fma(v[q], w[1][dx][q], dx == 0 ? bf_mul(u[q], w[0][dx][q]) : bf_fma(u[q], w[0][dx][q], accB[o][q]));
                        accC[o][q] = dx == 0 ? bf_mul(v[q], w[0][dx][q]) : bf_fma(v[q], w[0][dx][q], accC[o][q]);
                    }
                }
            }
            anchor(ld64, accB[7][0], accB[7][1], accB[7][2], 0);
            __syncwarp();
            if (elect_one()) {
                mbar_arrive(bars + (BAR_A - SM_BAR) + bo0);
                mbar_arrive(bars + (BAR_E - SM_BAR) + bo0);
                mbar_arrive(bars + (BAR_A - SM_BAR) + bo1);
                mbar_arrive(bars + (BAR_E - SM_BAR) + bo1);
            }
        }
        int end = wk.rows;
        const int marks[4] = {wk.rows - PREFETCH_ROWS, wk.rows - 11, wk.nA + 2, wk.nA + 2 - PREFETCH_ROWS};
#pragma unroll
        for (int k = 0; k < 4; k++) end = marks[k] > r ? min(end, marks[k]) : end;
        const bool fetch = r < wk.rows - PREFETCH_ROWS;
        aim(r + PREFETCH_ROWS);
        px = opaque_uniform(px);
        const int py_end = opaque_uniform(py + wk.dir * (end - r));
        r = end;
#pragma unroll 1
        do {
            mbar_wait(bars + bo, par);
            const uint32_t so = bo * (SLOT_BYTES / 32);
            uint32_t out[8][3];
#pragma unroll
            for (int p = 0; p < 10; p++) {
                uint32_t xv[3];
                lds64(xv[0], xv[1], so + ld64 + p * 192);
                lds32(xv[2], so + ld32 + p * 192);
#pragma unroll
                for (int dd = 0; dd < 3; dd++) {
                    const int dx = K_PD ? 2 - dd : dd, o = p - dx;
                    if (o < 0 || o > 7) continue;
#pragma unroll
                    for (int qq = 0; qq < 3; qq++) {
                        const int q = (qq + K_PQ) % 3;
                        out[o][q] = bf_fma(xv[q], w[2][dx][q], dx == 0 ? accB[o][q] : out[o][q]);
                        accB[o][q] = bf_fma(xv[q], w[1][dx][q], dx == 0 ? accC[o][q] : accB[o][q]);
                        accC[o][q] = dx == 0 ? bf_mul(xv[q], w[0][dx][q]) : bf_fma(xv[q], w[0][dx][q], accC[o][q]);
                    }
                }
            }
            __syncwarp();
#pragma unroll
            for (int oo = 0; oo < 8; oo++) {
                const int o = K_PS ? 7 - oo : oo;
                sts64(so + st64 + o * 16, out[o][0], out[o][1]);
                sts32(so + st32 + o * 16, out[o][2]);
            }
            __syncwarp();
            if (elect_one()) mbar_arrive(bars + (BAR_A - SM_BAR) + bo);
            if (fetch) request();
            advance();
            py += wk.dir;
        } while (py != py_end);
        if (((wk.rows - r) & ~8) == PREFETCH_ROWS) event(wk.rows - r == PREFETCH_ROWS);
    }
}

template <bool SCALED, int K0 = 0, int K1 = 3>
__device__ __forceinline__ void gelu_sq(uint32_t (&d)[24], uint32_t (&keep)[24], uint32_t sq_addr, uint32_t scale2) {
    pin(d);
#pragma unroll
    for (int k = K0; k < K1; k++) {
        uint32_t hs[4];
        lds128(hs[0], hs[1], hs[2], hs[3], sq_addr + k * SQ_ROW);
#pragma unroll
        for (int qq = 0; qq < 4; qq++) {
            const int q = K_QS == 0 ? qq : K_QS == 1 ? 3 - qq : K_QS == 2 ? (qq >> 1 | (qq & 1) << 1) : (qq + 1) & 3;
            uint32_t g0 = gelu2(d[8 * k + 2 * q]), g1 = gelu2(d[8 * k + 2 * q + 1]);
            keep[8 * k + 2 * q] = g0;
            keep[8 * k + 2 * q + 1] = g1;
            if (SCALED) { g0 = h_mul(g0, scale2); g1 = h_mul(g1, scale2); }
            hs[q] = (K_GS >> (q & 1) & 1) ? h_fma(g0, g0, h_fma(g1, g1, hs[q])) : h_fma(g1, g1, h_fma(g0, g0, hs[q]));
        }
        sts128(sq_addr + k * SQ_ROW, hs[0], hs[1], hs[2], hs[3]);
    }
}
__device__ __forceinline__ void gelu_sq_reg(uint32_t (&d)[24], uint32_t (&hs)[12]) {
    pin(d);
#pragma unroll
    for (int qq = 0; qq < 12; qq++) {
        const int q = K_QR == 0 ? qq : K_QR == 1 ? 11 - qq : K_QR == 2 ? qq ^ 1 : qq * 5 % 12;
        const uint32_t g0 = gelu2(d[2 * q]), g1 = gelu2(d[2 * q + 1]);
        hs[q] = (K_GR >> (q & 1) & 1) ? h_fma(g0, g0, h_fma(g1, g1, hs[q])) : h_fma(g1, g1, h_fma(g0, g0, hs[q]));
    }
}
__device__ __forceinline__ void gelu_to(uint32_t (&g)[12], uint32_t (&d)[12]) {
    pin(d);
#pragma unroll
    for (int q = 0; q < 12; q++) g[q] = gelu2(d[q]);
    pin(g);
}
__device__ __forceinline__ void load_tile(uint32_t (&raw)[6][4], uint32_t addr) {
#pragma unroll
    for (int s = 0; s < 6; s++) ldsm4(raw[s], addr + s * 2 * A_LBO);
}
template <class F>
__device__ __forceinline__ void layer_norm(uint32_t (&raw)[6][4], uint64_t ones, F at) {
    constexpr int NS = 6 / K_CHAIN;
    uint32_t sq[NS][4];
#pragma unroll
    for (int s = 0; s < 6; s++)
#pragma unroll
        for (int q = 0; q < 4; q++) sq[s % NS][q] = s < NS ? bf_mul(raw[s][q], raw[s][q]) : bf_fma(raw[s][q], raw[s][q], sq[s % NS][q]);
    float sum[4], ssq[4];
    at(23);
    wg_fence();
    wgmma_rowsum<0>(sum, raw[0], ones);
#pragma unroll
    for (int s = 1; s < 6; s++) wgmma_rowsum<1>(sum, raw[s], ones);
    wgmma_rowsum<0>(ssq, sq[0], ones);
#pragma unroll
    for (int s = 1; s < NS; s++) wgmma_rowsum<1>(ssq, sq[s], ones);
    wg_commit();
    at(22);
    wg_wait<0>();
    at(0);
    uint32_t sc[2], sh[2];
#pragma unroll
    for (int h = 0; h < 2; h++) {
        asm volatile("" : "+f"(sum[2 * h]), "+f"(ssq[2 * h])::"memory");
        constexpr float EPS = 1e-5f / (KZ * KZ);
        const float m = sum[2 * h] * (1.f / (CH * KZ));
        float rstd;
        asm("rsqrt.approx.ftz.f32 %0, %1;" : "=f"(rstd) : "f"(fmaxf(fmaf(-m, m, fmaf(ssq[2 * h], 1.f / (CH * KZ * KZ), EPS)), EPS)));
        sc[h] = pack_bf2(rstd, rstd);
        const float shift = sum[2 * h] * (-1.f / CH) * bf_hi(sc[h]);
        sh[h] = pack_bf2(shift, shift);
    }
#pragma unroll
    for (int s = 0; s < 6; s++)
#pragma unroll
        for (int q = 0; q < 4; q++) {
            const uint32_t v = bf_fma(raw[s][q], sc[q & 1], sh[q & 1]);
            raw[s][q] = pack_h2(bf_lo(v), bf_hi(v));
        }
}
struct Cursor {
    int slot;
    uint32_t par;
    __device__ __forceinline__ void advance(int n) {
        slot += n;
        if (slot >= NSLOT) { slot -= NSLOT; par ^= 1; }
    }
};
struct Descs {
    uint64_t w1[8][6];
    uint64_t w2[24];
    uint64_t ones;
};
template <int E0, int N>
__device__ __forceinline__ void gemm1_chunk(uint32_t (&d)[N], const uint32_t (&a)[6][4], const Descs& ds, int zero) {
#pragma unroll
    for (int s = 0; s < 6; s++) wgmma(d, a[s][0], a[s][1], a[s][2], a[s][3], ds.w1[E0 / 48][s], s ? 1 : zero);
}
template <int E0, int N>
__device__ __forceinline__ void gemm2_chunk(uint32_t (&acc)[24], const uint32_t (&g)[N], const Descs& ds) {
#pragma unroll
    for (int s = 0; s < N / 4; s++) wgmma(acc, g[4 * s], g[4 * s + 1], g[4 * s + 2], g[4 * s + 3], ds.w2[E0 / 16 + s], 1);
}

struct __align__(64) Params {
    Split sp;
    int zero;
    const __nv_bfloat16 *x, *dw, *w2, *gamma, *beta;
    __nv_bfloat16* out;
    Scratch* sc;
    Descs ds;
};

__global__ void __launch_bounds__(NTHREADS, 1)
block_kernel(const __grid_constant__ CUtensorMap tmap, const __grid_constant__ CUtensorMap tmap_w1, const __grid_constant__ Params pm) {
    const Split& sp = pm.sp;
    const Descs& ds = pm.ds;
    const int& zero = pm.zero;
    const __nv_bfloat16 *const &x = pm.x, *const &dw = pm.dw, *const &w2 = pm.w2, *const &gamma = pm.gamma, *const &beta = pm.beta;
    __nv_bfloat16* const& out = pm.out;
    Scratch* const& sc = pm.sc;
    extern __shared__ __align__(1024) uint8_t smem[];
    constexpr uint32_t sb = SB;
    const int tid = threadIdx.x;
    const Work wk = get_work(blockIdx.x, sp);
    constexpr uint32_t s_red = sb + SM_RED;
    if (smem_u32(smem) != SB) __trap();

    const int warp_id = __shfl_sync(~0u, tid >> 5, 0);
    PROF(0);
    const int cw = warp_id - 4, wgi = cw >> 2, w4 = warp_id & 3;
    if (elect_one()) {
        static_assert(3 * NSLOT * 4 == 8 + 4 * 16 && BAR_F == BAR_W + 48, "barrier shares");
        const int b = warp_id - 8;
        const uint32_t bar = b < 0 ? sb + BAR_X + warp_id * 8 : b < 7 ? sb + BAR_W + b * 8 : sb + BAR_PIN;
        mbar_init(bar, 1);
#pragma unroll
        for (int k = 0; k < 4; k++) mbar_init(sb + BAR_X + (8 + 4 * warp_id + k) * 8, 1);
        mbar_init(sb + BAR_R + warp_id * 8, 1);
        fence_async();
        if (b < 0) {
            issue_region(&tmap, sb + SM_RING + warp_id * REGION_BYTES, bar, w4, ((wk.tA & 511) + wk.dir * wgi) << 16 | (wk.tA >> 9) * TILE_W);
        } else if (b < 6) {
            mbar_expect_tx(bar, 64 * CH * 2);
            tma_2d(sb + SM_W2 + b * (64 * CH * 2), &tmap_w1, bar, 64 * b, 0);
        } else if (b == 6) {
            mbar_expect_tx(bar, 9 * CH * 2);
            bulk_load(sb + SM_FILTER, dw, 9 * CH * 2, bar);
        }
    }
    __syncwarp();
    const int ntiles = wk.nA + wk.nB;
    const int rank = (wgi + wk.lent + 2 * (ntiles - 1)) % NCONS | (wgi >> 2 & 3);
    const int spare = wk.rows % NSLOT, spare2 = spare == NSLOT - 1 ? 0 : spare + 1;
    const uint32_t sq_base = sb + (wgi < 0 ? SM_RING + spare * SLOT_BYTES : SM_SQ + rank * 2 * SQ_HALF);
    const uint32_t sq_upper = wgi < 0 ? (spare2 - spare) * SLOT_BYTES : SQ_HALF;
    const uint32_t bar_a = sb + BAR_A + w4 * 8, bar_e = sb + BAR_E + w4 * 8;
    const bool prepares = gridDim.x - blockIdx.x <= W2_GROUPS / 2, helps = !wk.lent && wk.index < 8 * LENT * sp.lenders;
    auto max_w1 = [&](uint32_t lane) { return __uint_as_float(__reduce_max_sync(~0u, lane < 4 * NCONS ? ldsi(s_red + RED_MAX + lane * 4) : 0)); };
    auto square_scale = [&](uint32_t lane) {
        const float f = pow2i(square_exp(bound_exp(max_w1(lane))));
        return pack_h2(f, f);
    };
    uint32_t a_addr, sq;
    const uint32_t sq_warp = sq_base + w4 * 512;
    auto set_addresses = [&]() {
        a_addr = opaque(sb + SM_RING + w4 * REGION_BYTES + ((tid >> 3) & 1) * A_SBO + ((tid >> 4) & 1) * A_LBO + (tid & 7) * 16);
        sq = opaque(sq_base + (tid & 127) * 16);
    };
    uint32_t turn, turn_end, so, so_sum, bo, bo_sum, off;
    auto set_run = [&](int j, int stop, int row) {
        const int slot = row % NSLOT, both = 2 * (row % 3) + 3;
        turn = opaque_uniform(row / 3);
        turn_end = opaque_uniform(row / 3 + (stop - j + NCONS - 1) / NCONS);
        so = opaque_uniform(slot * SLOT_BYTES);
        so_sum = opaque_uniform(both * SLOT_BYTES);
        bo = opaque_uniform(bar_a + slot * 32);
        bo_sum = opaque_uniform(2 * bar_a + both * 32);
        off = opaque_uniform(tile_offset(wk.tile(j)) + w4 * WARP_BYTES - sq_warp);
    };
    const int nrest = ntiles - 4;
    int jt;
    Cursor cur;
    int fast_from;
    if (warp_id < 4) {
        const int q = (gridDim.x - 1 - blockIdx.x) * 2 + (w4 >> 1);
        conv_producer(wk, &tmap, sb, warp_id, [&](bool second) {
            if (!second) {
                if (blockIdx.x == 0) {
#pragma unroll 1
                    for (int e = tid; e < EX; e += 128) *sc->sum(e) = 0;
                    sc->bias[tid] = 0.f;
                }
                if (blockIdx.x == 0 || wk.lent) signal(&sc->early);
            } else if (prepares || helps) {
                spin_until(&sc->early, (ldsi(s_red + RED_LAUNCH) + 1) * 4 * (sp.lenders + 1));
                if (elect_one()) {
                    if (helps) prefetch_l2(reinterpret_cast<const char*>(out) + sp.lent_off[wk.index / 8] + w4 * WARP_BYTES, WARP_BYTES);
                    if (prepares) { prefetch_l2(w2 + 8 * q * CH, 8 * CH * 2); prefetch_l2(beta + 8 * q, 16); }
                }
            }
        });
        set_addresses();
        const int lane = lane_id(), g = lane >> 2, t = lane & 3;
        const int piece = wk.index;
        uint32_t a[6][4];
        unsigned short bt_raw;
        if (prepares) {
#pragma unroll
            for (int m = 0; m < 3; m++) ldg128(a[m], w2 + (8 * q + g) * CH + 32 * m + 8 * t);
            asm volatile("ld.global.nc.u16 %0, [%1];" : "=h"(bt_raw) : "l"(beta + 8 * q + g) : "memory");
        } else if (helps) {
#pragma unroll
            for (int s = 0; s < 6; s++) ldg128(a[s], reinterpret_cast<const char*>(out) + sp.lent_off[piece / 8] + w4 * WARP_BYTES + lane * 16 + s * 512);
        }
        mbar_wait_once(bar_e + spare2 * 32, (wk.rows - 5) / NSLOT & 1);
        mbar_wait_once(bar_e + spare * 32, (wk.rows - 6) / NSLOT & 1);
        named_bar(1, 128);
#pragma unroll
        for (int k = 0; k < 6; k++) { sts128(sq + k * SQ_ROW, 0, 0, 0, 0); sts128(sq + sq_upper + k * SQ_ROW, 0, 0, 0, 0); }
        if (prepares) {
            const int half = w4 & 1;
            uint32_t rmax = 0;
#pragma unroll
            for (int m = 0; m < 3; m++) rmax = bf_absmax(bf_absmax(rmax, bf_absmax(a[m][0], a[m][1])), bf_absmax(a[m][2], a[m][3]));
            uint2 u = half ? make_uint2(a[0][2], a[0][3]) : make_uint2(a[0][0], a[0][1]), u1 = half ? make_uint2(a[1][2], a[1][3]) : make_uint2(a[1][0], a[1][1]);
            const uint2 u2 = half ? make_uint2(a[2][2], a[2][3]) : make_uint2(a[2][0], a[2][1]);
            const float bt = bf_lo(bt_raw);
            rmax = bf_absmax(rmax, __shfl_xor_sync(~0u, rmax, 1));
            rmax = bf_absmax(rmax, __shfl_xor_sync(~0u, rmax, 2));
            const float mx = fmaxf(fabsf(bf_lo(rmax)), fabsf(bf_hi(rmax))), rs = pow2i(row_exp(mx));
            if (t == 0 && !half) sc->w2max[8 * q + g] = mx;
#pragma unroll 1
            for (int m = 0; m < 3; m++, u = u1, u1 = u2) {
                float f[4];
#pragma unroll
                for (int k = 0; k < 2; k++) {
                    const float lo = bf_lo(k ? u.y : u.x), hi = bf_hi(k ? u.y : u.x);
                    sc->w2h[(4 * m + 2 * half + k) * 1536 + q * 32 + lane] = transpose8x8(pack_h2(lo * rs, hi * rs));
                    f[2 * k] = lo * bt;
                    f[2 * k + 1] = hi * bt;
                }
                const float r0 = (g & 2 ? f[2] : f[0]) + __shfl_xor_sync(~0u, g & 2 ? f[0] : f[2], 8);
                const float r1 = (g & 2 ? f[3] : f[1]) + __shfl_xor_sync(~0u, g & 2 ? f[1] : f[3], 8);
                float r = (g & 1 ? r1 : r0) + __shfl_xor_sync(~0u, g & 1 ? r0 : r1, 4);
                r += __shfl_xor_sync(~0u, r, 16);
                if (g < 4) atomicAdd(&sc->bias[32 * m + 8 * t + 4 * half + g], r);
            }
            asm volatile("fence.proxy.async.global;" ::: "memory");
            __syncwarp();
            named_arrive(3, 256);
        } else
        if (helps) {
            uint32_t d[12], gl[12];
            const uint32_t scale2 = square_scale(lane);
            wg_fence();
#pragma unroll
            for (int s = 0; s < 6; s++) wgmma(d, a[s][0], a[s][1], a[s][2], a[s][3], ds.w1[0][s] + piece % 8 * (6 * 1536 / 16), s ? 1 : 0);
            wg_commit();
            wg_wait<0>();
            gelu_to(gl, d);
#pragma unroll
            for (int s = 0; s < 3; s++) {
                sc->lent[((piece / 8 * 4 + w4) * 24 + piece % 8 * 3 + s) * 32 + lane] = make_uint4(gl[4 * s], gl[4 * s + 1], gl[4 * s + 2], gl[4 * s + 3]);
                uint32_t hs[2];
#pragma unroll
                for (int k = 0; k < 2; k++) {
                    const uint32_t g0 = h_mul(gl[4 * s + 2 * k], scale2), g1 = h_mul(gl[4 * s + 2 * k + 1], scale2);
                    hs[k] = h_fma(g1, g1, h_mul(g0, g0));
                }
                const int pair = piece % 4 * 3 + s;
                sts64(sq + (piece & 4 ? sq_upper : 0) + (pair >> 1) * SQ_ROW + (pair & 1) * 8, hs[0], hs[1]);
            }
        }
        jt = ntiles - 1;
        cur.slot = spare ? spare - 1 : NSLOT - 1;
        cur.par = (wk.rows - 1) / NSLOT & 1;
        fast_from = ntiles;
        turn = turn_end = so = so_sum = bo = bo_sum = off = rank;
    } else {
        set_addresses();
        if (wgi == NCONS - 1) named_arrive(4, 256);
        set_run(wk.lent + wgi, min(wk.nA, nrest), wk.lent + wgi + 2);
        jt = wgi < wk.lent ? wgi : wk.lent + wgi;
        cur = {2, 0};
        cur.advance(jt + (jt >= wk.nA ? 2 : 0));
        {
            const int ct = tid - 128, lane = tid & 31;
            const unsigned epoch = *reinterpret_cast<volatile unsigned*>(&sc->launch);
            const int r = lane & 7, mi = lane >> 3;
            const uint32_t src = sb + SM_W2 + (cw >> 1) * (64 * CH * 2) + r * 128 + ((((cw & 1) * 4 + mi) ^ r) * 16);
            const uint32_t dst = sb + SM_W1 + (4 * cw + mi) * 1536 + r * 16;
            const int code = row_code(wk, PREFETCH_ROWS - 1 + wgi);
            named_bar(0, NTHREADS);
            auto request = [&]() {
                if (elect_one())
                    issue_region(&tmap, sb + SM_RING + (PREFETCH_ROWS - 1 + wgi) * SLOT_BYTES + w4 * REGION_BYTES, sb + BAR_X + (cw + 8) * 8, w4, code);
                __syncwarp();
            };
#pragma unroll 1
            for (int k = 0; k < 2; k++) {
                if (wgi == k) request();
                mbar_wait_once(sb + BAR_W + (cw >> 1) * 8, 0);
            }
            uint32_t wmax[2] = {}, wsum[4] = {};
#pragma unroll K_UNR
            for (int c = 0; c < 12; c++) {
                uint32_t u[4];
                ldsm4_t(u, src + c * 1024);
#pragma unroll
                for (int q = 0; q < 4; q++) {
                    wmax[q & 1] = bf_absmax(wmax[q & 1], u[q]);
                    wsum[q] = bf_fma(u[q], 0x3f803f80u, wsum[q]);
                    u[q] = pack_h2(__uint_as_float(u[q] * (65536 + zero)), bf_hi(u[q]));
                }
                stsm4(dst + c * 128, u[0], u[1], u[2], u[3]);
            }
            const float w1max = warp_absmax(bf_absmax(wmax[0], wmax[1]));
            if (lane == 0) sts32(s_red + RED_MAX + cw * 4, __float_as_uint(w1max));
            bool center = false;
#pragma unroll
            for (int q = 0; q < 4; q++) {
#pragma unroll
                for (int o = 1; o <= 2; o <<= 1) wsum[q] = bf_fma(__shfl_xor_sync(~0u, wsum[q], o), 0x3f803f80u, wsum[q]);
                center |= fabsf(bf_lo(wsum[q]) + bf_hi(wsum[q])) > (0.15f * CH) * w1max;
            }
            if (__builtin_expect(__any_sync(~0u, center), 0)) {
                float mean[4] = {};
#pragma unroll 1
                for (int pass = 0; pass < 2; pass++) {
                    float sum[4] = {};
#pragma unroll 1
                    for (int c = 0; c < 12; c++) {
                        uint32_t u[4];
                        ldsm4_t(u, src + c * 1024);
#pragma unroll
                        for (int q = 0; q < 4; q++) {
                            sum[q] += bf_lo(u[q]) + bf_hi(u[q]);
                            u[q] = pack_h2(bf_lo(u[q]) - mean[q], bf_hi(u[q]) - mean[q]);
                        }
                        stsm4(dst + c * 128, u[0], u[1], u[2], u[3]);
                    }
#pragma unroll
                    for (int q = 0; q < 4; q++) {
                        sum[q] += __shfl_xor_sync(~0u, sum[q], 1);
                        sum[q] += __shfl_xor_sync(~0u, sum[q], 2);
                        mean[q] = sum[q] * (1.f / CH);
                    }
                }
            }
            if (!(cw & 2)) {
#pragma unroll
                for (int c = 0; c < 12; c++) sts128(src + c * 1024, 0, 0, 0, 0);
            }
            if (ct < 32) sts32(sb + SM_ONES + ct * 4, 0x3f803f80u);
            if (ct == 0) sts32(s_red + RED_LAUNCH, epoch);
            fence_async();
            named_bar(2, CONS_THREADS);
            if (wgi == 2) request();
        }
        PROF(1);
        if (cur.par) mbar_wait_once(bar_a, 0);
        fast_from = wk.lent;
        if (!__all_sync(~0u, plain_squares(bound_exp(max_w1(lane_id()))))) {
            fast_from = ntiles;
#pragma unroll 1
            for (int q = 0; q < 6; q++) sts128(sq + SQ_HALF + q * SQ_ROW, 0, 0, 0, 0);
        }
    }
    uint32_t k1[24], k2[24], k3[24];
    uint32_t here;
    constexpr int SQC = 3 * SQ_ROW;
    auto store_at = [&](const uint32_t (&a)[6][4], uint32_t off) {
        char* ap = reinterpret_cast<char*>(out) + (off + sq);
#pragma unroll
        for (int s = 0; s < 6; s++) stg128(ap + s * 512, a[s]);
    };
    const uint32_t own_bar = 4 + (wgi & 3), next_bar = 4 + (wgi == NCONS - 1 ? 0 : wgi + 1);
    for (;;) {
        if (jt >= fast_from) {
            uint32_t hs2[12] = {}, hs3[12] = {};
            const uint32_t step = wk.dir * (NCONS * IMG_W * CH * 2);
            int second = wk.nB;
#pragma unroll 1
            for (;;) {
#pragma unroll 1
                while (turn != turn_end) {
                    uint32_t a[6][4], d0[24], d1[24], unused[24];
#define AT(pos) \
    if (K_WAIT == pos) named_bar(own_bar, 256); \
    if (K_PASS == pos) named_arrive(next_bar, 256); \
    if (K_STG == pos) store_at(a, off); \
    if (K_REL == pos) { if (elect_one()) mbar_arrive(bo + (BAR_E - BAR_A)); }
                    AT(20)
                    mbar_wait(bo, turn >> 1 & 1);
                    load_tile(a, a_addr + so);
                    AT(21)
                    layer_norm(a, ds.ones, [&](int pos) { AT(pos) });
                    AT(1)
                    wg_fence();
                    gemm1_chunk<0>(d0, a, ds, 0);
                    wg_commit();
                    gemm1_chunk<96>(d1, a, ds, 0);
                    wg_commit();
                    AT(2)
                    wg_wait<1>();
                    AT(3)
                    gelu_sq<false, 0, 1>(d0, unused, sq, 0);
                    AT(4)
                    gelu_sq<false, 1, 2>(d0, unused, sq, 0);
                    AT(5)
                    gelu_sq<false, 2, 3>(d0, unused, sq, 0);
                    AT(6)
                    wg_fence();
                    gemm1_chunk<192>(d0, a, ds, zero);
                    wg_commit();
                    AT(7)
                    wg_wait<1>();
                    gelu_sq<false, 0, 1>(d1, unused, sq + SQC, 0);
                    AT(8)
                    gelu_sq<false, 1, 3>(d1, unused, sq + SQC, 0);
                    AT(9)
                    wg_fence();
                    gemm1_chunk<288>(d1, a, ds, zero);
                    wg_commit();
                    AT(10)
                    wg_wait<1>();
                    gelu_sq_reg(d0, hs2);
                    if (K_ANCH < 3) anchor(sq, hs2[4 * (K_ANCH % 3)], hs2[4 * (K_ANCH % 3) + 1], hs2[4 * (K_ANCH % 3) + 2], hs2[4 * (K_ANCH % 3) + 3]);
                    wg_wait<0>();
                    AT(11)
                    gelu_sq_reg(d1, hs3);
#undef AT
                    so = so_sum - so;
                    bo = bo_sum - bo;
                    off += step;
                    turn++;
                }
                if (!second) break;
                const int j = ntiles - second + (rank + second + 2) % NCONS;
                second = 0;
                set_run(j, nrest, j + 4);
            }
            jt = nrest + rank;
            cur.slot = (bo - bar_a) >> 5;
            cur.par = turn >> 1 & 1;
#pragma unroll
            for (int k = 0; k < 3; k++) {
                sts128(sq + SQ_HALF + k * SQ_ROW, hs2[4 * k], hs2[4 * k + 1], hs2[4 * k + 2], hs2[4 * k + 3]);
                sts128(sq + SQ_HALF + SQC + k * SQ_ROW, hs3[4 * k], hs3[4 * k + 1], hs3[4 * k + 2], hs3[4 * k + 3]);
            }
        }
        const bool last = jt >= nrest;
        here = tile_offset(wk.tile(jt));
        if (last) {
            const uint32_t next = ldsi(sb + SM_TILES + rank * 4);
            if (elect_one()) {
                prefetch_l2(reinterpret_cast<const char*>(x) + here + w4 * WARP_BYTES, WARP_BYTES);
                if (rank % ORDER_P >= ORDER_P - ORDER_Q) prefetch_l2(reinterpret_cast<const char*>(out) + next + w4 * WARP_BYTES, WARP_BYTES);
            }
        }
        uint32_t a[6][4], d0[24], d1[24], d3[24], k0[24];
#define AT(pos) \
    if (K_WAIT == pos && jt >= wk.lent) named_bar(own_bar, 256); \
    if (K_PASS == pos && jt >= wk.lent && jt + 2 < ntiles) named_arrive(next_bar, 256); \
    if (K_P0 == pos && jt == nrest + K_R0) named_arrive(7, 256);
        AT(20)
        mbar_wait_once(bar_a + cur.slot * 32, cur.par);
        load_tile(a, a_addr + cur.slot * SLOT_BYTES);
        AT(21)
        layer_norm(a, ds.ones, [&](int pos) { AT(pos) });
        AT(1)
        if (!last) {
            store_at(a, here + w4 * WARP_BYTES - sq_warp);
            __syncwarp();
            if (elect_one()) mbar_arrive(bar_e + cur.slot * 32);
            if (jt < wk.lent) {
                jt += LENT;
                cur.advance(LENT);
                continue;
            }
        }
        wg_fence();
        gemm1_chunk<0>(d0, a, ds, 0);
        wg_commit();
        gemm1_chunk<96>(d1, a, ds, 0);
        wg_commit();
        const uint32_t scale2 = square_scale(lane_id());
        AT(2)
        wg_wait<1>();
        AT(3)
        gelu_sq<true, 0, 1>(d0, k0, sq, scale2);
        AT(4)
        gelu_sq<true, 1, 2>(d0, k0, sq, scale2);
        AT(5)
        gelu_sq<true, 2, 3>(d0, k0, sq, scale2);
        AT(6)
        if (last) {
#pragma unroll
            for (int q = 0; q < 6; q++)
                sts128(sb + SM_RING + cur.slot * SLOT_BYTES + w4 * REGION_BYTES - sq_warp + sq + q * 512, k0[4 * q], k0[4 * q + 1], k0[4 * q + 2], k0[4 * q + 3]);
        }
        wg_fence();
        gemm1_chunk<192>(d0, a, ds, zero);
        wg_commit();
        AT(7)
        wg_wait<1>();
        gelu_sq<true>(d1, k1, sq + SQC, scale2);
        AT(9)
#undef AT
        wg_fence();
        gemm1_chunk<288>(d3, a, ds, 0);
        wg_commit();
        wg_wait<1>();
        gelu_sq<true>(d0, k2, sq + sq_upper, scale2);
        wg_wait<0>();
        gelu_sq<true>(d3, k3, sq + sq_upper + SQC, scale2);
        if (last) break;
        cur.advance(NCONS + ((jt < wk.nA && jt + NCONS >= wk.nA) ? 2 : 0));
        jt += NCONS;
    }
    const uint32_t lane = lane_id();
    uint32_t next_off = opaque_uniform(ldsi(sb + SM_TILES + rank * 4));
    const uint32_t s_fac = sb + SM_RING + spare * SLOT_BYTES + SQ_HALF;
    uint32_t inv_rho2;
    {
        const bool leader = rank == 0 && w4 == 0 && lane == 0;
        const int i0 = w4 * 32 + lane;
        float base[3], slope[3], reach[3], to_square;
        float2 bpair = make_float2(0.f, 0.f);
        unsigned epoch;
        if (rank == 0) {
            float gam[3], rmax[3];
#pragma unroll
            for (int m = 0; m < 3; m++) {
                unsigned short v;
                asm volatile("ld.global.nc.u16 %0, [%1];" : "=h"(v) : "l"(gamma + i0 + 128 * m) : "memory");
                gam[m] = bf_lo(v);
            }
            epoch = ldsi(s_red + RED_LAUNCH);
            if (prepares) {
                named_bar(3, 256);
                if (w4 == 1) signal(&sc->prep);
            }
            if (leader) {
                spin_until(&sc->prep, (epoch + 1) * (W2_GROUPS / 2));
                asm volatile("fence.proxy.async.global;" ::: "memory");
            }
            __syncwarp();
            named_bar(2, 128);
#pragma unroll
            for (int m = 0; m < 3; m++) rmax[m] = __ldcg(&sc->w2max[i0 + 128 * m]);
            if (i0 < 96) bpair = __ldcg(reinterpret_cast<const float2*>(&sc->bias[32 * (i0 % 24 >> 3) + 8 * (i0 / 24) + (i0 % 24 & 6)]));
            const float w1max = max_w1(lane);
            const float gbound = fmaxf(2.f * KZ * 9.7979590f * 192.f * w1max, 1.f) * 19.5959180f * INV_2KZ;
            const unsigned fixed = __reduce_max_sync(~0u, __float_as_uint(fmaf(gbound, fmaxf(fmaxf(rmax[0], rmax[1]), rmax[2]), fmaxf(fabsf(bpair.x), fabsf(bpair.y)))));
            if (lane == 0) sts32(s_red + 96 + w4 * 4, fixed);
#pragma unroll
            for (int m = 0; m < 3; m++) {
                base[m] = rmax[m] > 0.f ? pow2i(-row_exp(rmax[m])) * (INV_2KZ * CUT_GAIN) : 0.f;
                slope[m] = base[m] * gam[m];
                reach[m] = fabsf(gam[m]) * rmax[m] * gbound;
            }
            to_square = pow2i(-sum_exp(bound_exp(w1max))) * (INV_2KZ * INV_2KZ / 256);
        }
        if (rank >= 2) {
            named_arrive(12 + rank, CONS_THREADS);
        } else {
            const int rw = rank * 4 + w4, g = lane >> 2, t = lane & 3;
            const uint32_t pick = (g & 1) == (t & 1) ? (g & 2 ? 0x3c000000u : 0x00003c00u) : 0;
            const int be = bound_exp(max_w1(lane));
            const float to_fixed = pow2i(sum_exp(be) - 2 * square_exp(be));
            unsigned long long* dst = sc->sum(64 * rw + 32 * (t >> 1) + 8 * (g >> 1) + 2 * (t & 1) + (g & 1));
            const uint32_t rows = sb + (rw * 2 + (lane >> 3 & 1)) * SQ_ROW + ((lane >> 4) * 8 + (lane & 7)) * 16;
            float f[2][4] = {};
            named_bar(13, 256);
#pragma unroll 1
            for (int i = 0; i < 4; i++) {
                if (i == 2) {
                    named_bar(13, 256);
                    if (leader) {
                        fence_async();
                        mbar_expect_tx(sb + BAR_W, 4 * SQ_HALF);
                        bulk_load(sb + SM_W2, sc->w2h, 4 * SQ_HALF, sb + BAR_W);
                    }
                    __syncwarp();
                }
                const int from = i < 2 ? i : i ^ K_ORD;
                const uint32_t src = rows + (from < NCONS ? SM_SQ + from * 2 * SQ_HALF : rw < 3 ? SM_RING + spare * SLOT_BYTES : SM_RING + spare2 * SLOT_BYTES - SQ_HALF);
                if (i >= 2) named_bar(12 + from, CONS_THREADS);
                if (rw < 6) {
#pragma unroll
                    for (int r = 0; r < 8; r++) {
                        uint32_t u[4];
                        ldsm4_t(u, src + r * 256);
                        asm volatile("mma.sync.aligned.m16n8k16.row.col.f32.f16.f16.f32 {%0, %1, %2, %3}, {%4, %5, %6, %7}, {%8, %8}, {%0, %1, %2, %3};"
                                     : "+f"(f[r & 1][0]), "+f"(f[r & 1][1]), "+f"(f[r & 1][2]), "+f"(f[r & 1][3])
                                     : "r"(u[0]), "r"(u[1]), "r"(u[2]), "r"(u[3]), "r"(pick));
                    }
                }
            }
            if (rw < 6) {
#pragma unroll
                for (int r = 0; r < 2; r++)
                    atomicAdd(dst + r * 32, __float2ull_rn(fminf((t < 2 ? f[0][r] + f[1][r] : f[0][r + 2] + f[1][r + 2]) * to_fixed, 0x1p47f)) << 8 | 1);
            }
            PROF(2);
            named_bar(13, 256);
            if (leader) {
                fence_async();
                mbar_expect_tx(sb + BAR_W + 8, 2 * SQ_HALF);
                bulk_load(sb + SM_W2 + 4 * SQ_HALF, reinterpret_cast<const char*>(sc->w2h) + 4 * SQ_HALF, 2 * SQ_HALF, sb + BAR_W + 8);
            }
            if (helps && rw == 7) signal(&sc->lent_out);
        }
        if (rank == 0) {
            const uint32_t own_sum = (i0 >> 2) * 256 + (i0 & 3) * 8, own_fac = s_fac + i0 * 2;
            auto peek = [&](const void* p) {
                unsigned long long v;
                asm volatile("ld.relaxed.gpu.global.u64 %0, [%1];" : "=l"(v) : "l"(p) : "memory");
                return v;
            };
            const char* mine = reinterpret_cast<const char*>(sc->sums) + own_sum;
            unsigned n = 0;
            while (((unsigned)peek(sc->sum((blockIdx.x * 4 + w4) % (EX / 4) * 4)) & 255u) != gridDim.x)
                if (++n > SPIN_LIMIT) __trap();
            unsigned long long sum[3];
            for (;;) {
                bool all = true;
#pragma unroll
                for (int m = 0; m < 3; m++) {
                    sum[m] = peek(mine + m * (32 * 256));
                    all &= ((unsigned)sum[m] & 255u) == gridDim.x;
                }
                if (__all_sync(~0u, all)) break;
                if (++n > SPIN_LIMIT) __trap();
            }
            PROF(3);
            float gx[3];
#pragma unroll
            for (int m = 0; m < 3; m++) asm("sqrt.approx.ftz.f32 %0, %1;" : "=f"(gx[m]) : "f"(fmaf(__ull2float_rn(sum[m]), to_square, 1e-6f)));
            float tot = gx[0] + gx[1] + gx[2];
#pragma unroll
            for (int o = 16; o >= 1; o >>= 1) tot += __shfl_xor_sync(~0u, tot, o);
            const unsigned vwarp = __reduce_max_sync(~0u, __float_as_uint(fmaxf(fmaxf(reach[0] * gx[0], reach[1] * gx[1]), reach[2] * gx[2])));
            if (lane == 0) { sts32(s_red + 64 + w4 * 4, __float_as_uint(tot)); sts32(s_red + 80 + w4 * 4, vwarp); }
            named_bar(2, 128);
            uint32_t u[4], v[4], w[4];
            lds128(u[0], u[1], u[2], u[3], s_red + 64);
            lds128(v[0], v[1], v[2], v[3], s_red + 80);
            lds128(w[0], w[1], w[2], w[3], s_red + 96);
            tot = (__uint_as_float(u[0]) + __uint_as_float(u[1])) + (__uint_as_float(u[2]) + __uint_as_float(u[3]));
            const float vmax = __uint_as_float(max(max(v[0], v[1]), max(v[2], v[3]))), fmax2 = __uint_as_float(max(max(w[0], w[1]), max(w[2], w[3])));
            float inv_mean;
            asm("rcp.approx.ftz.f32 %0, %1;" : "=f"(inv_mean) : "f"(fmaf(tot, 1.f / EX, 1e-6f)));
            const int rho_e = 14 - ilog2f(fmaf(vmax, inv_mean, 2.f * fmax2));
            const float rho = pow2i(rho_e), inv_rho = pow2i(-rho_e);
            inv_rho2 = pack_bf2(inv_rho, inv_rho);
#pragma unroll
            for (int m = 0; m < 3; m++) {
                const float f = fmaf(slope[m] * gx[m], inv_mean, base[m]) * rho;
                asm volatile("st.shared.u16 [%0], %1;" ::"r"(own_fac + 256 * m), "h"((unsigned short)pack_h2(f, 0.f)) : "memory");
            }
            if (i0 < 96) sts32(sb + SM_BIASH + i0 * 4, pack_h2(bpair.x * rho, bpair.y * rho));
            if (i0 == 96) sts32(s_red + RED_INV_RHO, inv_rho2);
            named_arrive(12, NTHREADS);
            if (blockIdx.x == 0 && leader) sc->launch = epoch + 1;
            if (wk.lent) spin_until(&sc->lent_out, (epoch + 1) * 8 * LENT * sp.lenders);
        } else {
            const int rw = rank * 4 - 4 + w4;
            const uint32_t row = sb + SM_W2 + rw * 512 + lane * 16;
            uint32_t u[W2_EARLY][4], f2[4];
#pragma unroll
            for (int nb = 0; nb < W2_EARLY; nb++) {
                if (nb % 8 == 0) mbar_wait_once(sb + BAR_W + nb, 1);
                lds128(u[nb][0], u[nb][1], u[nb][2], u[nb][3], row + nb * 6144);
            }
            if (W2_EARLY <= 8) mbar_wait_once(sb + BAR_W + 8, 1);
            named_bar(12, NTHREADS);
            PROF(3);
            lds128(f2[0], f2[1], f2[2], f2[3], s_fac + rw * 64 + (lane >> 3) * 16);
            lds32(inv_rho2, s_red + RED_INV_RHO);
#pragma unroll
            for (int nb = 0; nb < 12; nb++) {
                uint32_t v[4];
                if (nb < W2_EARLY) { v[0] = u[nb % W2_EARLY][0]; v[1] = u[nb % W2_EARLY][1]; v[2] = u[nb % W2_EARLY][2]; v[3] = u[nb % W2_EARLY][3]; }
                else lds128(v[0], v[1], v[2], v[3], row + nb * 6144);
                sts128(row + nb * 6144, h_cut8(h_mul(v[0], f2[0])), h_cut8(h_mul(v[1], f2[1])), h_cut8(h_mul(v[2], f2[2])), h_cut8(h_mul(v[3], f2[3])));
            }
            fence_async();
            named_arrive(8, NTHREADS);
        }
    }
    uint32_t a[6][4], acc[24], rpar = 0, tile_off = here;
    const uint32_t bias_addr = sb + SM_BIASH + (lane & 3) * 96, lane16 = lane * 16, lane_off = ((lane >> 2) * CH + 8 * (lane & 3)) * 2;
    const uint32_t stage = sb + SM_RING + (spare + rank) % NSLOT * SLOT_BYTES + w4 * WARP_BYTES, bar_r = sb + BAR_R + warp_id * 8;
    auto load_bias = [&]() {
#pragma unroll
        for (int q = 0; q < 6; q++) lds128(acc[4 * q], acc[4 * q + 1], acc[4 * q + 2], acc[4 * q + 3], bias_addr + q * 16);
    };
    auto load_frags = [&]() {
#pragma unroll
        for (int s = 0; s < 6; s++) ldg128(a[s], reinterpret_cast<const char*>(out) + next_off + w4 * WARP_BYTES + lane16 + s * 512);
    };
    auto stage_x = [&]() {
        if (elect_one()) {
            mbar_expect_tx(bar_r, WARP_BYTES);
            bulk_load_stream(stage, reinterpret_cast<const char*>(x) + tile_off + w4 * WARP_BYTES, WARP_BYTES, bar_r);
        }
    };
    {
        named_bar(8 + rank, rank ? 256 : NTHREADS);
        if (rank == 0) PROF(4);
        load_bias();
        pin(k1); pin(k2); pin(k3);
        wg_fence();
        gemm2_chunk<KA>(acc, KX(KA), ds);
        wg_commit();
        gemm2_chunk<KB>(acc, KX(KB), ds);
        wg_commit();
        gemm2_chunk<KC>(acc, KX(KC), ds);
        wg_commit();
        stage_x();
        wg_wait<2>();
        uint32_t k0[24];
#pragma unroll
        for (int q = 0; q < 6; q++)
            lds128(k0[4 * q], k0[4 * q + 1], k0[4 * q + 2], k0[4 * q + 3], sb + SM_RING + cur.slot * SLOT_BYTES + w4 * REGION_BYTES + lane16 + q * 512);
        pin(k0);
        wg_fence();
        gemm2_chunk<0>(acc, k0, ds);
        wg_commit();
        if (rank < NCONS) named_arrive(9 + rank, 256);
        wg_wait<2>();
        load_frags();
        if (lane16 == 0) mbar_arrive(sb + BAR_PIN);
        if (!K_RW) mbar_wait(bar_r, rpar);
        wg_wait<0>();
    }
    auto lent = [&](uint32_t entry) { return &sc->lent[((wk.index * LENT + (entry & 3) - 1) * 4 + w4) * (24 * 32)]; };
    for (jt = rank - 4; jt < nrest; jt += 4) {
        if (jt >= zero) {
        tile_off = next_off;
        lds32(next_off, sb + SM_TILES + (jt + 4) * 4);
        if (tile_off & 3) {
            const uint4* src = lent(tile_off) + lane;
            tile_off &= ~3u;
            next_off = __shfl_sync(~0u, next_off, 0);
            stage_x();
            if (elect_one()) prefetch_l2(reinterpret_cast<const char*>(out) + next_off + w4 * WARP_BYTES, WARP_BYTES);
            load_bias();
#pragma unroll 1
            for (int half = 0; half < 2; half++, src += 12 * 32) {
                uint32_t gl[48];
#pragma unroll
                for (int s = 0; s < 12; s++) ldg128(reinterpret_cast<uint32_t (&)[4]>(gl[4 * s]), src + s * 32);
                if (!half) {
                    named_bar(4 + rank, 256);
                    named_arrive(4 + ((rank + 1) & 3), 256);
                }
                pin(gl);
                wg_fence();
#pragma unroll
                for (int s = 0; s < 12; s++) wgmma(acc, gl[4 * s], gl[4 * s + 1], gl[4 * s + 2], gl[4 * s + 3], ds.w2[12 * half + s], 1);
                wg_commit();
                wg_wait<0>();
            }
            load_frags();
            if (!K_RW) mbar_wait(bar_r, rpar);
        } else {
            uint32_t d0[12], d1[12], g0[12], g1[12];
            if (jt >= S2_FIRST) named_bar(4 + rank, 256);
            wg_fence();
            gemm1_chunk<0>(d0, a, ds, 0);
            wg_commit();
            gemm1_chunk<48>(d1, a, ds, 0);
            wg_commit();
            load_bias();
            next_off = __shfl_sync(~0u, next_off, 0);
            const bool more = jt + 4 < nrest && !(next_off & 3);
            wg_wait<1>();
#define CNX_STEP(C, D, G)                                              \
    gelu_to(G, D);                                                     \
    wg_fence();                                                        \
    if (C < 6) gemm1_chunk<48 * (C < 6 ? C + 2 : 0)>(D, a, ds, zero); \
    gemm2_chunk<48 * C>(acc, G, ds);                                  \
    wg_commit();                                                       \
    wg_wait<(C < 7 ? 1 : 0)>();
            CNX_STEP(0, d0, g0)
            CNX_STEP(1, d1, g1)
            if (jt + 1 >= S2_FIRST && jt + 1 < nrest) named_arrive(4 + ((rank + 1) & 3), 256);
            stage_x();
            if (elect_one()) {
                if (more) prefetch_l2(reinterpret_cast<const char*>(out) + next_off + w4 * WARP_BYTES, WARP_BYTES);
                else if (next_off & 3) prefetch_l2(lent(next_off), 24 * 32 * 16);
            }
            CNX_STEP(2, d0, g0)
            CNX_STEP(3, d1, g1)
            CNX_STEP(4, d0, g0)
            CNX_STEP(5, d1, g1)
            CNX_STEP(6, d0, g0)
#pragma unroll
            for (int s = 0; s < 6; s++) ldg128_if(more, a[s], reinterpret_cast<const char*>(out) + next_off + w4 * WARP_BYTES + lane16 + s * 512);
            if (lane16 == 0) mbar_arrive(sb + BAR_PIN);
            if (!K_RW) mbar_wait(bar_r, rpar);
            CNX_STEP(7, d1, g1)
#undef CNX_STEP
        }
        }
        {
            if (K_RW) mbar_wait(bar_r, rpar);
            pin(acc);
            rpar ^= 1;
            uint4* op = reinterpret_cast<uint4*>(reinterpret_cast<char*>(out) + tile_off + w4 * WARP_BYTES + lane_off);
#pragma unroll
            for (int h = 0; h < 2; h++)
#pragma unroll
                for (int m = 0; m < 3; m++) {
                    uint32_t xin[4], o[4];
                    lds128(xin[0], xin[1], xin[2], xin[3], stage + lane_off + h * 1536 + m * 64);
#pragma unroll
                    for (int q = 0; q < 4; q++) {
                        const uint32_t v = acc[2 * (4 * m + q) + h];
                        o[q] = bf_fma(pack_bf2(h_lo(v), h_hi(v)), inv_rho2, xin[q]);
                    }
                    __stcs(op + h * 96 + m * 4, make_uint4(o[0], o[1], o[2], o[3]));
                }
            __syncwarp();
        }
    }
    PROF(5);
}

}

typedef CUresult (*EncodeTiledFn)(CUtensorMap*, CUtensorMapDataType, cuuint32_t, void*, const cuuint64_t*, const cuuint64_t*,
                                  const cuuint32_t*, const cuuint32_t*, CUtensorMapInterleave, CUtensorMapSwizzle,
                                  CUtensorMapL2promotion, CUtensorMapFloatOOBfill);

extern "C" void kernel_launch(void* const* d_in, const int* in_sizes, int n_in, void* d_out, int out_size) {
    using namespace cnx;
    static EncodeTiledFn encode = nullptr;
    static int num_sms = 0;
    static Scratch* scratch = nullptr;
    if (!encode) {
        void* fn = nullptr;
        cudaDriverEntryPointQueryResult qr;
        cudaGetDriverEntryPoint("cuTensorMapEncodeTiled", &fn, cudaEnableDefault, &qr);
        encode = (EncodeTiledFn)fn;
        cudaGetSymbolAddress((void**)&scratch, g_scratch);
        int dev = 0;
        cudaGetDevice(&dev);
        cudaDeviceGetAttribute(&num_sms, cudaDevAttrMultiProcessorCount, dev);
        if (num_sms > MAX_CTAS) num_sms = MAX_CTAS;
        cudaFuncSetAttribute(block_kernel, cudaFuncAttributeMaxDynamicSharedMemorySize, SM_TOTAL);
    }
    CUtensorMap tm;
    cuuint64_t dims[3] = {(cuuint64_t)CH, (cuuint64_t)IMG_W, (cuuint64_t)IMG_H};
    cuuint64_t strides[2] = {(cuuint64_t)CH * 2, (cuuint64_t)CH * 2 * IMG_W};
    cuuint32_t box[3] = {(cuuint32_t)CH, (cuuint32_t)REGION_PX, 1};
    cuuint32_t estr[3] = {1, 1, 1};
    encode(&tm, CU_TENSOR_MAP_DATA_TYPE_BFLOAT16, 3, d_in[0], dims, strides, box, estr, CU_TENSOR_MAP_INTERLEAVE_NONE,
           CU_TENSOR_MAP_SWIZZLE_NONE, CU_TENSOR_MAP_L2_PROMOTION_L2_128B, CU_TENSOR_MAP_FLOAT_OOB_FILL_NONE);
    Params pm = {};
    Descs& ds = pm.ds;
    for (int c = 0; c < 8; c++)
        for (int k = 0; k < 6; k++) ds.w1[c][k] = make_desc(SB + SM_W1 + c * 6 * 1536 + k * 256, 128, 1536);
    for (int k = 0; k < 24; k++) ds.w2[k] = make_desc(SB + SM_W2 + k * 256, 128, 6144);
    ds.ones = make_desc(SB + SM_ONES, 0, 0);
    CUtensorMap tw;
    cuuint64_t wdims[2] = {(cuuint64_t)EX, (cuuint64_t)CH};
    cuuint64_t wstrides[1] = {(cuuint64_t)EX * 2};
    cuuint32_t wbox[2] = {64, (cuuint32_t)CH};
    encode(&tw, CU_TENSOR_MAP_DATA_TYPE_BFLOAT16, 2, d_in[2], wdims, wstrides, wbox, estr, CU_TENSOR_MAP_INTERLEAVE_NONE,
           CU_TENSOR_MAP_SWIZZLE_128B, CU_TENSOR_MAP_L2_PROMOTION_L2_128B, CU_TENSOR_MAP_FLOAT_OOB_FILL_NONE);
    Split& sp = pm.sp;
    sp = {NTILES / num_sms, NTILES % num_sms, 1, 1 << 16, 0, {}};
    if (sp.per_cta + 9 > MAX_ROWS) return;
    if (sp.extra && sp.extra * (8 * LENT + 1) + W2_GROUPS / 2 <= num_sms && sp.per_cta >= 5 * LENT + 8) {
        sp.period = num_sms / sp.extra;
        sp.inv_period = 65535 / sp.period + 1;
        sp.lenders = sp.extra;
        for (int l = 0; l < sp.extra; l++) {
            const Work w = get_work((l + 1) * sp.period - sp.period / 2 - 1, sp);
            for (int e = 0; e < LENT; e++) sp.lent_off[l * LENT + e] = tile_offset(w.tile(e));
            if (w.nA < 2 * LENT) sp.lenders = 0;
        }
    }
    pm.x = (const __nv_bfloat16*)d_in[0];
    pm.dw = (const __nv_bfloat16*)d_in[1];
    pm.w2 = (const __nv_bfloat16*)d_in[3];
    pm.gamma = (const __nv_bfloat16*)d_in[4];
    pm.beta = (const __nv_bfloat16*)d_in[5];
    pm.out = (__nv_bfloat16*)d_out;
    pm.sc = scratch;
    block_kernel<<<num_sms, NTHREADS, SM_TOTAL>>>(tm, tw, pm);
}
```

```cpp
#include <cuda_runtime.h>
#include <cuda_bf16.h>
#include <cuda_fp16.h>
#include <cuda.h>
#include <stdint.h>

namespace cnx {

constexpr int IMG_H = 512, IMG_W = 512, CH = 96, EX = 384;
constexpr int TILE_W = 64;
constexpr int NTILES = (IMG_W / TILE_W) * IMG_H;
constexpr int NSLOT = 6;
constexpr int REGION_PX = 18;
constexpr int REGION_BYTES = REGION_PX * CH * 2;
constexpr int SLOT_BYTES = 4 * REGION_BYTES;
constexpr int A_LBO = 144, A_SBO = 12 * A_LBO;
constexpr int PREFETCH_ROWS = 3;
constexpr int NCONS = 3;
constexpr int CONS_THREADS = 128 * NCONS;
constexpr int NTHREADS = 128 + CONS_THREADS;
constexpr int MAX_ROWS = 52;
constexpr int TILE_BYTES = TILE_W * CH * 2, WARP_BYTES = TILE_BYTES / 4;
constexpr int ORDER_P = 3;
constexpr int W2_EARLY = 9;
static_assert(MAX_ROWS <= 128, "one table entry per producer thread");
static_assert(2 * A_SBO == REGION_BYTES && REGION_BYTES % 128 == 0, "region layout");

constexpr uint32_t SB = 1024;
constexpr int SM_W1 = 0;
constexpr int SM_W2 = SM_W1 + CH * EX * 2;
constexpr int SM_RING = SM_W2 + CH * EX * 2;
constexpr int SM_BIASH = SM_RING + NSLOT * SLOT_BYTES;
constexpr int SM_RED = SM_BIASH + 384;
constexpr int RED_MAX = 0, RED_LAUNCH = 48, RED_INV_RHO = 52;
constexpr int SM_TILES = SM_RED + 256;
constexpr int SM_ONES = SM_TILES + MAX_ROWS * 4;
constexpr int SM_BAR = SM_ONES + 128;
constexpr int BAR_X = SM_BAR;
constexpr int BAR_A = BAR_X + NSLOT * 4 * 8;
constexpr int BAR_E = BAR_A + NSLOT * 4 * 8;
constexpr int BAR_PIN = BAR_E + NSLOT * 4 * 8;
constexpr int BAR_W = BAR_PIN + 8;
constexpr int BAR_F = BAR_W + 6 * 8;
constexpr int BAR_R = BAR_F + 8;
constexpr int SM_TOTAL = BAR_R + 16 * 8;
constexpr int SM_FILTER = SM_RING + (NSLOT - 1) * SLOT_BYTES + 9 * 128;
constexpr int SM_SQ = SM_W2;
constexpr int SQ_ROW = 128 * 16, SQ_HALF = 6 * SQ_ROW;
static_assert(SM_ONES % 16 == 0 && SM_TOTAL <= 232448, "shared memory budget");

constexpr float KZ = 0.3292034911525734f;
constexpr uint32_t GELU_C2 = 0x40d940d9u;
constexpr float INV_2KZ = 0.5f / KZ;
constexpr unsigned SPIN_LIMIT = 1u << 19;

constexpr int MAX_CTAS = 255;
constexpr int W2_GROUPS = EX / 8;
constexpr int LENT = 3, MAX_LENDERS = MAX_CTAS / (8 * LENT + 1);
struct Scratch {
    uint32_t w2h[EX * CH / 2];
    float w2max[EX];
    float bias[CH + 32];
    unsigned long long sums[EX / 4][32];
    __device__ __forceinline__ unsigned long long* sum(int e) { return &sums[e >> 2][e & 3]; }
    uint4 lent[MAX_LENDERS * LENT * 8 * 4 * 3 * 32];
    unsigned launch, pad0[31], early, pad1[31], prep, pad2[31], lent_out, pad3[31];
};
__device__ __align__(128) Scratch g_scratch;

#define PROF(k)

__device__ __forceinline__ uint32_t smem_u32(const void* p) { return (uint32_t)__cvta_generic_to_shared(p); }
__device__ __forceinline__ void mbar_init(uint32_t bar, uint32_t cnt) {
    asm volatile("mbarrier.init.shared::cta.b64 [%0], %1;" ::"r"(bar), "r"(cnt) : "memory");
}
__device__ __forceinline__ void mbar_arrive(uint32_t bar) {
    asm volatile("mbarrier.arrive.shared::cta.b64 _, [%0];" ::"r"(bar) : "memory");
}
__device__ __forceinline__ void mbar_expect_tx(uint32_t bar, uint32_t bytes) {
    asm volatile("mbarrier.arrive.expect_tx.shared::cta.b64 _, [%0], %1;" ::"r"(bar), "r"(bytes) : "memory");
}
__device__ __forceinline__ bool mbar_try(uint32_t bar, uint32_t par) {
    uint32_t ok;
    asm volatile("{\n.reg .pred p;\nmbarrier.try_wait.parity.shared::cta.b64 p, [%1], %2;\nselp.u32 %0, 1, 0, p;\n}\n"
                 : "=r"(ok) : "r"(bar), "r"(par) : "memory");
    return ok != 0;
}
__device__ __forceinline__ void mbar_wait(uint32_t bar, uint32_t par) {
    unsigned n = 0;
    while (!mbar_try(bar, par)) {
        if (++n > SPIN_LIMIT) __trap();
    }
}
__device__ __forceinline__ void mbar_wait_once(uint32_t bar, uint32_t par) {
    unsigned n = 0;
    bool ok;
#pragma unroll 1
    do {
        ok = mbar_try(bar, par);
        if (++n > SPIN_LIMIT) __trap();
    } while (!ok);
}
__device__ __forceinline__ bool elect_one() {
    uint32_t ok;
    asm volatile("{\n.reg .pred p;\nelect.sync _|p, 0xffffffff;\nselp.u32 %0, 1, 0, p;\n}\n" : "=r"(ok));
    return ok != 0;
}
__device__ __forceinline__ uint32_t opaque(uint32_t v) { return __shfl_sync(~0u, v, threadIdx.x & 31); }
__device__ __forceinline__ uint32_t lane_id() { uint32_t v; asm volatile("mov.u32 %0, %%laneid;" : "=r"(v)); return v; }
__device__ __forceinline__ uint32_t opaque_uniform(uint32_t v) { return __shfl_sync(~0u, v, 0); }
__device__ __forceinline__ void named_bar(int id, int n) { asm volatile("bar.sync %0, %1;" ::"r"(id), "r"(n) : "memory"); }
__device__ __forceinline__ void named_arrive(int id, int n) { asm volatile("bar.arrive %0, %1;" ::"r"(id), "r"(n) : "memory"); }
__device__ __forceinline__ void fence_async() { asm volatile("fence.proxy.async.shared::cta;" ::: "memory"); }
constexpr uint64_t EVICT_FIRST = 0x12F0000000000000ull;
__device__ __forceinline__ void tma_row(uint32_t dst, const CUtensorMap* tm, uint32_t bar, int x, int y) {
    asm volatile("cp.async.bulk.tensor.3d.shared::cluster.global.mbarrier::complete_tx::bytes.L2::cache_hint [%0], [%1, {%3, %4, %5}], [%2], %6;"
                 ::"r"(dst), "l"(tm), "r"(bar), "r"(0), "r"(x), "r"(y), "l"(EVICT_FIRST) : "memory");
}
__device__ __forceinline__ void bulk_load_stream(uint32_t dst, const void* src, uint32_t bytes, uint32_t bar) {
    asm volatile("cp.async.bulk.shared::cluster.global.mbarrier::complete_tx::bytes.L2::cache_hint [%0], [%1], %2, [%3], %4;"
                 ::"r"(dst), "l"(src), "r"(bytes), "r"(bar), "l"(EVICT_FIRST) : "memory");
}
__device__ __forceinline__ void prefetch_l2(const void* src, uint32_t bytes) {
    asm volatile("cp.async.bulk.prefetch.L2.global [%0], %1;" ::"l"(src), "r"(bytes) : "memory");
}
__device__ __forceinline__ void tma_2d(uint32_t dst, const CUtensorMap* tm, uint32_t bar, int x, int y) {
    asm volatile("cp.async.bulk.tensor.2d.shared::cluster.global.mbarrier::complete_tx::bytes [%0], [%1, {%3, %4}], [%2];"
                 ::"r"(dst), "l"(tm), "r"(bar), "r"(x), "r"(y) : "memory");
}
__device__ __forceinline__ void bulk_load(uint32_t dst, const void* src, uint32_t bytes, uint32_t bar) {
    asm volatile("cp.async.bulk.shared::cluster.global.mbarrier::complete_tx::bytes [%0], [%1], %2, [%3];"
                 ::"r"(dst), "l"(src), "r"(bytes), "r"(bar) : "memory");
}
__device__ __forceinline__ void wg_fence() { asm volatile("wgmma.fence.sync.aligned;" ::: "memory"); }
__device__ __forceinline__ void wg_commit() { asm volatile("wgmma.commit_group.sync.aligned;" ::: "memory"); }
template <int N> __device__ __forceinline__ void wg_wait() { asm volatile("wgmma.wait_group.sync.aligned %0;" ::"n"(N) : "memory"); }
template <int N> __device__ __forceinline__ void pin(uint32_t (&d)[N]) {
#pragma unroll
    for (int q = 0; q < N; q++) asm volatile("" : "+r"(d[q])::"memory");
}
__device__ __forceinline__ void stg128(void* p, const uint32_t (&v)[4]) {
    asm volatile("st.global.v4.u32 [%0], {%1, %2, %3, %4};" ::"l"(p), "r"(v[0]), "r"(v[1]), "r"(v[2]), "r"(v[3]) : "memory");
}
__device__ __forceinline__ void ldg128(uint32_t (&v)[4], const void* p) {
    asm volatile("ld.global.L1::no_allocate.v4.u32 {%0, %1, %2, %3}, [%4];" : "=r"(v[0]), "=r"(v[1]), "=r"(v[2]), "=r"(v[3]) : "l"(p) : "memory");
}
__device__ __forceinline__ void ldg128_if(bool on, uint32_t (&v)[4], const void* p) {
    asm volatile("{\n.reg .pred p;\nsetp.ne.b32 p, %5, 0;\n@p ld.global.L1::no_allocate.v4.u32 {%0, %1, %2, %3}, [%4];\n}\n"
                 : "+r"(v[0]), "+r"(v[1]), "+r"(v[2]), "+r"(v[3]) : "l"(p), "r"((int)on) : "memory");
}
__host__ __device__ constexpr uint64_t make_desc(uint32_t addr, uint32_t lbo, uint32_t sbo) {
    return (uint64_t)((addr & 0x3FFFF) >> 4) | ((uint64_t)(lbo >> 4) << 16) | ((uint64_t)(sbo >> 4) << 32);
}
__device__ __forceinline__ void wgmma(uint32_t (&d)[12], uint32_t a0, uint32_t a1, uint32_t a2, uint32_t a3, uint64_t db, int acc) {
    asm volatile("{\n.reg .pred p;\nsetp.ne.b32 p, %17, 0;\n"
                 "wgmma.mma_async.sync.aligned.m64n48k16.f16.f16.f16 "
                 "{%0, %1, %2, %3, %4, %5, %6, %7, %8, %9, %10, %11}, "
                 "{%12, %13, %14, %15}, %16, p, 1, 1, 0;\n}\n"
                 : "+r"(d[0]), "+r"(d[1]), "+r"(d[2]), "+r"(d[3]), "+r"(d[4]), "+r"(d[5]), "+r"(d[6]), "+r"(d[7]), "+r"(d[8]), "+r"(d[9]), "+r"(d[10]), "+r"(d[11])
                 : "r"(a0), "r"(a1), "r"(a2), "r"(a3), "l"(db), "r"(acc));
}
__device__ __forceinline__ void wgmma(uint32_t (&d)[24], uint32_t a0, uint32_t a1, uint32_t a2, uint32_t a3, uint64_t db, int acc) {
    asm volatile("{\n.reg .pred p;\nsetp.ne.b32 p, %29, 0;\n"
                 "wgmma.mma_async.sync.aligned.m64n96k16.f16.f16.f16 "
                 "{%0, %1, %2, %3, %4, %5, %6, %7, %8, %9, %10, %11, %12, %13, %14, %15, %16, %17, %18, %19, %20, %21, %22, %23}, "
                 "{%24, %25, %26, %27}, %28, p, 1, 1, 0;\n}\n"
                 : "+r"(d[0]), "+r"(d[1]), "+r"(d[2]), "+r"(d[3]), "+r"(d[4]), "+r"(d[5]), "+r"(d[6]), "+r"(d[7]), "+r"(d[8]), "+r"(d[9]), "+r"(d[10]), "+r"(d[11]), "+r"(d[12]), "+r"(d[13]), "+r"(d[14]), "+r"(d[15]), "+r"(d[16]), "+r"(d[17]), "+r"(d[18]), "+r"(d[19]), "+r"(d[20]), "+r"(d[21]), "+r"(d[22]), "+r"(d[23])
                 : "r"(a0), "r"(a1), "r"(a2), "r"(a3), "l"(db), "r"(acc));
}
template <int ACC>
__device__ __forceinline__ void wgmma_rowsum(float (&d)[4], const uint32_t (&a)[4], uint64_t ones) {
    asm volatile("{\n.reg .pred p;\nsetp.ne.b32 p, %9, 0;\n"
                 "wgmma.mma_async.sync.aligned.m64n8k16.f32.bf16.bf16 {%0, %1, %2, %3}, {%4, %5, %6, %7}, %8, p, 1, 1, 0;\n}\n"
                 : "+f"(d[0]), "+f"(d[1]), "+f"(d[2]), "+f"(d[3])
                 : "r"(a[0]), "r"(a[1]), "r"(a[2]), "r"(a[3]), "l"(ones), "n"(ACC));
}
__device__ __forceinline__ void ldsm4(uint32_t (&r)[4], uint32_t addr) {
    asm volatile("ldmatrix.sync.aligned.m8n8.x4.shared.b16 {%0, %1, %2, %3}, [%4];"
                 : "=r"(r[0]), "=r"(r[1]), "=r"(r[2]), "=r"(r[3]) : "r"(addr) : "memory");
}
__device__ __forceinline__ void ldsm4_t(uint32_t (&r)[4], uint32_t addr) {
    asm volatile("ldmatrix.sync.aligned.m8n8.x4.trans.shared.b16 {%0, %1, %2, %3}, [%4];"
                 : "=r"(r[0]), "=r"(r[1]), "=r"(r[2]), "=r"(r[3]) : "r"(addr) : "memory");
}
__device__ __forceinline__ void stsm4(uint32_t addr, uint32_t a, uint32_t b, uint32_t c, uint32_t d) {
    asm volatile("stmatrix.sync.aligned.m8n8.x4.shared.b16 [%0], {%1, %2, %3, %4};"
                 ::"r"(addr), "r"(a), "r"(b), "r"(c), "r"(d) : "memory");
}
__device__ __forceinline__ uint32_t transpose8x8(uint32_t v) {
    uint32_t d; asm volatile("movmatrix.sync.aligned.m8n8.trans.b16 %0, %1;" : "=r"(d) : "r"(v)); return d;
}
__device__ __forceinline__ void spin_until(const unsigned* counter, unsigned target) {
    unsigned n = 0, c;
    do {
        asm volatile("ld.acquire.gpu.global.u32 %0, [%1];" : "=r"(c) : "l"(counter) : "memory");
        if (++n > SPIN_LIMIT) __trap();
    } while ((int)(c - target) < 0);
}
__device__ __forceinline__ void signal(unsigned* counter) {
    __syncwarp();
    if (elect_one()) asm volatile("red.release.gpu.global.add.u32 [%0], 1;" ::"l"(counter) : "memory");
    __syncwarp();
}
__device__ __forceinline__ void lds128(uint32_t& a, uint32_t& b, uint32_t& c, uint32_t& d, uint32_t addr) {
    asm volatile("ld.shared.v4.u32 {%0, %1, %2, %3}, [%4];" : "=r"(a), "=r"(b), "=r"(c), "=r"(d) : "r"(addr) : "memory");
}
__device__ __forceinline__ void lds64(uint32_t& a, uint32_t& b, uint32_t addr) {
    asm volatile("ld.shared.v2.u32 {%0, %1}, [%2];" : "=r"(a), "=r"(b) : "r"(addr) : "memory");
}
__device__ __forceinline__ void lds32(uint32_t& a, uint32_t addr) {
    asm volatile("ld.shared.u32 %0, [%1];" : "=r"(a) : "r"(addr) : "memory");
}
__device__ __forceinline__ int ldsi(uint32_t addr) {
    uint32_t v;
    lds32(v, addr);
    return (int)v;
}
__device__ __forceinline__ float ldsf(uint32_t addr) {
    uint32_t v;
    lds32(v, addr);
    return __uint_as_float(v);
}
__device__ __forceinline__ void sts32(uint32_t addr, uint32_t a) {
    asm volatile("st.shared.u32 [%0], %1;" ::"r"(addr), "r"(a) : "memory");
}
__device__ __forceinline__ void sts128(uint32_t addr, uint32_t a, uint32_t b, uint32_t c, uint32_t d) {
    asm volatile("st.shared.v4.u32 [%0], {%1, %2, %3, %4};" ::"r"(addr), "r"(a), "r"(b), "r"(c), "r"(d) : "memory");
}
__device__ __forceinline__ void sts64(uint32_t addr, uint32_t a, uint32_t b) {
    asm volatile("st.shared.v2.u32 [%0], {%1, %2};" ::"r"(addr), "r"(a), "r"(b) : "memory");
}
__device__ __forceinline__ void anchor(uint32_t addr, uint32_t a, uint32_t b, uint32_t c, uint32_t d) {
    asm volatile("{\n.reg .pred p;\nsetp.eq.b32 p, %0, 0;\n@p st.shared.v4.u32 [%0], {%1, %2, %3, %4};\n}\n"
                 ::"r"(addr), "r"(a), "r"(b), "r"(c), "r"(d) : "memory");
}
__device__ __forceinline__ uint32_t bf_fma(uint32_t a, uint32_t b, uint32_t c) {
    uint32_t d; asm("fma.rn.bf16x2 %0, %1, %2, %3;" : "=r"(d) : "r"(a), "r"(b), "r"(c)); return d;
}
__device__ __forceinline__ uint32_t bf_mul(uint32_t a, uint32_t b) {
    uint32_t d; asm("mul.rn.bf16x2 %0, %1, %2;" : "=r"(d) : "r"(a), "r"(b)); return d;
}
__device__ __forceinline__ uint32_t bf_absmax(uint32_t a, uint32_t b) {
    uint32_t d; asm("max.xorsign.abs.bf16x2 %0, %1, %2;" : "=r"(d) : "r"(a), "r"(b)); return d;
}
__device__ __forceinline__ uint32_t h_fma(uint32_t a, uint32_t b, uint32_t c) {
    uint32_t d; asm("fma.rn.f16x2 %0, %1, %2, %3;" : "=r"(d) : "r"(a), "r"(b), "r"(c)); return d;
}
__device__ __forceinline__ uint32_t h_mul(uint32_t a, uint32_t b) {
    uint32_t d; asm("mul.rn.f16x2 %0, %1, %2;" : "=r"(d) : "r"(a), "r"(b)); return d;
}
__device__ __forceinline__ uint32_t h_cut8(uint32_t v) { return v & 0xfff8fff8u; }
constexpr float CUT_GAIN = 1.f + 0.4375f * 0.7213f / 128;
__device__ __forceinline__ uint32_t h_tanh(uint32_t a) {
    uint32_t d; asm("tanh.approx.f16x2 %0, %1;" : "=r"(d) : "r"(a)); return d;
}
__device__ __forceinline__ uint32_t pack_h2(float lo, float hi) {
    uint32_t d; asm("cvt.rn.f16x2.f32 %0, %1, %2;" : "=r"(d) : "f"(hi), "f"(lo)); return d;
}
__device__ __forceinline__ uint32_t pack_bf2(float lo, float hi) {
    uint32_t d; asm("cvt.rn.bf16x2.f32 %0, %1, %2;" : "=r"(d) : "f"(hi), "f"(lo)); return d;
}
__device__ __forceinline__ float bf_lo(uint32_t v) { return __uint_as_float(v << 16); }
__device__ __forceinline__ float bf_hi(uint32_t v) { return __uint_as_float(v & 0xffff0000u); }
__device__ __forceinline__ float h_lo(uint32_t v) { return __low2float(*reinterpret_cast<__half2*>(&v)); }
__device__ __forceinline__ float h_hi(uint32_t v) { return __high2float(*reinterpret_cast<__half2*>(&v)); }
__device__ __forceinline__ float warp_absmax(uint32_t v) {
    return __uint_as_float(__reduce_max_sync(~0u, max((v & 0x7fffu) << 16, v & 0x7fff0000u)));
}
__device__ __forceinline__ uint32_t gelu2(uint32_t z) {
    uint32_t p = h_fma(z, z, GELU_C2);
    uint32_t t = h_tanh(h_mul(z, p));
    return h_fma(z, t, z);
}
__device__ __forceinline__ float pow2i(int e) { return __uint_as_float((uint32_t)(e + 127) << 23); }
__device__ __forceinline__ int ilog2f(float v) {
    int e = (int)((__float_as_uint(v) >> 23) & 0xff) - 127;
    return max(-100, min(100, e));
}

__device__ __forceinline__ int bound_exp(float w1max) { return w1max > 0.f ? ilog2f(2.f * KZ * 96.f * w1max) : 0; }
__device__ __forceinline__ bool plain_squares(int e) { return (unsigned)(4 - e) <= 6; }
__device__ __forceinline__ int square_exp(int e) { return plain_squares(e) ? 0 : max(-14, min(4 - e, 14)); }
__device__ __forceinline__ int sum_exp(int e) { return max(-90, min(90, 33 - 2 * e)); }
__device__ __forceinline__ int row_exp(float m) { return 2 - ilog2f(m); }

struct Split {
    int per_cta, extra, period, inv_period, lenders;
    uint32_t lent_off[MAX_LENDERS * LENT];
    __host__ __device__ __forceinline__ int longer_before(int cta) const {
        const int n = (cta + period / 2) * inv_period >> 16;
        return n < extra ? n : extra;
    }
};
struct Work {
    int tA, tB, nA, nB, dir, rows, lent, index;
    __host__ __device__ __forceinline__ int tile(int j) const { return j < nA ? tA + dir * j : tB + dir * (j - nA); }
};
__host__ __device__ __forceinline__ Work get_work(int cta, const Split& sp) {
    Work w;
    const int before = sp.longer_before(cta), longer = sp.longer_before(cta + 1) - before;
    w.lent = longer && sp.lenders ? LENT : 0;
    w.index = longer ? before : cta - before;
    const int t0 = cta * sp.per_cta + before, t1 = t0 + sp.per_cta + longer;
    const int tm = t1 < (t0 | 511) + 1 ? t1 : (t0 | 511) + 1;
    const bool swap = t1 > tm && t1 - tm < tm - t0, down = cta & 1;
    w.nA = swap ? t1 - tm : tm - t0;
    w.nB = t1 - t0 - w.nA;
    w.tA = down ? (swap ? tm : t0) : (swap ? t1 : tm) - 1;
    w.tB = down ? (swap ? t0 : tm) : (swap ? tm : t1) - 1;
    w.dir = down ? 1 : -1;
    w.rows = w.nA + 2 + (w.nB ? w.nB + 2 : 0);
    return w;
}
__device__ __forceinline__ int row_code(const Work& w, int i) {
    const bool in_a = i < w.nA + 2;
    const int t = in_a ? w.tA : w.tB;
    return ((t & 511) + w.dir * ((in_a ? i : i - (w.nA + 2)) - 1)) << 16 | (t >> 9) * TILE_W;
}
__host__ __device__ __forceinline__ uint32_t tile_offset(int tile) { return ((tile & 511) * IMG_W + (tile >> 9) * TILE_W) * (CH * 2); }
__device__ __forceinline__ int tile_order(int j, int n) {
    return j % ORDER_P == ORDER_P - 1 ? j / ORDER_P : n - 1 - (j - j / ORDER_P);
}
__device__ __forceinline__ void issue_region(const CUtensorMap* tm, uint32_t dst, uint32_t bar, int warp, int code) {
    mbar_expect_tx(bar, REGION_BYTES);
    tma_row(dst, tm, bar, (code & 0xffff) + (16 * warp - 1), code >> 16);
}

template <class Event>
__device__ __forceinline__ void conv_producer(const Work& wk, const CUtensorMap* tm, uint32_t sb, int warp, Event event) {
    const int lane = threadIdx.x & 31;
    const int j = lane & 15, grp = lane >> 4;
    const uint32_t reg0 = sb + SM_RING + warp * REGION_BYTES;
    const uint32_t bars = sb + SM_BAR + warp * 8;
    if (warp * 32 + lane < MAX_ROWS) {
        const int i = warp * 32 + lane, before = min(i / 5, wk.lent);
        const bool back = i % 5 == 0 && i > 0 && i / 5 <= wk.lent;
        sts32(sb + SM_TILES + i * 4, back ? tile_offset(wk.tile(before - 1)) | before
                                          : tile_offset(wk.tile(wk.lent + tile_order(i - before, wk.nA + wk.nB - 4 - wk.lent))));
    }
    const uint32_t ld64 = opaque(reg0 + grp * 8 * 192 + j * 8), ld32 = opaque(reg0 + grp * 8 * 192 + 128 + j * 4);
    const uint32_t st64 = opaque(reg0 + grp * A_SBO + (j >> 1) * A_LBO + (j & 1) * 8);
    const uint32_t st32 = opaque(reg0 + grp * A_SBO + (8 + (j >> 2)) * A_LBO + (j & 3) * 4);
    named_bar(0, NTHREADS);
    uint32_t w[3][3][3];
    mbar_wait_once(sb + BAR_F, 0);
#pragma unroll
    for (int tap = 0; tap < 9; tap++) {
        const uint32_t p = sb + SM_FILTER + (3 + wk.dir * 3 * (tap / 3 - 1) + tap % 3) * (CH * 2);
        lds64(w[tap / 3][tap % 3][0], w[tap / 3][tap % 3][1], p + 8 * j);
        lds32(w[tap / 3][tap % 3][2], p + 128 + 4 * j);
    }
#pragma unroll
    for (int tap = 0; tap < 9; tap++) sts64(reg0 + (NSLOT - 1) * SLOT_BYTES + tap * 128 + j * 8, w[tap / 3][tap % 3][1], w[tap / 3][tap % 3][0]);
    named_bar(1, 128);
#pragma unroll
    for (int tap = 0; tap < 9; tap++) lds64(w[tap / 3][tap % 3][1], w[tap / 3][tap % 3][0], reg0 + (NSLOT - 1) * SLOT_BYTES + tap * 128 + j * 8);
    static_assert(2 * PREFETCH_ROWS == NSLOT && SLOT_BYTES % 32 == 0, "slot arithmetic");
    uint32_t bo = 0, par = 0, pbo = PREFETCH_ROWS * 32, ppar = 1;
    int px, py;
    auto request = [&]() {
        mbar_wait_once(bars + (BAR_E - SM_BAR) + pbo, ppar);
        if (elect_one()) {
            mbar_expect_tx(bars + pbo, REGION_BYTES);
            tma_row(reg0 + pbo * (SLOT_BYTES / 32), tm, bars + pbo, px, py);
        }
    };
    auto advance = [&]() {
        bo += 32;
        if (bo == NSLOT * 32) { bo = 0; par ^= 1; }
        pbo += 32;
        if (pbo == NSLOT * 32) { pbo = 0; ppar ^= 1; }
    };
    auto aim = [&](int row) {
        const int code = row_code(wk, row);
        px = (code & 0xffff) + (16 * warp - 1);
        py = code >> 16;
    };
    uint32_t accB[8][3], accC[8][3];
    int r = 0;
#pragma unroll 1
    while (r < wk.rows) {
        if (r == 0 || r == wk.nA + 2) {
            const uint32_t bo0 = bo;
            uint32_t bo1;
#pragma unroll 1
            for (int k = 0; k < 2; k++, r++) {
                mbar_wait_once(bars + bo, par);
                bo1 = bo;
                if (r >= 2) {
                    aim(r + PREFETCH_ROWS);
                    request();
                }
                advance();
            }
            const uint32_t so0 = bo0 * (SLOT_BYTES / 32), so1 = bo1 * (SLOT_BYTES / 32);
#pragma unroll
            for (int p = 0; p < 10; p++) {
                uint32_t u[3], v[3];
                lds64(u[0], u[1], so0 + ld64 + p * 192);
                lds32(u[2], so0 + ld32 + p * 192);
                lds64(v[0], v[1], so1 + ld64 + p * 192);
                lds32(v[2], so1 + ld32 + p * 192);
#pragma unroll
                for (int dx = 0; dx < 3; dx++) {
                    const int o = p - dx;
                    if (o < 0 || o > 7) continue;
#pragma unroll
                    for (int q = 0; q < 3; q++) {
                        accB[o][q] = bf_fma(v[q], w[1][dx][q], dx == 0 ? bf_mul(u[q], w[0][dx][q]) : bf_fma(u[q], w[0][dx][q], accB[o][q]));
                        accC[o][q] = dx == 0 ? bf_mul(v[q], w[0][dx][q]) : bf_fma(v[q], w[0][dx][q], accC[o][q]);
                    }
                }
            }
            anchor(ld64, accB[7][0], accB[7][1], accB[7][2], 0);
            __syncwarp();
            if (elect_one()) {
                mbar_arrive(bars + (BAR_A - SM_BAR) + bo0);
                mbar_arrive(bars + (BAR_E - SM_BAR) + bo0);
                mbar_arrive(bars + (BAR_A - SM_BAR) + bo1);
                mbar_arrive(bars + (BAR_E - SM_BAR) + bo1);
            }
        }
        int end = wk.rows;
        const int marks[4] = {wk.rows - PREFETCH_ROWS, wk.rows - 11, wk.nA + 2, wk.nA + 2 - PREFETCH_ROWS};
#pragma unroll
        for (int k = 0; k < 4; k++) end = marks[k] > r ? min(end, marks[k]) : end;
        const bool fetch = r < wk.rows - PREFETCH_ROWS;
        aim(r + PREFETCH_ROWS);
        px = opaque_uniform(px);
        const int py_end = opaque_uniform(py + wk.dir * (end - r));
        r = end;
#pragma unroll 1
        do {
            mbar_wait(bars + bo, par);
            const uint32_t so = bo * (SLOT_BYTES / 32);
            uint32_t out[8][3];
#pragma unroll
            for (int p = 0; p < 10; p++) {
                uint32_t xv[3];
                lds64(xv[0], xv[1], so + ld64 + p * 192);
                lds32(xv[2], so + ld32 + p * 192);
#pragma unroll
                for (int dx = 0; dx < 3; dx++) {
                    const int o = p - dx;
                    if (o < 0 || o > 7) continue;
#pragma unroll
                    for (int q = 0; q < 3; q++) {
                        out[o][q] = bf_fma(xv[q], w[2][dx][q], dx == 0 ? accB[o][q] : out[o][q]);
                        accB[o][q] = bf_fma(xv[q], w[1][dx][q], dx == 0 ? accC[o][q] : accB[o][q]);
                        accC[o][q] = dx == 0 ? bf_mul(xv[q], w[0][dx][q]) : bf_fma(xv[q], w[0][dx][q], accC[o][q]);
                    }
                }
            }
            __syncwarp();
#pragma unroll
            for (int o = 0; o < 8; o++) {
                sts64(so + st64 + o * 16, out[o][0], out[o][1]);
                sts32(so + st32 + o * 16, out[o][2]);
            }
            __syncwarp();
            if (elect_one()) mbar_arrive(bars + (BAR_A - SM_BAR) + bo);
            if (fetch) request();
            advance();
            py += wk.dir;
        } while (py != py_end);
        if (((wk.rows - r) & ~8) == PREFETCH_ROWS) event(wk.rows - r == PREFETCH_ROWS);
    }
}

template <bool SCALED, int K0 = 0, int K1 = 3>
__device__ __forceinline__ void gelu_sq(uint32_t (&d)[24], uint32_t (&keep)[24], uint32_t sq_addr, uint32_t scale2) {
    pin(d);
#pragma unroll
    for (int k = K0; k < K1; k++) {
        uint32_t hs[4];
        lds128(hs[0], hs[1], hs[2], hs[3], sq_addr + k * SQ_ROW);
#pragma unroll
        for (int q = 0; q < 4; q++) {
            uint32_t g0 = gelu2(d[8 * k + 2 * q]), g1 = gelu2(d[8 * k + 2 * q + 1]);
            keep[8 * k + 2 * q] = g0;
            keep[8 * k + 2 * q + 1] = g1;
            if (SCALED) { g0 = h_mul(g0, scale2); g1 = h_mul(g1, scale2); }
            hs[q] = h_fma(g1, g1, h_fma(g0, g0, hs[q]));
        }
        sts128(sq_addr + k * SQ_ROW, hs[0], hs[1], hs[2], hs[3]);
    }
}
__device__ __forceinline__ void gelu_sq_reg(uint32_t (&d)[24], uint32_t (&hs)[12]) {
    pin(d);
#pragma unroll
    for (int q = 0; q < 12; q++) {
        const uint32_t g0 = gelu2(d[2 * q]), g1 = gelu2(d[2 * q + 1]);
        hs[q] = h_fma(g1, g1, h_fma(g0, g0, hs[q]));
    }
}
__device__ __forceinline__ void gelu_to(uint32_t (&g)[12], uint32_t (&d)[12]) {
    pin(d);
#pragma unroll
    for (int q = 0; q < 12; q++) g[q] = gelu2(d[q]);
    pin(g);
}
__device__ __forceinline__ void load_tile(uint32_t (&raw)[6][4], uint32_t addr) {
#pragma unroll
    for (int s = 0; s < 6; s++) ldsm4(raw[s], addr + s * 2 * A_LBO);
}
template <class F>
__device__ __forceinline__ void layer_norm(uint32_t (&raw)[6][4], uint64_t ones, F meanwhile) {
    constexpr int NS = 2;
    uint32_t sq[NS][4];
#pragma unroll
    for (int s = 0; s < 6; s++)
#pragma unroll
        for (int q = 0; q < 4; q++) sq[s % NS][q] = s < NS ? bf_mul(raw[s][q], raw[s][q]) : bf_fma(raw[s][q], raw[s][q], sq[s % NS][q]);
    float sum[4], ssq[4];
    wg_fence();
    wgmma_rowsum<0>(sum, raw[0], ones);
#pragma unroll
    for (int s = 1; s < 6; s++) wgmma_rowsum<1>(sum, raw[s], ones);
    wgmma_rowsum<0>(ssq, sq[0], ones);
#pragma unroll
    for (int s = 1; s < NS; s++) wgmma_rowsum<1>(ssq, sq[s], ones);
    wg_commit();
    meanwhile();
    wg_wait<0>();
    uint32_t sc[2], sh[2];
#pragma unroll
    for (int h = 0; h < 2; h++) {
        asm volatile("" : "+f"(sum[2 * h]), "+f"(ssq[2 * h])::"memory");
        constexpr float EPS = 1e-5f / (KZ * KZ);
        const float m = sum[2 * h] * (1.f / (CH * KZ));
        float rstd;
        asm("rsqrt.approx.ftz.f32 %0, %1;" : "=f"(rstd) : "f"(fmaxf(fmaf(-m, m, fmaf(ssq[2 * h], 1.f / (CH * KZ * KZ), EPS)), EPS)));
        sc[h] = pack_bf2(rstd, rstd);
        const float shift = sum[2 * h] * (-1.f / CH) * bf_hi(sc[h]);
        sh[h] = pack_bf2(shift, shift);
    }
#pragma unroll
    for (int s = 0; s < 6; s++)
#pragma unroll
        for (int q = 0; q < 4; q++) {
            const uint32_t v = bf_fma(raw[s][q], sc[q & 1], sh[q & 1]);
            raw[s][q] = pack_h2(bf_lo(v), bf_hi(v));
        }
}
struct Cursor {
    int slot;
    uint32_t par;
    __device__ __forceinline__ void advance(int n) {
        slot += n;
        if (slot >= NSLOT) { slot -= NSLOT; par ^= 1; }
    }
};
struct Descs {
    uint64_t w1[8][6];
    uint64_t w2[24];
    uint64_t ones;
};
template <int E0, int N>
__device__ __forceinline__ void gemm1_chunk(uint32_t (&d)[N], const uint32_t (&a)[6][4], const Descs& ds, int zero) {
#pragma unroll
    for (int s = 0; s < 6; s++) wgmma(d, a[s][0], a[s][1], a[s][2], a[s][3], ds.w1[E0 / 48][s], s ? 1 : zero);
}
template <int E0, int N>
__device__ __forceinline__ void gemm2_chunk(uint32_t (&acc)[24], const uint32_t (&g)[N], const Descs& ds) {
#pragma unroll
    for (int s = 0; s < N / 4; s++) wgmma(acc, g[4 * s], g[4 * s + 1], g[4 * s + 2], g[4 * s + 3], ds.w2[E0 / 16 + s], 1);
}

struct __align__(64) Params {
    Split sp;
    int zero;
    const __nv_bfloat16 *x, *dw, *w2, *gamma, *beta;
    __nv_bfloat16* out;
    Scratch* sc;
    Descs ds;
};

__global__ void __launch_bounds__(NTHREADS, 1)
block_kernel(const __grid_constant__ CUtensorMap tmap, const __grid_constant__ CUtensorMap tmap_w1, const __grid_constant__ Params pm) {
    const Split& sp = pm.sp;
    const Descs& ds = pm.ds;
    const int& zero = pm.zero;
    const __nv_bfloat16 *const &x = pm.x, *const &dw = pm.dw, *const &w2 = pm.w2, *const &gamma = pm.gamma, *const &beta = pm.beta;
    __nv_bfloat16* const& out = pm.out;
    Scratch* const& sc = pm.sc;
    extern __shared__ __align__(1024) uint8_t smem[];
    constexpr uint32_t sb = SB;
    const int tid = threadIdx.x;
    const Work wk = get_work(blockIdx.x, sp);
    constexpr uint32_t s_red = sb + SM_RED;
    if (smem_u32(smem) != SB) __trap();

    const int warp_id = __shfl_sync(~0u, tid >> 5, 0);
    PROF(0);
    const int cw = warp_id - 4, wgi = cw >> 2, w4 = warp_id & 3;
    if (elect_one()) {
        static_assert(3 * NSLOT * 4 == 8 + 4 * 16 && BAR_F == BAR_W + 48, "barrier shares");
        const int b = warp_id - 8;
        const uint32_t bar = b < 0 ? sb + BAR_X + warp_id * 8 : b < 7 ? sb + BAR_W + b * 8 : sb + BAR_PIN;
        mbar_init(bar, 1);
#pragma unroll
        for (int k = 0; k < 4; k++) mbar_init(sb + BAR_X + (8 + 4 * warp_id + k) * 8, 1);
        mbar_init(sb + BAR_R + warp_id * 8, 1);
        fence_async();
        if (b < 0) {
            issue_region(&tmap, sb + SM_RING + warp_id * REGION_BYTES, bar, w4, ((wk.tA & 511) + wk.dir * wgi) << 16 | (wk.tA >> 9) * TILE_W);
        } else if (b < 6) {
            mbar_expect_tx(bar, 64 * CH * 2);
            tma_2d(sb + SM_W2 + b * (64 * CH * 2), &tmap_w1, bar, 64 * b, 0);
        } else if (b == 6) {
            mbar_expect_tx(bar, 9 * CH * 2);
            bulk_load(sb + SM_FILTER, dw, 9 * CH * 2, bar);
        }
    }
    __syncwarp();
    const int ntiles = wk.nA + wk.nB;
    const int rank = (wgi + wk.lent + 2 * (ntiles - 1)) % NCONS | (wgi >> 2 & 3);
    const int spare = wk.rows % NSLOT, spare2 = spare == NSLOT - 1 ? 0 : spare + 1;
    const uint32_t sq_base = sb + (wgi < 0 ? SM_RING + spare * SLOT_BYTES : SM_SQ + rank * 2 * SQ_HALF);
    const uint32_t sq_upper = wgi < 0 ? (spare2 - spare) * SLOT_BYTES : SQ_HALF;
    const uint32_t bar_a = sb + BAR_A + w4 * 8, bar_e = sb + BAR_E + w4 * 8;
    const bool prepares = gridDim.x - blockIdx.x <= W2_GROUPS / 2, helps = !wk.lent && wk.index < 8 * LENT * sp.lenders;
    auto max_w1 = [&](uint32_t lane) { return __uint_as_float(__reduce_max_sync(~0u, lane < 4 * NCONS ? ldsi(s_red + RED_MAX + lane * 4) : 0)); };
    auto square_scale = [&](uint32_t lane) {
        const float f = pow2i(square_exp(bound_exp(max_w1(lane))));
        return pack_h2(f, f);
    };
    uint32_t a_addr, sq;
    const uint32_t sq_warp = sq_base + w4 * 512;
    auto set_addresses = [&]() {
        a_addr = opaque(sb + SM_RING + w4 * REGION_BYTES + ((tid >> 3) & 1) * A_SBO + ((tid >> 4) & 1) * A_LBO + (tid & 7) * 16);
        sq = opaque(sq_base + (tid & 127) * 16);
    };
    uint32_t turn, turn_end, so, so_sum, bo, bo_sum, off;
    auto set_run = [&](int j, int stop, int row) {
        const int slot = row % NSLOT, both = 2 * (row % 3) + 3;
        turn = opaque_uniform(row / 3);
        turn_end = opaque_uniform(row / 3 + (stop - j + NCONS - 1) / NCONS);
        so = opaque_uniform(slot * SLOT_BYTES);
        so_sum = opaque_uniform(both * SLOT_BYTES);
        bo = opaque_uniform(bar_a + slot * 32);
        bo_sum = opaque_uniform(2 * bar_a + both * 32);
        off = opaque_uniform(tile_offset(wk.tile(j)) + w4 * WARP_BYTES - sq_warp);
    };
    const int nrest = ntiles - 4;
    int jt;
    Cursor cur;
    int fast_from;
    if (warp_id < 4) {
        const int q = (gridDim.x - 1 - blockIdx.x) * 2 + (w4 >> 1);
        conv_producer(wk, &tmap, sb, warp_id, [&](bool second) {
            if (!second) {
                if (blockIdx.x == 0) {
#pragma unroll 1
                    for (int e = tid; e < EX; e += 128) *sc->sum(e) = 0;
                    sc->bias[tid] = 0.f;
                }
                if (blockIdx.x == 0 || wk.lent) signal(&sc->early);
            } else if (prepares || helps) {
                spin_until(&sc->early, (ldsi(s_red + RED_LAUNCH) + 1) * 4 * (sp.lenders + 1));
                if (elect_one()) {
                    if (helps) prefetch_l2(reinterpret_cast<const char*>(out) + sp.lent_off[wk.index / 8] + w4 * WARP_BYTES, WARP_BYTES);
                    if (prepares) { prefetch_l2(w2 + 8 * q * CH, 8 * CH * 2); prefetch_l2(beta + 8 * q, 16); }
                }
            }
        });
        set_addresses();
        const int lane = lane_id(), g = lane >> 2, t = lane & 3;
        const int piece = wk.index;
        uint32_t a[6][4];
        unsigned short bt_raw;
        if (prepares) {
#pragma unroll
            for (int m = 0; m < 3; m++) ldg128(a[m], w2 + (8 * q + g) * CH + 32 * m + 8 * t);
            asm volatile("ld.global.nc.u16 %0, [%1];" : "=h"(bt_raw) : "l"(beta + 8 * q + g) : "memory");
        } else if (helps) {
#pragma unroll
            for (int s = 0; s < 6; s++) ldg128(a[s], reinterpret_cast<const char*>(out) + sp.lent_off[piece / 8] + w4 * WARP_BYTES + lane * 16 + s * 512);
        }
        mbar_wait_once(bar_e + spare2 * 32, (wk.rows - 5) / NSLOT & 1);
        mbar_wait_once(bar_e + spare * 32, (wk.rows - 6) / NSLOT & 1);
        named_bar(1, 128);
#pragma unroll
        for (int k = 0; k < 6; k++) { sts128(sq + k * SQ_ROW, 0, 0, 0, 0); sts128(sq + sq_upper + k * SQ_ROW, 0, 0, 0, 0); }
        if (prepares) {
            const int half = w4 & 1;
            uint32_t rmax = 0;
#pragma unroll
            for (int m = 0; m < 3; m++) rmax = bf_absmax(bf_absmax(rmax, bf_absmax(a[m][0], a[m][1])), bf_absmax(a[m][2], a[m][3]));
            uint2 u = half ? make_uint2(a[0][2], a[0][3]) : make_uint2(a[0][0], a[0][1]), u1 = half ? make_uint2(a[1][2], a[1][3]) : make_uint2(a[1][0], a[1][1]);
            const uint2 u2 = half ? make_uint2(a[2][2], a[2][3]) : make_uint2(a[2][0], a[2][1]);
            const float bt = bf_lo(bt_raw);
            rmax = bf_absmax(rmax, __shfl_xor_sync(~0u, rmax, 1));
            rmax = bf_absmax(rmax, __shfl_xor_sync(~0u, rmax, 2));
            const float mx = fmaxf(fabsf(bf_lo(rmax)), fabsf(bf_hi(rmax))), rs = pow2i(row_exp(mx));
            if (t == 0 && !half) sc->w2max[8 * q + g] = mx;
#pragma unroll 1
            for (int m = 0; m < 3; m++, u = u1, u1 = u2) {
                float f[4];
#pragma unroll
                for (int k = 0; k < 2; k++) {
                    const float lo = bf_lo(k ? u.y : u.x), hi = bf_hi(k ? u.y : u.x);
                    sc->w2h[(4 * m + 2 * half + k) * 1536 + q * 32 + lane] = transpose8x8(pack_h2(lo * rs, hi * rs));
                    f[2 * k] = lo * bt;
                    f[2 * k + 1] = hi * bt;
                }
                const float r0 = (g & 2 ? f[2] : f[0]) + __shfl_xor_sync(~0u, g & 2 ? f[0] : f[2], 8);
                const float r1 = (g & 2 ? f[3] : f[1]) + __shfl_xor_sync(~0u, g & 2 ? f[1] : f[3], 8);
                float r = (g & 1 ? r1 : r0) + __shfl_xor_sync(~0u, g & 1 ? r0 : r1, 4);
                r += __shfl_xor_sync(~0u, r, 16);
                if (g < 4) atomicAdd(&sc->bias[32 * m + 8 * t + 4 * half + g], r);
            }
            asm volatile("fence.proxy.async.global;" ::: "memory");
            __syncwarp();
            named_arrive(3, 256);
        } else
        if (helps) {
            uint32_t d[12], gl[12];
            const uint32_t scale2 = square_scale(lane);
            wg_fence();
#pragma unroll
            for (int s = 0; s < 6; s++) wgmma(d, a[s][0], a[s][1], a[s][2], a[s][3], ds.w1[0][s] + piece % 8 * (6 * 1536 / 16), s ? 1 : 0);
            wg_commit();
            wg_wait<0>();
            gelu_to(gl, d);
#pragma unroll
            for (int s = 0; s < 3; s++) {
                sc->lent[((piece / 8 * 4 + w4) * 24 + piece % 8 * 3 + s) * 32 + lane] = make_uint4(gl[4 * s], gl[4 * s + 1], gl[4 * s + 2], gl[4 * s + 3]);
                uint32_t hs[2];
#pragma unroll
                for (int k = 0; k < 2; k++) {
                    const uint32_t g0 = h_mul(gl[4 * s + 2 * k], scale2), g1 = h_mul(gl[4 * s + 2 * k + 1], scale2);
                    hs[k] = h_fma(g1, g1, h_mul(g0, g0));
                }
                const int pair = piece % 4 * 3 + s;
                sts64(sq + (piece & 4 ? sq_upper : 0) + (pair >> 1) * SQ_ROW + (pair & 1) * 8, hs[0], hs[1]);
            }
        }
        jt = ntiles - 1;
        cur.slot = spare ? spare - 1 : NSLOT - 1;
        cur.par = (wk.rows - 1) / NSLOT & 1;
        fast_from = ntiles;
        turn = turn_end = so = so_sum = bo = bo_sum = off = rank;
    } else {
        set_addresses();
        if (wgi == NCONS - 1) named_arrive(4, 256);
        set_run(wk.lent + wgi, min(wk.nA, nrest), wk.lent + wgi + 2);
        jt = wgi < wk.lent ? wgi : wk.lent + wgi;
        cur = {2, 0};
        cur.advance(jt + (jt >= wk.nA ? 2 : 0));
        {
            const int ct = tid - 128, lane = tid & 31;
            const unsigned epoch = *reinterpret_cast<volatile unsigned*>(&sc->launch);
            const int r = lane & 7, mi = lane >> 3;
            const uint32_t src = sb + SM_W2 + (cw >> 1) * (64 * CH * 2) + r * 128 + ((((cw & 1) * 4 + mi) ^ r) * 16);
            const uint32_t dst = sb + SM_W1 + (4 * cw + mi) * 1536 + r * 16;
            const int code = row_code(wk, PREFETCH_ROWS - 1 + wgi);
            named_bar(0, NTHREADS);
            auto request = [&]() {
                if (elect_one())
                    issue_region(&tmap, sb + SM_RING + (PREFETCH_ROWS - 1 + wgi) * SLOT_BYTES + w4 * REGION_BYTES, sb + BAR_X + (cw + 8) * 8, w4, code);
                __syncwarp();
            };
#pragma unroll 1
            for (int k = 0; k < 2; k++) {
                if (wgi == k) request();
                mbar_wait_once(sb + BAR_W + (cw >> 1) * 8, 0);
            }
            uint32_t wmax[2] = {}, wsum[4] = {};
#pragma unroll 3
            for (int c = 0; c < 12; c++) {
                uint32_t u[4];
                ldsm4_t(u, src + c * 1024);
#pragma unroll
                for (int q = 0; q < 4; q++) {
                    wmax[q & 1] = bf_absmax(wmax[q & 1], u[q]);
                    wsum[q] = bf_fma(u[q], 0x3f803f80u, wsum[q]);
                    u[q] = pack_h2(__uint_as_float(u[q] * (65536 + zero)), bf_hi(u[q]));
                }
                stsm4(dst + c * 128, u[0], u[1], u[2], u[3]);
            }
            const float w1max = warp_absmax(bf_absmax(wmax[0], wmax[1]));
            if (lane == 0) sts32(s_red + RED_MAX + cw * 4, __float_as_uint(w1max));
            bool center = false;
#pragma unroll
            for (int q = 0; q < 4; q++) {
#pragma unroll
                for (int o = 1; o <= 2; o <<= 1) wsum[q] = bf_fma(__shfl_xor_sync(~0u, wsum[q], o), 0x3f803f80u, wsum[q]);
                center |= fabsf(bf_lo(wsum[q]) + bf_hi(wsum[q])) > (0.15f * CH) * w1max;
            }
            if (__builtin_expect(__any_sync(~0u, center), 0)) {
                float mean[4] = {};
#pragma unroll 1
                for (int pass = 0; pass < 2; pass++) {
                    float sum[4] = {};
#pragma unroll 1
                    for (int c = 0; c < 12; c++) {
                        uint32_t u[4];
                        ldsm4_t(u, src + c * 1024);
#pragma unroll
                        for (int q = 0; q < 4; q++) {
                            sum[q] += bf_lo(u[q]) + bf_hi(u[q]);
                            u[q] = pack_h2(bf_lo(u[q]) - mean[q], bf_hi(u[q]) - mean[q]);
                        }
                        stsm4(dst + c * 128, u[0], u[1], u[2], u[3]);
                    }
#pragma unroll
                    for (int q = 0; q < 4; q++) {
                        sum[q] += __shfl_xor_sync(~0u, sum[q], 1);
                        sum[q] += __shfl_xor_sync(~0u, sum[q], 2);
                        mean[q] = sum[q] * (1.f / CH);
                    }
                }
            }
            if (!(cw & 2)) {
#pragma unroll
                for (int c = 0; c < 12; c++) sts128(src + c * 1024, 0, 0, 0, 0);
            }
            if (ct < 32) sts32(sb + SM_ONES + ct * 4, 0x3f803f80u);
            if (ct == 0) sts32(s_red + RED_LAUNCH, epoch);
            fence_async();
            named_bar(2, CONS_THREADS);
            if (wgi == 2) request();
        }
        PROF(1);
        if (cur.par) mbar_wait_once(bar_a, 0);
        fast_from = wk.lent;
        if (!__all_sync(~0u, plain_squares(bound_exp(max_w1(lane_id()))))) {
            fast_from = ntiles;
#pragma unroll 1
            for (int q = 0; q < 6; q++) sts128(sq + SQ_HALF + q * SQ_ROW, 0, 0, 0, 0);
        }
    }
    uint32_t k1[24], k2[24], k3[24];
    uint32_t here;
    constexpr int SQC = 3 * SQ_ROW;
    auto store_at = [&](const uint32_t (&a)[6][4], uint32_t off) {
        char* ap = reinterpret_cast<char*>(out) + (off + sq);
#pragma unroll
        for (int s = 0; s < 6; s++) stg128(ap + s * 512, a[s]);
    };
    const uint32_t own_bar = 4 + wgi, next_bar = 4 + (wgi == NCONS - 1 ? 0 : wgi + 1);
    for (;;) {
        if (jt >= fast_from) {
            uint32_t hs2[12] = {}, hs3[12] = {};
            const uint32_t step = wk.dir * (NCONS * IMG_W * CH * 2);
            int second = wk.nB;
#pragma unroll 1
            for (;;) {
#pragma unroll 1
                while (turn != turn_end) {
                    uint32_t a[6][4], d0[24], d1[24], unused[24];
                    mbar_wait(bo, turn >> 1 & 1);
                    load_tile(a, a_addr + so);
                    layer_norm(a, ds.ones, [&]() { named_bar(own_bar, 256); });
                    wg_fence();
                    gemm1_chunk<0>(d0, a, ds, 0);
                    wg_commit();
                    gemm1_chunk<96>(d1, a, ds, 0);
                    wg_commit();
                    wg_wait<1>();
                    gelu_sq<false, 0, 1>(d0, unused, sq, 0);
                    gelu_sq<false, 1, 2>(d0, unused, sq, 0);
                    store_at(a, off);
                    gelu_sq<false, 2, 3>(d0, unused, sq, 0);
                    if (elect_one()) mbar_arrive(bo + (BAR_E - BAR_A));
                    wg_fence();
                    gemm1_chunk<192>(d0, a, ds, zero);
                    wg_commit();
                    named_arrive(next_bar, 256);
                    wg_wait<1>();
                    gelu_sq<false, 0, 1>(d1, unused, sq + SQC, 0);
                    gelu_sq<false, 1, 3>(d1, unused, sq + SQC, 0);
                    wg_fence();
                    gemm1_chunk<288>(d1, a, ds, zero);
                    wg_commit();
                    wg_wait<1>();
                    gelu_sq_reg(d0, hs2);
                    anchor(sq, hs2[8], hs2[9], hs2[10], hs2[11]);
                    wg_wait<0>();
                    gelu_sq_reg(d1, hs3);
                    so = so_sum - so;
                    bo = bo_sum - bo;
                    off += step;
                    turn++;
                }
                if (!second) break;
                const int j = ntiles - second + (rank + second + 2) % NCONS;
                second = 0;
                set_run(j, nrest, j + 4);
            }
            jt = nrest + rank;
            cur.slot = (bo - bar_a) >> 5;
            cur.par = turn >> 1 & 1;
#pragma unroll
            for (int k = 0; k < 3; k++) {
                sts128(sq + SQ_HALF + k * SQ_ROW, hs2[4 * k], hs2[4 * k + 1], hs2[4 * k + 2], hs2[4 * k + 3]);
                sts128(sq + SQ_HALF + SQC + k * SQ_ROW, hs3[4 * k], hs3[4 * k + 1], hs3[4 * k + 2], hs3[4 * k + 3]);
            }
        }
        const bool last = jt >= nrest;
        here = tile_offset(wk.tile(jt));
        if (last) {
            const uint32_t next = ldsi(sb + SM_TILES + rank * 4);
            if (elect_one()) {
                prefetch_l2(reinterpret_cast<const char*>(x) + here + w4 * WARP_BYTES, WARP_BYTES);
                if (rank == ORDER_P - 1) prefetch_l2(reinterpret_cast<const char*>(out) + next + w4 * WARP_BYTES, WARP_BYTES);
            }
        }
        uint32_t a[6][4], d0[24], d1[24], d3[24], k0[24];
        mbar_wait_once(bar_a + cur.slot * 32, cur.par);
        load_tile(a, a_addr + cur.slot * SLOT_BYTES);
        layer_norm(a, ds.ones, [&]() { if (jt >= wk.lent && wgi >= 0) named_bar(own_bar, 256); });
        if (!last) {
            store_at(a, here + w4 * WARP_BYTES - sq_warp);
            __syncwarp();
            if (elect_one()) mbar_arrive(bar_e + cur.slot * 32);
            if (jt < wk.lent) {
                jt += LENT;
                cur.advance(LENT);
                continue;
            }
        }
        wg_fence();
        gemm1_chunk<0>(d0, a, ds, 0);
        wg_commit();
        gemm1_chunk<96>(d1, a, ds, 0);
        wg_commit();
        const uint32_t scale2 = square_scale(lane_id());
        wg_wait<1>();
        gelu_sq<true>(d0, k0, sq, scale2);
        if (last) {
#pragma unroll
            for (int q = 0; q < 6; q++)
                sts128(sb + SM_RING + cur.slot * SLOT_BYTES + w4 * REGION_BYTES - sq_warp + sq + q * 512, k0[4 * q], k0[4 * q + 1], k0[4 * q + 2], k0[4 * q + 3]);
        }
        wg_fence();
        gemm1_chunk<192>(d0, a, ds, zero);
        wg_commit();
        if (jt + 2 < ntiles) named_arrive(next_bar, 256);
        wg_wait<1>();
        gelu_sq<true>(d1, k1, sq + SQC, scale2);
        wg_fence();
        gemm1_chunk<288>(d3, a, ds, 0);
        wg_commit();
        wg_wait<1>();
        gelu_sq<true>(d0, k2, sq + sq_upper, scale2);
        wg_wait<0>();
        gelu_sq<true>(d3, k3, sq + sq_upper + SQC, scale2);
        if (last) break;
        cur.advance(NCONS + ((jt < wk.nA && jt + NCONS >= wk.nA) ? 2 : 0));
        jt += NCONS;
    }
    const uint32_t lane = lane_id();
    uint32_t next_off = opaque_uniform(ldsi(sb + SM_TILES + rank * 4));
    const uint32_t s_fac = sb + SM_RING + spare * SLOT_BYTES + SQ_HALF;
    uint32_t inv_rho2;
    {
        const bool leader = rank == 0 && w4 == 0 && lane == 0;
        const int i0 = w4 * 32 + lane;
        float base[3], slope[3], reach[3], to_square;
        float2 bpair = make_float2(0.f, 0.f);
        unsigned epoch;
        if (rank == 0) {
            float gam[3], rmax[3];
#pragma unroll
            for (int m = 0; m < 3; m++) {
                unsigned short v;
                asm volatile("ld.global.nc.u16 %0, [%1];" : "=h"(v) : "l"(gamma + i0 + 128 * m) : "memory");
                gam[m] = bf_lo(v);
            }
            epoch = ldsi(s_red + RED_LAUNCH);
            if (prepares) {
                named_bar(3, 256);
                if (w4 == 1) signal(&sc->prep);
            }
            if (leader) {
                spin_until(&sc->prep, (epoch + 1) * (W2_GROUPS / 2));
                asm volatile("fence.proxy.async.global;" ::: "memory");
            }
            __syncwarp();
            named_bar(2, 128);
#pragma unroll
            for (int m = 0; m < 3; m++) rmax[m] = __ldcg(&sc->w2max[i0 + 128 * m]);
            if (i0 < 96) bpair = __ldcg(reinterpret_cast<const float2*>(&sc->bias[32 * (i0 % 24 >> 3) + 8 * (i0 / 24) + (i0 % 24 & 6)]));
            const float w1max = max_w1(lane);
            const float gbound = fmaxf(2.f * KZ * 9.7979590f * 192.f * w1max, 1.f) * 19.5959180f * INV_2KZ;
            const unsigned fixed = __reduce_max_sync(~0u, __float_as_uint(fmaf(gbound, fmaxf(fmaxf(rmax[0], rmax[1]), rmax[2]), fmaxf(fabsf(bpair.x), fabsf(bpair.y)))));
            if (lane == 0) sts32(s_red + 96 + w4 * 4, fixed);
#pragma unroll
            for (int m = 0; m < 3; m++) {
                base[m] = rmax[m] > 0.f ? pow2i(-row_exp(rmax[m])) * (INV_2KZ * CUT_GAIN) : 0.f;
                slope[m] = base[m] * gam[m];
                reach[m] = fabsf(gam[m]) * rmax[m] * gbound;
            }
            to_square = pow2i(-sum_exp(bound_exp(w1max))) * (INV_2KZ * INV_2KZ / 256);
        }
        if (rank >= 2) {
            named_arrive(12 + rank, CONS_THREADS);
        } else {
            const int rw = rank * 4 + w4, g = lane >> 2, t = lane & 3;
            const uint32_t pick = (g & 1) == (t & 1) ? (g & 2 ? 0x3c000000u : 0x00003c00u) : 0;
            const int be = bound_exp(max_w1(lane));
            const float to_fixed = pow2i(sum_exp(be) - 2 * square_exp(be));
            unsigned long long* dst = sc->sum(64 * rw + 32 * (t >> 1) + 8 * (g >> 1) + 2 * (t & 1) + (g & 1));
            const uint32_t rows = sb + (rw * 2 + (lane >> 3 & 1)) * SQ_ROW + ((lane >> 4) * 8 + (lane & 7)) * 16;
            float f[2][4] = {};
            named_bar(13, 256);
#pragma unroll 1
            for (int i = 0; i < 4; i++) {
                if (i == 2) {
                    named_bar(13, 256);
                    if (leader) {
                        fence_async();
                        mbar_expect_tx(sb + BAR_W, 4 * SQ_HALF);
                        bulk_load(sb + SM_W2, sc->w2h, 4 * SQ_HALF, sb + BAR_W);
                    }
                    __syncwarp();
                }
                const uint32_t src = rows + (i < NCONS ? SM_SQ + i * 2 * SQ_HALF : rw < 3 ? SM_RING + spare * SLOT_BYTES : SM_RING + spare2 * SLOT_BYTES - SQ_HALF);
                if (i >= 2) named_bar(12 + i, CONS_THREADS);
                if (rw < 6) {
#pragma unroll
                    for (int r = 0; r < 8; r++) {
                        uint32_t u[4];
                        ldsm4_t(u, src + r * 256);
                        asm volatile("mma.sync.aligned.m16n8k16.row.col.f32.f16.f16.f32 {%0, %1, %2, %3}, {%4, %5, %6, %7}, {%8, %8}, {%0, %1, %2, %3};"
                                     : "+f"(f[r & 1][0]), "+f"(f[r & 1][1]), "+f"(f[r & 1][2]), "+f"(f[r & 1][3])
                                     : "r"(u[0]), "r"(u[1]), "r"(u[2]), "r"(u[3]), "r"(pick));
                    }
                }
            }
            if (rw < 6) {
#pragma unroll
                for (int r = 0; r < 2; r++)
                    atomicAdd(dst + r * 32, __float2ull_rn(fminf((t < 2 ? f[0][r] + f[1][r] : f[0][r + 2] + f[1][r + 2]) * to_fixed, 0x1p47f)) << 8 | 1);
            }
            PROF(2);
            named_bar(13, 256);
            if (leader) {
                fence_async();
                mbar_expect_tx(sb + BAR_W + 8, 2 * SQ_HALF);
                bulk_load(sb + SM_W2 + 4 * SQ_HALF, reinterpret_cast<const char*>(sc->w2h) + 4 * SQ_HALF, 2 * SQ_HALF, sb + BAR_W + 8);
            }
            if (helps && rw == 7) signal(&sc->lent_out);
        }
        if (rank == 0) {
            const uint32_t own_sum = (i0 >> 2) * 256 + (i0 & 3) * 8, own_fac = s_fac + i0 * 2;
            auto peek = [&](const void* p) {
                unsigned long long v;
                asm volatile("ld.relaxed.gpu.global.u64 %0, [%1];" : "=l"(v) : "l"(p) : "memory");
                return v;
            };
            const char* mine = reinterpret_cast<const char*>(sc->sums) + own_sum;
            unsigned n = 0;
            while (((unsigned)peek(sc->sum((blockIdx.x * 4 + w4) % (EX / 4) * 4)) & 255u) != gridDim.x)
                if (++n > SPIN_LIMIT) __trap();
            unsigned long long sum[3];
            for (;;) {
                bool all = true;
#pragma unroll
                for (int m = 0; m < 3; m++) {
                    sum[m] = peek(mine + m * (32 * 256));
                    all &= ((unsigned)sum[m] & 255u) == gridDim.x;
                }
                if (__all_sync(~0u, all)) break;
                if (++n > SPIN_LIMIT) __trap();
            }
            PROF(3);
            float gx[3];
#pragma unroll
            for (int m = 0; m < 3; m++) asm("sqrt.approx.ftz.f32 %0, %1;" : "=f"(gx[m]) : "f"(fmaf(__ull2float_rn(sum[m]), to_square, 1e-6f)));
            float tot = gx[0] + gx[1] + gx[2];
#pragma unroll
            for (int o = 16; o >= 1; o >>= 1) tot += __shfl_xor_sync(~0u, tot, o);
            const unsigned vwarp = __reduce_max_sync(~0u, __float_as_uint(fmaxf(fmaxf(reach[0] * gx[0], reach[1] * gx[1]), reach[2] * gx[2])));
            if (lane == 0) { sts32(s_red + 64 + w4 * 4, __float_as_uint(tot)); sts32(s_red + 80 + w4 * 4, vwarp); }
            named_bar(2, 128);
            uint32_t u[4], v[4], w[4];
            lds128(u[0], u[1], u[2], u[3], s_red + 64);
            lds128(v[0], v[1], v[2], v[3], s_red + 80);
            lds128(w[0], w[1], w[2], w[3], s_red + 96);
            tot = (__uint_as_float(u[0]) + __uint_as_float(u[1])) + (__uint_as_float(u[2]) + __uint_as_float(u[3]));
            const float vmax = __uint_as_float(max(max(v[0], v[1]), max(v[2], v[3]))), fmax2 = __uint_as_float(max(max(w[0], w[1]), max(w[2], w[3])));
            float inv_mean;
            asm("rcp.approx.ftz.f32 %0, %1;" : "=f"(inv_mean) : "f"(fmaf(tot, 1.f / EX, 1e-6f)));
            const int rho_e = 14 - ilog2f(fmaf(vmax, inv_mean, 2.f * fmax2));
            const float rho = pow2i(rho_e), inv_rho = pow2i(-rho_e);
            inv_rho2 = pack_bf2(inv_rho, inv_rho);
#pragma unroll
            for (int m = 0; m < 3; m++) {
                const float f = fmaf(slope[m] * gx[m], inv_mean, base[m]) * rho;
                asm volatile("st.shared.u16 [%0], %1;" ::"r"(own_fac + 256 * m), "h"((unsigned short)pack_h2(f, 0.f)) : "memory");
            }
            if (i0 < 96) sts32(sb + SM_BIASH + i0 * 4, pack_h2(bpair.x * rho, bpair.y * rho));
            if (i0 == 96) sts32(s_red + RED_INV_RHO, inv_rho2);
            named_arrive(12, NTHREADS);
            if (blockIdx.x == 0 && leader) sc->launch = epoch + 1;
            if (wk.lent) spin_until(&sc->lent_out, (epoch + 1) * 8 * LENT * sp.lenders);
        } else {
            const int rw = rank * 4 - 4 + w4;
            const uint32_t row = sb + SM_W2 + rw * 512 + lane * 16;
            uint32_t u[W2_EARLY][4], f2[4];
#pragma unroll
            for (int nb = 0; nb < W2_EARLY; nb++) {
                if (nb % 8 == 0) mbar_wait_once(sb + BAR_W + nb, 1);
                lds128(u[nb][0], u[nb][1], u[nb][2], u[nb][3], row + nb * 6144);
            }
            named_bar(12, NTHREADS);
            PROF(3);
            lds128(f2[0], f2[1], f2[2], f2[3], s_fac + rw * 64 + (lane >> 3) * 16);
            lds32(inv_rho2, s_red + RED_INV_RHO);
#pragma unroll
            for (int nb = 0; nb < 12; nb++) {
                uint32_t v[4];
                if (nb < W2_EARLY) { v[0] = u[nb % W2_EARLY][0]; v[1] = u[nb % W2_EARLY][1]; v[2] = u[nb % W2_EARLY][2]; v[3] = u[nb % W2_EARLY][3]; }
                else lds128(v[0], v[1], v[2], v[3], row + nb * 6144);
                sts128(row + nb * 6144, h_cut8(h_mul(v[0], f2[0])), h_cut8(h_mul(v[1], f2[1])), h_cut8(h_mul(v[2], f2[2])), h_cut8(h_mul(v[3], f2[3])));
            }
            fence_async();
            named_arrive(8, NTHREADS);
        }
    }
    uint32_t a[6][4], acc[24], rpar = 0, tile_off = here;
    const uint32_t bias_addr = sb + SM_BIASH + (lane & 3) * 96, lane16 = lane * 16, lane_off = ((lane >> 2) * CH + 8 * (lane & 3)) * 2;
    const uint32_t stage = sb + SM_RING + (spare + rank) % NSLOT * SLOT_BYTES + w4 * WARP_BYTES, bar_r = sb + BAR_R + warp_id * 8;
    auto load_bias = [&]() {
#pragma unroll
        for (int q = 0; q < 6; q++) lds128(acc[4 * q], acc[4 * q + 1], acc[4 * q + 2], acc[4 * q + 3], bias_addr + q * 16);
    };
    auto load_frags = [&]() {
#pragma unroll
        for (int s = 0; s < 6; s++) ldg128(a[s], reinterpret_cast<const char*>(out) + next_off + w4 * WARP_BYTES + lane16 + s * 512);
    };
    auto stage_x = [&]() {
        if (elect_one()) {
            mbar_expect_tx(bar_r, WARP_BYTES);
            bulk_load_stream(stage, reinterpret_cast<const char*>(x) + tile_off + w4 * WARP_BYTES, WARP_BYTES, bar_r);
        }
    };
    {
        named_bar(8 + rank, rank ? 256 : NTHREADS);
        if (rank == 0) PROF(4);
        load_bias();
        pin(k1); pin(k2); pin(k3);
        wg_fence();
        gemm2_chunk<288>(acc, k3, ds);
        wg_commit();
        gemm2_chunk<96>(acc, k1, ds);
        wg_commit();
        gemm2_chunk<192>(acc, k2, ds);
        wg_commit();
        stage_x();
        wg_wait<2>();
        uint32_t k0[24];
#pragma unroll
        for (int q = 0; q < 6; q++)
            lds128(k0[4 * q], k0[4 * q + 1], k0[4 * q + 2], k0[4 * q + 3], sb + SM_RING + cur.slot * SLOT_BYTES + w4 * REGION_BYTES + lane16 + q * 512);
        pin(k0);
        wg_fence();
        gemm2_chunk<0>(acc, k0, ds);
        wg_commit();
        if (rank < NCONS) named_arrive(9 + rank, 256);
        wg_wait<2>();
        load_frags();
        if (lane16 == 0) mbar_arrive(sb + BAR_PIN);
        mbar_wait(bar_r, rpar);
        wg_wait<0>();
    }
    auto lent = [&](uint32_t entry) { return &sc->lent[((wk.index * LENT + (entry & 3) - 1) * 4 + w4) * (24 * 32)]; };
    for (jt = rank - 4; jt < nrest; jt += 4) {
        if (jt >= zero) {
        tile_off = next_off;
        lds32(next_off, sb + SM_TILES + (jt + 4) * 4);
        if (tile_off & 3) {
            const uint4* src = lent(tile_off) + lane;
            tile_off &= ~3u;
            next_off = __shfl_sync(~0u, next_off, 0);
            stage_x();
            if (elect_one()) prefetch_l2(reinterpret_cast<const char*>(out) + next_off + w4 * WARP_BYTES, WARP_BYTES);
            load_bias();
#pragma unroll 1
            for (int half = 0; half < 2; half++, src += 12 * 32) {
                uint32_t gl[48];
#pragma unroll
                for (int s = 0; s < 12; s++) ldg128(reinterpret_cast<uint32_t (&)[4]>(gl[4 * s]), src + s * 32);
                if (!half) {
                    named_bar(4 + rank, 256);
                    named_arrive(4 + ((rank + 1) & 3), 256);
                }
                pin(gl);
                wg_fence();
#pragma unroll
                for (int s = 0; s < 12; s++) wgmma(acc, gl[4 * s], gl[4 * s + 1], gl[4 * s + 2], gl[4 * s + 3], ds.w2[12 * half + s], 1);
                wg_commit();
                wg_wait<0>();
            }
            load_frags();
            mbar_wait(bar_r, rpar);
        } else {
            uint32_t d0[12], d1[12], g0[12], g1[12];
            if (jt) named_bar(4 + rank, 256);
            wg_fence();
            gemm1_chunk<0>(d0, a, ds, 0);
            wg_commit();
            gemm1_chunk<48>(d1, a, ds, 0);
            wg_commit();
            load_bias();
            next_off = __shfl_sync(~0u, next_off, 0);
            const bool more = jt + 4 < nrest && !(next_off & 3);
            wg_wait<1>();
#define CNX_STEP(C, D, G)                                              \
    gelu_to(G, D);                                                     \
    wg_fence();                                                        \
    if (C < 6) gemm1_chunk<48 * (C < 6 ? C + 2 : 0)>(D, a, ds, zero); \
    gemm2_chunk<48 * C>(acc, G, ds);                                  \
    wg_commit();                                                       \
    wg_wait<(C < 7 ? 1 : 0)>();
            CNX_STEP(0, d0, g0)
            CNX_STEP(1, d1, g1)
            if (jt + 1 < nrest) named_arrive(4 + ((rank + 1) & 3), 256);
            stage_x();
            if (elect_one()) {
                if (more) prefetch_l2(reinterpret_cast<const char*>(out) + next_off + w4 * WARP_BYTES, WARP_BYTES);
                else if (next_off & 3) prefetch_l2(lent(next_off), 24 * 32 * 16);
            }
            CNX_STEP(2, d0, g0)
            CNX_STEP(3, d1, g1)
            CNX_STEP(4, d0, g0)
            CNX_STEP(5, d1, g1)
            CNX_STEP(6, d0, g0)
#pragma unroll
            for (int s = 0; s < 6; s++) ldg128_if(more, a[s], reinterpret_cast<const char*>(out) + next_off + w4 * WARP_BYTES + lane16 + s * 512);
            if (lane16 == 0) mbar_arrive(sb + BAR_PIN);
            mbar_wait(bar_r, rpar);
            CNX_STEP(7, d1, g1)
#undef CNX_STEP
        }
        }
        {
            pin(acc);
            rpar ^= 1;
            uint4* op = reinterpret_cast<uint4*>(reinterpret_cast<char*>(out) + tile_off + w4 * WARP_BYTES + lane_off);
#pragma unroll
            for (int h = 0; h < 2; h++)
#pragma unroll
                for (int m = 0; m < 3; m++) {
                    uint32_t xin[4], o[4];
                    lds128(xin[0], xin[1], xin[2], xin[3], stage + lane_off + h * 1536 + m * 64);
#pragma unroll
                    for (int q = 0; q < 4; q++) {
                        const uint32_t v = acc[2 * (4 * m + q) + h];
                        o[q] = bf_fma(pack_bf2(h_lo(v), h_hi(v)), inv_rho2, xin[q]);
                    }
                    __stcs(op + h * 96 + m * 4, make_uint4(o[0], o[1], o[2], o[3]));
                }
            __syncwarp();
        }
    }
    PROF(5);
}

}

typedef CUresult (*EncodeTiledFn)(CUtensorMap*, CUtensorMapDataType, cuuint32_t, void*, const cuuint64_t*, const cuuint64_t*,
                                  const cuuint32_t*, const cuuint32_t*, CUtensorMapInterleave, CUtensorMapSwizzle,
                                  CUtensorMapL2promotion, CUtensorMapFloatOOBfill);

extern "C" void kernel_launch(void* const* d_in, const int* in_sizes, int n_in, void* d_out, int out_size) {
    using namespace cnx;
    static EncodeTiledFn encode = nullptr;
    static int num_sms = 0;
    static Scratch* scratch = nullptr;
    if (!encode) {
        void* fn = nullptr;
        cudaDriverEntryPointQueryResult qr;
        cudaGetDriverEntryPoint("cuTensorMapEncodeTiled", &fn, cudaEnableDefault, &qr);
        encode = (EncodeTiledFn)fn;
        cudaGetSymbolAddress((void**)&scratch, g_scratch);
        int dev = 0;
        cudaGetDevice(&dev);
        cudaDeviceGetAttribute(&num_sms, cudaDevAttrMultiProcessorCount, dev);
        if (num_sms > MAX_CTAS) num_sms = MAX_CTAS;
        cudaFuncSetAttribute(block_kernel, cudaFuncAttributeMaxDynamicSharedMemorySize, SM_TOTAL);
    }
    CUtensorMap tm;
    cuuint64_t dims[3] = {(cuuint64_t)CH, (cuuint64_t)IMG_W, (cuuint64_t)IMG_H};
    cuuint64_t strides[2] = {(cuuint64_t)CH * 2, (cuuint64_t)CH * 2 * IMG_W};
    cuuint32_t box[3] = {(cuuint32_t)CH, (cuuint32_t)REGION_PX, 1};
    cuuint32_t estr[3] = {1, 1, 1};
    encode(&tm, CU_TENSOR_MAP_DATA_TYPE_BFLOAT16, 3, d_in[0], dims, strides, box, estr, CU_TENSOR_MAP_INTERLEAVE_NONE,
           CU_TENSOR_MAP_SWIZZLE_NONE, CU_TENSOR_MAP_L2_PROMOTION_L2_128B, CU_TENSOR_MAP_FLOAT_OOB_FILL_NONE);
    Params pm = {};
    Descs& ds = pm.ds;
    for (int c = 0; c < 8; c++)
        for (int k = 0; k < 6; k++) ds.w1[c][k] = make_desc(SB + SM_W1 + c * 6 * 1536 + k * 256, 128, 1536);
    for (int k = 0; k < 24; k++) ds.w2[k] = make_desc(SB + SM_W2 + k * 256, 128, 6144);
    ds.ones = make_desc(SB + SM_ONES, 0, 0);
    CUtensorMap tw;
    cuuint64_t wdims[2] = {(cuuint64_t)EX, (cuuint64_t)CH};
    cuuint64_t wstrides[1] = {(cuuint64_t)EX * 2};
    cuuint32_t wbox[2] = {64, (cuuint32_t)CH};
    encode(&tw, CU_TENSOR_MAP_DATA_TYPE_BFLOAT16, 2, d_in[2], wdims, wstrides, wbox, estr, CU_TENSOR_MAP_INTERLEAVE_NONE,
           CU_TENSOR_MAP_SWIZZLE_128B, CU_TENSOR_MAP_L2_PROMOTION_L2_128B, CU_TENSOR_MAP_FLOAT_OOB_FILL_NONE);
    Split& sp = pm.sp;
    sp = {NTILES / num_sms, NTILES % num_sms, 1, 1 << 16, 0, {}};
    if (sp.per_cta + 9 > MAX_ROWS) return;
    if (sp.extra && sp.extra * (8 * LENT + 1) + W2_GROUPS / 2 <= num_sms && sp.per_cta >= 5 * LENT + 8) {
        sp.period = num_sms / sp.extra;
        sp.inv_period = 65535 / sp.period + 1;
        sp.lenders = sp.extra;
        for (int l = 0; l < sp.extra; l++) {
            const Work w = get_work((l + 1) * sp.period - sp.period / 2 - 1, sp);
            for (int e = 0; e < LENT; e++) sp.lent_off[l * LENT + e] = tile_offset(w.tile(e));
            if (w.nA < 2 * LENT) sp.lenders = 0;
        }
    }
    pm.x = (const __nv_bfloat16*)d_in[0];
    pm.dw = (const __nv_bfloat16*)d_in[1];
    pm.w2 = (const __nv_bfloat16*)d_in[3];
    pm.gamma = (const __nv_bfloat16*)d_in[4];
    pm.beta = (const __nv_bfloat16*)d_in[5];
    pm.out = (__nv_bfloat16*)d_out;
    pm.sc = scratch;
    block_kernel<<<num_sms, NTHREADS, SM_TOTAL>>>(tm, tw, pm);
}
```

```cpp
#include <cuda_runtime.h>
#include <cuda_bf16.h>
#include <cuda_fp16.h>
#include <cuda.h>
#include <stdint.h>

namespace cnx {

constexpr int IMG_H = 512, IMG_W = 512, CH = 96, EX = 384;
constexpr int TILE_W = 64;
constexpr int NTILES = (IMG_W / TILE_W) * IMG_H;
constexpr int NSLOT = 6;
constexpr int REGION_PX = 18;
constexpr int REGION_BYTES = REGION_PX * CH * 2;
constexpr int SLOT_BYTES = 4 * REGION_BYTES;
constexpr int A_LBO = 144, A_SBO = 12 * A_LBO;
constexpr int PREFETCH_ROWS = 3;
constexpr int NCONS = 3;
constexpr int CONS_THREADS = 128 * NCONS;
constexpr int NTHREADS = 128 + CONS_THREADS;
constexpr int MAX_ROWS = 52;
constexpr int TILE_BYTES = TILE_W * CH * 2, WARP_BYTES = TILE_BYTES / 4;
constexpr int ORDER_P = 3;
constexpr int W2_EARLY = 9;
static_assert(MAX_ROWS <= 128, "one table entry per producer thread");
static_assert(2 * A_SBO == REGION_BYTES && REGION_BYTES % 128 == 0, "region layout");

constexpr uint32_t SB = 1024;
constexpr int SM_W1 = 0;
constexpr int SM_W2 = SM_W1 + CH * EX * 2;
constexpr int SM_RING = SM_W2 + CH * EX * 2;
constexpr int SM_BIASH = SM_RING + NSLOT * SLOT_BYTES;
constexpr int SM_RED = SM_BIASH + 384;
constexpr int RED_MAX = 0, RED_LAUNCH = 48, RED_INV_RHO = 52;
constexpr int SM_TILES = SM_RED + 256;
constexpr int SM_ONES = SM_TILES + MAX_ROWS * 4;
constexpr int SM_BAR = SM_ONES + 128;
constexpr int BAR_X = SM_BAR;
constexpr int BAR_A = BAR_X + NSLOT * 4 * 8;
constexpr int BAR_E = BAR_A + NSLOT * 4 * 8;
constexpr int BAR_PIN = BAR_E + NSLOT * 4 * 8;
constexpr int BAR_W = BAR_PIN + 8;
constexpr int BAR_F = BAR_W + 6 * 8;
constexpr int BAR_R = BAR_F + 8;
constexpr int SM_TOTAL = BAR_R + 16 * 8;
constexpr int SM_FILTER = SM_RING + (NSLOT - 1) * SLOT_BYTES + 9 * 128;
constexpr int SM_SQ = SM_W2;
constexpr int SQ_ROW = 128 * 16, SQ_HALF = 6 * SQ_ROW;
static_assert(SM_ONES % 16 == 0 && SM_TOTAL <= 232448, "shared memory budget");

constexpr float KZ = 0.3292034911525734f;
constexpr uint32_t GELU_C2 = 0x40d940d9u;
constexpr float INV_2KZ = 0.5f / KZ;
constexpr unsigned SPIN_LIMIT = 1u << 19;

constexpr int MAX_CTAS = 255;
constexpr int W2_GROUPS = EX / 8;
constexpr int LENT = 3, MAX_LENDERS = MAX_CTAS / (8 * LENT + 1);
struct Scratch {
    uint32_t w2h[EX * CH / 2];
    float w2max[EX];
    float bias[CH + 32];
    unsigned long long sums[EX / 4][32];
    __device__ __forceinline__ unsigned long long* sum(int e) { return &sums[e >> 2][e & 3]; }
    uint4 lent[MAX_LENDERS * LENT * 8 * 4 * 3 * 32];
    unsigned launch, pad0[31], early, pad1[31], prep, pad2[31], lent_out, pad3[31];
};
__device__ __align__(128) Scratch g_scratch;

#define PROF(k)

__device__ __forceinline__ uint32_t smem_u32(const void* p) { return (uint32_t)__cvta_generic_to_shared(p); }
__device__ __forceinline__ void mbar_init(uint32_t bar, uint32_t cnt) {
    asm volatile("mbarrier.init.shared::cta.b64 [%0], %1;" ::"r"(bar), "r"(cnt) : "memory");
}
__device__ __forceinline__ void mbar_arrive(uint32_t bar) {
    asm volatile("mbarrier.arrive.shared::cta.b64 _, [%0];" ::"r"(bar) : "memory");
}
__device__ __forceinline__ void mbar_expect_tx(uint32_t bar, uint32_t bytes) {
    asm volatile("mbarrier.arrive.expect_tx.shared::cta.b64 _, [%0], %1;" ::"r"(bar), "r"(bytes) : "memory");
}
__device__ __forceinline__ bool mbar_try(uint32_t bar, uint32_t par) {
    uint32_t ok;
    asm volatile("{\n.reg .pred p;\nmbarrier.try_wait.parity.shared::cta.b64 p, [%1], %2;\nselp.u32 %0, 1, 0, p;\n}\n"
                 : "=r"(ok) : "r"(bar), "r"(par) : "memory");
    return ok != 0;
}
__device__ __forceinline__ void mbar_wait(uint32_t bar, uint32_t par) {
    unsigned n = 0;
    while (!mbar_try(bar, par)) {
        if (++n > SPIN_LIMIT) __trap();
    }
}
__device__ __forceinline__ void mbar_wait_once(uint32_t bar, uint32_t par) {
    unsigned n = 0;
    bool ok;
#pragma unroll 1
    do {
        ok = mbar_try(bar, par);
        if (++n > SPIN_LIMIT) __trap();
    } while (!ok);
}
__device__ __forceinline__ bool elect_one() {
    uint32_t ok;
    asm volatile("{\n.reg .pred p;\nelect.sync _|p, 0xffffffff;\nselp.u32 %0, 1, 0, p;\n}\n" : "=r"(ok));
    return ok != 0;
}
__device__ __forceinline__ uint32_t opaque(uint32_t v) { return __shfl_sync(~0u, v, threadIdx.x & 31); }
__device__ __forceinline__ uint32_t lane_id() { uint32_t v; asm volatile("mov.u32 %0, %%laneid;" : "=r"(v)); return v; }
__device__ __forceinline__ uint32_t opaque_uniform(uint32_t v) { return __shfl_sync(~0u, v, 0); }
__device__ __forceinline__ void named_bar(int id, int n) { asm volatile("bar.sync %0, %1;" ::"r"(id), "r"(n) : "memory"); }
__device__ __forceinline__ void named_arrive(int id, int n) { asm volatile("bar.arrive %0, %1;" ::"r"(id), "r"(n) : "memory"); }
__device__ __forceinline__ void fence_async() { asm volatile("fence.proxy.async.shared::cta;" ::: "memory"); }
constexpr uint64_t EVICT_FIRST = 0x12F0000000000000ull;
__device__ __forceinline__ void tma_row(uint32_t dst, const CUtensorMap* tm, uint32_t bar, int x, int y) {
    asm volatile("cp.async.bulk.tensor.3d.shared::cluster.global.mbarrier::complete_tx::bytes.L2::cache_hint [%0], [%1, {%3, %4, %5}], [%2], %6;"
                 ::"r"(dst), "l"(tm), "r"(bar), "r"(0), "r"(x), "r"(y), "l"(EVICT_FIRST) : "memory");
}
__device__ __forceinline__ void bulk_load_stream(uint32_t dst, const void* src, uint32_t bytes, uint32_t bar) {
    asm volatile("cp.async.bulk.shared::cluster.global.mbarrier::complete_tx::bytes.L2::cache_hint [%0], [%1], %2, [%3], %4;"
                 ::"r"(dst), "l"(src), "r"(bytes), "r"(bar), "l"(EVICT_FIRST) : "memory");
}
__device__ __forceinline__ void prefetch_l2(const void* src, uint32_t bytes) {
    asm volatile("cp.async.bulk.prefetch.L2.global [%0], %1;" ::"l"(src), "r"(bytes) : "memory");
}
__device__ __forceinline__ void tma_2d(uint32_t dst, const CUtensorMap* tm, uint32_t bar, int x, int y) {
    asm volatile("cp.async.bulk.tensor.2d.shared::cluster.global.mbarrier::complete_tx::bytes [%0], [%1, {%3, %4}], [%2];"
                 ::"r"(dst), "l"(tm), "r"(bar), "r"(x), "r"(y) : "memory");
}
__device__ __forceinline__ void bulk_load(uint32_t dst, const void* src, uint32_t bytes, uint32_t bar) {
    asm volatile("cp.async.bulk.shared::cluster.global.mbarrier::complete_tx::bytes [%0], [%1], %2, [%3];"
                 ::"r"(dst), "l"(src), "r"(bytes), "r"(bar) : "memory");
}
__device__ __forceinline__ void wg_fence() { asm volatile("wgmma.fence.sync.aligned;" ::: "memory"); }
__device__ __forceinline__ void wg_commit() { asm volatile("wgmma.commit_group.sync.aligned;" ::: "memory"); }
template <int N> __device__ __forceinline__ void wg_wait() { asm volatile("wgmma.wait_group.sync.aligned %0;" ::"n"(N) : "memory"); }
template <int N> __device__ __forceinline__ void pin(uint32_t (&d)[N]) {
#pragma unroll
    for (int q = 0; q < N; q++) asm volatile("" : "+r"(d[q])::"memory");
}
__device__ __forceinline__ void stg128(void* p, const uint32_t (&v)[4]) {
    asm volatile("st.global.v4.u32 [%0], {%1, %2, %3, %4};" ::"l"(p), "r"(v[0]), "r"(v[1]), "r"(v[2]), "r"(v[3]) : "memory");
}
__device__ __forceinline__ void ldg128(uint32_t (&v)[4], const void* p) {
    asm volatile("ld.global.L1::no_allocate.v4.u32 {%0, %1, %2, %3}, [%4];" : "=r"(v[0]), "=r"(v[1]), "=r"(v[2]), "=r"(v[3]) : "l"(p) : "memory");
}
__device__ __forceinline__ void ldg128_if(bool on, uint32_t (&v)[4], const void* p) {
    asm volatile("{\n.reg .pred p;\nsetp.ne.b32 p, %5, 0;\n@p ld.global.L1::no_allocate.v4.u32 {%0, %1, %2, %3}, [%4];\n}\n"
                 : "+r"(v[0]), "+r"(v[1]), "+r"(v[2]), "+r"(v[3]) : "l"(p), "r"((int)on) : "memory");
}
__host__ __device__ constexpr uint64_t make_desc(uint32_t addr, uint32_t lbo, uint32_t sbo) {
    return (uint64_t)((addr & 0x3FFFF) >> 4) | ((uint64_t)(lbo >> 4) << 16) | ((uint64_t)(sbo >> 4) << 32);
}
__device__ __forceinline__ void wgmma(uint32_t (&d)[12], uint32_t a0, uint32_t a1, uint32_t a2, uint32_t a3, uint64_t db, int acc) {
    asm volatile("{\n.reg .pred p;\nsetp.ne.b32 p, %17, 0;\n"
                 "wgmma.mma_async.sync.aligned.m64n48k16.f16.f16.f16 "
                 "{%0, %1, %2, %3, %4, %5, %6, %7, %8, %9, %10, %11}, "
                 "{%12, %13, %14, %15}, %16, p, 1, 1, 0;\n}\n"
                 : "+r"(d[0]), "+r"(d[1]), "+r"(d[2]), "+r"(d[3]), "+r"(d[4]), "+r"(d[5]), "+r"(d[6]), "+r"(d[7]), "+r"(d[8]), "+r"(d[9]), "+r"(d[10]), "+r"(d[11])
                 : "r"(a0), "r"(a1), "r"(a2), "r"(a3), "l"(db), "r"(acc));
}
__device__ __forceinline__ void wgmma(uint32_t (&d)[24], uint32_t a0, uint32_t a1, uint32_t a2, uint32_t a3, uint64_t db, int acc) {
    asm volatile("{\n.reg .pred p;\nsetp.ne.b32 p, %29, 0;\n"
                 "wgmma.mma_async.sync.aligned.m64n96k16.f16.f16.f16 "
                 "{%0, %1, %2, %3, %4, %5, %6, %7, %8, %9, %10, %11, %12, %13, %14, %15, %16, %17, %18, %19, %20, %21, %22, %23}, "
                 "{%24, %25, %26, %27}, %28, p, 1, 1, 0;\n}\n"
                 : "+r"(d[0]), "+r"(d[1]), "+r"(d[2]), "+r"(d[3]), "+r"(d[4]), "+r"(d[5]), "+r"(d[6]), "+r"(d[7]), "+r"(d[8]), "+r"(d[9]), "+r"(d[10]), "+r"(d[11]), "+r"(d[12]), "+r"(d[13]), "+r"(d[14]), "+r"(d[15]), "+r"(d[16]), "+r"(d[17]), "+r"(d[18]), "+r"(d[19]), "+r"(d[20]), "+r"(d[21]), "+r"(d[22]), "+r"(d[23])
                 : "r"(a0), "r"(a1), "r"(a2), "r"(a3), "l"(db), "r"(acc));
}
template <int ACC>
__device__ __forceinline__ void wgmma_rowsum(float (&d)[4], const uint32_t (&a)[4], uint64_t ones) {
    asm volatile("{\n.reg .pred p;\nsetp.ne.b32 p, %9, 0;\n"
                 "wgmma.mma_async.sync.aligned.m64n8k16.f32.bf16.bf16 {%0, %1, %2, %3}, {%4, %5, %6, %7}, %8, p, 1, 1, 0;\n}\n"
                 : "+f"(d[0]), "+f"(d[1]), "+f"(d[2]), "+f"(d[3])
                 : "r"(a[0]), "r"(a[1]), "r"(a[2]), "r"(a[3]), "l"(ones), "n"(ACC));
}
__device__ __forceinline__ void ldsm4(uint32_t (&r)[4], uint32_t addr) {
    asm volatile("ldmatrix.sync.aligned.m8n8.x4.shared.b16 {%0, %1, %2, %3}, [%4];"
                 : "=r"(r[0]), "=r"(r[1]), "=r"(r[2]), "=r"(r[3]) : "r"(addr) : "memory");
}
__device__ __forceinline__ void ldsm4_t(uint32_t (&r)[4], uint32_t addr) {
    asm volatile("ldmatrix.sync.aligned.m8n8.x4.trans.shared.b16 {%0, %1, %2, %3}, [%4];"
                 : "=r"(r[0]), "=r"(r[1]), "=r"(r[2]), "=r"(r[3]) : "r"(addr) : "memory");
}
__device__ __forceinline__ void stsm4(uint32_t addr, uint32_t a, uint32_t b, uint32_t c, uint32_t d) {
    asm volatile("stmatrix.sync.aligned.m8n8.x4.shared.b16 [%0], {%1, %2, %3, %4};"
                 ::"r"(addr), "r"(a), "r"(b), "r"(c), "r"(d) : "memory");
}
__device__ __forceinline__ uint32_t transpose8x8(uint32_t v) {
    uint32_t d; asm volatile("movmatrix.sync.aligned.m8n8.trans.b16 %0, %1;" : "=r"(d) : "r"(v)); return d;
}
__device__ __forceinline__ void spin_until(const unsigned* counter, unsigned target) {
    unsigned n = 0, c;
    do {
        asm volatile("ld.acquire.gpu.global.u32 %0, [%1];" : "=r"(c) : "l"(counter) : "memory");
        if (++n > SPIN_LIMIT) __trap();
    } while ((int)(c - target) < 0);
}
__device__ __forceinline__ void signal(unsigned* counter) {
    __syncwarp();
    if (elect_one()) asm volatile("red.release.gpu.global.add.u32 [%0], 1;" ::"l"(counter) : "memory");
    __syncwarp();
}
__device__ __forceinline__ void lds128(uint32_t& a, uint32_t& b, uint32_t& c, uint32_t& d, uint32_t addr) {
    asm volatile("ld.shared.v4.u32 {%0, %1, %2, %3}, [%4];" : "=r"(a), "=r"(b), "=r"(c), "=r"(d) : "r"(addr) : "memory");
}
__device__ __forceinline__ void lds64(uint32_t& a, uint32_t& b, uint32_t addr) {
    asm volatile("ld.shared.v2.u32 {%0, %1}, [%2];" : "=r"(a), "=r"(b) : "r"(addr) : "memory");
}
__device__ __forceinline__ void lds32(uint32_t& a, uint32_t addr) {
    asm volatile("ld.shared.u32 %0, [%1];" : "=r"(a) : "r"(addr) : "memory");
}
__device__ __forceinline__ int ldsi(uint32_t addr) {
    uint32_t v;
    lds32(v, addr);
    return (int)v;
}
__device__ __forceinline__ float ldsf(uint32_t addr) {
    uint32_t v;
    lds32(v, addr);
    return __uint_as_float(v);
}
__device__ __forceinline__ void sts32(uint32_t addr, uint32_t a) {
    asm volatile("st.shared.u32 [%0], %1;" ::"r"(addr), "r"(a) : "memory");
}
__device__ __forceinline__ void sts128(uint32_t addr, uint32_t a, uint32_t b, uint32_t c, uint32_t d) {
    asm volatile("st.shared.v4.u32 [%0], {%1, %2, %3, %4};" ::"r"(addr), "r"(a), "r"(b), "r"(c), "r"(d) : "memory");
}
__device__ __forceinline__ void sts64(uint32_t addr, uint32_t a, uint32_t b) {
    asm volatile("st.shared.v2.u32 [%0], {%1, %2};" ::"r"(addr), "r"(a), "r"(b) : "memory");
}
__device__ __forceinline__ void anchor(uint32_t addr, uint32_t a, uint32_t b, uint32_t c, uint32_t d) {
    asm volatile("{\n.reg .pred p;\nsetp.eq.b32 p, %0, 0;\n@p st.shared.v4.u32 [%0], {%1, %2, %3, %4};\n}\n"
                 ::"r"(addr), "r"(a), "r"(b), "r"(c), "r"(d) : "memory");
}
__device__ __forceinline__ uint32_t bf_fma(uint32_t a, uint32_t b, uint32_t c) {
    uint32_t d; asm("fma.rn.bf16x2 %0, %1, %2, %3;" : "=r"(d) : "r"(a), "r"(b), "r"(c)); return d;
}
__device__ __forceinline__ uint32_t bf_mul(uint32_t a, uint32_t b) {
    uint32_t d; asm("mul.rn.bf16x2 %0, %1, %2;" : "=r"(d) : "r"(a), "r"(b)); return d;
}
__device__ __forceinline__ uint32_t bf_absmax(uint32_t a, uint32_t b) {
    uint32_t d; asm("max.xorsign.abs.bf16x2 %0, %1, %2;" : "=r"(d) : "r"(a), "r"(b)); return d;
}
__device__ __forceinline__ uint32_t h_fma(uint32_t a, uint32_t b, uint32_t c) {
    uint32_t d; asm("fma.rn.f16x2 %0, %1, %2, %3;" : "=r"(d) : "r"(a), "r"(b), "r"(c)); return d;
}
__device__ __forceinline__ uint32_t h_mul(uint32_t a, uint32_t b) {
    uint32_t d; asm("mul.rn.f16x2 %0, %1, %2;" : "=r"(d) : "r"(a), "r"(b)); return d;
}
__device__ __forceinline__ uint32_t h_cut8(uint32_t v) { return v & 0xfff8fff8u; }
constexpr float CUT_GAIN = 1.f + 0.4375f * 0.7213f / 128;
__device__ __forceinline__ uint32_t h_tanh(uint32_t a) {
    uint32_t d; asm("tanh.approx.f16x2 %0, %1;" : "=r"(d) : "r"(a)); return d;
}
__device__ __forceinline__ uint32_t pack_h2(float lo, float hi) {
    uint32_t d; asm("cvt.rn.f16x2.f32 %0, %1, %2;" : "=r"(d) : "f"(hi), "f"(lo)); return d;
}
__device__ __forceinline__ uint32_t pack_bf2(float lo, float hi) {
    uint32_t d; asm("cvt.rn.bf16x2.f32 %0, %1, %2;" : "=r"(d) : "f"(hi), "f"(lo)); return d;
}
__device__ __forceinline__ float bf_lo(uint32_t v) { return __uint_as_float(v << 16); }
__device__ __forceinline__ float bf_hi(uint32_t v) { return __uint_as_float(v & 0xffff0000u); }
__device__ __forceinline__ float h_lo(uint32_t v) { return __low2float(*reinterpret_cast<__half2*>(&v)); }
__device__ __forceinline__ float h_hi(uint32_t v) { return __high2float(*reinterpret_cast<__half2*>(&v)); }
__device__ __forceinline__ float warp_absmax(uint32_t v) {
    return __uint_as_float(__reduce_max_sync(~0u, max((v & 0x7fffu) << 16, v & 0x7fff0000u)));
}
__device__ __forceinline__ uint32_t gelu2(uint32_t z) {
    uint32_t p = h_fma(z, z, GELU_C2);
    uint32_t t = h_tanh(h_mul(z, p));
    return h_fma(z, t, z);
}
__device__ __forceinline__ float pow2i(int e) { return __uint_as_float((uint32_t)(e + 127) << 23); }
__device__ __forceinline__ int ilog2f(float v) {
    int e = (int)((__float_as_uint(v) >> 23) & 0xff) - 127;
    return max(-100, min(100, e));
}

__device__ __forceinline__ int bound_exp(float w1max) { return w1max > 0.f ? ilog2f(2.f * KZ * 96.f * w1max) : 0; }
__device__ __forceinline__ bool plain_squares(int e) { return (unsigned)(4 - e) <= 6; }
__device__ __forceinline__ int square_exp(int e) { return plain_squares(e) ? 0 : max(-14, min(4 - e, 14)); }
__device__ __forceinline__ int sum_exp(int e) { return max(-90, min(90, 33 - 2 * e)); }
__device__ __forceinline__ int row_exp(float m) { return 2 - ilog2f(m); }

struct Split {
    int per_cta, extra, period, inv_period, lenders;
    uint32_t lent_off[MAX_LENDERS * LENT];
    __host__ __device__ __forceinline__ int longer_before(int cta) const {
        const int n = (cta + period / 2) * inv_period >> 16;
        return n < extra ? n : extra;
    }
};
struct Work {
    int tA, tB, nA, nB, dir, rows, lent, index;
    __host__ __device__ __forceinline__ int tile(int j) const { return j < nA ? tA + dir * j : tB + dir * (j - nA); }
};
__host__ __device__ __forceinline__ Work get_work(int cta, const Split& sp) {
    Work w;
    const int before = sp.longer_before(cta), longer = sp.longer_before(cta + 1) - before;
    w.lent = longer && sp.lenders ? LENT : 0;
    w.index = longer ? before : cta - before;
    const int t0 = cta * sp.per_cta + before, t1 = t0 + sp.per_cta + longer;
    const int tm = t1 < (t0 | 511) + 1 ? t1 : (t0 | 511) + 1;
    const bool swap = t1 > tm && t1 - tm < tm - t0, down = cta & 1;
    w.nA = swap ? t1 - tm : tm - t0;
    w.nB = t1 - t0 - w.nA;
    w.tA = down ? (swap ? tm : t0) : (swap ? t1 : tm) - 1;
    w.tB = down ? (swap ? t0 : tm) : (swap ? tm : t1) - 1;
    w.dir = down ? 1 : -1;
    w.rows = w.nA + 2 + (w.nB ? w.nB + 2 : 0);
    return w;
}
__device__ __forceinline__ int row_code(const Work& w, int i) {
    const bool in_a = i < w.nA + 2;
    const int t = in_a ? w.tA : w.tB;
    return ((t & 511) + w.dir * ((in_a ? i : i - (w.nA + 2)) - 1)) << 16 | (t >> 9) * TILE_W;
}
__host__ __device__ __forceinline__ uint32_t tile_offset(int tile) { return ((tile & 511) * IMG_W + (tile >> 9) * TILE_W) * (CH * 2); }
__device__ __forceinline__ int tile_order(int j, int n) {
    return j % ORDER_P == ORDER_P - 1 ? j / ORDER_P : n - 1 - (j - j / ORDER_P);
}
__device__ __forceinline__ void issue_region(const CUtensorMap* tm, uint32_t dst, uint32_t bar, int warp, int code) {
    mbar_expect_tx(bar, REGION_BYTES);
    tma_row(dst, tm, bar, (code & 0xffff) + (16 * warp - 1), code >> 16);
}

template <class Event>
__device__ __forceinline__ void conv_producer(const Work& wk, const CUtensorMap* tm, uint32_t sb, int warp, Event event) {
    const int lane = threadIdx.x & 31;
    const int j = lane & 15, grp = lane >> 4;
    const uint32_t reg0 = sb + SM_RING + warp * REGION_BYTES;
    const uint32_t bars = sb + SM_BAR + warp * 8;
    if (warp * 32 + lane < MAX_ROWS) {
        const int i = warp * 32 + lane, before = min(i / 5, wk.lent);
        const bool back = i % 5 == 0 && i > 0 && i / 5 <= wk.lent;
        sts32(sb + SM_TILES + i * 4, back ? tile_offset(wk.tile(before - 1)) | before
                                          : tile_offset(wk.tile(wk.lent + tile_order(i - before, wk.nA + wk.nB - 4 - wk.lent))));
    }
    const uint32_t ld64 = opaque(reg0 + grp * 8 * 192 + j * 8), ld32 = opaque(reg0 + grp * 8 * 192 + 128 + j * 4);
    const uint32_t st64 = opaque(reg0 + grp * A_SBO + (j >> 1) * A_LBO + (j & 1) * 8);
    const uint32_t st32 = opaque(reg0 + grp * A_SBO + (8 + (j >> 2)) * A_LBO + (j & 3) * 4);
    named_bar(0, NTHREADS);
    uint32_t w[3][3][3];
    mbar_wait_once(sb + BAR_F, 0);
#pragma unroll
    for (int tap = 0; tap < 9; tap++) {
        const uint32_t p = sb + SM_FILTER + (3 + wk.dir * 3 * (tap / 3 - 1) + tap % 3) * (CH * 2);
        lds64(w[tap / 3][tap % 3][0], w[tap / 3][tap % 3][1], p + 8 * j);
        lds32(w[tap / 3][tap % 3][2], p + 128 + 4 * j);
    }
#pragma unroll
    for (int tap = 0; tap < 9; tap++) sts64(reg0 + (NSLOT - 1) * SLOT_BYTES + tap * 128 + j * 8, w[tap / 3][tap % 3][1], w[tap / 3][tap % 3][0]);
    named_bar(1, 128);
#pragma unroll
    for (int tap = 0; tap < 9; tap++) lds64(w[tap / 3][tap % 3][1], w[tap / 3][tap % 3][0], reg0 + (NSLOT - 1) * SLOT_BYTES + tap * 128 + j * 8);
    static_assert(2 * PREFETCH_ROWS == NSLOT && SLOT_BYTES % 32 == 0, "slot arithmetic");
    uint32_t bo = 0, par = 0, pbo = PREFETCH_ROWS * 32, ppar = 1;
    int px, py;
    auto request = [&]() {
        mbar_wait_once(bars + (BAR_E - SM_BAR) + pbo, ppar);
        if (elect_one()) {
            mbar_expect_tx(bars + pbo, REGION_BYTES);
            tma_row(reg0 + pbo * (SLOT_BYTES / 32), tm, bars + pbo, px, py);
        }
    };
    auto advance = [&]() {
        bo += 32;
        if (bo == NSLOT * 32) { bo = 0; par ^= 1; }
        pbo += 32;
        if (pbo == NSLOT * 32) { pbo = 0; ppar ^= 1; }
    };
    auto aim = [&](int row) {
        const int code = row_code(wk, row);
        px = (code & 0xffff) + (16 * warp - 1);
        py = code >> 16;
    };
    uint32_t accB[8][3], accC[8][3];
    int r = 0;
#pragma unroll 1
    while (r < wk.rows) {
        if (r == 0 || r == wk.nA + 2) {
            const uint32_t bo0 = bo;
            uint32_t bo1;
#pragma unroll 1
            for (int k = 0; k < 2; k++, r++) {
                mbar_wait_once(bars + bo, par);
                bo1 = bo;
                if (r >= 2) {
                    aim(r + PREFETCH_ROWS);
                    request();
                }
                advance();
            }
            const uint32_t so0 = bo0 * (SLOT_BYTES / 32), so1 = bo1 * (SLOT_BYTES / 32);
#pragma unroll
            for (int p = 0; p < 10; p++) {
                uint32_t u[3], v[3];
                lds64(u[0], u[1], so0 + ld64 + p * 192);
                lds32(u[2], so0 + ld32 + p * 192);
                lds64(v[0], v[1], so1 + ld64 + p * 192);
                lds32(v[2], so1 + ld32 + p * 192);
#pragma unroll
                for (int dx = 0; dx < 3; dx++) {
                    const int o = p - dx;
                    if (o < 0 || o > 7) continue;
#pragma unroll
                    for (int q = 0; q < 3; q++) {
                        accB[o][q] = bf_fma(v[q], w[1][dx][q], dx == 0 ? bf_mul(u[q], w[0][dx][q]) : bf_fma(u[q], w[0][dx][q], accB[o][q]));
                        accC[o][q] = dx == 0 ? bf_mul(v[q], w[0][dx][q]) : bf_fma(v[q], w[0][dx][q], accC[o][q]);
                    }
                }
            }
            anchor(ld64, accB[7][0], accB[7][1], accB[7][2], 0);
            __syncwarp();
            if (elect_one()) {
                mbar_arrive(bars + (BAR_A - SM_BAR) + bo0);
                mbar_arrive(bars + (BAR_E - SM_BAR) + bo0);
                mbar_arrive(bars + (BAR_A - SM_BAR) + bo1);
                mbar_arrive(bars + (BAR_E - SM_BAR) + bo1);
            }
        }
        int end = wk.rows;
        const int marks[4] = {wk.rows - PREFETCH_ROWS, wk.rows - 11, wk.nA + 2, wk.nA + 2 - PREFETCH_ROWS};
#pragma unroll
        for (int k = 0; k < 4; k++) end = marks[k] > r ? min(end, marks[k]) : end;
        const bool fetch = r < wk.rows - PREFETCH_ROWS;
        aim(r + PREFETCH_ROWS);
        px = opaque_uniform(px);
        const int py_end = opaque_uniform(py + wk.dir * (end - r));
        r = end;
#pragma unroll 1
        do {
            mbar_wait(bars + bo, par);
            const uint32_t so = bo * (SLOT_BYTES / 32);
            uint32_t out[8][3];
#pragma unroll
            for (int p = 0; p < 10; p++) {
                uint32_t xv[3];
                lds64(xv[0], xv[1], so + ld64 + p * 192);
                lds32(xv[2], so + ld32 + p * 192);
#pragma unroll
                for (int dx = 0; dx < 3; dx++) {
                    const int o = p - dx;
                    if (o < 0 || o > 7) continue;
#pragma unroll
                    for (int q = 0; q < 3; q++) {
                        out[o][q] = bf_fma(xv[q], w[2][dx][q], dx == 0 ? accB[o][q] : out[o][q]);
                        accB[o][q] = bf_fma(xv[q], w[1][dx][q], dx == 0 ? accC[o][q] : accB[o][q]);
                        accC[o][q] = dx == 0 ? bf_mul(xv[q], w[0][dx][q]) : bf_fma(xv[q], w[0][dx][q], accC[o][q]);
                    }
                }
            }
            __syncwarp();
#pragma unroll
            for (int o = 0; o < 8; o++) {
                sts64(so + st64 + o * 16, out[o][0], out[o][1]);
                sts32(so + st32 + o * 16, out[o][2]);
            }
            __syncwarp();
            if (elect_one()) mbar_arrive(bars + (BAR_A - SM_BAR) + bo);
            if (fetch) request();
            advance();
            py += wk.dir;
        } while (py != py_end);
        if (((wk.rows - r) & ~8) == PREFETCH_ROWS) event(wk.rows - r == PREFETCH_ROWS);
    }
}

template <bool SCALED, int K0 = 0, int K1 = 3>
__device__ __forceinline__ void gelu_sq(uint32_t (&d)[24], uint32_t (&keep)[24], uint32_t sq_addr, uint32_t scale2) {
    pin(d);
#pragma unroll
    for (int k = K0; k < K1; k++) {
        uint32_t hs[4];
        lds128(hs[0], hs[1], hs[2], hs[3], sq_addr + k * SQ_ROW);
#pragma unroll
        for (int q = 0; q < 4; q++) {
            uint32_t g0 = gelu2(d[8 * k + 2 * q]), g1 = gelu2(d[8 * k + 2 * q + 1]);
            keep[8 * k + 2 * q] = g0;
            keep[8 * k + 2 * q + 1] = g1;
            if (SCALED) { g0 = h_mul(g0, scale2); g1 = h_mul(g1, scale2); }
            hs[q] = h_fma(g1, g1, h_fma(g0, g0, hs[q]));
        }
        sts128(sq_addr + k * SQ_ROW, hs[0], hs[1], hs[2], hs[3]);
    }
}
__device__ __forceinline__ void gelu_sq_reg(uint32_t (&d)[24], uint32_t (&hs)[12]) {
    pin(d);
#pragma unroll
    for (int q = 0; q < 12; q++) {
        const uint32_t g0 = gelu2(d[2 * q]), g1 = gelu2(d[2 * q + 1]);
        hs[q] = h_fma(g1, g1, h_fma(g0, g0, hs[q]));
    }
}
__device__ __forceinline__ void gelu_to(uint32_t (&g)[12], uint32_t (&d)[12]) {
    pin(d);
#pragma unroll
    for (int q = 0; q < 12; q++) g[q] = gelu2(d[q]);
    pin(g);
}
__device__ __forceinline__ void load_tile(uint32_t (&raw)[6][4], uint32_t addr) {
#pragma unroll
    for (int s = 0; s < 6; s++) ldsm4(raw[s], addr + s * 2 * A_LBO);
}
template <class F>
__device__ __forceinline__ void layer_norm(uint32_t (&raw)[6][4], uint64_t ones, F meanwhile) {
    constexpr int NS = 2;
    uint32_t sq[NS][4];
#pragma unroll
    for (int s = 0; s < 6; s++)
#pragma unroll
        for (int q = 0; q < 4; q++) sq[s % NS][q] = s < NS ? bf_mul(raw[s][q], raw[s][q]) : bf_fma(raw[s][q], raw[s][q], sq[s % NS][q]);
    float sum[4], ssq[4];
    wg_fence();
    wgmma_rowsum<0>(sum, raw[0], ones);
#pragma unroll
    for (int s = 1; s < 6; s++) wgmma_rowsum<1>(sum, raw[s], ones);
    wgmma_rowsum<0>(ssq, sq[0], ones);
#pragma unroll
    for (int s = 1; s < NS; s++) wgmma_rowsum<1>(ssq, sq[s], ones);
    wg_commit();
    meanwhile();
    wg_wait<0>();
    uint32_t sc[2], sh[2];
#pragma unroll
    for (int h = 0; h < 2; h++) {
        asm volatile("" : "+f"(sum[2 * h]), "+f"(ssq[2 * h])::"memory");
        constexpr float EPS = 1e-5f / (KZ * KZ);
        const float m = sum[2 * h] * (1.f / (CH * KZ));
        float rstd;
        asm("rsqrt.approx.ftz.f32 %0, %1;" : "=f"(rstd) : "f"(fmaxf(fmaf(-m, m, fmaf(ssq[2 * h], 1.f / (CH * KZ * KZ), EPS)), EPS)));
        sc[h] = pack_bf2(rstd, rstd);
        const float shift = sum[2 * h] * (-1.f / CH) * bf_hi(sc[h]);
        sh[h] = pack_bf2(shift, shift);
    }
#pragma unroll
    for (int s = 0; s < 6; s++)
#pragma unroll
        for (int q = 0; q < 4; q++) {
            const uint32_t v = bf_fma(raw[s][q], sc[q & 1], sh[q & 1]);
            raw[s][q] = pack_h2(bf_lo(v), bf_hi(v));
        }
}
struct Cursor {
    int slot;
    uint32_t par;
    __device__ __forceinline__ void advance(int n) {
        slot += n;
        if (slot >= NSLOT) { slot -= NSLOT; par ^= 1; }
    }
};
struct Descs {
    uint64_t w1[8][6];
    uint64_t w2[24];
    uint64_t ones;
};
template <int E0, int N>
__device__ __forceinline__ void gemm1_chunk(uint32_t (&d)[N], const uint32_t (&a)[6][4], const Descs& ds, int zero) {
#pragma unroll
    for (int s = 0; s < 6; s++) wgmma(d, a[s][0], a[s][1], a[s][2], a[s][3], ds.w1[E0 / 48][s], s ? 1 : zero);
}
template <int E0, int N>
__device__ __forceinline__ void gemm2_chunk(uint32_t (&acc)[24], const uint32_t (&g)[N], const Descs& ds) {
#pragma unroll
    for (int s = 0; s < N / 4; s++) wgmma(acc, g[4 * s], g[4 * s + 1], g[4 * s + 2], g[4 * s + 3], ds.w2[E0 / 16 + s], 1);
}

struct __align__(64) Params {
    Split sp;
    int zero;
    const __nv_bfloat16 *x, *dw, *w2, *gamma, *beta;
    __nv_bfloat16* out;
    Scratch* sc;
    Descs ds;
};

__global__ void __launch_bounds__(NTHREADS, 1)
block_kernel(const __grid_constant__ CUtensorMap tmap, const __grid_constant__ CUtensorMap tmap_w1, const __grid_constant__ Params pm) {
    const Split& sp = pm.sp;
    const Descs& ds = pm.ds;
    const int& zero = pm.zero;
    const __nv_bfloat16 *const &x = pm.x, *const &dw = pm.dw, *const &w2 = pm.w2, *const &gamma = pm.gamma, *const &beta = pm.beta;
    __nv_bfloat16* const& out = pm.out;
    Scratch* const& sc = pm.sc;
    extern __shared__ __align__(1024) uint8_t smem[];
    constexpr uint32_t sb = SB;
    const int tid = threadIdx.x;
    const Work wk = get_work(blockIdx.x, sp);
    constexpr uint32_t s_red = sb + SM_RED;
    if (smem_u32(smem) != SB) __trap();

    const int warp_id = __shfl_sync(~0u, tid >> 5, 0);
    PROF(0);
    const int cw = warp_id - 4, wgi = cw >> 2, w4 = warp_id & 3;
    if (elect_one()) {
        static_assert(3 * NSLOT * 4 == 8 + 4 * 16 && BAR_F == BAR_W + 48, "barrier shares");
        const int b = warp_id - 8;
        const uint32_t bar = b < 0 ? sb + BAR_X + warp_id * 8 : b < 7 ? sb + BAR_W + b * 8 : sb + BAR_PIN;
        mbar_init(bar, 1);
#pragma unroll
        for (int k = 0; k < 4; k++) mbar_init(sb + BAR_X + (8 + 4 * warp_id + k) * 8, 1);
        mbar_init(sb + BAR_R + warp_id * 8, 1);
        fence_async();
        if (b < 0) {
            issue_region(&tmap, sb + SM_RING + warp_id * REGION_BYTES, bar, w4, ((wk.tA & 511) + wk.dir * wgi) << 16 | (wk.tA >> 9) * TILE_W);
        } else if (b < 6) {
            mbar_expect_tx(bar, 64 * CH * 2);
            tma_2d(sb + SM_W2 + b * (64 * CH * 2), &tmap_w1, bar, 64 * b, 0);
        } else if (b == 6) {
            mbar_expect_tx(bar, 9 * CH * 2);
            bulk_load(sb + SM_FILTER, dw, 9 * CH * 2, bar);
        }
    }
    __syncwarp();
    const int ntiles = wk.nA + wk.nB;
    const int rank = (wgi + wk.lent + 2 * (ntiles - 1)) % NCONS | (wgi >> 2 & 3);
    const int spare = wk.rows % NSLOT, spare2 = spare == NSLOT - 1 ? 0 : spare + 1;
    const uint32_t sq_base = sb + (wgi < 0 ? SM_RING + spare * SLOT_BYTES : SM_SQ + rank * 2 * SQ_HALF);
    const uint32_t sq_upper = wgi < 0 ? (spare2 - spare) * SLOT_BYTES : SQ_HALF;
    const uint32_t bar_a = sb + BAR_A + w4 * 8, bar_e = sb + BAR_E + w4 * 8;
    const bool prepares = gridDim.x - blockIdx.x <= W2_GROUPS / 2, helps = !wk.lent && wk.index < 8 * LENT * sp.lenders;
    auto max_w1 = [&](uint32_t lane) { return __uint_as_float(__reduce_max_sync(~0u, lane < 4 * NCONS ? ldsi(s_red + RED_MAX + lane * 4) : 0)); };
    auto square_scale = [&](uint32_t lane) {
        const float f = pow2i(square_exp(bound_exp(max_w1(lane))));
        return pack_h2(f, f);
    };
    uint32_t a_addr, sq;
    const uint32_t sq_warp = sq_base + w4 * 512;
    auto set_addresses = [&]() {
        a_addr = opaque(sb + SM_RING + w4 * REGION_BYTES + ((tid >> 3) & 1) * A_SBO + ((tid >> 4) & 1) * A_LBO + (tid & 7) * 16);
        sq = opaque(sq_base + (tid & 127) * 16);
    };
    uint32_t turn, turn_end, so, so_sum, bo, bo_sum, off;
    auto set_run = [&](int j, int stop, int row) {
        const int slot = row % NSLOT, both = 2 * (row % 3) + 3;
        turn = opaque_uniform(row / 3);
        turn_end = opaque_uniform(row / 3 + (stop - j + NCONS - 1) / NCONS);
        so = opaque_uniform(slot * SLOT_BYTES);
        so_sum = opaque_uniform(both * SLOT_BYTES);
        bo = opaque_uniform(bar_a + slot * 32);
        bo_sum = opaque_uniform(2 * bar_a + both * 32);
        off = opaque_uniform(tile_offset(wk.tile(j)) + w4 * WARP_BYTES - sq_warp);
    };
    const int nrest = ntiles - 4;
    int jt;
    Cursor cur;
    int fast_from;
    if (warp_id < 4) {
        const int q = (gridDim.x - 1 - blockIdx.x) * 2 + (w4 >> 1);
        conv_producer(wk, &tmap, sb, warp_id, [&](bool second) {
            if (!second) {
                if (blockIdx.x == 0) {
#pragma unroll 1
                    for (int e = tid; e < EX; e += 128) *sc->sum(e) = 0;
                    sc->bias[tid] = 0.f;
                }
                if (blockIdx.x == 0 || wk.lent) signal(&sc->early);
            } else if (prepares || helps) {
                spin_until(&sc->early, (ldsi(s_red + RED_LAUNCH) + 1) * 4 * (sp.lenders + 1));
                if (elect_one()) {
                    if (helps) prefetch_l2(reinterpret_cast<const char*>(out) + sp.lent_off[wk.index / 8] + w4 * WARP_BYTES, WARP_BYTES);
                    if (prepares) { prefetch_l2(w2 + 8 * q * CH, 8 * CH * 2); prefetch_l2(beta + 8 * q, 16); }
                }
            }
        });
        set_addresses();
        const int lane = lane_id(), g = lane >> 2, t = lane & 3;
        const int piece = wk.index;
        uint32_t a[6][4];
        unsigned short bt_raw;
        if (prepares) {
#pragma unroll
            for (int m = 0; m < 3; m++) ldg128(a[m], w2 + (8 * q + g) * CH + 32 * m + 8 * t);
            asm volatile("ld.global.nc.u16 %0, [%1];" : "=h"(bt_raw) : "l"(beta + 8 * q + g) : "memory");
        } else if (helps) {
#pragma unroll
            for (int s = 0; s < 6; s++) ldg128(a[s], reinterpret_cast<const char*>(out) + sp.lent_off[piece / 8] + w4 * WARP_BYTES + lane * 16 + s * 512);
        }
        mbar_wait_once(bar_e + spare2 * 32, (wk.rows - 5) / NSLOT & 1);
        mbar_wait_once(bar_e + spare * 32, (wk.rows - 6) / NSLOT & 1);
        named_bar(1, 128);
#pragma unroll
        for (int k = 0; k < 6; k++) { sts128(sq + k * SQ_ROW, 0, 0, 0, 0); sts128(sq + sq_upper + k * SQ_ROW, 0, 0, 0, 0); }
        if (prepares) {
            const int half = w4 & 1;
            uint32_t rmax = 0;
#pragma unroll
            for (int m = 0; m < 3; m++) rmax = bf_absmax(bf_absmax(rmax, bf_absmax(a[m][0], a[m][1])), bf_absmax(a[m][2], a[m][3]));
            uint2 u = half ? make_uint2(a[0][2], a[0][3]) : make_uint2(a[0][0], a[0][1]), u1 = half ? make_uint2(a[1][2], a[1][3]) : make_uint2(a[1][0], a[1][1]);
            const uint2 u2 = half ? make_uint2(a[2][2], a[2][3]) : make_uint2(a[2][0], a[2][1]);
            const float bt = bf_lo(bt_raw);
            rmax = bf_absmax(rmax, __shfl_xor_sync(~0u, rmax, 1));
            rmax = bf_absmax(rmax, __shfl_xor_sync(~0u, rmax, 2));
            const float mx = fmaxf(fabsf(bf_lo(rmax)), fabsf(bf_hi(rmax))), rs = pow2i(row_exp(mx));
            if (t == 0 && !half) sc->w2max[8 * q + g] = mx;
#pragma unroll 1
            for (int m = 0; m < 3; m++, u = u1, u1 = u2) {
                float f[4];
#pragma unroll
                for (int k = 0; k < 2; k++) {
                    const float lo = bf_lo(k ? u.y : u.x), hi = bf_hi(k ? u.y : u.x);
                    sc->w2h[(4 * m + 2 * half + k) * 1536 + q * 32 + lane] = transpose8x8(pack_h2(lo * rs, hi * rs));
                    f[2 * k] = lo * bt;
                    f[2 * k + 1] = hi * bt;
                }
                const float r0 = (g & 2 ? f[2] : f[0]) + __shfl_xor_sync(~0u, g & 2 ? f[0] : f[2], 8);
                const float r1 = (g & 2 ? f[3] : f[1]) + __shfl_xor_sync(~0u, g & 2 ? f[1] : f[3], 8);
                float r = (g & 1 ? r1 : r0) + __shfl_xor_sync(~0u, g & 1 ? r0 : r1, 4);
                r += __shfl_xor_sync(~0u, r, 16);
                if (g < 4) atomicAdd(&sc->bias[32 * m + 8 * t + 4 * half + g], r);
            }
            asm volatile("fence.proxy.async.global;" ::: "memory");
            __syncwarp();
            named_arrive(3, 256);
        } else
        if (helps) {
            uint32_t d[12], gl[12];
            const uint32_t scale2 = square_scale(lane);
            wg_fence();
#pragma unroll
            for (int s = 0; s < 6; s++) wgmma(d, a[s][0], a[s][1], a[s][2], a[s][3], ds.w1[0][s] + piece % 8 * (6 * 1536 / 16), s ? 1 : 0);
            wg_commit();
            wg_wait<0>();
            gelu_to(gl, d);
#pragma unroll
            for (int s = 0; s < 3; s++) {
                sc->lent[((piece / 8 * 4 + w4) * 24 + piece % 8 * 3 + s) * 32 + lane] = make_uint4(gl[4 * s], gl[4 * s + 1], gl[4 * s + 2], gl[4 * s + 3]);
                uint32_t hs[2];
#pragma unroll
                for (int k = 0; k < 2; k++) {
                    const uint32_t g0 = h_mul(gl[4 * s + 2 * k], scale2), g1 = h_mul(gl[4 * s + 2 * k + 1], scale2);
                    hs[k] = h_fma(g1, g1, h_mul(g0, g0));
                }
                const int pair = piece % 4 * 3 + s;
                sts64(sq + (piece & 4 ? sq_upper : 0) + (pair >> 1) * SQ_ROW + (pair & 1) * 8, hs[0], hs[1]);
            }
        }
        jt = ntiles - 1;
        cur.slot = spare ? spare - 1 : NSLOT - 1;
        cur.par = (wk.rows - 1) / NSLOT & 1;
        fast_from = ntiles;
        turn = turn_end = so = so_sum = bo = bo_sum = off = rank;
    } else {
        set_addresses();
        if (wgi == NCONS - 1) named_arrive(4, 256);
        set_run(wk.lent + wgi, min(wk.nA, nrest), wk.lent + wgi + 2);
        jt = wgi < wk.lent ? wgi : wk.lent + wgi;
        cur = {2, 0};
        cur.advance(jt + (jt >= wk.nA ? 2 : 0));
        {
            const int ct = tid - 128, lane = tid & 31;
            const unsigned epoch = *reinterpret_cast<volatile unsigned*>(&sc->launch);
            const int r = lane & 7, mi = lane >> 3;
            const uint32_t src = sb + SM_W2 + (cw >> 1) * (64 * CH * 2) + r * 128 + ((((cw & 1) * 4 + mi) ^ r) * 16);
            const uint32_t dst = sb + SM_W1 + (4 * cw + mi) * 1536 + r * 16;
            const int code = row_code(wk, PREFETCH_ROWS - 1 + wgi);
            named_bar(0, NTHREADS);
            auto request = [&]() {
                if (elect_one())
                    issue_region(&tmap, sb + SM_RING + (PREFETCH_ROWS - 1 + wgi) * SLOT_BYTES + w4 * REGION_BYTES, sb + BAR_X + (cw + 8) * 8, w4, code);
                __syncwarp();
            };
#pragma unroll 1
            for (int k = 0; k < 2; k++) {
                if (wgi == k) request();
                mbar_wait_once(sb + BAR_W + (cw >> 1) * 8, 0);
            }
            uint32_t wmax[2] = {}, wsum[4] = {};
#pragma unroll 3
            for (int c = 0; c < 12; c++) {
                uint32_t u[4];
                ldsm4_t(u, src + c * 1024);
#pragma unroll
                for (int q = 0; q < 4; q++) {
                    wmax[q & 1] = bf_absmax(wmax[q & 1], u[q]);
                    wsum[q] = bf_fma(u[q], 0x3f803f80u, wsum[q]);
                    u[q] = pack_h2(__uint_as_float(u[q] * (65536 + zero)), bf_hi(u[q]));
                }
                stsm4(dst + c * 128, u[0], u[1], u[2], u[3]);
            }
            const float w1max = warp_absmax(bf_absmax(wmax[0], wmax[1]));
            if (lane == 0) sts32(s_red + RED_MAX + cw * 4, __float_as_uint(w1max));
            bool center = false;
#pragma unroll
            for (int q = 0; q < 4; q++) {
#pragma unroll
                for (int o = 1; o <= 2; o <<= 1) wsum[q] = bf_fma(__shfl_xor_sync(~0u, wsum[q], o), 0x3f803f80u, wsum[q]);
                center |= fabsf(bf_lo(wsum[q]) + bf_hi(wsum[q])) > (0.15f * CH) * w1max;
            }
            if (__builtin_expect(__any_sync(~0u, center), 0)) {
                float mean[4] = {};
#pragma unroll 1
                for (int pass = 0; pass < 2; pass++) {
                    float sum[4] = {};
#pragma unroll 1
                    for (int c = 0; c < 12; c++) {
                        uint32_t u[4];
                        ldsm4_t(u, src + c * 1024);
#pragma unroll
                        for (int q = 0; q < 4; q++) {
                            sum[q] += bf_lo(u[q]) + bf_hi(u[q]);
                            u[q] = pack_h2(bf_lo(u[q]) - mean[q], bf_hi(u[q]) - mean[q]);
                        }
                        stsm4(dst + c * 128, u[0], u[1], u[2], u[3]);
                    }
#pragma unroll
                    for (int q = 0; q < 4; q++) {
                        sum[q] += __shfl_xor_sync(~0u, sum[q], 1);
                        sum[q] += __shfl_xor_sync(~0u, sum[q], 2);
                        mean[q] = sum[q] * (1.f / CH);
                    }
                }
            }
            if (!(cw & 2)) {
#pragma unroll
                for (int c = 0; c < 12; c++) sts128(src + c * 1024, 0, 0, 0, 0);
            }
            if (ct < 32) sts32(sb + SM_ONES + ct * 4, 0x3f803f80u);
            if (ct == 0) sts32(s_red + RED_LAUNCH, epoch);
            fence_async();
            named_bar(2, CONS_THREADS);
            if (wgi == 2) request();
        }
        PROF(1);
        if (cur.par) mbar_wait_once(bar_a, 0);
        fast_from = wk.lent;
        if (!__all_sync(~0u, plain_squares(bound_exp(max_w1(lane_id()))))) {
            fast_from = ntiles;
#pragma unroll 1
            for (int q = 0; q < 6; q++) sts128(sq + SQ_HALF + q * SQ_ROW, 0, 0, 0, 0);
        }
    }
    uint32_t k1[24], k2[24], k3[24];
    uint32_t here;
    constexpr int SQC = 3 * SQ_ROW;
    auto store_at = [&](const uint32_t (&a)[6][4], uint32_t off) {
        char* ap = reinterpret_cast<char*>(out) + (off + sq);
#pragma unroll
        for (int s = 0; s < 6; s++) stg128(ap + s * 512, a[s]);
    };
    const uint32_t own_bar = 4 + wgi, next_bar = 4 + (wgi == NCONS - 1 ? 0 : wgi + 1);
    for (;;) {
        if (jt >= fast_from) {
            uint32_t hs2[12] = {}, hs3[12] = {};
            const uint32_t step = wk.dir * (NCONS * IMG_W * CH * 2);
            int second = wk.nB;
#pragma unroll 1
            for (;;) {
#pragma unroll 1
                while (turn != turn_end) {
                    uint32_t a[6][4], d0[24], d1[24], unused[24];
                    mbar_wait(bo, turn >> 1 & 1);
                    load_tile(a, a_addr + so);
                    layer_norm(a, ds.ones, [&]() { named_bar(own_bar, 256); });
                    wg_fence();
                    gemm1_chunk<0>(d0, a, ds, 0);
                    wg_commit();
                    gemm1_chunk<96>(d1, a, ds, 0);
                    wg_commit();
                    wg_wait<1>();
                    gelu_sq<false, 0, 1>(d0, unused, sq, 0);
                    gelu_sq<false, 1, 2>(d0, unused, sq, 0);
                    store_at(a, off);
                    gelu_sq<false, 2, 3>(d0, unused, sq, 0);
                    if (elect_one()) mbar_arrive(bo + (BAR_E - BAR_A));
                    wg_fence();
                    gemm1_chunk<192>(d0, a, ds, zero);
                    wg_commit();
                    named_arrive(next_bar, 256);
                    wg_wait<1>();
                    gelu_sq<false, 0, 1>(d1, unused, sq + SQC, 0);
                    gelu_sq<false, 1, 3>(d1, unused, sq + SQC, 0);
                    wg_fence();
                    gemm1_chunk<288>(d1, a, ds, zero);
                    wg_commit();
                    wg_wait<1>();
                    gelu_sq_reg(d0, hs2);
                    anchor(sq, hs2[8], hs2[9], hs2[10], hs2[11]);
                    wg_wait<0>();
                    gelu_sq_reg(d1, hs3);
                    so = so_sum - so;
                    bo = bo_sum - bo;
                    off += step;
                    turn++;
                }
                if (!second) break;
                const int j = ntiles - second + (rank + second + 2) % NCONS;
                second = 0;
                set_run(j, nrest, j + 4);
            }
            jt = nrest + rank;
            cur.slot = (bo - bar_a) >> 5;
            cur.par = turn >> 1 & 1;
#pragma unroll
            for (int k = 0; k < 3; k++) {
                sts128(sq + SQ_HALF + k * SQ_ROW, hs2[4 * k], hs2[4 * k + 1], hs2[4 * k + 2], hs2[4 * k + 3]);
                sts128(sq + SQ_HALF + SQC + k * SQ_ROW, hs3[4 * k], hs3[4 * k + 1], hs3[4 * k + 2], hs3[4 * k + 3]);
            }
        }
        const bool last = jt >= nrest;
        here = tile_offset(wk.tile(jt));
        if (last) {
            const uint32_t next = ldsi(sb + SM_TILES + rank * 4);
            if (elect_one()) {
                prefetch_l2(reinterpret_cast<const char*>(x) + here + w4 * WARP_BYTES, WARP_BYTES);
                if (rank == ORDER_P - 1) prefetch_l2(reinterpret_cast<const char*>(out) + next + w4 * WARP_BYTES, WARP_BYTES);
            }
        }
        uint32_t a[6][4], d0[24], d1[24], d3[24], k0[24];
        mbar_wait_once(bar_a + cur.slot * 32, cur.par);
        load_tile(a, a_addr + cur.slot * SLOT_BYTES);
        layer_norm(a, ds.ones, [&]() { if (jt >= wk.lent && wgi >= 0) named_bar(own_bar, 256); });
        if (!last) {
            store_at(a, here + w4 * WARP_BYTES - sq_warp);
            __syncwarp();
            if (elect_one()) mbar_arrive(bar_e + cur.slot * 32);
            if (jt < wk.lent) {
                jt += LENT;
                cur.advance(LENT);
                continue;
            }
        }
        wg_fence();
        gemm1_chunk<0>(d0, a, ds, 0);
        wg_commit();
        gemm1_chunk<96>(d1, a, ds, 0);
        wg_commit();
        const uint32_t scale2 = square_scale(lane_id());
        wg_wait<1>();
        gelu_sq<true>(d0, k0, sq, scale2);
        if (last) {
#pragma unroll
            for (int q = 0; q < 6; q++)
                sts128(sb + SM_RING + cur.slot * SLOT_BYTES + w4 * REGION_BYTES - sq_warp + sq + q * 512, k0[4 * q], k0[4 * q + 1], k0[4 * q + 2], k0[4 * q + 3]);
        }
        wg_fence();
        gemm1_chunk<192>(d0, a, ds, zero);
        wg_commit();
        if (jt + 2 < ntiles) named_arrive(next_bar, 256);
        wg_wait<1>();
        gelu_sq<true>(d1, k1, sq + SQC, scale2);
        wg_fence();
        gemm1_chunk<288>(d3, a, ds, 0);
        wg_commit();
        wg_wait<1>();
        gelu_sq<true>(d0, k2, sq + sq_upper, scale2);
        wg_wait<0>();
        gelu_sq<true>(d3, k3, sq + sq_upper + SQC, scale2);
        if (last) break;
        cur.advance(NCONS + ((jt < wk.nA && jt + NCONS >= wk.nA) ? 2 : 0));
        jt += NCONS;
    }
    const uint32_t lane = lane_id();
    uint32_t next_off = opaque_uniform(ldsi(sb + SM_TILES + rank * 4));
    const uint32_t s_fac = sb + SM_RING + spare * SLOT_BYTES + SQ_HALF;
    uint32_t inv_rho2;
    {
        const bool leader = rank == 0 && w4 == 0 && lane == 0;
        const int i0 = w4 * 32 + lane;
        float base[3], slope[3], reach[3], to_square;
        float2 bpair = make_float2(0.f, 0.f);
        unsigned epoch;
        if (rank == 0) {
            float gam[3], rmax[3];
#pragma unroll
            for (int m = 0; m < 3; m++) {
                unsigned short v;
                asm volatile("ld.global.nc.u16 %0, [%1];" : "=h"(v) : "l"(gamma + i0 + 128 * m) : "memory");
                gam[m] = bf_lo(v);
            }
            epoch = ldsi(s_red + RED_LAUNCH);
            if (prepares) {
                named_bar(3, 256);
                if (w4 == 1) signal(&sc->prep);
            }
            if (leader) {
                spin_until(&sc->prep, (epoch + 1) * (W2_GROUPS / 2));
                asm volatile("fence.proxy.async.global;" ::: "memory");
            }
            __syncwarp();
            named_bar(2, 128);
#pragma unroll
            for (int m = 0; m < 3; m++) rmax[m] = __ldcg(&sc->w2max[i0 + 128 * m]);
            if (i0 < 96) bpair = __ldcg(reinterpret_cast<const float2*>(&sc->bias[32 * (i0 % 24 >> 3) + 8 * (i0 / 24) + (i0 % 24 & 6)]));
            const float w1max = max_w1(lane);
            const float gbound = fmaxf(2.f * KZ * 9.7979590f * 192.f * w1max, 1.f) * 19.5959180f * INV_2KZ;
            const unsigned fixed = __reduce_max_sync(~0u, __float_as_uint(fmaf(gbound, fmaxf(fmaxf(rmax[0], rmax[1]), rmax[2]), fmaxf(fabsf(bpair.x), fabsf(bpair.y)))));
            if (lane == 0) sts32(s_red + 96 + w4 * 4, fixed);
#pragma unroll
            for (int m = 0; m < 3; m++) {
                base[m] = rmax[m] > 0.f ? pow2i(-row_exp(rmax[m])) * (INV_2KZ * CUT_GAIN) : 0.f;
                slope[m] = base[m] * gam[m];
                reach[m] = fabsf(gam[m]) * rmax[m] * gbound;
            }
            to_square = pow2i(-sum_exp(bound_exp(w1max))) * (INV_2KZ * INV_2KZ / 256);
        }
        if (rank >= 2) {
            named_arrive(12 + rank, CONS_THREADS);
        } else {
            const int rw = rank * 4 + w4, g = lane >> 2, t = lane & 3;
            const uint32_t pick = (g & 1) == (t & 1) ? (g & 2 ? 0x3c000000u : 0x00003c00u) : 0;
            const int be = bound_exp(max_w1(lane));
            const float to_fixed = pow2i(sum_exp(be) - 2 * square_exp(be));
            unsigned long long* dst = sc->sum(64 * rw + 32 * (t >> 1) + 8 * (g >> 1) + 2 * (t & 1) + (g & 1));
            const uint32_t rows = sb + (rw * 2 + (lane >> 3 & 1)) * SQ_ROW + ((lane >> 4) * 8 + (lane & 7)) * 16;
            float f[2][4] = {};
            named_bar(13, 256);
#pragma unroll 1
            for (int i = 0; i < 4; i++) {
                if (i == 2) {
                    named_bar(13, 256);
                    if (leader) {
                        fence_async();
                        mbar_expect_tx(sb + BAR_W, 4 * SQ_HALF);
                        bulk_load(sb + SM_W2, sc->w2h, 4 * SQ_HALF, sb + BAR_W);
                    }
                    __syncwarp();
                }
                const uint32_t src = rows + (i < NCONS ? SM_SQ + i * 2 * SQ_HALF : rw < 3 ? SM_RING + spare * SLOT_BYTES : SM_RING + spare2 * SLOT_BYTES - SQ_HALF);
                if (i >= 2) named_bar(12 + i, CONS_THREADS);
                if (rw < 6) {
#pragma unroll
                    for (int r = 0; r < 8; r++) {
                        uint32_t u[4];
                        ldsm4_t(u, src + r * 256);
                        asm volatile("mma.sync.aligned.m16n8k16.row.col.f32.f16.f16.f32 {%0, %1, %2, %3}, {%4, %5, %6, %7}, {%8, %8}, {%0, %1, %2, %3};"
                                     : "+f"(f[r & 1][0]), "+f"(f[r & 1][1]), "+f"(f[r & 1][2]), "+f"(f[r & 1][3])
                                     : "r"(u[0]), "r"(u[1]), "r"(u[2]), "r"(u[3]), "r"(pick));
                    }
                }
            }
            if (rw < 6) {
#pragma unroll
                for (int r = 0; r < 2; r++)
                    atomicAdd(dst + r * 32, __float2ull_rn(fminf((t < 2 ? f[0][r] + f[1][r] : f[0][r + 2] + f[1][r + 2]) * to_fixed, 0x1p47f)) << 8 | 1);
            }
            PROF(2);
            named_bar(13, 256);
            if (leader) {
                fence_async();
                mbar_expect_tx(sb + BAR_W + 8, 2 * SQ_HALF);
                bulk_load(sb + SM_W2 + 4 * SQ_HALF, reinterpret_cast<const char*>(sc->w2h) + 4 * SQ_HALF, 2 * SQ_HALF, sb + BAR_W + 8);
            }
            if (helps && rw == 7) signal(&sc->lent_out);
        }
        if (rank == 0) {
            const uint32_t own_sum = (i0 >> 2) * 256 + (i0 & 3) * 8, own_fac = s_fac + i0 * 2;
            auto peek = [&](const void* p) {
                unsigned long long v;
                asm volatile("ld.relaxed.gpu.global.u64 %0, [%1];" : "=l"(v) : "l"(p) : "memory");
                return v;
            };
            const char* mine = reinterpret_cast<const char*>(sc->sums) + own_sum;
            unsigned n = 0;
            while (((unsigned)peek(sc->sum((blockIdx.x * 4 + w4) % (EX / 4) * 4)) & 255u) != gridDim.x)
                if (++n > SPIN_LIMIT) __trap();
            unsigned long long sum[3];
            for (;;) {
                bool all = true;
#pragma unroll
                for (int m = 0; m < 3; m++) {
                    sum[m] = peek(mine + m * (32 * 256));
                    all &= ((unsigned)sum[m] & 255u) == gridDim.x;
                }
                if (__all_sync(~0u, all)) break;
                if (++n > SPIN_LIMIT) __trap();
            }
            PROF(3);
            float gx[3];
#pragma unroll
            for (int m = 0; m < 3; m++) asm("sqrt.approx.ftz.f32 %0, %1;" : "=f"(gx[m]) : "f"(fmaf(__ull2float_rn(sum[m]), to_square, 1e-6f)));
            float tot = gx[0] + gx[1] + gx[2];
#pragma unroll
            for (int o = 16; o >= 1; o >>= 1) tot += __shfl_xor_sync(~0u, tot, o);
            const unsigned vwarp = __reduce_max_sync(~0u, __float_as_uint(fmaxf(fmaxf(reach[0] * gx[0], reach[1] * gx[1]), reach[2] * gx[2])));
            if (lane == 0) { sts32(s_red + 64 + w4 * 4, __float_as_uint(tot)); sts32(s_red + 80 + w4 * 4, vwarp); }
            named_bar(2, 128);
            uint32_t u[4], v[4], w[4];
            lds128(u[0], u[1], u[2], u[3], s_red + 64);
            lds128(v[0], v[1], v[2], v[3], s_red + 80);
            lds128(w[0], w[1], w[2], w[3], s_red + 96);
            tot = (__uint_as_float(u[0]) + __uint_as_float(u[1])) + (__uint_as_float(u[2]) + __uint_as_float(u[3]));
            const float vmax = __uint_as_float(max(max(v[0], v[1]), max(v[2], v[3]))), fmax2 = __uint_as_float(max(max(w[0], w[1]), max(w[2], w[3])));
            float inv_mean;
            asm("rcp.approx.ftz.f32 %0, %1;" : "=f"(inv_mean) : "f"(fmaf(tot, 1.f / EX, 1e-6f)));
            const int rho_e = 14 - ilog2f(fmaf(vmax, inv_mean, 2.f * fmax2));
            const float rho = pow2i(rho_e), inv_rho = pow2i(-rho_e);
            inv_rho2 = pack_bf2(inv_rho, inv_rho);
#pragma unroll
            for (int m = 0; m < 3; m++) {
                const float f = fmaf(slope[m] * gx[m], inv_mean, base[m]) * rho;
                asm volatile("st.shared.u16 [%0], %1;" ::"r"(own_fac + 256 * m), "h"((unsigned short)pack_h2(f, 0.f)) : "memory");
            }
            if (i0 < 96) sts32(sb + SM_BIASH + i0 * 4, pack_h2(bpair.x * rho, bpair.y * rho));
            if (i0 == 96) sts32(s_red + RED_INV_RHO, inv_rho2);
            named_arrive(12, NTHREADS);
            if (blockIdx.x == 0 && leader) sc->launch = epoch + 1;
            if (wk.lent) spin_until(&sc->lent_out, (epoch + 1) * 8 * LENT * sp.lenders);
        } else {
            const int rw = rank * 4 - 4 + w4;
            const uint32_t row = sb + SM_W2 + rw * 512 + lane * 16;
            uint32_t u[W2_EARLY][4], f2[4];
#pragma unroll
            for (int nb = 0; nb < W2_EARLY; nb++) {
                if (nb % 8 == 0) mbar_wait_once(sb + BAR_W + nb, 1);
                lds128(u[nb][0], u[nb][1], u[nb][2], u[nb][3], row + nb * 6144);
            }
            named_bar(12, NTHREADS);
            PROF(3);
            lds128(f2[0], f2[1], f2[2], f2[3], s_fac + rw * 64 + (lane >> 3) * 16);
            lds32(inv_rho2, s_red + RED_INV_RHO);
#pragma unroll
            for (int nb = 0; nb < 12; nb++) {
                uint32_t v[4];
                if (nb < W2_EARLY) { v[0] = u[nb % W2_EARLY][0]; v[1] = u[nb % W2_EARLY][1]; v[2] = u[nb % W2_EARLY][2]; v[3] = u[nb % W2_EARLY][3]; }
                else lds128(v[0], v[1], v[2], v[3], row + nb * 6144);
                sts128(row + nb * 6144, h_cut8(h_mul(v[0], f2[0])), h_cut8(h_mul(v[1], f2[1])), h_cut8(h_mul(v[2], f2[2])), h_cut8(h_mul(v[3], f2[3])));
            }
            fence_async();
            named_arrive(8, NTHREADS);
        }
    }
    uint32_t a[6][4], acc[24], rpar = 0, tile_off = here;
    const uint32_t bias_addr = sb + SM_BIASH + (lane & 3) * 96, lane16 = lane * 16, lane_off = ((lane >> 2) * CH + 8 * (lane & 3)) * 2;
    const uint32_t stage = sb + SM_RING + (spare + rank) % NSLOT * SLOT_BYTES + w4 * WARP_BYTES, bar_r = sb + BAR_R + warp_id * 8;
    auto load_bias = [&]() {
#pragma unroll
        for (int q = 0; q < 6; q++) lds128(acc[4 * q], acc[4 * q + 1], acc[4 * q + 2], acc[4 * q + 3], bias_addr + q * 16);
    };
    auto load_frags = [&]() {
#pragma unroll
        for (int s = 0; s < 6; s++) ldg128(a[s], reinterpret_cast<const char*>(out) + next_off + w4 * WARP_BYTES + lane16 + s * 512);
    };
    auto stage_x = [&]() {
        if (elect_one()) {
            mbar_expect_tx(bar_r, WARP_BYTES);
            bulk_load_stream(stage, reinterpret_cast<const char*>(x) + tile_off + w4 * WARP_BYTES, WARP_BYTES, bar_r);
        }
    };
    {
        named_bar(8 + rank, rank ? 256 : NTHREADS);
        if (rank == 0) PROF(4);
        load_bias();
        pin(k1); pin(k2); pin(k3);
        wg_fence();
        gemm2_chunk<288>(acc, k3, ds);
        wg_commit();
        gemm2_chunk<96>(acc, k1, ds);
        wg_commit();
        gemm2_chunk<192>(acc, k2, ds);
        wg_commit();
        stage_x();
        wg_wait<2>();
        uint32_t k0[24];
#pragma unroll
        for (int q = 0; q < 6; q++)
            lds128(k0[4 * q], k0[4 * q + 1], k0[4 * q + 2], k0[4 * q + 3], sb + SM_RING + cur.slot * SLOT_BYTES + w4 * REGION_BYTES + lane16 + q * 512);
        pin(k0);
        wg_fence();
        gemm2_chunk<0>(acc, k0, ds);
        wg_commit();
        if (rank < NCONS) named_arrive(9 + rank, 256);
        wg_wait<2>();
        load_frags();
        if (lane16 == 0) mbar_arrive(sb + BAR_PIN);
        mbar_wait(bar_r, rpar);
        wg_wait<0>();
    }
    auto lent = [&](uint32_t entry) { return &sc->lent[((wk.index * LENT + (entry & 3) - 1) * 4 + w4) * (24 * 32)]; };
    for (jt = rank - 4; jt < nrest; jt += 4) {
        if (jt >= zero) {
        tile_off = next_off;
        lds32(next_off, sb + SM_TILES + (jt + 4) * 4);
        if (tile_off & 3) {
            const uint4* src = lent(tile_off) + lane;
            tile_off &= ~3u;
            next_off = __shfl_sync(~0u, next_off, 0);
            stage_x();
            if (elect_one()) prefetch_l2(reinterpret_cast<const char*>(out) + next_off + w4 * WARP_BYTES, WARP_BYTES);
            load_bias();
#pragma unroll 1
            for (int half = 0; half < 2; half++, src += 12 * 32) {
                uint32_t gl[48];
#pragma unroll
                for (int s = 0; s < 12; s++) ldg128(reinterpret_cast<uint32_t (&)[4]>(gl[4 * s]), src + s * 32);
                if (!half) {
                    named_bar(4 + rank, 256);
                    named_arrive(4 + ((rank + 1) & 3), 256);
                }
                pin(gl);
                wg_fence();
#pragma unroll
                for (int s = 0; s < 12; s++) wgmma(acc, gl[4 * s], gl[4 * s + 1], gl[4 * s + 2], gl[4 * s + 3], ds.w2[12 * half + s], 1);
                wg_commit();
                wg_wait<0>();
            }
            load_frags();
            mbar_wait(bar_r, rpar);
        } else {
            uint32_t d0[12], d1[12], g0[12], g1[12];
            next_off = __shfl_sync(~0u, next_off, 0);
            const bool more = jt + 4 < nrest && !(next_off & 3);
            load_bias();
            wg_fence();
            gemm1_chunk<0>(d0, a, ds, 0);
            wg_commit();
            if (jt) named_bar(4 + rank, 256);
            gemm1_chunk<48>(d1, a, ds, 0);
            wg_commit();
            wg_wait<1>();
#define CNX_STEP(C, D, G)                                                   \
    gelu_to(G, D);                                                          \
    wg_fence();                                                             \
    if (C < 6) gemm1_chunk<48 * (C < 6 ? C + 2 : 0)>(D, a, ds, zero);      \
    gemm2_chunk<48 * C>(acc, G, ds);                                       \
    wg_commit();                                                            \
    if (C == 1 && jt + 1 < nrest) named_arrive(4 + ((rank + 1) & 3), 256); \
    wg_wait<(C < 7 ? 1 : 0)>();
            CNX_STEP(0, d0, g0)
            stage_x();
            if (elect_one()) {
                if (more) prefetch_l2(reinterpret_cast<const char*>(out) + next_off + w4 * WARP_BYTES, WARP_BYTES);
                else if (next_off & 3) prefetch_l2(lent(next_off), 24 * 32 * 16);
            }
            CNX_STEP(1, d1, g1)
            CNX_STEP(2, d0, g0)
            CNX_STEP(3, d1, g1)
            CNX_STEP(4, d0, g0)
            CNX_STEP(5, d1, g1)
            CNX_STEP(6, d0, g0)
#pragma unroll
            for (int s = 0; s < 6; s++) ldg128_if(more, a[s], reinterpret_cast<const char*>(out) + next_off + w4 * WARP_BYTES + lane16 + s * 512);
            if (lane16 == 0) mbar_arrive(sb + BAR_PIN);
            mbar_wait(bar_r, rpar);
            CNX_STEP(7, d1, g1)
#undef CNX_STEP
        }
        }
        {
            pin(acc);
            rpar ^= 1;
            uint4* op = reinterpret_cast<uint4*>(reinterpret_cast<char*>(out) + tile_off + w4 * WARP_BYTES + lane_off);
#pragma unroll
            for (int h = 0; h < 2; h++)
#pragma unroll
                for (int m = 0; m < 3; m++) {
                    uint32_t xin[4], o[4];
                    lds128(xin[0], xin[1], xin[2], xin[3], stage + lane_off + h * 1536 + m * 64);
#pragma unroll
                    for (int q = 0; q < 4; q++) {
                        const uint32_t v = acc[2 * (4 * m + q) + h];
                        o[q] = bf_fma(pack_bf2(h_lo(v), h_hi(v)), inv_rho2, xin[q]);
                    }
                    __stcs(op + h * 96 + m * 4, make_uint4(o[0], o[1], o[2], o[3]));
                }
            __syncwarp();
        }
    }
    PROF(5);
}

}

typedef CUresult (*EncodeTiledFn)(CUtensorMap*, CUtensorMapDataType, cuuint32_t, void*, const cuuint64_t*, const cuuint64_t*,
                                  const cuuint32_t*, const cuuint32_t*, CUtensorMapInterleave, CUtensorMapSwizzle,
                                  CUtensorMapL2promotion, CUtensorMapFloatOOBfill);

extern "C" void kernel_launch(void* const* d_in, const int* in_sizes, int n_in, void* d_out, int out_size) {
    using namespace cnx;
    static EncodeTiledFn encode = nullptr;
    static int num_sms = 0;
    static Scratch* scratch = nullptr;
    if (!encode) {
        void* fn = nullptr;
        cudaDriverEntryPointQueryResult qr;
        cudaGetDriverEntryPoint("cuTensorMapEncodeTiled", &fn, cudaEnableDefault, &qr);
        encode = (EncodeTiledFn)fn;
        cudaGetSymbolAddress((void**)&scratch, g_scratch);
        int dev = 0;
        cudaGetDevice(&dev);
        cudaDeviceGetAttribute(&num_sms, cudaDevAttrMultiProcessorCount, dev);
        if (num_sms > MAX_CTAS) num_sms = MAX_CTAS;
        cudaFuncSetAttribute(block_kernel, cudaFuncAttributeMaxDynamicSharedMemorySize, SM_TOTAL);
    }
    CUtensorMap tm;
    cuuint64_t dims[3] = {(cuuint64_t)CH, (cuuint64_t)IMG_W, (cuuint64_t)IMG_H};
    cuuint64_t strides[2] = {(cuuint64_t)CH * 2, (cuuint64_t)CH * 2 * IMG_W};
    cuuint32_t box[3] = {(cuuint32_t)CH, (cuuint32_t)REGION_PX, 1};
    cuuint32_t estr[3] = {1, 1, 1};
    encode(&tm, CU_TENSOR_MAP_DATA_TYPE_BFLOAT16, 3, d_in[0], dims, strides, box, estr, CU_TENSOR_MAP_INTERLEAVE_NONE,
           CU_TENSOR_MAP_SWIZZLE_NONE, CU_TENSOR_MAP_L2_PROMOTION_L2_128B, CU_TENSOR_MAP_FLOAT_OOB_FILL_NONE);
    Params pm = {};
    Descs& ds = pm.ds;
    for (int c = 0; c < 8; c++)
        for (int k = 0; k < 6; k++) ds.w1[c][k] = make_desc(SB + SM_W1 + c * 6 * 1536 + k * 256, 128, 1536);
    for (int k = 0; k < 24; k++) ds.w2[k] = make_desc(SB + SM_W2 + k * 256, 128, 6144);
    ds.ones = make_desc(SB + SM_ONES, 0, 0);
    CUtensorMap tw;
    cuuint64_t wdims[2] = {(cuuint64_t)EX, (cuuint64_t)CH};
    cuuint64_t wstrides[1] = {(cuuint64_t)EX * 2};
    cuuint32_t wbox[2] = {64, (cuuint32_t)CH};
    encode(&tw, CU_TENSOR_MAP_DATA_TYPE_BFLOAT16, 2, d_in[2], wdims, wstrides, wbox, estr, CU_TENSOR_MAP_INTERLEAVE_NONE,
           CU_TENSOR_MAP_SWIZZLE_128B, CU_TENSOR_MAP_L2_PROMOTION_L2_128B, CU_TENSOR_MAP_FLOAT_OOB_FILL_NONE);
    Split& sp = pm.sp;
    sp = {NTILES / num_sms, NTILES % num_sms, 1, 1 << 16, 0, {}};
    if (sp.per_cta + 9 > MAX_ROWS) return;
    if (sp.extra && sp.extra * (8 * LENT + 1) + W2_GROUPS / 2 <= num_sms && sp.per_cta >= 5 * LENT + 8) {
        sp.period = num_sms / sp.extra;
        sp.inv_period = 65535 / sp.period + 1;
        sp.lenders = sp.extra;
        for (int l = 0; l < sp.extra; l++) {
            const Work w = get_work((l + 1) * sp.period - sp.period / 2 - 1, sp);
            for (int e = 0; e < LENT; e++) sp.lent_off[l * LENT + e] = tile_offset(w.tile(e));
            if (w.nA < 2 * LENT) sp.lenders = 0;
        }
    }
    pm.x = (const __nv_bfloat16*)d_in[0];
    pm.dw = (const __nv_bfloat16*)d_in[1];
    pm.w2 = (const __nv_bfloat16*)d_in[3];
    pm.gamma = (const __nv_bfloat16*)d_in[4];
    pm.beta = (const __nv_bfloat16*)d_in[5];
    pm.out = (__nv_bfloat16*)d_out;
    pm.sc = scratch;
    block_kernel<<<num_sms, NTHREADS, SM_TOTAL>>>(tm, tw, pm);
}
```

```cpp
#include <cuda_runtime.h>
#include <cuda_bf16.h>
#include <cuda_fp16.h>
#include <cuda.h>
#include <stdint.h>

namespace cnx {

constexpr int IMG_H = 512, IMG_W = 512, CH = 96, EX = 384;
constexpr int TILE_W = 64;
constexpr int NTILES = (IMG_W / TILE_W) * IMG_H;
constexpr int NSLOT = 6;
constexpr int REGION_PX = 18;
constexpr int REGION_BYTES = REGION_PX * CH * 2;
constexpr int SLOT_BYTES = 4 * REGION_BYTES;
constexpr int A_LBO = 144, A_SBO = 12 * A_LBO;
constexpr int PREFETCH_ROWS = 3;
constexpr int NCONS = 3;
constexpr int CONS_THREADS = 128 * NCONS;
constexpr int NTHREADS = 128 + CONS_THREADS;
constexpr int MAX_ROWS = 52;
constexpr int TILE_BYTES = TILE_W * CH * 2, WARP_BYTES = TILE_BYTES / 4;
constexpr int ORDER_P = 3;
constexpr int W2_EARLY = 9;
static_assert(MAX_ROWS <= 128, "one table entry per producer thread");
static_assert(2 * A_SBO == REGION_BYTES && REGION_BYTES % 128 == 0, "region layout");

constexpr uint32_t SB = 1024;
constexpr int SM_W1 = 0;
constexpr int SM_W2 = SM_W1 + CH * EX * 2;
constexpr int SM_RING = SM_W2 + CH * EX * 2;
constexpr int SM_BIASH = SM_RING + NSLOT * SLOT_BYTES;
constexpr int SM_RED = SM_BIASH + 384;
constexpr int RED_MAX = 0, RED_LAUNCH = 48, RED_INV_RHO = 52;
constexpr int SM_TILES = SM_RED + 256;
constexpr int SM_ONES = SM_TILES + MAX_ROWS * 4;
constexpr int SM_BAR = SM_ONES + 128;
constexpr int BAR_X = SM_BAR;
constexpr int BAR_A = BAR_X + NSLOT * 4 * 8;
constexpr int BAR_E = BAR_A + NSLOT * 4 * 8;
constexpr int BAR_PIN = BAR_E + NSLOT * 4 * 8;
constexpr int BAR_W = BAR_PIN + 8;
constexpr int BAR_F = BAR_W + 6 * 8;
constexpr int BAR_R = BAR_F + 8;
constexpr int SM_TOTAL = BAR_R + 16 * 8;
constexpr int SM_FILTER = SM_RING + (NSLOT - 1) * SLOT_BYTES + 9 * 128;
constexpr int SM_SQ = SM_W2;
constexpr int SQ_ROW = 128 * 16, SQ_HALF = 6 * SQ_ROW;
static_assert(SM_ONES % 16 == 0 && SM_TOTAL <= 232448, "shared memory budget");

constexpr float KZ = 0.3292034911525734f;
constexpr uint32_t GELU_C2 = 0x40d940d9u;
constexpr float INV_2KZ = 0.5f / KZ;
constexpr unsigned SPIN_LIMIT = 1u << 19;

constexpr int MAX_CTAS = 255;
constexpr int W2_GROUPS = EX / 8;
constexpr int LENT = 3, MAX_LENDERS = MAX_CTAS / (8 * LENT + 1);
struct Scratch {
    uint32_t w2h[EX * CH / 2];
    float w2max[EX];
    float bias[CH + 32];
    unsigned long long sums[EX / 4][32];
    __device__ __forceinline__ unsigned long long* sum(int e) { return &sums[e >> 2][e & 3]; }
    uint4 lent[MAX_LENDERS * LENT * 8 * 4 * 3 * 32];
    unsigned launch, pad0[31], early, pad1[31], prep, pad2[31], lent_out, pad3[31];
};
__device__ __align__(128) Scratch g_scratch;

#define PROF(k)

__device__ __forceinline__ uint32_t smem_u32(const void* p) { return (uint32_t)__cvta_generic_to_shared(p); }
__device__ __forceinline__ void mbar_init(uint32_t bar, uint32_t cnt) {
    asm volatile("mbarrier.init.shared::cta.b64 [%0], %1;" ::"r"(bar), "r"(cnt) : "memory");
}
__device__ __forceinline__ void mbar_arrive(uint32_t bar) {
    asm volatile("mbarrier.arrive.shared::cta.b64 _, [%0];" ::"r"(bar) : "memory");
}
__device__ __forceinline__ void mbar_expect_tx(uint32_t bar, uint32_t bytes) {
    asm volatile("mbarrier.arrive.expect_tx.shared::cta.b64 _, [%0], %1;" ::"r"(bar), "r"(bytes) : "memory");
}
__device__ __forceinline__ bool mbar_try(uint32_t bar, uint32_t par) {
    uint32_t ok;
    asm volatile("{\n.reg .pred p;\nmbarrier.try_wait.parity.shared::cta.b64 p, [%1], %2;\nselp.u32 %0, 1, 0, p;\n}\n"
                 : "=r"(ok) : "r"(bar), "r"(par) : "memory");
    return ok != 0;
}
__device__ __forceinline__ void mbar_wait(uint32_t bar, uint32_t par) {
    unsigned n = 0;
    while (!mbar_try(bar, par)) {
        if (++n > SPIN_LIMIT) __trap();
    }
}
__device__ __forceinline__ void mbar_wait_once(uint32_t bar, uint32_t par) {
    unsigned n = 0;
    bool ok;
#pragma unroll 1
    do {
        ok = mbar_try(bar, par);
        if (++n > SPIN_LIMIT) __trap();
    } while (!ok);
}
__device__ __forceinline__ bool elect_one() {
    uint32_t ok;
    asm volatile("{\n.reg .pred p;\nelect.sync _|p, 0xffffffff;\nselp.u32 %0, 1, 0, p;\n}\n" : "=r"(ok));
    return ok != 0;
}
__device__ __forceinline__ uint32_t opaque(uint32_t v) { return __shfl_sync(~0u, v, threadIdx.x & 31); }
__device__ __forceinline__ uint32_t lane_id() { uint32_t v; asm volatile("mov.u32 %0, %%laneid;" : "=r"(v)); return v; }
__device__ __forceinline__ uint32_t opaque_uniform(uint32_t v) { return __shfl_sync(~0u, v, 0); }
__device__ __forceinline__ void named_bar(int id, int n) { asm volatile("bar.sync %0, %1;" ::"r"(id), "r"(n) : "memory"); }
__device__ __forceinline__ void named_arrive(int id, int n) { asm volatile("bar.arrive %0, %1;" ::"r"(id), "r"(n) : "memory"); }
__device__ __forceinline__ void fence_async() { asm volatile("fence.proxy.async.shared::cta;" ::: "memory"); }
constexpr uint64_t EVICT_FIRST = 0x12F0000000000000ull;
__device__ __forceinline__ void tma_row(uint32_t dst, const CUtensorMap* tm, uint32_t bar, int x, int y) {
    asm volatile("cp.async.bulk.tensor.3d.shared::cluster.global.mbarrier::complete_tx::bytes.L2::cache_hint [%0], [%1, {%3, %4, %5}], [%2], %6;"
                 ::"r"(dst), "l"(tm), "r"(bar), "r"(0), "r"(x), "r"(y), "l"(EVICT_FIRST) : "memory");
}
__device__ __forceinline__ void bulk_load_stream(uint32_t dst, const void* src, uint32_t bytes, uint32_t bar) {
    asm volatile("cp.async.bulk.shared::cluster.global.mbarrier::complete_tx::bytes.L2::cache_hint [%0], [%1], %2, [%3], %4;"
                 ::"r"(dst), "l"(src), "r"(bytes), "r"(bar), "l"(EVICT_FIRST) : "memory");
}
__device__ __forceinline__ void prefetch_l2(const void* src, uint32_t bytes) {
    asm volatile("cp.async.bulk.prefetch.L2.global [%0], %1;" ::"l"(src), "r"(bytes) : "memory");
}
__device__ __forceinline__ void tma_2d(uint32_t dst, const CUtensorMap* tm, uint32_t bar, int x, int y) {
    asm volatile("cp.async.bulk.tensor.2d.shared::cluster.global.mbarrier::complete_tx::bytes [%0], [%1, {%3, %4}], [%2];"
                 ::"r"(dst), "l"(tm), "r"(bar), "r"(x), "r"(y) : "memory");
}
__device__ __forceinline__ void bulk_load(uint32_t dst, const void* src, uint32_t bytes, uint32_t bar) {
    asm volatile("cp.async.bulk.shared::cluster.global.mbarrier::complete_tx::bytes [%0], [%1], %2, [%3];"
                 ::"r"(dst), "l"(src), "r"(bytes), "r"(bar) : "memory");
}
__device__ __forceinline__ void wg_fence() { asm volatile("wgmma.fence.sync.aligned;" ::: "memory"); }
__device__ __forceinline__ void wg_commit() { asm volatile("wgmma.commit_group.sync.aligned;" ::: "memory"); }
template <int N> __device__ __forceinline__ void wg_wait() { asm volatile("wgmma.wait_group.sync.aligned %0;" ::"n"(N) : "memory"); }
template <int N> __device__ __forceinline__ void pin(uint32_t (&d)[N]) {
#pragma unroll
    for (int q = 0; q < N; q++) asm volatile("" : "+r"(d[q])::"memory");
}
__device__ __forceinline__ void stg128(void* p, const uint32_t (&v)[4]) {
    asm volatile("st.global.v4.u32 [%0], {%1, %2, %3, %4};" ::"l"(p), "r"(v[0]), "r"(v[1]), "r"(v[2]), "r"(v[3]) : "memory");
}
__device__ __forceinline__ void ldg128(uint32_t (&v)[4], const void* p) {
    asm volatile("ld.global.L1::no_allocate.v4.u32 {%0, %1, %2, %3}, [%4];" : "=r"(v[0]), "=r"(v[1]), "=r"(v[2]), "=r"(v[3]) : "l"(p) : "memory");
}
__device__ __forceinline__ void ldg128_if(bool on, uint32_t (&v)[4], const void* p) {
    asm volatile("{\n.reg .pred p;\nsetp.ne.b32 p, %5, 0;\n@p ld.global.L1::no_allocate.v4.u32 {%0, %1, %2, %3}, [%4];\n}\n"
                 : "+r"(v[0]), "+r"(v[1]), "+r"(v[2]), "+r"(v[3]) : "l"(p), "r"((int)on) : "memory");
}
__host__ __device__ constexpr uint64_t make_desc(uint32_t addr, uint32_t lbo, uint32_t sbo) {
    return (uint64_t)((addr & 0x3FFFF) >> 4) | ((uint64_t)(lbo >> 4) << 16) | ((uint64_t)(sbo >> 4) << 32);
}
__device__ __forceinline__ void wgmma(uint32_t (&d)[12], uint32_t a0, uint32_t a1, uint32_t a2, uint32_t a3, uint64_t db, int acc) {
    asm volatile("{\n.reg .pred p;\nsetp.ne.b32 p, %17, 0;\n"
                 "wgmma.mma_async.sync.aligned.m64n48k16.f16.f16.f16 "
                 "{%0, %1, %2, %3, %4, %5, %6, %7, %8, %9, %10, %11}, "
                 "{%12, %13, %14, %15}, %16, p, 1, 1, 0;\n}\n"
                 : "+r"(d[0]), "+r"(d[1]), "+r"(d[2]), "+r"(d[3]), "+r"(d[4]), "+r"(d[5]), "+r"(d[6]), "+r"(d[7]), "+r"(d[8]), "+r"(d[9]), "+r"(d[10]), "+r"(d[11])
                 : "r"(a0), "r"(a1), "r"(a2), "r"(a3), "l"(db), "r"(acc));
}
__device__ __forceinline__ void wgmma(uint32_t (&d)[24], uint32_t a0, uint32_t a1, uint32_t a2, uint32_t a3, uint64_t db, int acc) {
    asm volatile("{\n.reg .pred p;\nsetp.ne.b32 p, %29, 0;\n"
                 "wgmma.mma_async.sync.aligned.m64n96k16.f16.f16.f16 "
                 "{%0, %1, %2, %3, %4, %5, %6, %7, %8, %9, %10, %11, %12, %13, %14, %15, %16, %17, %18, %19, %20, %21, %22, %23}, "
                 "{%24, %25, %26, %27}, %28, p, 1, 1, 0;\n}\n"
                 : "+r"(d[0]), "+r"(d[1]), "+r"(d[2]), "+r"(d[3]), "+r"(d[4]), "+r"(d[5]), "+r"(d[6]), "+r"(d[7]), "+r"(d[8]), "+r"(d[9]), "+r"(d[10]), "+r"(d[11]), "+r"(d[12]), "+r"(d[13]), "+r"(d[14]), "+r"(d[15]), "+r"(d[16]), "+r"(d[17]), "+r"(d[18]), "+r"(d[19]), "+r"(d[20]), "+r"(d[21]), "+r"(d[22]), "+r"(d[23])
                 : "r"(a0), "r"(a1), "r"(a2), "r"(a3), "l"(db), "r"(acc));
}
template <int ACC>
__device__ __forceinline__ void wgmma_rowsum(float (&d)[4], const uint32_t (&a)[4], uint64_t ones) {
    asm volatile("{\n.reg .pred p;\nsetp.ne.b32 p, %9, 0;\n"
                 "wgmma.mma_async.sync.aligned.m64n8k16.f32.bf16.bf16 {%0, %1, %2, %3}, {%4, %5, %6, %7}, %8, p, 1, 1, 0;\n}\n"
                 : "+f"(d[0]), "+f"(d[1]), "+f"(d[2]), "+f"(d[3])
                 : "r"(a[0]), "r"(a[1]), "r"(a[2]), "r"(a[3]), "l"(ones), "n"(ACC));
}
__device__ __forceinline__ void ldsm4(uint32_t (&r)[4], uint32_t addr) {
    asm volatile("ldmatrix.sync.aligned.m8n8.x4.shared.b16 {%0, %1, %2, %3}, [%4];"
                 : "=r"(r[0]), "=r"(r[1]), "=r"(r[2]), "=r"(r[3]) : "r"(addr) : "memory");
}
__device__ __forceinline__ void ldsm4_t(uint32_t (&r)[4], uint32_t addr) {
    asm volatile("ldmatrix.sync.aligned.m8n8.x4.trans.shared.b16 {%0, %1, %2, %3}, [%4];"
                 : "=r"(r[0]), "=r"(r[1]), "=r"(r[2]), "=r"(r[3]) : "r"(addr) : "memory");
}
__device__ __forceinline__ void stsm4(uint32_t addr, uint32_t a, uint32_t b, uint32_t c, uint32_t d) {
    asm volatile("stmatrix.sync.aligned.m8n8.x4.shared.b16 [%0], {%1, %2, %3, %4};"
                 ::"r"(addr), "r"(a), "r"(b), "r"(c), "r"(d) : "memory");
}
__device__ __forceinline__ uint32_t transpose8x8(uint32_t v) {
    uint32_t d; asm volatile("movmatrix.sync.aligned.m8n8.trans.b16 %0, %1;" : "=r"(d) : "r"(v)); return d;
}
__device__ __forceinline__ void spin_until(const unsigned* counter, unsigned target) {
    unsigned n = 0, c;
    do {
        asm volatile("ld.acquire.gpu.global.u32 %0, [%1];" : "=r"(c) : "l"(counter) : "memory");
        if (++n > SPIN_LIMIT) __trap();
    } while ((int)(c - target) < 0);
}
__device__ __forceinline__ void signal(unsigned* counter) {
    __syncwarp();
    if (elect_one()) asm volatile("red.release.gpu.global.add.u32 [%0], 1;" ::"l"(counter) : "memory");
    __syncwarp();
}
__device__ __forceinline__ void lds128(uint32_t& a, uint32_t& b, uint32_t& c, uint32_t& d, uint32_t addr) {
    asm volatile("ld.shared.v4.u32 {%0, %1, %2, %3}, [%4];" : "=r"(a), "=r"(b), "=r"(c), "=r"(d) : "r"(addr) : "memory");
}
__device__ __forceinline__ void lds64(uint32_t& a, uint32_t& b, uint32_t addr) {
    asm volatile("ld.shared.v2.u32 {%0, %1}, [%2];" : "=r"(a), "=r"(b) : "r"(addr) : "memory");
}
__device__ __forceinline__ void lds32(uint32_t& a, uint32_t addr) {
    asm volatile("ld.shared.u32 %0, [%1];" : "=r"(a) : "r"(addr) : "memory");
}
__device__ __forceinline__ int ldsi(uint32_t addr) {
    uint32_t v;
    lds32(v, addr);
    return (int)v;
}
__device__ __forceinline__ float ldsf(uint32_t addr) {
    uint32_t v;
    lds32(v, addr);
    return __uint_as_float(v);
}
__device__ __forceinline__ void sts32(uint32_t addr, uint32_t a) {
    asm volatile("st.shared.u32 [%0], %1;" ::"r"(addr), "r"(a) : "memory");
}
__device__ __forceinline__ void sts128(uint32_t addr, uint32_t a, uint32_t b, uint32_t c, uint32_t d) {
    asm volatile("st.shared.v4.u32 [%0], {%1, %2, %3, %4};" ::"r"(addr), "r"(a), "r"(b), "r"(c), "r"(d) : "memory");
}
__device__ __forceinline__ void sts64(uint32_t addr, uint32_t a, uint32_t b) {
    asm volatile("st.shared.v2.u32 [%0], {%1, %2};" ::"r"(addr), "r"(a), "r"(b) : "memory");
}
__device__ __forceinline__ void anchor(uint32_t addr, uint32_t a, uint32_t b, uint32_t c, uint32_t d) {
    asm volatile("{\n.reg .pred p;\nsetp.eq.b32 p, %0, 0;\n@p st.shared.v4.u32 [%0], {%1, %2, %3, %4};\n}\n"
                 ::"r"(addr), "r"(a), "r"(b), "r"(c), "r"(d) : "memory");
}
__device__ __forceinline__ uint32_t bf_fma(uint32_t a, uint32_t b, uint32_t c) {
    uint32_t d; asm("fma.rn.bf16x2 %0, %1, %2, %3;" : "=r"(d) : "r"(a), "r"(b), "r"(c)); return d;
}
__device__ __forceinline__ uint32_t bf_mul(uint32_t a, uint32_t b) {
    uint32_t d; asm("mul.rn.bf16x2 %0, %1, %2;" : "=r"(d) : "r"(a), "r"(b)); return d;
}
__device__ __forceinline__ uint32_t bf_absmax(uint32_t a, uint32_t b) {
    uint32_t d; asm("max.xorsign.abs.bf16x2 %0, %1, %2;" : "=r"(d) : "r"(a), "r"(b)); return d;
}
__device__ __forceinline__ uint32_t h_fma(uint32_t a, uint32_t b, uint32_t c) {
    uint32_t d; asm("fma.rn.f16x2 %0, %1, %2, %3;" : "=r"(d) : "r"(a), "r"(b), "r"(c)); return d;
}
__device__ __forceinline__ uint32_t h_mul(uint32_t a, uint32_t b) {
    uint32_t d; asm("mul.rn.f16x2 %0, %1, %2;" : "=r"(d) : "r"(a), "r"(b)); return d;
}
__device__ __forceinline__ uint32_t h_cut8(uint32_t v) { return v & 0xfff8fff8u; }
constexpr float CUT_GAIN = 1.f + 0.4375f * 0.7213f / 128;
__device__ __forceinline__ uint32_t h_tanh(uint32_t a) {
    uint32_t d; asm("tanh.approx.f16x2 %0, %1;" : "=r"(d) : "r"(a)); return d;
}
__device__ __forceinline__ uint32_t pack_h2(float lo, float hi) {
    uint32_t d; asm("cvt.rn.f16x2.f32 %0, %1, %2;" : "=r"(d) : "f"(hi), "f"(lo)); return d;
}
__device__ __forceinline__ uint32_t pack_bf2(float lo, float hi) {
    uint32_t d; asm("cvt.rn.bf16x2.f32 %0, %1, %2;" : "=r"(d) : "f"(hi), "f"(lo)); return d;
}
__device__ __forceinline__ float bf_lo(uint32_t v) { return __uint_as_float(v << 16); }
__device__ __forceinline__ float bf_hi(uint32_t v) { return __uint_as_float(v & 0xffff0000u); }
__device__ __forceinline__ float h_lo(uint32_t v) { return __low2float(*reinterpret_cast<__half2*>(&v)); }
__device__ __forceinline__ float h_hi(uint32_t v) { return __high2float(*reinterpret_cast<__half2*>(&v)); }
__device__ __forceinline__ float warp_absmax(uint32_t v) {
    return __uint_as_float(__reduce_max_sync(~0u, max((v & 0x7fffu) << 16, v & 0x7fff0000u)));
}
__device__ __forceinline__ uint32_t gelu2(uint32_t z) {
    uint32_t p = h_fma(z, z, GELU_C2);
    uint32_t t = h_tanh(h_mul(z, p));
    return h_fma(z, t, z);
}
__device__ __forceinline__ float pow2i(int e) { return __uint_as_float((uint32_t)(e + 127) << 23); }
__device__ __forceinline__ int ilog2f(float v) {
    int e = (int)((__float_as_uint(v) >> 23) & 0xff) - 127;
    return max(-100, min(100, e));
}

__device__ __forceinline__ int bound_exp(float w1max) { return w1max > 0.f ? ilog2f(2.f * KZ * 96.f * w1max) : 0; }
__device__ __forceinline__ bool plain_squares(int e) { return (unsigned)(4 - e) <= 6; }
__device__ __forceinline__ int square_exp(int e) { return plain_squares(e) ? 0 : max(-14, min(4 - e, 14)); }
__device__ __forceinline__ int sum_exp(int e) { return max(-90, min(90, 33 - 2 * e)); }
__device__ __forceinline__ int row_exp(float m) { return 2 - ilog2f(m); }

struct Split {
    int per_cta, extra, period, inv_period, lenders;
    uint32_t lent_off[MAX_LENDERS * LENT];
    __host__ __device__ __forceinline__ int longer_before(int cta) const {
        const int n = (cta + period / 2) * inv_period >> 16;
        return n < extra ? n : extra;
    }
};
struct Work {
    int tA, tB, nA, nB, dir, rows, lent, index;
    __host__ __device__ __forceinline__ int tile(int j) const { return j < nA ? tA + dir * j : tB + dir * (j - nA); }
};
__host__ __device__ __forceinline__ Work get_work(int cta, const Split& sp) {
    Work w;
    const int before = sp.longer_before(cta), longer = sp.longer_before(cta + 1) - before;
    w.lent = longer && sp.lenders ? LENT : 0;
    w.index = longer ? before : cta - before;
    const int t0 = cta * sp.per_cta + before, t1 = t0 + sp.per_cta + longer;
    const int tm = t1 < (t0 | 511) + 1 ? t1 : (t0 | 511) + 1;
    const bool swap = t1 > tm && t1 - tm < tm - t0, down = cta & 1;
    w.nA = swap ? t1 - tm : tm - t0;
    w.nB = t1 - t0 - w.nA;
    w.tA = down ? (swap ? tm : t0) : (swap ? t1 : tm) - 1;
    w.tB = down ? (swap ? t0 : tm) : (swap ? tm : t1) - 1;
    w.dir = down ? 1 : -1;
    w.rows = w.nA + 2 + (w.nB ? w.nB + 2 : 0);
    return w;
}
__device__ __forceinline__ int row_code(const Work& w, int i) {
    const bool in_a = i < w.nA + 2;
    const int t = in_a ? w.tA : w.tB;
    return ((t & 511) + w.dir * ((in_a ? i : i - (w.nA + 2)) - 1)) << 16 | (t >> 9) * TILE_W;
}
__host__ __device__ __forceinline__ uint32_t tile_offset(int tile) { return ((tile & 511) * IMG_W + (tile >> 9) * TILE_W) * (CH * 2); }
__device__ __forceinline__ int tile_order(int j, int n) {
    return j % ORDER_P == ORDER_P - 1 ? j / ORDER_P : n - 1 - (j - j / ORDER_P);
}
__device__ __forceinline__ void issue_region(const CUtensorMap* tm, uint32_t dst, uint32_t bar, int warp, int code) {
    mbar_expect_tx(bar, REGION_BYTES);
    tma_row(dst, tm, bar, (code & 0xffff) + (16 * warp - 1), code >> 16);
}

template <class Event>
__device__ __forceinline__ void conv_producer(const Work& wk, const CUtensorMap* tm, uint32_t sb, int warp, Event event) {
    const int lane = threadIdx.x & 31;
    const int j = lane & 15, grp = lane >> 4;
    const uint32_t reg0 = sb + SM_RING + warp * REGION_BYTES;
    const uint32_t bars = sb + SM_BAR + warp * 8;
    if (warp * 32 + lane < MAX_ROWS) {
        const int i = warp * 32 + lane, before = min(i / 5, wk.lent);
        const bool back = i % 5 == 0 && i > 0 && i / 5 <= wk.lent;
        sts32(sb + SM_TILES + i * 4, back ? tile_offset(wk.tile(before - 1)) | before
                                          : tile_offset(wk.tile(wk.lent + tile_order(i - before, wk.nA + wk.nB - 4 - wk.lent))));
    }
    const uint32_t ld64 = opaque(reg0 + grp * 8 * 192 + j * 8), ld32 = opaque(reg0 + grp * 8 * 192 + 128 + j * 4);
    const uint32_t st64 = opaque(reg0 + grp * A_SBO + (j >> 1) * A_LBO + (j & 1) * 8);
    const uint32_t st32 = opaque(reg0 + grp * A_SBO + (8 + (j >> 2)) * A_LBO + (j & 3) * 4);
    named_bar(0, NTHREADS);
    uint32_t w[3][3][3];
    mbar_wait_once(sb + BAR_F, 0);
#pragma unroll
    for (int tap = 0; tap < 9; tap++) {
        const uint32_t p = sb + SM_FILTER + (3 + wk.dir * 3 * (tap / 3 - 1) + tap % 3) * (CH * 2);
        lds64(w[tap / 3][tap % 3][0], w[tap / 3][tap % 3][1], p + 8 * j);
        lds32(w[tap / 3][tap % 3][2], p + 128 + 4 * j);
    }
#pragma unroll
    for (int tap = 0; tap < 9; tap++) sts64(reg0 + (NSLOT - 1) * SLOT_BYTES + tap * 128 + j * 8, w[tap / 3][tap % 3][1], w[tap / 3][tap % 3][0]);
    named_bar(1, 128);
#pragma unroll
    for (int tap = 0; tap < 9; tap++) lds64(w[tap / 3][tap % 3][1], w[tap / 3][tap % 3][0], reg0 + (NSLOT - 1) * SLOT_BYTES + tap * 128 + j * 8);
    static_assert(2 * PREFETCH_ROWS == NSLOT && SLOT_BYTES % 32 == 0, "slot arithmetic");
    uint32_t bo = 0, par = 0, pbo = PREFETCH_ROWS * 32, ppar = 1;
    int px, py;
    auto request = [&]() {
        mbar_wait_once(bars + (BAR_E - SM_BAR) + pbo, ppar);
        if (elect_one()) {
            mbar_expect_tx(bars + pbo, REGION_BYTES);
            tma_row(reg0 + pbo * (SLOT_BYTES / 32), tm, bars + pbo, px, py);
        }
    };
    auto advance = [&]() {
        bo += 32;
        if (bo == NSLOT * 32) { bo = 0; par ^= 1; }
        pbo += 32;
        if (pbo == NSLOT * 32) { pbo = 0; ppar ^= 1; }
    };
    auto aim = [&](int row) {
        const int code = row_code(wk, row);
        px = (code & 0xffff) + (16 * warp - 1);
        py = code >> 16;
    };
    uint32_t accB[8][3], accC[8][3];
    int r = 0;
#pragma unroll 1
    while (r < wk.rows) {
        if (r == 0 || r == wk.nA + 2) {
            const uint32_t bo0 = bo;
            uint32_t bo1;
#pragma unroll 1
            for (int k = 0; k < 2; k++, r++) {
                mbar_wait_once(bars + bo, par);
                bo1 = bo;
                if (r >= 2) {
                    aim(r + PREFETCH_ROWS);
                    request();
                }
                advance();
            }
            const uint32_t so0 = bo0 * (SLOT_BYTES / 32), so1 = bo1 * (SLOT_BYTES / 32);
#pragma unroll
            for (int p = 0; p < 10; p++) {
                uint32_t u[3], v[3];
                lds64(u[0], u[1], so0 + ld64 + p * 192);
                lds32(u[2], so0 + ld32 + p * 192);
                lds64(v[0], v[1], so1 + ld64 + p * 192);
                lds32(v[2], so1 + ld32 + p * 192);
#pragma unroll
                for (int dx = 0; dx < 3; dx++) {
                    const int o = p - dx;
                    if (o < 0 || o > 7) continue;
#pragma unroll
                    for (int q = 0; q < 3; q++) {
                        accB[o][q] = bf_fma(v[q], w[1][dx][q], dx == 0 ? bf_mul(u[q], w[0][dx][q]) : bf_fma(u[q], w[0][dx][q], accB[o][q]));
                        accC[o][q] = dx == 0 ? bf_mul(v[q], w[0][dx][q]) : bf_fma(v[q], w[0][dx][q], accC[o][q]);
                    }
                }
            }
            anchor(ld64, accB[7][0], accB[7][1], accB[7][2], 0);
            __syncwarp();
            if (elect_one()) {
                mbar_arrive(bars + (BAR_A - SM_BAR) + bo0);
                mbar_arrive(bars + (BAR_E - SM_BAR) + bo0);
                mbar_arrive(bars + (BAR_A - SM_BAR) + bo1);
                mbar_arrive(bars + (BAR_E - SM_BAR) + bo1);
            }
        }
        int end = wk.rows;
        const int marks[4] = {wk.rows - PREFETCH_ROWS, wk.rows - 11, wk.nA + 2, wk.nA + 2 - PREFETCH_ROWS};
#pragma unroll
        for (int k = 0; k < 4; k++) end = marks[k] > r ? min(end, marks[k]) : end;
        const bool fetch = r < wk.rows - PREFETCH_ROWS;
        aim(r + PREFETCH_ROWS);
        px = opaque_uniform(px);
        const int py_end = opaque_uniform(py + wk.dir * (end - r));
        r = end;
#pragma unroll 1
        do {
            mbar_wait(bars + bo, par);
            const uint32_t so = bo * (SLOT_BYTES / 32);
            uint32_t out[8][3];
#pragma unroll
            for (int p = 0; p < 10; p++) {
                uint32_t xv[3];
                lds64(xv[0], xv[1], so + ld64 + p * 192);
                lds32(xv[2], so + ld32 + p * 192);
#pragma unroll
                for (int dx = 0; dx < 3; dx++) {
                    const int o = p - dx;
                    if (o < 0 || o > 7) continue;
#pragma unroll
                    for (int q = 0; q < 3; q++) {
                        out[o][q] = bf_fma(xv[q], w[2][dx][q], dx == 0 ? accB[o][q] : out[o][q]);
                        accB[o][q] = bf_fma(xv[q], w[1][dx][q], dx == 0 ? accC[o][q] : accB[o][q]);
                        accC[o][q] = dx == 0 ? bf_mul(xv[q], w[0][dx][q]) : bf_fma(xv[q], w[0][dx][q], accC[o][q]);
                    }
                }
            }
            __syncwarp();
#pragma unroll
            for (int o = 0; o < 8; o++) {
                sts64(so + st64 + o * 16, out[o][0], out[o][1]);
                sts32(so + st32 + o * 16, out[o][2]);
            }
            __syncwarp();
            if (elect_one()) mbar_arrive(bars + (BAR_A - SM_BAR) + bo);
            if (fetch) request();
            advance();
            py += wk.dir;
        } while (py != py_end);
        if (((wk.rows - r) & ~8) == PREFETCH_ROWS) event(wk.rows - r == PREFETCH_ROWS);
    }
}

template <bool SCALED, int K0 = 0, int K1 = 3>
__device__ __forceinline__ void gelu_sq(uint32_t (&d)[24], uint32_t (&keep)[24], uint32_t sq_addr, uint32_t scale2) {
    pin(d);
#pragma unroll
    for (int k = K0; k < K1; k++) {
        uint32_t hs[4];
        lds128(hs[0], hs[1], hs[2], hs[3], sq_addr + k * SQ_ROW);
#pragma unroll
        for (int q = 0; q < 4; q++) {
            uint32_t g0 = gelu2(d[8 * k + 2 * q]), g1 = gelu2(d[8 * k + 2 * q + 1]);
            keep[8 * k + 2 * q] = g0;
            keep[8 * k + 2 * q + 1] = g1;
            if (SCALED) { g0 = h_mul(g0, scale2); g1 = h_mul(g1, scale2); }
            hs[q] = h_fma(g1, g1, h_fma(g0, g0, hs[q]));
        }
        sts128(sq_addr + k * SQ_ROW, hs[0], hs[1], hs[2], hs[3]);
    }
}
__device__ __forceinline__ void gelu_sq_reg(uint32_t (&d)[24], uint32_t (&hs)[12]) {
    pin(d);
#pragma unroll
    for (int q = 0; q < 12; q++) {
        const uint32_t g0 = gelu2(d[2 * q]), g1 = gelu2(d[2 * q + 1]);
        hs[q] = h_fma(g1, g1, h_fma(g0, g0, hs[q]));
    }
}
__device__ __forceinline__ void gelu_to(uint32_t (&g)[12], uint32_t (&d)[12]) {
    pin(d);
#pragma unroll
    for (int q = 0; q < 12; q++) g[q] = gelu2(d[q]);
    pin(g);
}
__device__ __forceinline__ void load_tile(uint32_t (&raw)[6][4], uint32_t addr) {
#pragma unroll
    for (int s = 0; s < 6; s++) ldsm4(raw[s], addr + s * 2 * A_LBO);
}
template <class F>
__device__ __forceinline__ void layer_norm(uint32_t (&raw)[6][4], uint64_t ones, F meanwhile) {
    constexpr int NS = 2;
    uint32_t sq[NS][4];
#pragma unroll
    for (int s = 0; s < 6; s++)
#pragma unroll
        for (int q = 0; q < 4; q++) sq[s % NS][q] = s < NS ? bf_mul(raw[s][q], raw[s][q]) : bf_fma(raw[s][q], raw[s][q], sq[s % NS][q]);
    float sum[4], ssq[4];
    wg_fence();
    wgmma_rowsum<0>(sum, raw[0], ones);
#pragma unroll
    for (int s = 1; s < 6; s++) wgmma_rowsum<1>(sum, raw[s], ones);
    wgmma_rowsum<0>(ssq, sq[0], ones);
#pragma unroll
    for (int s = 1; s < NS; s++) wgmma_rowsum<1>(ssq, sq[s], ones);
    wg_commit();
    meanwhile();
    wg_wait<0>();
    uint32_t sc[2], sh[2];
#pragma unroll
    for (int h = 0; h < 2; h++) {
        asm volatile("" : "+f"(sum[2 * h]), "+f"(ssq[2 * h])::"memory");
        constexpr float EPS = 1e-5f / (KZ * KZ);
        const float m = sum[2 * h] * (1.f / (CH * KZ));
        float rstd;
        asm("rsqrt.approx.ftz.f32 %0, %1;" : "=f"(rstd) : "f"(fmaxf(fmaf(-m, m, fmaf(ssq[2 * h], 1.f / (CH * KZ * KZ), EPS)), EPS)));
        sc[h] = pack_bf2(rstd, rstd);
        const float shift = sum[2 * h] * (-1.f / CH) * bf_hi(sc[h]);
        sh[h] = pack_bf2(shift, shift);
    }
#pragma unroll
    for (int s = 0; s < 6; s++)
#pragma unroll
        for (int q = 0; q < 4; q++) {
            const uint32_t v = bf_fma(raw[s][q], sc[q & 1], sh[q & 1]);
            raw[s][q] = pack_h2(bf_lo(v), bf_hi(v));
        }
}
struct Cursor {
    int slot;
    uint32_t par;
    __device__ __forceinline__ void advance(int n) {
        slot += n;
        if (slot >= NSLOT) { slot -= NSLOT; par ^= 1; }
    }
};
struct Descs {
    uint64_t w1[8][6];
    uint64_t w2[24];
    uint64_t ones;
};
template <int E0, int N>
__device__ __forceinline__ void gemm1_chunk(uint32_t (&d)[N], const uint32_t (&a)[6][4], const Descs& ds, int zero) {
#pragma unroll
    for (int s = 0; s < 6; s++) wgmma(d, a[s][0], a[s][1], a[s][2], a[s][3], ds.w1[E0 / 48][s], s ? 1 : zero);
}
template <int E0, int N>
__device__ __forceinline__ void gemm2_chunk(uint32_t (&acc)[24], const uint32_t (&g)[N], const Descs& ds) {
#pragma unroll
    for (int s = 0; s < N / 4; s++) wgmma(acc, g[4 * s], g[4 * s + 1], g[4 * s + 2], g[4 * s + 3], ds.w2[E0 / 16 + s], 1);
}

struct __align__(64) Params {
    Split sp;
    int zero;
    const __nv_bfloat16 *x, *dw, *w2, *gamma, *beta;
    __nv_bfloat16* out;
    Scratch* sc;
    Descs ds;
};

__global__ void __launch_bounds__(NTHREADS, 1)
block_kernel(const __grid_constant__ CUtensorMap tmap, const __grid_constant__ CUtensorMap tmap_w1, const __grid_constant__ Params pm) {
    const Split& sp = pm.sp;
    const Descs& ds = pm.ds;
    const int& zero = pm.zero;
    const __nv_bfloat16 *const &x = pm.x, *const &dw = pm.dw, *const &w2 = pm.w2, *const &gamma = pm.gamma, *const &beta = pm.beta;
    __nv_bfloat16* const& out = pm.out;
    Scratch* const& sc = pm.sc;
    extern __shared__ __align__(1024) uint8_t smem[];
    constexpr uint32_t sb = SB;
    const int tid = threadIdx.x;
    const Work wk = get_work(blockIdx.x, sp);
    constexpr uint32_t s_red = sb + SM_RED;
    if (smem_u32(smem) != SB) __trap();

    const int warp_id = __shfl_sync(~0u, tid >> 5, 0);
    PROF(0);
    const int cw = warp_id - 4, wgi = cw >> 2, w4 = warp_id & 3;
    if (elect_one()) {
        static_assert(3 * NSLOT * 4 == 8 + 4 * 16 && BAR_F == BAR_W + 48, "barrier shares");
        const int b = warp_id - 8;
        const uint32_t bar = b < 0 ? sb + BAR_X + warp_id * 8 : b < 7 ? sb + BAR_W + b * 8 : sb + BAR_PIN;
        mbar_init(bar, 1);
#pragma unroll
        for (int k = 0; k < 4; k++) mbar_init(sb + BAR_X + (8 + 4 * warp_id + k) * 8, 1);
        mbar_init(sb + BAR_R + warp_id * 8, 1);
        fence_async();
        if (b < 0) {
            issue_region(&tmap, sb + SM_RING + warp_id * REGION_BYTES, bar, w4, ((wk.tA & 511) + wk.dir * wgi) << 16 | (wk.tA >> 9) * TILE_W);
        } else if (b < 6) {
            mbar_expect_tx(bar, 64 * CH * 2);
            tma_2d(sb + SM_W2 + b * (64 * CH * 2), &tmap_w1, bar, 64 * b, 0);
        } else if (b == 6) {
            mbar_expect_tx(bar, 9 * CH * 2);
            bulk_load(sb + SM_FILTER, dw, 9 * CH * 2, bar);
        }
    }
    __syncwarp();
    const int ntiles = wk.nA + wk.nB;
    const int rank = (wgi + wk.lent + 2 * (ntiles - 1)) % NCONS | (wgi >> 2 & 3);
    const int spare = wk.rows % NSLOT, spare2 = spare == NSLOT - 1 ? 0 : spare + 1;
    const uint32_t sq_base = sb + (wgi < 0 ? SM_RING + spare * SLOT_BYTES : SM_SQ + rank * 2 * SQ_HALF);
    const uint32_t sq_upper = wgi < 0 ? (spare2 - spare) * SLOT_BYTES : SQ_HALF;
    const uint32_t bar_a = sb + BAR_A + w4 * 8, bar_e = sb + BAR_E + w4 * 8;
    const int from_end = gridDim.x - 1 - sp.lenders - (sp.lenders ? wk.index : blockIdx.x);
    const bool prepares = !wk.lent && from_end < W2_GROUPS / 2, helps = !wk.lent && wk.index < 8 * LENT * sp.lenders;
    auto max_w1 = [&](uint32_t lane) { return __uint_as_float(__reduce_max_sync(~0u, lane < 4 * NCONS ? ldsi(s_red + RED_MAX + lane * 4) : 0)); };
    auto square_scale = [&](uint32_t lane) {
        const float f = pow2i(square_exp(bound_exp(max_w1(lane))));
        return pack_h2(f, f);
    };
    uint32_t a_addr, sq;
    const uint32_t sq_warp = sq_base + w4 * 512;
    auto set_addresses = [&]() {
        a_addr = opaque(sb + SM_RING + w4 * REGION_BYTES + ((tid >> 3) & 1) * A_SBO + ((tid >> 4) & 1) * A_LBO + (tid & 7) * 16);
        sq = opaque(sq_base + (tid & 127) * 16);
    };
    uint32_t turn, turn_end, so, so_sum, bo, bo_sum, off;
    auto set_run = [&](int j, int stop, int row) {
        const int slot = row % NSLOT, both = 2 * (row % 3) + 3;
        turn = opaque_uniform(row / 3);
        turn_end = opaque_uniform(row / 3 + (stop - j + NCONS - 1) / NCONS);
        so = opaque_uniform(slot * SLOT_BYTES);
        so_sum = opaque_uniform(both * SLOT_BYTES);
        bo = opaque_uniform(bar_a + slot * 32);
        bo_sum = opaque_uniform(2 * bar_a + both * 32);
        off = opaque_uniform(tile_offset(wk.tile(j)) + w4 * WARP_BYTES - sq_warp);
    };
    const int nrest = ntiles - 4;
    int jt;
    Cursor cur;
    int fast_from;
    if (warp_id < 4) {
        const int q = from_end * 2 + (w4 >> 1);
        conv_producer(wk, &tmap, sb, warp_id, [&](bool second) {
            if (!second) {
                if (blockIdx.x == 0) {
#pragma unroll 1
                    for (int e = tid; e < EX; e += 128) *sc->sum(e) = 0;
                    sc->bias[tid] = 0.f;
                }
                if (blockIdx.x == 0 || wk.lent) signal(&sc->early);
            } else if (prepares || helps) {
                spin_until(&sc->early, (ldsi(s_red + RED_LAUNCH) + 1) * 4 * (sp.lenders + 1));
                if (elect_one()) {
                    if (helps) prefetch_l2(reinterpret_cast<const char*>(out) + sp.lent_off[wk.index / 8] + w4 * WARP_BYTES, WARP_BYTES);
                    if (prepares) { prefetch_l2(w2 + 8 * q * CH, 8 * CH * 2); prefetch_l2(beta + 8 * q, 16); }
                }
            }
        });
        set_addresses();
        const int lane = lane_id(), g = lane >> 2, t = lane & 3;
        const int piece = wk.index;
        uint32_t a[6][4];
        unsigned short bt_raw;
        if (prepares) {
#pragma unroll
            for (int m = 0; m < 3; m++) ldg128(a[m], w2 + (8 * q + g) * CH + 32 * m + 8 * t);
            asm volatile("ld.global.nc.u16 %0, [%1];" : "=h"(bt_raw) : "l"(beta + 8 * q + g) : "memory");
        } else if (helps) {
#pragma unroll
            for (int s = 0; s < 6; s++) ldg128(a[s], reinterpret_cast<const char*>(out) + sp.lent_off[piece / 8] + w4 * WARP_BYTES + lane * 16 + s * 512);
        }
        mbar_wait_once(bar_e + spare2 * 32, (wk.rows - 5) / NSLOT & 1);
        mbar_wait_once(bar_e + spare * 32, (wk.rows - 6) / NSLOT & 1);
        named_bar(1, 128);
#pragma unroll
        for (int k = 0; k < 6; k++) { sts128(sq + k * SQ_ROW, 0, 0, 0, 0); sts128(sq + sq_upper + k * SQ_ROW, 0, 0, 0, 0); }
        if (prepares) {
            const int half = w4 & 1;
            uint32_t rmax = 0;
#pragma unroll
            for (int m = 0; m < 3; m++) rmax = bf_absmax(bf_absmax(rmax, bf_absmax(a[m][0], a[m][1])), bf_absmax(a[m][2], a[m][3]));
            uint2 u = half ? make_uint2(a[0][2], a[0][3]) : make_uint2(a[0][0], a[0][1]), u1 = half ? make_uint2(a[1][2], a[1][3]) : make_uint2(a[1][0], a[1][1]);
            const uint2 u2 = half ? make_uint2(a[2][2], a[2][3]) : make_uint2(a[2][0], a[2][1]);
            const float bt = bf_lo(bt_raw);
            rmax = bf_absmax(rmax, __shfl_xor_sync(~0u, rmax, 1));
            rmax = bf_absmax(rmax, __shfl_xor_sync(~0u, rmax, 2));
            const float mx = fmaxf(fabsf(bf_lo(rmax)), fabsf(bf_hi(rmax))), rs = pow2i(row_exp(mx));
            if (t == 0 && !half) sc->w2max[8 * q + g] = mx;
#pragma unroll 1
            for (int m = 0; m < 3; m++, u = u1, u1 = u2) {
                float f[4];
#pragma unroll
                for (int k = 0; k < 2; k++) {
                    const float lo = bf_lo(k ? u.y : u.x), hi = bf_hi(k ? u.y : u.x);
                    sc->w2h[(4 * m + 2 * half + k) * 1536 + q * 32 + lane] = transpose8x8(pack_h2(lo * rs, hi * rs));
                    f[2 * k] = lo * bt;
                    f[2 * k + 1] = hi * bt;
                }
                const float r0 = (g & 2 ? f[2] : f[0]) + __shfl_xor_sync(~0u, g & 2 ? f[0] : f[2], 8);
                const float r1 = (g & 2 ? f[3] : f[1]) + __shfl_xor_sync(~0u, g & 2 ? f[1] : f[3], 8);
                float r = (g & 1 ? r1 : r0) + __shfl_xor_sync(~0u, g & 1 ? r0 : r1, 4);
                r += __shfl_xor_sync(~0u, r, 16);
                if (g < 4) atomicAdd(&sc->bias[32 * m + 8 * t + 4 * half + g], r);
            }
            asm volatile("fence.proxy.async.global;" ::: "memory");
            signal(&sc->prep);
        } else
        if (helps) {
            uint32_t d[12], gl[12];
            const uint32_t scale2 = square_scale(lane);
            wg_fence();
#pragma unroll
            for (int s = 0; s < 6; s++) wgmma(d, a[s][0], a[s][1], a[s][2], a[s][3], ds.w1[0][s] + piece % 8 * (6 * 1536 / 16), s ? 1 : 0);
            wg_commit();
            wg_wait<0>();
            gelu_to(gl, d);
#pragma unroll
            for (int s = 0; s < 3; s++) {
                sc->lent[((piece / 8 * 4 + w4) * 24 + piece % 8 * 3 + s) * 32 + lane] = make_uint4(gl[4 * s], gl[4 * s + 1], gl[4 * s + 2], gl[4 * s + 3]);
                uint32_t hs[2];
#pragma unroll
                for (int k = 0; k < 2; k++) {
                    const uint32_t g0 = h_mul(gl[4 * s + 2 * k], scale2), g1 = h_mul(gl[4 * s + 2 * k + 1], scale2);
                    hs[k] = h_fma(g1, g1, h_mul(g0, g0));
                }
                const int pair = piece % 4 * 3 + s;
                sts64(sq + (piece & 4 ? sq_upper : 0) + (pair >> 1) * SQ_ROW + (pair & 1) * 8, hs[0], hs[1]);
            }
        }
        jt = ntiles - 1;
        cur.slot = spare ? spare - 1 : NSLOT - 1;
        cur.par = (wk.rows - 1) / NSLOT & 1;
        fast_from = ntiles;
        turn = turn_end = so = so_sum = bo = bo_sum = off = rank;
    } else {
        set_addresses();
        if (wgi == NCONS - 1) named_arrive(4, 256);
        set_run(wk.lent + wgi, min(wk.nA, nrest), wk.lent + wgi + 2);
        jt = wgi < wk.lent ? wgi : wk.lent + wgi;
        cur = {2, 0};
        cur.advance(jt + (jt >= wk.nA ? 2 : 0));
        {
            const int ct = tid - 128, lane = tid & 31;
            const unsigned epoch = *reinterpret_cast<volatile unsigned*>(&sc->launch);
            const int r = lane & 7, mi = lane >> 3;
            const uint32_t src = sb + SM_W2 + (cw >> 1) * (64 * CH * 2) + r * 128 + ((((cw & 1) * 4 + mi) ^ r) * 16);
            const uint32_t dst = sb + SM_W1 + (4 * cw + mi) * 1536 + r * 16;
            const int code = row_code(wk, PREFETCH_ROWS - 1 + wgi);
            named_bar(0, NTHREADS);
            auto request = [&]() {
                if (elect_one())
                    issue_region(&tmap, sb + SM_RING + (PREFETCH_ROWS - 1 + wgi) * SLOT_BYTES + w4 * REGION_BYTES, sb + BAR_X + (cw + 8) * 8, w4, code);
                __syncwarp();
            };
#pragma unroll 1
            for (int k = 0; k < 2; k++) {
                if (wgi == k) request();
                mbar_wait_once(sb + BAR_W + (cw >> 1) * 8, 0);
            }
            uint32_t wmax[2] = {}, wsum[4] = {};
#pragma unroll 3
            for (int c = 0; c < 12; c++) {
                uint32_t u[4];
                ldsm4_t(u, src + c * 1024);
#pragma unroll
                for (int q = 0; q < 4; q++) {
                    wmax[q & 1] = bf_absmax(wmax[q & 1], u[q]);
                    wsum[q] = bf_fma(u[q], 0x3f803f80u, wsum[q]);
                    u[q] = pack_h2(__uint_as_float(u[q] * (65536 + zero)), bf_hi(u[q]));
                }
                stsm4(dst + c * 128, u[0], u[1], u[2], u[3]);
            }
            const float w1max = warp_absmax(bf_absmax(wmax[0], wmax[1]));
            if (lane == 0) sts32(s_red + RED_MAX + cw * 4, __float_as_uint(w1max));
            bool center = false;
#pragma unroll
            for (int q = 0; q < 4; q++) {
#pragma unroll
                for (int o = 1; o <= 2; o <<= 1) wsum[q] = bf_fma(__shfl_xor_sync(~0u, wsum[q], o), 0x3f803f80u, wsum[q]);
                center |= fabsf(bf_lo(wsum[q]) + bf_hi(wsum[q])) > (0.15f * CH) * w1max;
            }
            if (__builtin_expect(__any_sync(~0u, center), 0)) {
                float mean[4] = {};
#pragma unroll 1
                for (int pass = 0; pass < 2; pass++) {
                    float sum[4] = {};
#pragma unroll 1
                    for (int c = 0; c < 12; c++) {
                        uint32_t u[4];
                        ldsm4_t(u, src + c * 1024);
#pragma unroll
                        for (int q = 0; q < 4; q++) {
                            sum[q] += bf_lo(u[q]) + bf_hi(u[q]);
                            u[q] = pack_h2(bf_lo(u[q]) - mean[q], bf_hi(u[q]) - mean[q]);
                        }
                        stsm4(dst + c * 128, u[0], u[1], u[2], u[3]);
                    }
#pragma unroll
                    for (int q = 0; q < 4; q++) {
                        sum[q] += __shfl_xor_sync(~0u, sum[q], 1);
                        sum[q] += __shfl_xor_sync(~0u, sum[q], 2);
                        mean[q] = sum[q] * (1.f / CH);
                    }
                }
            }
            if (!(cw & 2)) {
#pragma unroll
                for (int c = 0; c < 12; c++) sts128(src + c * 1024, 0, 0, 0, 0);
            }
            if (ct < 32) sts32(sb + SM_ONES + ct * 4, 0x3f803f80u);
            if (ct == 0) sts32(s_red + RED_LAUNCH, epoch);
            fence_async();
            named_bar(2, CONS_THREADS);
            if (wgi == 2) request();
        }
        PROF(1);
        if (cur.par) mbar_wait_once(bar_a, 0);
        fast_from = wk.lent;
        if (!__all_sync(~0u, plain_squares(bound_exp(max_w1(lane_id()))))) {
            fast_from = ntiles;
#pragma unroll 1
            for (int q = 0; q < 6; q++) sts128(sq + SQ_HALF + q * SQ_ROW, 0, 0, 0, 0);
        }
    }
    uint32_t k1[24], k2[24], k3[24];
    uint32_t here;
    constexpr int SQC = 3 * SQ_ROW;
    auto store_at = [&](const uint32_t (&a)[6][4], uint32_t off) {
        char* ap = reinterpret_cast<char*>(out) + (off + sq);
#pragma unroll
        for (int s = 0; s < 6; s++) stg128(ap + s * 512, a[s]);
    };
    const uint32_t own_bar = 4 + wgi, next_bar = 4 + (wgi == NCONS - 1 ? 0 : wgi + 1);
    for (;;) {
        if (jt >= fast_from) {
            uint32_t hs2[12] = {}, hs3[12] = {};
            const uint32_t step = wk.dir * (NCONS * IMG_W * CH * 2);
            int second = wk.nB;
#pragma unroll 1
            for (;;) {
#pragma unroll 1
                while (turn != turn_end) {
                    uint32_t a[6][4], d0[24], d1[24], unused[24];
                    mbar_wait(bo, turn >> 1 & 1);
                    load_tile(a, a_addr + so);
                    layer_norm(a, ds.ones, [&]() { named_bar(own_bar, 256); });
                    wg_fence();
                    gemm1_chunk<0>(d0, a, ds, 0);
                    wg_commit();
                    gemm1_chunk<96>(d1, a, ds, 0);
                    wg_commit();
                    wg_wait<1>();
                    gelu_sq<false, 0, 1>(d0, unused, sq, 0);
                    gelu_sq<false, 1, 2>(d0, unused, sq, 0);
                    store_at(a, off);
                    gelu_sq<false, 2, 3>(d0, unused, sq, 0);
                    if (elect_one()) mbar_arrive(bo + (BAR_E - BAR_A));
                    wg_fence();
                    gemm1_chunk<192>(d0, a, ds, zero);
                    wg_commit();
                    named_arrive(next_bar, 256);
                    wg_wait<1>();
                    gelu_sq<false, 0, 1>(d1, unused, sq + SQC, 0);
                    gelu_sq<false, 1, 3>(d1, unused, sq + SQC, 0);
                    wg_fence();
                    gemm1_chunk<288>(d1, a, ds, zero);
                    wg_commit();
                    wg_wait<1>();
                    gelu_sq_reg(d0, hs2);
                    anchor(sq, hs2[8], hs2[9], hs2[10], hs2[11]);
                    wg_wait<0>();
                    gelu_sq_reg(d1, hs3);
                    so = so_sum - so;
                    bo = bo_sum - bo;
                    off += step;
                    turn++;
                }
                if (!second) break;
                const int j = ntiles - second + (rank + second + 2) % NCONS;
                second = 0;
                set_run(j, nrest, j + 4);
            }
            jt = nrest + rank;
            cur.slot = (bo - bar_a) >> 5;
            cur.par = turn >> 1 & 1;
#pragma unroll
            for (int k = 0; k < 3; k++) {
                sts128(sq + SQ_HALF + k * SQ_ROW, hs2[4 * k], hs2[4 * k + 1], hs2[4 * k + 2], hs2[4 * k + 3]);
                sts128(sq + SQ_HALF + SQC + k * SQ_ROW, hs3[4 * k], hs3[4 * k + 1], hs3[4 * k + 2], hs3[4 * k + 3]);
            }
        }
        const bool last = jt >= nrest;
        here = tile_offset(wk.tile(jt));
        if (last) {
            const uint32_t next = ldsi(sb + SM_TILES + rank * 4);
            if (elect_one()) {
                prefetch_l2(reinterpret_cast<const char*>(x) + here + w4 * WARP_BYTES, WARP_BYTES);
                if (rank == ORDER_P - 1) prefetch_l2(reinterpret_cast<const char*>(out) + next + w4 * WARP_BYTES, WARP_BYTES);
            }
        }
        uint32_t a[6][4], d0[24], d1[24], d3[24], k0[24];
        mbar_wait_once(bar_a + cur.slot * 32, cur.par);
        load_tile(a, a_addr + cur.slot * SLOT_BYTES);
        layer_norm(a, ds.ones, [&]() { if (jt >= wk.lent && wgi >= 0) named_bar(own_bar, 256); });
        if (!last) {
            store_at(a, here + w4 * WARP_BYTES - sq_warp);
            __syncwarp();
            if (elect_one()) mbar_arrive(bar_e + cur.slot * 32);
            if (jt < wk.lent) {
                jt += LENT;
                cur.advance(LENT);
                continue;
            }
        }
        wg_fence();
        gemm1_chunk<0>(d0, a, ds, 0);
        wg_commit();
        gemm1_chunk<96>(d1, a, ds, 0);
        wg_commit();
        const uint32_t scale2 = square_scale(lane_id());
        wg_wait<1>();
        gelu_sq<true>(d0, k0, sq, scale2);
        if (last) {
#pragma unroll
            for (int q = 0; q < 6; q++)
                sts128(sb + SM_RING + cur.slot * SLOT_BYTES + w4 * REGION_BYTES - sq_warp + sq + q * 512, k0[4 * q], k0[4 * q + 1], k0[4 * q + 2], k0[4 * q + 3]);
        }
        wg_fence();
        gemm1_chunk<192>(d0, a, ds, zero);
        wg_commit();
        if (jt + 2 < ntiles) named_arrive(next_bar, 256);
        wg_wait<1>();
        gelu_sq<true>(d1, k1, sq + SQC, scale2);
        wg_fence();
        gemm1_chunk<288>(d3, a, ds, 0);
        wg_commit();
        wg_wait<1>();
        gelu_sq<true>(d0, k2, sq + sq_upper, scale2);
        wg_wait<0>();
        gelu_sq<true>(d3, k3, sq + sq_upper + SQC, scale2);
        if (last) break;
        cur.advance(NCONS + ((jt < wk.nA && jt + NCONS >= wk.nA) ? 2 : 0));
        jt += NCONS;
    }
    const uint32_t lane = lane_id();
    uint32_t next_off = opaque_uniform(ldsi(sb + SM_TILES + rank * 4));
    const uint32_t s_fac = sb + SM_RING + spare * SLOT_BYTES + SQ_HALF;
    uint32_t inv_rho2;
    {
        if (rank == 0) {
            const int g = lane >> 2, t = lane & 3, i0 = w4 * 32 + lane;
            const bool leader = i0 == 0;
            const uint32_t pick = (g & 1) == (t & 1) ? (g & 2 ? 0x3c000000u : 0x00003c00u) : 0;
            const int be = bound_exp(max_w1(lane));
            const float to_fixed = pow2i(sum_exp(be) - 2 * square_exp(be));
            const uint32_t two_rows = sb + (w4 * 3 + (lane >> 3 & 1)) * SQ_ROW + ((lane >> 4) * 8 + (lane & 7)) * 16;
            const uint32_t third_row = sb + (w4 * 3 + 2) * SQ_ROW + lane * 16;
            unsigned short gam_raw[3];
            float rmax[3], f[3][4] = {};
            float2 bpair = make_float2(0.f, 0.f);
#pragma unroll 1
            for (int i = 0; i < 4; i++) {
                if (i == 1 && leader) {
                    spin_until(&sc->prep, (ldsi(s_red + RED_LAUNCH) + 1) * (W2_GROUPS * 2));
                    asm volatile("fence.proxy.async.global;" ::: "memory");
                    mbar_expect_tx(sb + BAR_W, 6 * SQ_HALF);
                }
                __syncwarp();
                named_bar(2, 128);
                if (i && leader) {
                    fence_async();
                    bulk_load(sb + SM_W2 + (i - 1) * 2 * SQ_HALF, reinterpret_cast<const char*>(sc->w2h) + (i - 1) * 2 * SQ_HALF, 2 * SQ_HALF, sb + BAR_W);
                }
                if (i == 1) {
#pragma unroll
                    for (int m = 0; m < 3; m++) {
                        asm volatile("ld.global.nc.u16 %0, [%1];" : "=h"(gam_raw[m]) : "l"(gamma + i0 + 128 * m) : "memory");
                        asm volatile("ld.global.cg.f32 %0, [%1];" : "=f"(rmax[m]) : "l"(&sc->w2max[i0 + 128 * m]) : "memory");
                    }
                    if (i0 < 96)
                        asm volatile("ld.global.cg.v2.f32 {%0, %1}, [%2];" : "=f"(bpair.x), "=f"(bpair.y)
                                     : "l"(&sc->bias[32 * (i0 % 24 >> 3) + 8 * (i0 / 24) + (i0 % 24 & 6)]) : "memory");
                }
                __syncwarp();
                const uint32_t from = i < NCONS ? SM_SQ + i * 2 * SQ_HALF : w4 < 2 ? SM_RING + spare * SLOT_BYTES : SM_RING + spare2 * SLOT_BYTES - SQ_HALF;
                if (i) named_bar(12 + i, 256);
#pragma unroll
                for (int r = 0; r < 12; r++) {
                    uint32_t u[4];
                    ldsm4_t(u, from + (r % 3 == 2 ? third_row + r / 3 * 512 : two_rows + (r / 3 * 2 + r % 3) * 256));
                    asm volatile("mma.sync.aligned.m16n8k16.row.col.f32.f16.f16.f32 {%0, %1, %2, %3}, {%4, %5, %6, %7}, {%8, %8}, {%0, %1, %2, %3};"
                                 : "+f"(f[r % 3][0]), "+f"(f[r % 3][1]), "+f"(f[r % 3][2]), "+f"(f[r % 3][3])
                                 : "r"(u[0]), "r"(u[1]), "r"(u[2]), "r"(u[3]), "r"(pick));
                }
            }
            unsigned long long* dst = sc->sum(96 * w4 + 8 * (g >> 1) + 2 * (t & 1) + (g & 1));
#pragma unroll
            for (int r = 0; r < 3; r++) {
                const float tot = r < 2 ? (t < 2 ? f[0][r & 1] + f[1][r & 1] : f[0][r + 2 & 3] + f[1][r + 2 & 3]) : (t < 2 ? f[2][0] + f[2][2] : f[2][1] + f[2][3]);
                atomicAdd(dst + (r < 2 ? (t >> 1) * 8 + r : 16 + (t >> 1)) * 32, __float2ull_rn(fminf(tot * to_fixed, 0x1p47f)) << 8 | 1);
            }
            PROF(2);
            float base[3], slope[3], reach[3];
            const float w1max = max_w1(lane);
            const float gbound = fmaxf(2.f * KZ * 9.7979590f * 192.f * w1max, 1.f) * 19.5959180f * INV_2KZ;
            const unsigned fixed = __reduce_max_sync(~0u, __float_as_uint(fmaf(gbound, fmaxf(fmaxf(rmax[0], rmax[1]), rmax[2]), fmaxf(fabsf(bpair.x), fabsf(bpair.y)))));
            if (lane == 0) sts32(s_red + 96 + w4 * 4, fixed);
#pragma unroll
            for (int m = 0; m < 3; m++) {
                base[m] = rmax[m] > 0.f ? pow2i(-row_exp(rmax[m])) * (INV_2KZ * CUT_GAIN) : 0.f;
                slope[m] = base[m] * bf_lo(gam_raw[m]);
                reach[m] = fabsf(bf_lo(gam_raw[m])) * rmax[m] * gbound;
            }
            const float to_square = pow2i(-sum_exp(bound_exp(w1max))) * (INV_2KZ * INV_2KZ / 256);
#pragma unroll
            for (int m = 0; m < 3; m++) anchor(sq, __float_as_uint(base[m]), __float_as_uint(slope[m]), __float_as_uint(reach[m]), __float_as_uint(to_square));
            const unsigned epoch = ldsi(s_red + RED_LAUNCH);
            const uint32_t own_sum = (i0 >> 2) * 256 + (i0 & 3) * 8, own_fac = s_fac + i0 * 2;
            auto peek = [&](const void* p) {
                unsigned long long v;
                asm volatile("ld.relaxed.gpu.global.u64 %0, [%1];" : "=l"(v) : "l"(p) : "memory");
                return v;
            };
            const char* mine = reinterpret_cast<const char*>(sc->sums) + own_sum;
            unsigned n = 0;
            while (((unsigned)peek(sc->sum((blockIdx.x * 4 + w4) % (EX / 4) * 4)) & 255u) != gridDim.x)
                if (++n > SPIN_LIMIT) __trap();
            unsigned long long sum[3];
            for (;;) {
                bool all = true;
#pragma unroll
                for (int m = 0; m < 3; m++) {
                    sum[m] = peek(mine + m * (32 * 256));
                    all &= ((unsigned)sum[m] & 255u) == gridDim.x;
                }
                if (__all_sync(~0u, all)) break;
                if (++n > SPIN_LIMIT) __trap();
            }
            PROF(3);
            float gx[3];
#pragma unroll
            for (int m = 0; m < 3; m++) asm("sqrt.approx.ftz.f32 %0, %1;" : "=f"(gx[m]) : "f"(fmaf(__ull2float_rn(sum[m]), to_square, 1e-6f)));
            float tot = gx[0] + gx[1] + gx[2];
#pragma unroll
            for (int o = 16; o >= 1; o >>= 1) tot += __shfl_xor_sync(~0u, tot, o);
            const unsigned vwarp = __reduce_max_sync(~0u, __float_as_uint(fmaxf(fmaxf(reach[0] * gx[0], reach[1] * gx[1]), reach[2] * gx[2])));
            if (lane == 0) { sts32(s_red + 64 + w4 * 4, __float_as_uint(tot)); sts32(s_red + 80 + w4 * 4, vwarp); }
            named_bar(2, 128);
            uint32_t u[4], v[4], w[4];
            lds128(u[0], u[1], u[2], u[3], s_red + 64);
            lds128(v[0], v[1], v[2], v[3], s_red + 80);
            lds128(w[0], w[1], w[2], w[3], s_red + 96);
            tot = (__uint_as_float(u[0]) + __uint_as_float(u[1])) + (__uint_as_float(u[2]) + __uint_as_float(u[3]));
            const float vmax = __uint_as_float(max(max(v[0], v[1]), max(v[2], v[3]))), fmax2 = __uint_as_float(max(max(w[0], w[1]), max(w[2], w[3])));
            float inv_mean;
            asm("rcp.approx.ftz.f32 %0, %1;" : "=f"(inv_mean) : "f"(fmaf(tot, 1.f / EX, 1e-6f)));
            const int rho_e = 14 - ilog2f(fmaf(vmax, inv_mean, 2.f * fmax2));
            const float rho = pow2i(rho_e), inv_rho = pow2i(-rho_e);
            inv_rho2 = pack_bf2(inv_rho, inv_rho);
#pragma unroll
            for (int m = 0; m < 3; m++) {
                const float f = fmaf(slope[m] * gx[m], inv_mean, base[m]) * rho;
                asm volatile("st.shared.u16 [%0], %1;" ::"r"(own_fac + 256 * m), "h"((unsigned short)pack_h2(f, 0.f)) : "memory");
            }
            if (i0 < 96) sts32(sb + SM_BIASH + i0 * 4, pack_h2(bpair.x * rho, bpair.y * rho));
            if (i0 == 96) sts32(s_red + RED_INV_RHO, inv_rho2);
            named_arrive(12, NTHREADS);
            if (blockIdx.x == 0 && leader) sc->launch = epoch + 1;
            if (wk.lent) spin_until(&sc->lent_out, (epoch + 1) * 32 * LENT * sp.lenders);
        } else {
            named_arrive(12 + rank, 256);
            if (helps && rank == NCONS) signal(&sc->lent_out);
            const int rw = rank * 4 - 4 + w4;
            const uint32_t row = sb + SM_W2 + rw * 512 + lane * 16;
            uint32_t u[W2_EARLY][4], f2[4];
            mbar_wait_once(sb + BAR_W, 1);
#pragma unroll
            for (int nb = 0; nb < W2_EARLY; nb++) {
                lds128(u[nb][0], u[nb][1], u[nb][2], u[nb][3], row + nb * 6144);
            }
            named_bar(12, NTHREADS);
            PROF(3);
            lds128(f2[0], f2[1], f2[2], f2[3], s_fac + rw * 64 + (lane >> 3) * 16);
            lds32(inv_rho2, s_red + RED_INV_RHO);
#pragma unroll
            for (int nb = 0; nb < 12; nb++) {
                uint32_t v[4];
                if (nb < W2_EARLY) { v[0] = u[nb % W2_EARLY][0]; v[1] = u[nb % W2_EARLY][1]; v[2] = u[nb % W2_EARLY][2]; v[3] = u[nb % W2_EARLY][3]; }
                else lds128(v[0], v[1], v[2], v[3], row + nb * 6144);
                sts128(row + nb * 6144, h_cut8(h_mul(v[0], f2[0])), h_cut8(h_mul(v[1], f2[1])), h_cut8(h_mul(v[2], f2[2])), h_cut8(h_mul(v[3], f2[3])));
            }
            fence_async();
            named_arrive(8, NTHREADS);
        }
    }
    uint32_t a[6][4], acc[24], rpar = 0, tile_off = here;
    const uint32_t bias_addr = sb + SM_BIASH + (lane & 3) * 96, lane16 = lane * 16, lane_off = ((lane >> 2) * CH + 8 * (lane & 3)) * 2;
    const uint32_t stage = sb + SM_RING + (spare + rank) % NSLOT * SLOT_BYTES + w4 * WARP_BYTES, bar_r = sb + BAR_R + warp_id * 8;
    auto load_bias = [&]() {
#pragma unroll
        for (int q = 0; q < 6; q++) lds128(acc[4 * q], acc[4 * q + 1], acc[4 * q + 2], acc[4 * q + 3], bias_addr + q * 16);
    };
    auto load_frags = [&]() {
#pragma unroll
        for (int s = 0; s < 6; s++) ldg128(a[s], reinterpret_cast<const char*>(out) + next_off + w4 * WARP_BYTES + lane16 + s * 512);
    };
    auto stage_x = [&]() {
        if (elect_one()) {
            mbar_expect_tx(bar_r, WARP_BYTES);
            bulk_load_stream(stage, reinterpret_cast<const char*>(x) + tile_off + w4 * WARP_BYTES, WARP_BYTES, bar_r);
        }
    };
    {
        named_bar(8 + rank, rank ? 256 : NTHREADS);
        if (rank == 0) PROF(4);
        load_bias();
        pin(k1); pin(k2); pin(k3);
        wg_fence();
        gemm2_chunk<288>(acc, k3, ds);
        wg_commit();
        gemm2_chunk<96>(acc, k1, ds);
        wg_commit();
        gemm2_chunk<192>(acc, k2, ds);
        wg_commit();
        stage_x();
        wg_wait<2>();
        uint32_t k0[24];
#pragma unroll
        for (int q = 0; q < 6; q++)
            lds128(k0[4 * q], k0[4 * q + 1], k0[4 * q + 2], k0[4 * q + 3], sb + SM_RING + cur.slot * SLOT_BYTES + w4 * REGION_BYTES + lane16 + q * 512);
        pin(k0);
        wg_fence();
        gemm2_chunk<0>(acc, k0, ds);
        wg_commit();
        if (rank < NCONS) named_arrive(9 + rank, 256);
        wg_wait<2>();
        load_frags();
        if (lane16 == 0) mbar_arrive(sb + BAR_PIN);
        mbar_wait(bar_r, rpar);
        wg_wait<0>();
    }
    auto lent = [&](uint32_t entry) { return &sc->lent[((wk.index * LENT + (entry & 3) - 1) * 4 + w4) * (24 * 32)]; };
    for (jt = rank - 4; jt < nrest; jt += 4) {
        if (jt >= zero) {
        tile_off = next_off;
        lds32(next_off, sb + SM_TILES + (jt + 4) * 4);
        if (tile_off & 3) {
            const uint4* src = lent(tile_off) + lane;
            tile_off &= ~3u;
            next_off = __shfl_sync(~0u, next_off, 0);
            stage_x();
            if (elect_one()) prefetch_l2(reinterpret_cast<const char*>(out) + next_off + w4 * WARP_BYTES, WARP_BYTES);
            load_bias();
#pragma unroll 1
            for (int half = 0; half < 2; half++, src += 12 * 32) {
                uint32_t gl[48];
#pragma unroll
                for (int s = 0; s < 12; s++) ldg128(reinterpret_cast<uint32_t (&)[4]>(gl[4 * s]), src + s * 32);
                if (!half) {
                    named_bar(4 + rank, 256);
                    named_arrive(4 + ((rank + 1) & 3), 256);
                }
                pin(gl);
                wg_fence();
#pragma unroll
                for (int s = 0; s < 12; s++) wgmma(acc, gl[4 * s], gl[4 * s + 1], gl[4 * s + 2], gl[4 * s + 3], ds.w2[12 * half + s], 1);
                wg_commit();
                wg_wait<0>();
            }
            load_frags();
            mbar_wait(bar_r, rpar);
        } else {
            uint32_t d0[12], d1[12], g0[12], g1[12];
            next_off = __shfl_sync(~0u, next_off, 0);
            const bool more = jt + 4 < nrest && !(next_off & 3);
            load_bias();
            wg_fence();
            gemm1_chunk<0>(d0, a, ds, 0);
            wg_commit();
            if (jt) named_bar(4 + rank, 256);
            gemm1_chunk<48>(d1, a, ds, 0);
            wg_commit();
            wg_wait<1>();
#define CNX_STEP(C, D, G)                                                   \
    gelu_to(G, D);                                                          \
    wg_fence();                                                             \
    if (C < 6) gemm1_chunk<48 * (C < 6 ? C + 2 : 0)>(D, a, ds, zero);      \
    gemm2_chunk<48 * C>(acc, G, ds);                                       \
    wg_commit();                                                            \
    if (C == 1 && jt + 1 < nrest) named_arrive(4 + ((rank + 1) & 3), 256); \
    wg_wait<(C < 7 ? 1 : 0)>();
            CNX_STEP(0, d0, g0)
            stage_x();
            if (elect_one()) {
                if (more) prefetch_l2(reinterpret_cast<const char*>(out) + next_off + w4 * WARP_BYTES, WARP_BYTES);
                else if (next_off & 3) prefetch_l2(lent(next_off), 24 * 32 * 16);
            }
            CNX_STEP(1, d1, g1)
            CNX_STEP(2, d0, g0)
            CNX_STEP(3, d1, g1)
            CNX_STEP(4, d0, g0)
            CNX_STEP(5, d1, g1)
            CNX_STEP(6, d0, g0)
#pragma unroll
            for (int s = 0; s < 6; s++) ldg128_if(more, a[s], reinterpret_cast<const char*>(out) + next_off + w4 * WARP_BYTES + lane16 + s * 512);
            if (lane16 == 0) mbar_arrive(sb + BAR_PIN);
            mbar_wait(bar_r, rpar);
            CNX_STEP(7, d1, g1)
#undef CNX_STEP
        }
        }
        {
            pin(acc);
            rpar ^= 1;
            uint4* op = reinterpret_cast<uint4*>(reinterpret_cast<char*>(out) + tile_off + w4 * WARP_BYTES + lane_off);
#pragma unroll
            for (int h = 0; h < 2; h++)
#pragma unroll
                for (int m = 0; m < 3; m++) {
                    uint32_t xin[4], o[4];
                    lds128(xin[0], xin[1], xin[2], xin[3], stage + lane_off + h * 1536 + m * 64);
#pragma unroll
                    for (int q = 0; q < 4; q++) {
                        const uint32_t v = acc[2 * (4 * m + q) + h];
                        o[q] = bf_fma(pack_bf2(h_lo(v), h_hi(v)), inv_rho2, xin[q]);
                    }
                    __stcs(op + h * 96 + m * 4, make_uint4(o[0], o[1], o[2], o[3]));
                }
            __syncwarp();
        }
    }
    PROF(5);
}

}

typedef CUresult (*EncodeTiledFn)(CUtensorMap*, CUtensorMapDataType, cuuint32_t, void*, const cuuint64_t*, const cuuint64_t*,
                                  const cuuint32_t*, const cuuint32_t*, CUtensorMapInterleave, CUtensorMapSwizzle,
                                  CUtensorMapL2promotion, CUtensorMapFloatOOBfill);

extern "C" void kernel_launch(void* const* d_in, const int* in_sizes, int n_in, void* d_out, int out_size) {
    using namespace cnx;
    static EncodeTiledFn encode = nullptr;
    static int num_sms = 0;
    static Scratch* scratch = nullptr;
    if (!encode) {
        void* fn = nullptr;
        cudaDriverEntryPointQueryResult qr;
        cudaGetDriverEntryPoint("cuTensorMapEncodeTiled", &fn, cudaEnableDefault, &qr);
        encode = (EncodeTiledFn)fn;
        cudaGetSymbolAddress((void**)&scratch, g_scratch);
        int dev = 0;
        cudaGetDevice(&dev);
        cudaDeviceGetAttribute(&num_sms, cudaDevAttrMultiProcessorCount, dev);
        if (num_sms > MAX_CTAS) num_sms = MAX_CTAS;
        cudaFuncSetAttribute(block_kernel, cudaFuncAttributeMaxDynamicSharedMemorySize, SM_TOTAL);
    }
    CUtensorMap tm;
    cuuint64_t dims[3] = {(cuuint64_t)CH, (cuuint64_t)IMG_W, (cuuint64_t)IMG_H};
    cuuint64_t strides[2] = {(cuuint64_t)CH * 2, (cuuint64_t)CH * 2 * IMG_W};
    cuuint32_t box[3] = {(cuuint32_t)CH, (cuuint32_t)REGION_PX, 1};
    cuuint32_t estr[3] = {1, 1, 1};
    encode(&tm, CU_TENSOR_MAP_DATA_TYPE_BFLOAT16, 3, d_in[0], dims, strides, box, estr, CU_TENSOR_MAP_INTERLEAVE_NONE,
           CU_TENSOR_MAP_SWIZZLE_NONE, CU_TENSOR_MAP_L2_PROMOTION_L2_128B, CU_TENSOR_MAP_FLOAT_OOB_FILL_NONE);
    Params pm = {};
    Descs& ds = pm.ds;
    for (int c = 0; c < 8; c++)
        for (int k = 0; k < 6; k++) ds.w1[c][k] = make_desc(SB + SM_W1 + c * 6 * 1536 + k * 256, 128, 1536);
    for (int k = 0; k < 24; k++) ds.w2[k] = make_desc(SB + SM_W2 + k * 256, 128, 6144);
    ds.ones = make_desc(SB + SM_ONES, 0, 0);
    CUtensorMap tw;
    cuuint64_t wdims[2] = {(cuuint64_t)EX, (cuuint64_t)CH};
    cuuint64_t wstrides[1] = {(cuuint64_t)EX * 2};
    cuuint32_t wbox[2] = {64, (cuuint32_t)CH};
    encode(&tw, CU_TENSOR_MAP_DATA_TYPE_BFLOAT16, 2, d_in[2], wdims, wstrides, wbox, estr, CU_TENSOR_MAP_INTERLEAVE_NONE,
           CU_TENSOR_MAP_SWIZZLE_128B, CU_TENSOR_MAP_L2_PROMOTION_L2_128B, CU_TENSOR_MAP_FLOAT_OOB_FILL_NONE);
    Split& sp = pm.sp;
    sp = {NTILES / num_sms, NTILES % num_sms, 1, 1 << 16, 0, {}};
    if (sp.per_cta + 9 > MAX_ROWS) return;
    if (sp.extra && sp.extra * (8 * LENT + 1) + W2_GROUPS / 2 <= num_sms && sp.per_cta >= 5 * LENT + 8) {
        sp.period = num_sms / sp.extra;
        sp.inv_period = 65535 / sp.period + 1;
        sp.lenders = sp.extra;
        for (int l = 0; l < sp.extra; l++) {
            const Work w = get_work((l + 1) * sp.period - sp.period / 2 - 1, sp);
            for (int e = 0; e < LENT; e++) sp.lent_off[l * LENT + e] = tile_offset(w.tile(e));
            if (w.nA < 2 * LENT) sp.lenders = 0;
        }
    }
    pm.x = (const __nv_bfloat16*)d_in[0];
    pm.dw = (const __nv_bfloat16*)d_in[1];
    pm.w2 = (const __nv_bfloat16*)d_in[3];
    pm.gamma = (const __nv_bfloat16*)d_in[4];
    pm.beta = (const __nv_bfloat16*)d_in[5];
    pm.out = (__nv_bfloat16*)d_out;
    pm.sc = scratch;
    block_kernel<<<num_sms, NTHREADS, SM_TOTAL>>>(tm, tw, pm);
}
```

```cpp
#include <cuda_runtime.h>
#include <cuda_bf16.h>
#include <cuda_fp16.h>
#include <cuda.h>
#include <stdint.h>

namespace cnx {

constexpr int IMG_H = 512, IMG_W = 512, CH = 96, EX = 384;
constexpr int TILE_W = 64;
constexpr int NTILES = (IMG_W / TILE_W) * IMG_H;
constexpr int NSLOT = 6;
constexpr int REGION_PX = 18;
constexpr int REGION_BYTES = REGION_PX * CH * 2;
constexpr int SLOT_BYTES = 4 * REGION_BYTES;
constexpr int A_LBO = 144, A_SBO = 12 * A_LBO;
constexpr int PREFETCH_ROWS = 3;
constexpr int NCONS = 3;
constexpr int CONS_THREADS = 128 * NCONS;
constexpr int NTHREADS = 128 + CONS_THREADS;
constexpr int MAX_ROWS = 52;
constexpr int TILE_BYTES = TILE_W * CH * 2, WARP_BYTES = TILE_BYTES / 4;
constexpr int ORDER_P = 3;
constexpr int W2_EARLY = 9;
static_assert(MAX_ROWS <= 128, "one table entry per producer thread");
static_assert(2 * A_SBO == REGION_BYTES && REGION_BYTES % 128 == 0, "region layout");

constexpr uint32_t SB = 1024;
constexpr int SM_W1 = 0;
constexpr int SM_W2 = SM_W1 + CH * EX * 2;
constexpr int SM_RING = SM_W2 + CH * EX * 2;
constexpr int SM_BIASH = SM_RING + NSLOT * SLOT_BYTES;
constexpr int SM_RED = SM_BIASH + 384;
constexpr int RED_MAX = 0, RED_LAUNCH = 48, RED_INV_RHO = 52, RED_JOB = 56;
constexpr int SM_TILES = SM_RED + 256;
constexpr int SM_ONES = SM_TILES + MAX_ROWS * 4;
constexpr int SM_BAR = SM_ONES + 128;
constexpr int BAR_X = SM_BAR;
constexpr int BAR_A = BAR_X + NSLOT * 4 * 8;
constexpr int BAR_E = BAR_A + NSLOT * 4 * 8;
constexpr int BAR_PIN = BAR_E + NSLOT * 4 * 8;
constexpr int BAR_W = BAR_PIN + 8;
constexpr int BAR_F = BAR_W + 6 * 8;
constexpr int BAR_R = BAR_F + 8;
constexpr int SM_TOTAL = BAR_R + 16 * 8;
constexpr int SM_FILTER = SM_RING + (NSLOT - 1) * SLOT_BYTES + 9 * 128;
constexpr int SM_SQ = SM_W2;
constexpr int SQ_ROW = 128 * 16, SQ_HALF = 6 * SQ_ROW;
static_assert(SM_ONES % 16 == 0 && SM_TOTAL <= 232448, "shared memory budget");

constexpr float KZ = 0.3292034911525734f;
constexpr uint32_t GELU_C2 = 0x40d940d9u;
constexpr float INV_2KZ = 0.5f / KZ;
constexpr unsigned SPIN_LIMIT = 1u << 19;

constexpr int MAX_CTAS = 170;
constexpr int W2_GROUPS = EX / 8;
constexpr int LENT = 3, MAX_LENDERS = MAX_CTAS / (8 * LENT + 1);
struct Scratch {
    uint32_t w2h[EX * CH / 2];
    float w2max[EX];
    float bias[CH + 32];
    unsigned long long sums[EX / 4][32];
    __device__ __forceinline__ unsigned long long* sum(int e) { return &sums[e >> 2][e & 3]; }
    uint4 lent[MAX_LENDERS * LENT * 8 * 4 * 3 * 32];
    unsigned launch, pad0[31], early, pad1[31], prep, pad2[31], lent_out, pad3[31];
    unsigned job;
};
__device__ __align__(128) Scratch g_scratch;

#define PROF(k)

__device__ __forceinline__ uint32_t smem_u32(const void* p) { return (uint32_t)__cvta_generic_to_shared(p); }
__device__ __forceinline__ void mbar_init(uint32_t bar, uint32_t cnt) {
    asm volatile("mbarrier.init.shared::cta.b64 [%0], %1;" ::"r"(bar), "r"(cnt) : "memory");
}
__device__ __forceinline__ void mbar_arrive(uint32_t bar) {
    asm volatile("mbarrier.arrive.shared::cta.b64 _, [%0];" ::"r"(bar) : "memory");
}
__device__ __forceinline__ void mbar_expect_tx(uint32_t bar, uint32_t bytes) {
    asm volatile("mbarrier.arrive.expect_tx.shared::cta.b64 _, [%0], %1;" ::"r"(bar), "r"(bytes) : "memory");
}
__device__ __forceinline__ bool mbar_try(uint32_t bar, uint32_t par) {
    uint32_t ok;
    asm volatile("{\n.reg .pred p;\nmbarrier.try_wait.parity.shared::cta.b64 p, [%1], %2;\nselp.u32 %0, 1, 0, p;\n}\n"
                 : "=r"(ok) : "r"(bar), "r"(par) : "memory");
    return ok != 0;
}
__device__ __forceinline__ void mbar_wait(uint32_t bar, uint32_t par) {
    unsigned n = 0;
    while (!mbar_try(bar, par)) {
        if (++n > SPIN_LIMIT) __trap();
    }
}
__device__ __forceinline__ void mbar_wait_once(uint32_t bar, uint32_t par) {
    unsigned n = 0;
    bool ok;
#pragma unroll 1
    do {
        ok = mbar_try(bar, par);
        if (++n > SPIN_LIMIT) __trap();
    } while (!ok);
}
__device__ __forceinline__ bool elect_one() {
    uint32_t ok;
    asm volatile("{\n.reg .pred p;\nelect.sync _|p, 0xffffffff;\nselp.u32 %0, 1, 0, p;\n}\n" : "=r"(ok));
    return ok != 0;
}
__device__ __forceinline__ uint32_t opaque(uint32_t v) { return __shfl_sync(~0u, v, threadIdx.x & 31); }
__device__ __forceinline__ uint32_t lane_id() { uint32_t v; asm volatile("mov.u32 %0, %%laneid;" : "=r"(v)); return v; }
__device__ __forceinline__ uint32_t opaque_uniform(uint32_t v) { return __shfl_sync(~0u, v, 0); }
__device__ __forceinline__ void named_bar(int id, int n) { asm volatile("bar.sync %0, %1;" ::"r"(id), "r"(n) : "memory"); }
__device__ __forceinline__ void named_arrive(int id, int n) { asm volatile("bar.arrive %0, %1;" ::"r"(id), "r"(n) : "memory"); }
__device__ __forceinline__ void fence_async() { asm volatile("fence.proxy.async.shared::cta;" ::: "memory"); }
constexpr uint64_t EVICT_FIRST = 0x12F0000000000000ull;
__device__ __forceinline__ void tma_row(uint32_t dst, const CUtensorMap* tm, uint32_t bar, int x, int y) {
    asm volatile("cp.async.bulk.tensor.3d.shared::cluster.global.mbarrier::complete_tx::bytes.L2::cache_hint [%0], [%1, {%3, %4, %5}], [%2], %6;"
                 ::"r"(dst), "l"(tm), "r"(bar), "r"(0), "r"(x), "r"(y), "l"(EVICT_FIRST) : "memory");
}
__device__ __forceinline__ void bulk_load_stream(uint32_t dst, const void* src, uint32_t bytes, uint32_t bar) {
    asm volatile("cp.async.bulk.shared::cluster.global.mbarrier::complete_tx::bytes.L2::cache_hint [%0], [%1], %2, [%3], %4;"
                 ::"r"(dst), "l"(src), "r"(bytes), "r"(bar), "l"(EVICT_FIRST) : "memory");
}
__device__ __forceinline__ void prefetch_l2(const void* src, uint32_t bytes) {
    asm volatile("cp.async.bulk.prefetch.L2.global [%0], %1;" ::"l"(src), "r"(bytes) : "memory");
}
__device__ __forceinline__ void tma_2d(uint32_t dst, const CUtensorMap* tm, uint32_t bar, int x, int y) {
    asm volatile("cp.async.bulk.tensor.2d.shared::cluster.global.mbarrier::complete_tx::bytes [%0], [%1, {%3, %4}], [%2];"
                 ::"r"(dst), "l"(tm), "r"(bar), "r"(x), "r"(y) : "memory");
}
__device__ __forceinline__ void bulk_load(uint32_t dst, const void* src, uint32_t bytes, uint32_t bar) {
    asm volatile("cp.async.bulk.shared::cluster.global.mbarrier::complete_tx::bytes [%0], [%1], %2, [%3];"
                 ::"r"(dst), "l"(src), "r"(bytes), "r"(bar) : "memory");
}
__device__ __forceinline__ void wg_fence() { asm volatile("wgmma.fence.sync.aligned;" ::: "memory"); }
__device__ __forceinline__ void wg_commit() { asm volatile("wgmma.commit_group.sync.aligned;" ::: "memory"); }
template <int N> __device__ __forceinline__ void wg_wait() { asm volatile("wgmma.wait_group.sync.aligned %0;" ::"n"(N) : "memory"); }
template <int N> __device__ __forceinline__ void pin(uint32_t (&d)[N]) {
#pragma unroll
    for (int q = 0; q < N; q++) asm volatile("" : "+r"(d[q])::"memory");
}
__device__ __forceinline__ void stg128(void* p, const uint32_t (&v)[4]) {
    asm volatile("st.global.v4.u32 [%0], {%1, %2, %3, %4};" ::"l"(p), "r"(v[0]), "r"(v[1]), "r"(v[2]), "r"(v[3]) : "memory");
}
__device__ __forceinline__ void ldg128(uint32_t (&v)[4], const void* p) {
    asm volatile("ld.global.L1::no_allocate.v4.u32 {%0, %1, %2, %3}, [%4];" : "=r"(v[0]), "=r"(v[1]), "=r"(v[2]), "=r"(v[3]) : "l"(p) : "memory");
}
__device__ __forceinline__ void ldg128_if(bool on, uint32_t (&v)[4], const void* p) {
    asm volatile("{\n.reg .pred p;\nsetp.ne.b32 p, %5, 0;\n@p ld.global.L1::no_allocate.v4.u32 {%0, %1, %2, %3}, [%4];\n}\n"
                 : "+r"(v[0]), "+r"(v[1]), "+r"(v[2]), "+r"(v[3]) : "l"(p), "r"((int)on) : "memory");
}
__host__ __device__ constexpr uint64_t make_desc(uint32_t addr, uint32_t lbo, uint32_t sbo) {
    return (uint64_t)((addr & 0x3FFFF) >> 4) | ((uint64_t)(lbo >> 4) << 16) | ((uint64_t)(sbo >> 4) << 32);
}
__device__ __forceinline__ void wgmma(uint32_t (&d)[12], uint32_t a0, uint32_t a1, uint32_t a2, uint32_t a3, uint64_t db, int acc) {
    asm volatile("{\n.reg .pred p;\nsetp.ne.b32 p, %17, 0;\n"
                 "wgmma.mma_async.sync.aligned.m64n48k16.f16.f16.f16 "
                 "{%0, %1, %2, %3, %4, %5, %6, %7, %8, %9, %10, %11}, "
                 "{%12, %13, %14, %15}, %16, p, 1, 1, 0;\n}\n"
                 : "+r"(d[0]), "+r"(d[1]), "+r"(d[2]), "+r"(d[3]), "+r"(d[4]), "+r"(d[5]), "+r"(d[6]), "+r"(d[7]), "+r"(d[8]), "+r"(d[9]), "+r"(d[10]), "+r"(d[11])
                 : "r"(a0), "r"(a1), "r"(a2), "r"(a3), "l"(db), "r"(acc));
}
__device__ __forceinline__ void wgmma(uint32_t (&d)[24], uint32_t a0, uint32_t a1, uint32_t a2, uint32_t a3, uint64_t db, int acc) {
    asm volatile("{\n.reg .pred p;\nsetp.ne.b32 p, %29, 0;\n"
                 "wgmma.mma_async.sync.aligned.m64n96k16.f16.f16.f16 "
                 "{%0, %1, %2, %3, %4, %5, %6, %7, %8, %9, %10, %11, %12, %13, %14, %15, %16, %17, %18, %19, %20, %21, %22, %23}, "
                 "{%24, %25, %26, %27}, %28, p, 1, 1, 0;\n}\n"
                 : "+r"(d[0]), "+r"(d[1]), "+r"(d[2]), "+r"(d[3]), "+r"(d[4]), "+r"(d[5]), "+r"(d[6]), "+r"(d[7]), "+r"(d[8]), "+r"(d[9]), "+r"(d[10]), "+r"(d[11]), "+r"(d[12]), "+r"(d[13]), "+r"(d[14]), "+r"(d[15]), "+r"(d[16]), "+r"(d[17]), "+r"(d[18]), "+r"(d[19]), "+r"(d[20]), "+r"(d[21]), "+r"(d[22]), "+r"(d[23])
                 : "r"(a0), "r"(a1), "r"(a2), "r"(a3), "l"(db), "r"(acc));
}
template <int ACC>
__device__ __forceinline__ void wgmma_rowsum(float (&d)[4], const uint32_t (&a)[4], uint64_t ones) {
    asm volatile("{\n.reg .pred p;\nsetp.ne.b32 p, %9, 0;\n"
                 "wgmma.mma_async.sync.aligned.m64n8k16.f32.bf16.bf16 {%0, %1, %2, %3}, {%4, %5, %6, %7}, %8, p, 1, 1, 0;\n}\n"
                 : "+f"(d[0]), "+f"(d[1]), "+f"(d[2]), "+f"(d[3])
                 : "r"(a[0]), "r"(a[1]), "r"(a[2]), "r"(a[3]), "l"(ones), "n"(ACC));
}
__device__ __forceinline__ void ldsm4(uint32_t (&r)[4], uint32_t addr) {
    asm volatile("ldmatrix.sync.aligned.m8n8.x4.shared.b16 {%0, %1, %2, %3}, [%4];"
                 : "=r"(r[0]), "=r"(r[1]), "=r"(r[2]), "=r"(r[3]) : "r"(addr) : "memory");
}
__device__ __forceinline__ void ldsm4_t(uint32_t (&r)[4], uint32_t addr) {
    asm volatile("ldmatrix.sync.aligned.m8n8.x4.trans.shared.b16 {%0, %1, %2, %3}, [%4];"
                 : "=r"(r[0]), "=r"(r[1]), "=r"(r[2]), "=r"(r[3]) : "r"(addr) : "memory");
}
__device__ __forceinline__ void stsm4(uint32_t addr, uint32_t a, uint32_t b, uint32_t c, uint32_t d) {
    asm volatile("stmatrix.sync.aligned.m8n8.x4.shared.b16 [%0], {%1, %2, %3, %4};"
                 ::"r"(addr), "r"(a), "r"(b), "r"(c), "r"(d) : "memory");
}
__device__ __forceinline__ uint32_t transpose8x8(uint32_t v) {
    uint32_t d; asm volatile("movmatrix.sync.aligned.m8n8.trans.b16 %0, %1;" : "=r"(d) : "r"(v)); return d;
}
__device__ __forceinline__ void spin_until(const unsigned* counter, unsigned target) {
    unsigned n = 0, c;
    do {
        asm volatile("ld.acquire.gpu.global.u32 %0, [%1];" : "=r"(c) : "l"(counter) : "memory");
        if (++n > SPIN_LIMIT) __trap();
    } while ((int)(c - target) < 0);
}
__device__ __forceinline__ void signal(unsigned* counter) {
    __syncwarp();
    if (elect_one()) asm volatile("red.release.gpu.global.add.u32 [%0], 1;" ::"l"(counter) : "memory");
    __syncwarp();
}
__device__ __forceinline__ void lds128(uint32_t& a, uint32_t& b, uint32_t& c, uint32_t& d, uint32_t addr) {
    asm volatile("ld.shared.v4.u32 {%0, %1, %2, %3}, [%4];" : "=r"(a), "=r"(b), "=r"(c), "=r"(d) : "r"(addr) : "memory");
}
__device__ __forceinline__ void lds64(uint32_t& a, uint32_t& b, uint32_t addr) {
    asm volatile("ld.shared.v2.u32 {%0, %1}, [%2];" : "=r"(a), "=r"(b) : "r"(addr) : "memory");
}
__device__ __forceinline__ void lds32(uint32_t& a, uint32_t addr) {
    asm volatile("ld.shared.u32 %0, [%1];" : "=r"(a) : "r"(addr) : "memory");
}
__device__ __forceinline__ int ldsi(uint32_t addr) {
    uint32_t v;
    lds32(v, addr);
    return (int)v;
}
__device__ __forceinline__ float ldsf(uint32_t addr) {
    uint32_t v;
    lds32(v, addr);
    return __uint_as_float(v);
}
__device__ __forceinline__ void sts32(uint32_t addr, uint32_t a) {
    asm volatile("st.shared.u32 [%0], %1;" ::"r"(addr), "r"(a) : "memory");
}
__device__ __forceinline__ void sts128(uint32_t addr, uint32_t a, uint32_t b, uint32_t c, uint32_t d) {
    asm volatile("st.shared.v4.u32 [%0], {%1, %2, %3, %4};" ::"r"(addr), "r"(a), "r"(b), "r"(c), "r"(d) : "memory");
}
__device__ __forceinline__ void sts64(uint32_t addr, uint32_t a, uint32_t b) {
    asm volatile("st.shared.v2.u32 [%0], {%1, %2};" ::"r"(addr), "r"(a), "r"(b) : "memory");
}
__device__ __forceinline__ void anchor(uint32_t addr, uint32_t a, uint32_t b, uint32_t c, uint32_t d) {
    asm volatile("{\n.reg .pred p;\nsetp.eq.b32 p, %0, 0;\n@p st.shared.v4.u32 [%0], {%1, %2, %3, %4};\n}\n"
                 ::"r"(addr), "r"(a), "r"(b), "r"(c), "r"(d) : "memory");
}
__device__ __forceinline__ uint32_t bf_fma(uint32_t a, uint32_t b, uint32_t c) {
    uint32_t d; asm("fma.rn.bf16x2 %0, %1, %2, %3;" : "=r"(d) : "r"(a), "r"(b), "r"(c)); return d;
}
__device__ __forceinline__ uint32_t bf_mul(uint32_t a, uint32_t b) {
    uint32_t d; asm("mul.rn.bf16x2 %0, %1, %2;" : "=r"(d) : "r"(a), "r"(b)); return d;
}
__device__ __forceinline__ uint32_t bf_absmax(uint32_t a, uint32_t b) {
    uint32_t d; asm("max.xorsign.abs.bf16x2 %0, %1, %2;" : "=r"(d) : "r"(a), "r"(b)); return d;
}
__device__ __forceinline__ uint32_t h_fma(uint32_t a, uint32_t b, uint32_t c) {
    uint32_t d; asm("fma.rn.f16x2 %0, %1, %2, %3;" : "=r"(d) : "r"(a), "r"(b), "r"(c)); return d;
}
__device__ __forceinline__ uint32_t h_mul(uint32_t a, uint32_t b) {
    uint32_t d; asm("mul.rn.f16x2 %0, %1, %2;" : "=r"(d) : "r"(a), "r"(b)); return d;
}
__device__ __forceinline__ uint32_t h_cut8(uint32_t v) { return v & 0xfff8fff8u; }
constexpr float CUT_GAIN = 1.f + 0.4375f * 0.7213f / 128;
__device__ __forceinline__ uint32_t h_tanh(uint32_t a) {
    uint32_t d; asm("tanh.approx.f16x2 %0, %1;" : "=r"(d) : "r"(a)); return d;
}
__device__ __forceinline__ uint32_t pack_h2(float lo, float hi) {
    uint32_t d; asm("cvt.rn.f16x2.f32 %0, %1, %2;" : "=r"(d) : "f"(hi), "f"(lo)); return d;
}
__device__ __forceinline__ uint32_t pack_bf2(float lo, float hi) {
    uint32_t d; asm("cvt.rn.bf16x2.f32 %0, %1, %2;" : "=r"(d) : "f"(hi), "f"(lo)); return d;
}
__device__ __forceinline__ float bf_lo(uint32_t v) { return __uint_as_float(v << 16); }
__device__ __forceinline__ float bf_hi(uint32_t v) { return __uint_as_float(v & 0xffff0000u); }
__device__ __forceinline__ float h_lo(uint32_t v) { return __low2float(*reinterpret_cast<__half2*>(&v)); }
__device__ __forceinline__ float h_hi(uint32_t v) { return __high2float(*reinterpret_cast<__half2*>(&v)); }
__device__ __forceinline__ float warp_absmax(uint32_t v) {
    return __uint_as_float(__reduce_max_sync(~0u, max((v & 0x7fffu) << 16, v & 0x7fff0000u)));
}
__device__ __forceinline__ uint32_t gelu2(uint32_t z) {
    uint32_t p = h_fma(z, z, GELU_C2);
    uint32_t t = h_tanh(h_mul(z, p));
    return h_fma(z, t, z);
}
__device__ __forceinline__ float pow2i(int e) { return __uint_as_float((uint32_t)(e + 127) << 23); }
__device__ __forceinline__ int ilog2f(float v) {
    int e = (int)((__float_as_uint(v) >> 23) & 0xff) - 127;
    return max(-100, min(100, e));
}

__device__ __forceinline__ int bound_exp(float w1max) { return w1max > 0.f ? ilog2f(2.f * KZ * 96.f * w1max) : 0; }
__device__ __forceinline__ bool plain_squares(int e) { return (unsigned)(4 - e) <= 6; }
__device__ __forceinline__ int square_exp(int e) { return plain_squares(e) ? 0 : max(-14, min(4 - e, 14)); }
__device__ __forceinline__ int sum_exp(int e) { return max(-90, min(90, 33 - 2 * e)); }
__device__ __forceinline__ int row_exp(float m) { return 2 - ilog2f(m); }

struct Split {
    int per_cta, extra, period, inv_period, lenders;
    uint32_t lent_off[MAX_LENDERS * LENT];
    __host__ __device__ __forceinline__ int longer_before(int cta) const {
        const int n = (cta + period / 2) * inv_period >> 16;
        return n < extra ? n : extra;
    }
};
struct Work {
    int tA, tB, nA, nB, dir, rows, lent, index;
    __host__ __device__ __forceinline__ int tile(int j) const { return j < nA ? tA + dir * j : tB + dir * (j - nA); }
};
__host__ __device__ __forceinline__ Work get_work(int cta, const Split& sp) {
    Work w;
    const int before = sp.longer_before(cta), longer = sp.longer_before(cta + 1) - before;
    w.lent = longer && sp.lenders ? LENT : 0;
    w.index = before;
    const int t0 = cta * sp.per_cta + before, t1 = t0 + sp.per_cta + longer;
    const int tm = t1 < (t0 | 511) + 1 ? t1 : (t0 | 511) + 1;
    const bool swap = t1 > tm && t1 - tm < tm - t0, down = cta & 1;
    w.nA = swap ? t1 - tm : tm - t0;
    w.nB = t1 - t0 - w.nA;
    w.tA = down ? (swap ? tm : t0) : (swap ? t1 : tm) - 1;
    w.tB = down ? (swap ? t0 : tm) : (swap ? tm : t1) - 1;
    w.dir = down ? 1 : -1;
    w.rows = w.nA + 2 + (w.nB ? w.nB + 2 : 0);
    return w;
}
__device__ __forceinline__ int row_code(const Work& w, int i) {
    const bool in_a = i < w.nA + 2;
    const int t = in_a ? w.tA : w.tB;
    return ((t & 511) + w.dir * ((in_a ? i : i - (w.nA + 2)) - 1)) << 16 | (t >> 9) * TILE_W;
}
__host__ __device__ __forceinline__ uint32_t tile_offset(int tile) { return ((tile & 511) * IMG_W + (tile >> 9) * TILE_W) * (CH * 2); }
__device__ __forceinline__ int tile_order(int j, int n) {
    return j % ORDER_P == ORDER_P - 1 ? j / ORDER_P : n - 1 - (j - j / ORDER_P);
}
__device__ __forceinline__ void issue_region(const CUtensorMap* tm, uint32_t dst, uint32_t bar, int warp, int code) {
    mbar_expect_tx(bar, REGION_BYTES);
    tma_row(dst, tm, bar, (code & 0xffff) + (16 * warp - 1), code >> 16);
}

template <class Event>
__device__ __forceinline__ void conv_producer(const Work& wk, const CUtensorMap* tm, uint32_t sb, int warp, Event event) {
    const int lane = threadIdx.x & 31;
    const int j = lane & 15, grp = lane >> 4;
    const uint32_t reg0 = sb + SM_RING + warp * REGION_BYTES;
    const uint32_t bars = sb + SM_BAR + warp * 8;
    if (warp * 32 + lane < MAX_ROWS) {
        const int i = warp * 32 + lane, before = min(i / 5, wk.lent);
        const bool back = i % 5 == 0 && i > 0 && i / 5 <= wk.lent;
        sts32(sb + SM_TILES + i * 4, back ? tile_offset(wk.tile(before - 1)) | before
                                          : tile_offset(wk.tile(wk.lent + tile_order(i - before, wk.nA + wk.nB - 4 - wk.lent))));
    }
    const uint32_t ld64 = opaque(reg0 + grp * 8 * 192 + j * 8), ld32 = opaque(reg0 + grp * 8 * 192 + 128 + j * 4);
    const uint32_t st64 = opaque(reg0 + grp * A_SBO + (j >> 1) * A_LBO + (j & 1) * 8);
    const uint32_t st32 = opaque(reg0 + grp * A_SBO + (8 + (j >> 2)) * A_LBO + (j & 3) * 4);
    named_bar(0, NTHREADS);
    uint32_t w[3][3][3];
    mbar_wait_once(sb + BAR_F, 0);
#pragma unroll
    for (int tap = 0; tap < 9; tap++) {
        const uint32_t p = sb + SM_FILTER + (3 + wk.dir * 3 * (tap / 3 - 1) + tap % 3) * (CH * 2);
        lds64(w[tap / 3][tap % 3][0], w[tap / 3][tap % 3][1], p + 8 * j);
        lds32(w[tap / 3][tap % 3][2], p + 128 + 4 * j);
    }
#pragma unroll
    for (int tap = 0; tap < 9; tap++) sts64(reg0 + (NSLOT - 1) * SLOT_BYTES + tap * 128 + j * 8, w[tap / 3][tap % 3][1], w[tap / 3][tap % 3][0]);
    named_bar(1, 128);
#pragma unroll
    for (int tap = 0; tap < 9; tap++) lds64(w[tap / 3][tap % 3][1], w[tap / 3][tap % 3][0], reg0 + (NSLOT - 1) * SLOT_BYTES + tap * 128 + j * 8);
    static_assert(2 * PREFETCH_ROWS == NSLOT && SLOT_BYTES % 32 == 0, "slot arithmetic");
    uint32_t bo = 0, par = 0, pbo = PREFETCH_ROWS * 32, ppar = 1;
    int px, py;
    auto request = [&]() {
        mbar_wait_once(bars + (BAR_E - SM_BAR) + pbo, ppar);
        if (elect_one()) {
            mbar_expect_tx(bars + pbo, REGION_BYTES);
            tma_row(reg0 + pbo * (SLOT_BYTES / 32), tm, bars + pbo, px, py);
        }
    };
    auto advance = [&]() {
        bo += 32;
        if (bo == NSLOT * 32) { bo = 0; par ^= 1; }
        pbo += 32;
        if (pbo == NSLOT * 32) { pbo = 0; ppar ^= 1; }
    };
    auto aim = [&](int row) {
        const int code = row_code(wk, row);
        px = (code & 0xffff) + (16 * warp - 1);
        py = code >> 16;
    };
    uint32_t accB[8][3], accC[8][3];
    int r = 0;
#pragma unroll 1
    while (r < wk.rows) {
        if (r == 0 || r == wk.nA + 2) {
            const uint32_t bo0 = bo;
            uint32_t bo1;
#pragma unroll 1
            for (int k = 0; k < 2; k++, r++) {
                mbar_wait_once(bars + bo, par);
                bo1 = bo;
                if (r >= 2) {
                    aim(r + PREFETCH_ROWS);
                    request();
                }
                advance();
            }
            const uint32_t so0 = bo0 * (SLOT_BYTES / 32), so1 = bo1 * (SLOT_BYTES / 32);
#pragma unroll
            for (int p = 0; p < 10; p++) {
                uint32_t u[3], v[3];
                lds64(u[0], u[1], so0 + ld64 + p * 192);
                lds32(u[2], so0 + ld32 + p * 192);
                lds64(v[0], v[1], so1 + ld64 + p * 192);
                lds32(v[2], so1 + ld32 + p * 192);
#pragma unroll
                for (int dx = 0; dx < 3; dx++) {
                    const int o = p - dx;
                    if (o < 0 || o > 7) continue;
#pragma unroll
                    for (int q = 0; q < 3; q++) {
                        accB[o][q] = bf_fma(v[q], w[1][dx][q], dx == 0 ? bf_mul(u[q], w[0][dx][q]) : bf_fma(u[q], w[0][dx][q], accB[o][q]));
                        accC[o][q] = dx == 0 ? bf_mul(v[q], w[0][dx][q]) : bf_fma(v[q], w[0][dx][q], accC[o][q]);
                    }
                }
            }
            anchor(ld64, accB[7][0], accB[7][1], accB[7][2], 0);
            __syncwarp();
            if (elect_one()) {
                mbar_arrive(bars + (BAR_A - SM_BAR) + bo0);
                mbar_arrive(bars + (BAR_E - SM_BAR) + bo0);
                mbar_arrive(bars + (BAR_A - SM_BAR) + bo1);
                mbar_arrive(bars + (BAR_E - SM_BAR) + bo1);
            }
        }
        int end = wk.rows;
        const int marks[4] = {wk.rows - PREFETCH_ROWS, wk.rows - 11, wk.nA + 2, wk.nA + 2 - PREFETCH_ROWS};
#pragma unroll
        for (int k = 0; k < 4; k++) end = marks[k] > r ? min(end, marks[k]) : end;
        const bool fetch = r < wk.rows - PREFETCH_ROWS;
        aim(r + PREFETCH_ROWS);
        px = opaque_uniform(px);
        const int py_end = opaque_uniform(py + wk.dir * (end - r));
        r = end;
#pragma unroll 1
        do {
            mbar_wait(bars + bo, par);
            const uint32_t so = bo * (SLOT_BYTES / 32);
            uint32_t out[8][3];
#pragma unroll
            for (int p = 0; p < 10; p++) {
                uint32_t xv[3];
                lds64(xv[0], xv[1], so + ld64 + p * 192);
                lds32(xv[2], so + ld32 + p * 192);
#pragma unroll
                for (int dx = 0; dx < 3; dx++) {
                    const int o = p - dx;
                    if (o < 0 || o > 7) continue;
#pragma unroll
                    for (int q = 0; q < 3; q++) {
                        out[o][q] = bf_fma(xv[q], w[2][dx][q], dx == 0 ? accB[o][q] : out[o][q]);
                        accB[o][q] = bf_fma(xv[q], w[1][dx][q], dx == 0 ? accC[o][q] : accB[o][q]);
                        accC[o][q] = dx == 0 ? bf_mul(xv[q], w[0][dx][q]) : bf_fma(xv[q], w[0][dx][q], accC[o][q]);
                    }
                }
            }
            __syncwarp();
#pragma unroll
            for (int o = 0; o < 8; o++) {
                sts64(so + st64 + o * 16, out[o][0], out[o][1]);
                sts32(so + st32 + o * 16, out[o][2]);
            }
            __syncwarp();
            if (elect_one()) mbar_arrive(bars + (BAR_A - SM_BAR) + bo);
            if (fetch) request();
            advance();
            py += wk.dir;
        } while (py != py_end);
        if (((wk.rows - r) & ~8) == PREFETCH_ROWS) event(wk.rows - r == PREFETCH_ROWS);
    }
}

template <bool SCALED, int K0 = 0, int K1 = 3>
__device__ __forceinline__ void gelu_sq(uint32_t (&d)[24], uint32_t (&keep)[24], uint32_t sq_addr, uint32_t scale2) {
    pin(d);
#pragma unroll
    for (int k = K0; k < K1; k++) {
        uint32_t hs[4];
        lds128(hs[0], hs[1], hs[2], hs[3], sq_addr + k * SQ_ROW);
#pragma unroll
        for (int q = 0; q < 4; q++) {
            uint32_t g0 = gelu2(d[8 * k + 2 * q]), g1 = gelu2(d[8 * k + 2 * q + 1]);
            keep[8 * k + 2 * q] = g0;
            keep[8 * k + 2 * q + 1] = g1;
            if (SCALED) { g0 = h_mul(g0, scale2); g1 = h_mul(g1, scale2); }
            hs[q] = h_fma(g1, g1, h_fma(g0, g0, hs[q]));
        }
        sts128(sq_addr + k * SQ_ROW, hs[0], hs[1], hs[2], hs[3]);
    }
}
__device__ __forceinline__ void gelu_sq_reg(uint32_t (&d)[24], uint32_t (&hs)[12]) {
    pin(d);
#pragma unroll
    for (int q = 0; q < 12; q++) {
        const uint32_t g0 = gelu2(d[2 * q]), g1 = gelu2(d[2 * q + 1]);
        hs[q] = h_fma(g1, g1, h_fma(g0, g0, hs[q]));
    }
}
__device__ __forceinline__ void gelu_to(uint32_t (&g)[12], uint32_t (&d)[12]) {
    pin(d);
#pragma unroll
    for (int q = 0; q < 12; q++) g[q] = gelu2(d[q]);
    pin(g);
}
__device__ __forceinline__ void load_tile(uint32_t (&raw)[6][4], uint32_t addr) {
#pragma unroll
    for (int s = 0; s < 6; s++) ldsm4(raw[s], addr + s * 2 * A_LBO);
}
template <class F>
__device__ __forceinline__ void layer_norm(uint32_t (&raw)[6][4], uint64_t ones, F meanwhile) {
    constexpr int NS = 2;
    uint32_t sq[NS][4];
#pragma unroll
    for (int s = 0; s < 6; s++)
#pragma unroll
        for (int q = 0; q < 4; q++) sq[s % NS][q] = s < NS ? bf_mul(raw[s][q], raw[s][q]) : bf_fma(raw[s][q], raw[s][q], sq[s % NS][q]);
    float sum[4], ssq[4];
    wg_fence();
    wgmma_rowsum<0>(sum, raw[0], ones);
#pragma unroll
    for (int s = 1; s < 6; s++) wgmma_rowsum<1>(sum, raw[s], ones);
    wgmma_rowsum<0>(ssq, sq[0], ones);
#pragma unroll
    for (int s = 1; s < NS; s++) wgmma_rowsum<1>(ssq, sq[s], ones);
    wg_commit();
    meanwhile();
    wg_wait<0>();
    uint32_t sc[2], sh[2];
#pragma unroll
    for (int h = 0; h < 2; h++) {
        asm volatile("" : "+f"(sum[2 * h]), "+f"(ssq[2 * h])::"memory");
        constexpr float EPS = 1e-5f / (KZ * KZ);
        const float m = sum[2 * h] * (1.f / (CH * KZ));
        float rstd;
        asm("rsqrt.approx.ftz.f32 %0, %1;" : "=f"(rstd) : "f"(fmaxf(fmaf(-m, m, fmaf(ssq[2 * h], 1.f / (CH * KZ * KZ), EPS)), EPS)));
        sc[h] = pack_bf2(rstd, rstd);
        const float shift = sum[2 * h] * (-1.f / CH) * bf_hi(sc[h]);
        sh[h] = pack_bf2(shift, shift);
    }
#pragma unroll
    for (int s = 0; s < 6; s++)
#pragma unroll
        for (int q = 0; q < 4; q++) {
            const uint32_t v = bf_fma(raw[s][q], sc[q & 1], sh[q & 1]);
            raw[s][q] = pack_h2(bf_lo(v), bf_hi(v));
        }
}
struct Cursor {
    int slot;
    uint32_t par;
    __device__ __forceinline__ void advance(int n) {
        slot += n;
        if (slot >= NSLOT) { slot -= NSLOT; par ^= 1; }
    }
};
struct Descs {
    uint64_t w1[8][6];
    uint64_t w2[24];
    uint64_t ones;
};
template <int E0, int N>
__device__ __forceinline__ void gemm1_chunk(uint32_t (&d)[N], const uint32_t (&a)[6][4], const Descs& ds, int zero) {
#pragma unroll
    for (int s = 0; s < 6; s++) wgmma(d, a[s][0], a[s][1], a[s][2], a[s][3], ds.w1[E0 / 48][s], s ? 1 : zero);
}
template <int E0, int N>
__device__ __forceinline__ void gemm2_chunk(uint32_t (&acc)[24], const uint32_t (&g)[N], const Descs& ds) {
#pragma unroll
    for (int s = 0; s < N / 4; s++) wgmma(acc, g[4 * s], g[4 * s + 1], g[4 * s + 2], g[4 * s + 3], ds.w2[E0 / 16 + s], 1);
}

struct __align__(64) Params {
    Split sp;
    int zero;
    const __nv_bfloat16 *x, *dw, *w2, *gamma, *beta;
    __nv_bfloat16* out;
    Scratch* sc;
    Descs ds;
};

__global__ void __launch_bounds__(NTHREADS, 1)
block_kernel(const __grid_constant__ CUtensorMap tmap, const __grid_constant__ CUtensorMap tmap_w1, const __grid_constant__ Params pm) {
    const Split& sp = pm.sp;
    const Descs& ds = pm.ds;
    const int& zero = pm.zero;
    const __nv_bfloat16 *const &x = pm.x, *const &dw = pm.dw, *const &w2 = pm.w2, *const &gamma = pm.gamma, *const &beta = pm.beta;
    __nv_bfloat16* const& out = pm.out;
    Scratch* const& sc = pm.sc;
    extern __shared__ __align__(1024) uint8_t smem[];
    constexpr uint32_t sb = SB;
    const int tid = threadIdx.x;
    const Work wk = get_work(blockIdx.x, sp);
    constexpr uint32_t s_red = sb + SM_RED;
    if (smem_u32(smem) != SB) __trap();

    const int warp_id = __shfl_sync(~0u, tid >> 5, 0);
    PROF(0);
    const int cw = warp_id - 4, wgi = cw >> 2, w4 = warp_id & 3;
    if (elect_one()) {
        static_assert(3 * NSLOT * 4 == 8 + 4 * 16 && BAR_F == BAR_W + 48, "barrier shares");
        const int b = warp_id - 8;
        const uint32_t bar = b < 0 ? sb + BAR_X + warp_id * 8 : b < 7 ? sb + BAR_W + b * 8 : sb + BAR_PIN;
        mbar_init(bar, 1);
#pragma unroll
        for (int k = 0; k < 4; k++) mbar_init(sb + BAR_X + (8 + 4 * warp_id + k) * 8, 1);
        mbar_init(sb + BAR_R + warp_id * 8, 1);
        fence_async();
        if (b < 0) {
            issue_region(&tmap, sb + SM_RING + warp_id * REGION_BYTES, bar, w4, ((wk.tA & 511) + wk.dir * wgi) << 16 | (wk.tA >> 9) * TILE_W);
        } else if (b < 6) {
            mbar_expect_tx(bar, 64 * CH * 2);
            tma_2d(sb + SM_W2 + b * (64 * CH * 2), &tmap_w1, bar, 64 * b, 0);
        } else if (b == 6) {
            mbar_expect_tx(bar, 9 * CH * 2);
            bulk_load(sb + SM_FILTER, dw, 9 * CH * 2, bar);
        }
    }
    __syncwarp();
    const int ntiles = wk.nA + wk.nB;
    const int rank = (wgi + wk.lent + 2 * (ntiles - 1)) % NCONS | (wgi >> 2 & 3);
    const int spare = wk.rows % NSLOT, spare2 = spare == NSLOT - 1 ? 0 : spare + 1;
    const uint32_t sq_base = sb + (wgi < 0 ? SM_RING + spare * SLOT_BYTES : SM_SQ + rank * 2 * SQ_HALF);
    const uint32_t sq_upper = wgi < 0 ? (spare2 - spare) * SLOT_BYTES : SQ_HALF;
    const uint32_t bar_a = sb + BAR_A + w4 * 8, bar_e = sb + BAR_E + w4 * 8;
    auto max_w1 = [&](uint32_t lane) { return __uint_as_float(__reduce_max_sync(~0u, lane < 4 * NCONS ? ldsi(s_red + RED_MAX + lane * 4) : 0)); };
    auto square_scale = [&](uint32_t lane) {
        const float f = pow2i(square_exp(bound_exp(max_w1(lane))));
        return pack_h2(f, f);
    };
    uint32_t a_addr, sq;
    const uint32_t sq_warp = sq_base + w4 * 512;
    auto set_addresses = [&]() {
        a_addr = opaque(sb + SM_RING + w4 * REGION_BYTES + ((tid >> 3) & 1) * A_SBO + ((tid >> 4) & 1) * A_LBO + (tid & 7) * 16);
        sq = opaque(sq_base + (tid & 127) * 16);
    };
    uint32_t turn, turn_end, so, so_sum, bo, bo_sum, off;
    auto set_run = [&](int j, int stop, int row) {
        const int slot = row % NSLOT, both = 2 * (row % 3) + 3;
        turn = opaque_uniform(row / 3);
        turn_end = opaque_uniform(row / 3 + (stop - j + NCONS - 1) / NCONS);
        so = opaque_uniform(slot * SLOT_BYTES);
        so_sum = opaque_uniform(both * SLOT_BYTES);
        bo = opaque_uniform(bar_a + slot * 32);
        bo_sum = opaque_uniform(2 * bar_a + both * 32);
        off = opaque_uniform(tile_offset(wk.tile(j)) + w4 * WARP_BYTES - sq_warp);
    };
    const int nrest = ntiles - 4;
    int jt;
    Cursor cur;
    int fast_from;
    if (warp_id < 4) {
        conv_producer(wk, &tmap, sb, warp_id, [&](bool second) {
            if (!second) {
                if (tid == 0) sts32(s_red + RED_JOB, wk.lent ? NTILES : atomicAdd(&sc->job, 1));
                if (blockIdx.x == 0) {
#pragma unroll 1
                    for (int e = tid; e < EX; e += 128) *sc->sum(e) = 0;
                    sc->bias[tid] = 0.f;
                }
                if (blockIdx.x == 0 || wk.lent) signal(&sc->early);
                __syncwarp();
            } else {
                const int piece = opaque_uniform(ldsi(s_red + RED_JOB)) - W2_GROUPS / 2, q = 2 * piece + W2_GROUPS + (w4 >> 1);
                if (piece < 8 * LENT * sp.lenders) {
                    spin_until(&sc->early, (ldsi(s_red + RED_LAUNCH) + 1) * 4 * (sp.lenders + 1));
                    if (elect_one()) {
                        if (piece >= 0) prefetch_l2(reinterpret_cast<const char*>(out) + sp.lent_off[piece / 8] + w4 * WARP_BYTES, WARP_BYTES);
                        else { prefetch_l2(w2 + 8 * q * CH, 8 * CH * 2); prefetch_l2(beta + 8 * q, 16); }
                    }
                }
            }
        });
        const int piece = opaque_uniform(ldsi(s_red + RED_JOB)) - W2_GROUPS / 2, q = 2 * piece + W2_GROUPS + (w4 >> 1);
        const bool prepares = piece < 0, helps = piece < 8 * LENT * sp.lenders;
        set_addresses();
        const int lane = lane_id(), g = lane >> 2, t = lane & 3;
        uint32_t a[6][4];
        unsigned short bt_raw;
        if (prepares) {
#pragma unroll
            for (int m = 0; m < 3; m++) ldg128(a[m], w2 + (8 * q + g) * CH + 32 * m + 8 * t);
            asm volatile("ld.global.nc.u16 %0, [%1];" : "=h"(bt_raw) : "l"(beta + 8 * q + g) : "memory");
        } else if (helps) {
#pragma unroll
            for (int s = 0; s < 6; s++) ldg128(a[s], reinterpret_cast<const char*>(out) + sp.lent_off[piece / 8] + w4 * WARP_BYTES + lane * 16 + s * 512);
        }
        mbar_wait_once(bar_e + spare2 * 32, (wk.rows - 5) / NSLOT & 1);
        mbar_wait_once(bar_e + spare * 32, (wk.rows - 6) / NSLOT & 1);
        named_bar(1, 128);
#pragma unroll
        for (int k = 0; k < 6; k++) { sts128(sq + k * SQ_ROW, 0, 0, 0, 0); sts128(sq + sq_upper + k * SQ_ROW, 0, 0, 0, 0); }
        if (prepares) {
            const int half = w4 & 1;
            uint32_t rmax = 0;
#pragma unroll
            for (int m = 0; m < 3; m++) rmax = bf_absmax(bf_absmax(rmax, bf_absmax(a[m][0], a[m][1])), bf_absmax(a[m][2], a[m][3]));
            uint2 u = half ? make_uint2(a[0][2], a[0][3]) : make_uint2(a[0][0], a[0][1]), u1 = half ? make_uint2(a[1][2], a[1][3]) : make_uint2(a[1][0], a[1][1]);
            const uint2 u2 = half ? make_uint2(a[2][2], a[2][3]) : make_uint2(a[2][0], a[2][1]);
            const float bt = bf_lo(bt_raw);
            rmax = bf_absmax(rmax, __shfl_xor_sync(~0u, rmax, 1));
            rmax = bf_absmax(rmax, __shfl_xor_sync(~0u, rmax, 2));
            const float mx = fmaxf(fabsf(bf_lo(rmax)), fabsf(bf_hi(rmax))), rs = pow2i(row_exp(mx));
            if (t == 0 && !half) sc->w2max[8 * q + g] = mx;
#pragma unroll 1
            for (int m = 0; m < 3; m++, u = u1, u1 = u2) {
                float f[4];
#pragma unroll
                for (int k = 0; k < 2; k++) {
                    const float lo = bf_lo(k ? u.y : u.x), hi = bf_hi(k ? u.y : u.x);
                    sc->w2h[(4 * m + 2 * half + k) * 1536 + q * 32 + lane] = transpose8x8(pack_h2(lo * rs, hi * rs));
                    f[2 * k] = lo * bt;
                    f[2 * k + 1] = hi * bt;
                }
                const float r0 = (g & 2 ? f[2] : f[0]) + __shfl_xor_sync(~0u, g & 2 ? f[0] : f[2], 8);
                const float r1 = (g & 2 ? f[3] : f[1]) + __shfl_xor_sync(~0u, g & 2 ? f[1] : f[3], 8);
                float r = (g & 1 ? r1 : r0) + __shfl_xor_sync(~0u, g & 1 ? r0 : r1, 4);
                r += __shfl_xor_sync(~0u, r, 16);
                if (g < 4) atomicAdd(&sc->bias[32 * m + 8 * t + 4 * half + g], r);
            }
            asm volatile("fence.proxy.async.global;" ::: "memory");
            signal(&sc->prep);
        } else
        if (helps) {
            uint32_t d[12], gl[12];
            const uint32_t scale2 = square_scale(lane);
            wg_fence();
#pragma unroll
            for (int s = 0; s < 6; s++) wgmma(d, a[s][0], a[s][1], a[s][2], a[s][3], ds.w1[0][s] + piece % 8 * (6 * 1536 / 16), s ? 1 : 0);
            wg_commit();
            wg_wait<0>();
            gelu_to(gl, d);
#pragma unroll
            for (int s = 0; s < 3; s++) {
                sc->lent[((piece / 8 * 4 + w4) * 24 + piece % 8 * 3 + s) * 32 + lane] = make_uint4(gl[4 * s], gl[4 * s + 1], gl[4 * s + 2], gl[4 * s + 3]);
                uint32_t hs[2];
#pragma unroll
                for (int k = 0; k < 2; k++) {
                    const uint32_t g0 = h_mul(gl[4 * s + 2 * k], scale2), g1 = h_mul(gl[4 * s + 2 * k + 1], scale2);
                    hs[k] = h_fma(g1, g1, h_mul(g0, g0));
                }
                const int pair = piece % 4 * 3 + s;
                sts64(sq + (piece & 4 ? sq_upper : 0) + (pair >> 1) * SQ_ROW + (pair & 1) * 8, hs[0], hs[1]);
            }
        }
        jt = ntiles - 1;
        cur.slot = spare ? spare - 1 : NSLOT - 1;
        cur.par = (wk.rows - 1) / NSLOT & 1;
        fast_from = ntiles;
        turn = turn_end = so = so_sum = bo = bo_sum = off = rank;
    } else {
        set_addresses();
        if (wgi == NCONS - 1) named_arrive(4, 256);
        set_run(wk.lent + wgi, min(wk.nA, nrest), wk.lent + wgi + 2);
        jt = wgi < wk.lent ? wgi : wk.lent + wgi;
        cur = {2, 0};
        cur.advance(jt + (jt >= wk.nA ? 2 : 0));
        {
            const int ct = tid - 128, lane = tid & 31;
            const unsigned epoch = *reinterpret_cast<volatile unsigned*>(&sc->launch);
            const int r = lane & 7, mi = lane >> 3;
            const uint32_t src = sb + SM_W2 + (cw >> 1) * (64 * CH * 2) + r * 128 + ((((cw & 1) * 4 + mi) ^ r) * 16);
            const uint32_t dst = sb + SM_W1 + (4 * cw + mi) * 1536 + r * 16;
            const int code = row_code(wk, PREFETCH_ROWS - 1 + wgi);
            named_bar(0, NTHREADS);
            auto request = [&]() {
                if (elect_one())
                    issue_region(&tmap, sb + SM_RING + (PREFETCH_ROWS - 1 + wgi) * SLOT_BYTES + w4 * REGION_BYTES, sb + BAR_X + (cw + 8) * 8, w4, code);
                __syncwarp();
            };
#pragma unroll 1
            for (int k = 0; k < 2; k++) {
                if (wgi == k) request();
                mbar_wait_once(sb + BAR_W + (cw >> 1) * 8, 0);
            }
            uint32_t wmax[2] = {}, wsum[4] = {};
#pragma unroll 3
            for (int c = 0; c < 12; c++) {
                uint32_t u[4];
                ldsm4_t(u, src + c * 1024);
#pragma unroll
                for (int q = 0; q < 4; q++) {
                    wmax[q & 1] = bf_absmax(wmax[q & 1], u[q]);
                    wsum[q] = bf_fma(u[q], 0x3f803f80u, wsum[q]);
                    u[q] = pack_h2(__uint_as_float(u[q] * (65536 + zero)), bf_hi(u[q]));
                }
                stsm4(dst + c * 128, u[0], u[1], u[2], u[3]);
            }
            const float w1max = warp_absmax(bf_absmax(wmax[0], wmax[1]));
            if (lane == 0) sts32(s_red + RED_MAX + cw * 4, __float_as_uint(w1max));
            bool center = false;
#pragma unroll
            for (int q = 0; q < 4; q++) {
#pragma unroll
                for (int o = 1; o <= 2; o <<= 1) wsum[q] = bf_fma(__shfl_xor_sync(~0u, wsum[q], o), 0x3f803f80u, wsum[q]);
                center |= fabsf(bf_lo(wsum[q]) + bf_hi(wsum[q])) > (0.15f * CH) * w1max;
            }
            if (__builtin_expect(__any_sync(~0u, center), 0)) {
                float mean[4] = {};
#pragma unroll 1
                for (int pass = 0; pass < 2; pass++) {
                    float sum[4] = {};
#pragma unroll 1
                    for (int c = 0; c < 12; c++) {
                        uint32_t u[4];
                        ldsm4_t(u, src + c * 1024);
#pragma unroll
                        for (int q = 0; q < 4; q++) {
                            sum[q] += bf_lo(u[q]) + bf_hi(u[q]);
                            u[q] = pack_h2(bf_lo(u[q]) - mean[q], bf_hi(u[q]) - mean[q]);
                        }
                        stsm4(dst + c * 128, u[0], u[1], u[2], u[3]);
                    }
#pragma unroll
                    for (int q = 0; q < 4; q++) {
                        sum[q] += __shfl_xor_sync(~0u, sum[q], 1);
                        sum[q] += __shfl_xor_sync(~0u, sum[q], 2);
                        mean[q] = sum[q] * (1.f / CH);
                    }
                }
            }
            if (!(cw & 2)) {
#pragma unroll
                for (int c = 0; c < 12; c++) sts128(src + c * 1024, 0, 0, 0, 0);
            }
            if (ct < 32) sts32(sb + SM_ONES + ct * 4, 0x3f803f80u);
            if (ct == 0) sts32(s_red + RED_LAUNCH, epoch);
            fence_async();
            named_bar(2, CONS_THREADS);
            if (wgi == 2) request();
        }
        PROF(1);
        if (cur.par) mbar_wait_once(bar_a, 0);
        fast_from = wk.lent;
        if (!__all_sync(~0u, plain_squares(bound_exp(max_w1(lane_id()))))) {
            fast_from = ntiles;
#pragma unroll 1
            for (int q = 0; q < 6; q++) sts128(sq + SQ_HALF + q * SQ_ROW, 0, 0, 0, 0);
        }
    }
    uint32_t k1[24], k2[24], k3[24];
    uint32_t here;
    constexpr int SQC = 3 * SQ_ROW;
    auto store_at = [&](const uint32_t (&a)[6][4], uint32_t off) {
        char* ap = reinterpret_cast<char*>(out) + (off + sq);
#pragma unroll
        for (int s = 0; s < 6; s++) stg128(ap + s * 512, a[s]);
    };
    const uint32_t own_bar = 4 + wgi, next_bar = 4 + (wgi == NCONS - 1 ? 0 : wgi + 1);
    for (;;) {
        if (jt >= fast_from) {
            uint32_t hs2[12] = {}, hs3[12] = {};
            const uint32_t step = wk.dir * (NCONS * IMG_W * CH * 2);
            int second = wk.nB;
#pragma unroll 1
            for (;;) {
#pragma unroll 1
                while (turn != turn_end) {
                    uint32_t a[6][4], d0[24], d1[24], unused[24];
                    mbar_wait(bo, turn >> 1 & 1);
                    load_tile(a, a_addr + so);
                    layer_norm(a, ds.ones, [&]() { named_bar(own_bar, 256); });
                    wg_fence();
                    gemm1_chunk<0>(d0, a, ds, 0);
                    wg_commit();
                    gemm1_chunk<96>(d1, a, ds, 0);
                    wg_commit();
                    wg_wait<1>();
                    gelu_sq<false, 0, 1>(d0, unused, sq, 0);
                    gelu_sq<false, 1, 2>(d0, unused, sq, 0);
                    store_at(a, off);
                    gelu_sq<false, 2, 3>(d0, unused, sq, 0);
                    if (elect_one()) mbar_arrive(bo + (BAR_E - BAR_A));
                    wg_fence();
                    gemm1_chunk<192>(d0, a, ds, zero);
                    wg_commit();
                    named_arrive(next_bar, 256);
                    wg_wait<1>();
                    gelu_sq<false, 0, 1>(d1, unused, sq + SQC, 0);
                    gelu_sq<false, 1, 3>(d1, unused, sq + SQC, 0);
                    wg_fence();
                    gemm1_chunk<288>(d1, a, ds, zero);
                    wg_commit();
                    wg_wait<1>();
                    gelu_sq_reg(d0, hs2);
                    anchor(sq, hs2[8], hs2[9], hs2[10], hs2[11]);
                    wg_wait<0>();
                    gelu_sq_reg(d1, hs3);
                    so = so_sum - so;
                    bo = bo_sum - bo;
                    off += step;
                    turn++;
                }
                if (!second) break;
                const int j = ntiles - second + (rank + second + 2) % NCONS;
                second = 0;
                set_run(j, nrest, j + 4);
            }
            jt = nrest + rank;
            cur.slot = (bo - bar_a) >> 5;
            cur.par = turn >> 1 & 1;
#pragma unroll
            for (int k = 0; k < 3; k++) {
                sts128(sq + SQ_HALF + k * SQ_ROW, hs2[4 * k], hs2[4 * k + 1], hs2[4 * k + 2], hs2[4 * k + 3]);
                sts128(sq + SQ_HALF + SQC + k * SQ_ROW, hs3[4 * k], hs3[4 * k + 1], hs3[4 * k + 2], hs3[4 * k + 3]);
            }
        }
        const bool last = jt >= nrest;
        here = tile_offset(wk.tile(jt));
        if (last) {
            const uint32_t next = ldsi(sb + SM_TILES + rank * 4);
            if (elect_one()) {
                prefetch_l2(reinterpret_cast<const char*>(x) + here + w4 * WARP_BYTES, WARP_BYTES);
                if (rank == ORDER_P - 1) prefetch_l2(reinterpret_cast<const char*>(out) + next + w4 * WARP_BYTES, WARP_BYTES);
            }
        }
        uint32_t a[6][4], d0[24], d1[24], d3[24], k0[24];
        mbar_wait_once(bar_a + cur.slot * 32, cur.par);
        load_tile(a, a_addr + cur.slot * SLOT_BYTES);
        layer_norm(a, ds.ones, [&]() { if (jt >= wk.lent && wgi >= 0) named_bar(own_bar, 256); });
        if (!last) {
            store_at(a, here + w4 * WARP_BYTES - sq_warp);
            __syncwarp();
            if (elect_one()) mbar_arrive(bar_e + cur.slot * 32);
            if (jt < wk.lent) {
                jt += LENT;
                cur.advance(LENT);
                continue;
            }
        }
        wg_fence();
        gemm1_chunk<0>(d0, a, ds, 0);
        wg_commit();
        gemm1_chunk<96>(d1, a, ds, 0);
        wg_commit();
        const uint32_t scale2 = square_scale(lane_id());
        wg_wait<1>();
        gelu_sq<true>(d0, k0, sq, scale2);
        if (last) {
#pragma unroll
            for (int q = 0; q < 6; q++)
                sts128(sb + SM_RING + cur.slot * SLOT_BYTES + w4 * REGION_BYTES - sq_warp + sq + q * 512, k0[4 * q], k0[4 * q + 1], k0[4 * q + 2], k0[4 * q + 3]);
        }
        wg_fence();
        gemm1_chunk<192>(d0, a, ds, zero);
        wg_commit();
        if (jt + 2 < ntiles) named_arrive(next_bar, 256);
        wg_wait<1>();
        gelu_sq<true>(d1, k1, sq + SQC, scale2);
        wg_fence();
        gemm1_chunk<288>(d3, a, ds, 0);
        wg_commit();
        wg_wait<1>();
        gelu_sq<true>(d0, k2, sq + sq_upper, scale2);
        wg_wait<0>();
        gelu_sq<true>(d3, k3, sq + sq_upper + SQC, scale2);
        if (last) break;
        cur.advance(NCONS + ((jt < wk.nA && jt + NCONS >= wk.nA) ? 2 : 0));
        jt += NCONS;
    }
    const uint32_t lane = lane_id();
    uint32_t next_off = opaque_uniform(ldsi(sb + SM_TILES + rank * 4));
    const uint32_t s_fac = sb + SM_RING + spare * SLOT_BYTES + SQ_HALF;
    uint32_t inv_rho2;
    {
        if (rank == 0) {
            const int g = lane >> 2, t = lane & 3, i0 = w4 * 32 + lane;
            const bool leader = i0 == 0;
            const uint32_t pick = (g & 1) == (t & 1) ? (g & 2 ? 0x3c000000u : 0x00003c00u) : 0;
            const int be = bound_exp(max_w1(lane));
            const float to_fixed = pow2i(sum_exp(be) - 2 * square_exp(be));
            const uint32_t two_rows = sb + (w4 * 3 + (lane >> 3 & 1)) * SQ_ROW + ((lane >> 4) * 8 + (lane & 7)) * 16;
            const uint32_t third_row = sb + (w4 * 3 + 2) * SQ_ROW + lane * 16;
            unsigned short gam_raw[3];
            float rmax[3], f[3][4] = {};
            float2 bpair = make_float2(0.f, 0.f);
#pragma unroll 1
            for (int i = 0; i < 4; i++) {
                if (i == 1 && leader) {
                    spin_until(&sc->prep, (ldsi(s_red + RED_LAUNCH) + 1) * (W2_GROUPS * 2));
                    asm volatile("fence.proxy.async.global;" ::: "memory");
                    mbar_expect_tx(sb + BAR_W, 6 * SQ_HALF);
                }
                __syncwarp();
                named_bar(2, 128);
                if (i && leader) {
                    fence_async();
                    bulk_load(sb + SM_W2 + (i - 1) * 2 * SQ_HALF, reinterpret_cast<const char*>(sc->w2h) + (i - 1) * 2 * SQ_HALF, 2 * SQ_HALF, sb + BAR_W);
                }
                if (i == 1) {
#pragma unroll
                    for (int m = 0; m < 3; m++) {
                        asm volatile("ld.global.nc.u16 %0, [%1];" : "=h"(gam_raw[m]) : "l"(gamma + i0 + 128 * m) : "memory");
                        asm volatile("ld.global.cg.f32 %0, [%1];" : "=f"(rmax[m]) : "l"(&sc->w2max[i0 + 128 * m]) : "memory");
                    }
                    if (i0 < 96)
                        asm volatile("ld.global.cg.v2.f32 {%0, %1}, [%2];" : "=f"(bpair.x), "=f"(bpair.y)
                                     : "l"(&sc->bias[32 * (i0 % 24 >> 3) + 8 * (i0 / 24) + (i0 % 24 & 6)]) : "memory");
                }
                __syncwarp();
                const uint32_t from = i < NCONS ? SM_SQ + i * 2 * SQ_HALF : w4 < 2 ? SM_RING + spare * SLOT_BYTES : SM_RING + spare2 * SLOT_BYTES - SQ_HALF;
                if (i) named_bar(12 + i, 256);
#pragma unroll
                for (int r = 0; r < 12; r++) {
                    uint32_t u[4];
                    ldsm4_t(u, from + (r % 3 == 2 ? third_row + r / 3 * 512 : two_rows + (r / 3 * 2 + r % 3) * 256));
                    asm volatile("mma.sync.aligned.m16n8k16.row.col.f32.f16.f16.f32 {%0, %1, %2, %3}, {%4, %5, %6, %7}, {%8, %8}, {%0, %1, %2, %3};"
                                 : "+f"(f[r % 3][0]), "+f"(f[r % 3][1]), "+f"(f[r % 3][2]), "+f"(f[r % 3][3])
                                 : "r"(u[0]), "r"(u[1]), "r"(u[2]), "r"(u[3]), "r"(pick));
                }
            }
            unsigned long long* dst = sc->sum(96 * w4 + 8 * (g >> 1) + 2 * (t & 1) + (g & 1));
#pragma unroll
            for (int r = 0; r < 3; r++) {
                const float tot = r < 2 ? (t < 2 ? f[0][r & 1] + f[1][r & 1] : f[0][r + 2 & 3] + f[1][r + 2 & 3]) : (t < 2 ? f[2][0] + f[2][2] : f[2][1] + f[2][3]);
                atomicAdd(dst + (r < 2 ? (t >> 1) * 8 + r : 16 + (t >> 1)) * 32, __float2ull_rn(fminf(tot * to_fixed, 0x1p47f)) << 8 | 1);
            }
            PROF(2);
            float base[3], slope[3], reach[3];
            const float w1max = max_w1(lane);
            const float gbound = fmaxf(2.f * KZ * 9.7979590f * 192.f * w1max, 1.f) * 19.5959180f * INV_2KZ;
            const unsigned fixed = __reduce_max_sync(~0u, __float_as_uint(fmaf(gbound, fmaxf(fmaxf(rmax[0], rmax[1]), rmax[2]), fmaxf(fabsf(bpair.x), fabsf(bpair.y)))));
            if (lane == 0) sts32(s_red + 96 + w4 * 4, fixed);
#pragma unroll
            for (int m = 0; m < 3; m++) {
                base[m] = rmax[m] > 0.f ? pow2i(-row_exp(rmax[m])) * (INV_2KZ * CUT_GAIN) : 0.f;
                slope[m] = base[m] * bf_lo(gam_raw[m]);
                reach[m] = fabsf(bf_lo(gam_raw[m])) * rmax[m] * gbound;
            }
            const float to_square = pow2i(-sum_exp(bound_exp(w1max))) * (INV_2KZ * INV_2KZ / 256);
#pragma unroll
            for (int m = 0; m < 3; m++) anchor(sq, __float_as_uint(base[m]), __float_as_uint(slope[m]), __float_as_uint(reach[m]), __float_as_uint(to_square));
            const unsigned epoch = ldsi(s_red + RED_LAUNCH);
            const uint32_t own_sum = (i0 >> 2) * 256 + (i0 & 3) * 8, own_fac = s_fac + i0 * 2;
            auto peek = [&](const void* p) {
                unsigned long long v;
                asm volatile("ld.relaxed.gpu.global.u64 %0, [%1];" : "=l"(v) : "l"(p) : "memory");
                return v;
            };
            const char* mine = reinterpret_cast<const char*>(sc->sums) + own_sum;
            unsigned n = 0;
            while (((unsigned)peek(sc->sum((blockIdx.x * 4 + w4) % (EX / 4) * 4)) & 255u) != gridDim.x)
                if (++n > SPIN_LIMIT) __trap();
            unsigned long long sum[3];
            for (;;) {
                bool all = true;
#pragma unroll
                for (int m = 0; m < 3; m++) {
                    sum[m] = peek(mine + m * (32 * 256));
                    all &= ((unsigned)sum[m] & 255u) == gridDim.x;
                }
                if (__all_sync(~0u, all)) break;
                if (++n > SPIN_LIMIT) __trap();
            }
            PROF(3);
            float gx[3];
#pragma unroll
            for (int m = 0; m < 3; m++) asm("sqrt.approx.ftz.f32 %0, %1;" : "=f"(gx[m]) : "f"(fmaf(__ull2float_rn(sum[m]), to_square, 1e-6f)));
            float tot = gx[0] + gx[1] + gx[2];
#pragma unroll
            for (int o = 16; o >= 1; o >>= 1) tot += __shfl_xor_sync(~0u, tot, o);
            const unsigned vwarp = __reduce_max_sync(~0u, __float_as_uint(fmaxf(fmaxf(reach[0] * gx[0], reach[1] * gx[1]), reach[2] * gx[2])));
            if (lane == 0) { sts32(s_red + 64 + w4 * 4, __float_as_uint(tot)); sts32(s_red + 80 + w4 * 4, vwarp); }
            named_bar(2, 128);
            uint32_t u[4], v[4], w[4];
            lds128(u[0], u[1], u[2], u[3], s_red + 64);
            lds128(v[0], v[1], v[2], v[3], s_red + 80);
            lds128(w[0], w[1], w[2], w[3], s_red + 96);
            tot = (__uint_as_float(u[0]) + __uint_as_float(u[1])) + (__uint_as_float(u[2]) + __uint_as_float(u[3]));
            const float vmax = __uint_as_float(max(max(v[0], v[1]), max(v[2], v[3]))), fmax2 = __uint_as_float(max(max(w[0], w[1]), max(w[2], w[3])));
            float inv_mean;
            asm("rcp.approx.ftz.f32 %0, %1;" : "=f"(inv_mean) : "f"(fmaf(tot, 1.f / EX, 1e-6f)));
            const int rho_e = 14 - ilog2f(fmaf(vmax, inv_mean, 2.f * fmax2));
            const float rho = pow2i(rho_e), inv_rho = pow2i(-rho_e);
            inv_rho2 = pack_bf2(inv_rho, inv_rho);
#pragma unroll
            for (int m = 0; m < 3; m++) {
                const float f = fmaf(slope[m] * gx[m], inv_mean, base[m]) * rho;
                asm volatile("st.shared.u16 [%0], %1;" ::"r"(own_fac + 256 * m), "h"((unsigned short)pack_h2(f, 0.f)) : "memory");
            }
            if (i0 < 96) sts32(sb + SM_BIASH + i0 * 4, pack_h2(bpair.x * rho, bpair.y * rho));
            if (i0 == 96) sts32(s_red + RED_INV_RHO, inv_rho2);
            named_arrive(12, NTHREADS);
            if (blockIdx.x == 0 && leader) { sc->launch = epoch + 1; sc->job = 0; }
            if (wk.lent) spin_until(&sc->lent_out, (epoch + 1) * 32 * LENT * sp.lenders);
        } else {
            named_arrive(12 + rank, 256);
            if (rank == NCONS && (unsigned)(ldsi(s_red + RED_JOB) - W2_GROUPS / 2) < 8 * LENT * sp.lenders) signal(&sc->lent_out);
            const int rw = rank * 4 - 4 + w4;
            const uint32_t row = sb + SM_W2 + rw * 512 + lane * 16;
            uint32_t u[W2_EARLY][4], f2[4];
            mbar_wait_once(sb + BAR_W, 1);
#pragma unroll
            for (int nb = 0; nb < W2_EARLY; nb++) {
                lds128(u[nb][0], u[nb][1], u[nb][2], u[nb][3], row + nb * 6144);
            }
            named_bar(12, NTHREADS);
            PROF(3);
            lds128(f2[0], f2[1], f2[2], f2[3], s_fac + rw * 64 + (lane >> 3) * 16);
            lds32(inv_rho2, s_red + RED_INV_RHO);
#pragma unroll
            for (int nb = 0; nb < 12; nb++) {
                uint32_t v[4];
                if (nb < W2_EARLY) { v[0] = u[nb % W2_EARLY][0]; v[1] = u[nb % W2_EARLY][1]; v[2] = u[nb % W2_EARLY][2]; v[3] = u[nb % W2_EARLY][3]; }
                else lds128(v[0], v[1], v[2], v[3], row + nb * 6144);
                sts128(row + nb * 6144, h_cut8(h_mul(v[0], f2[0])), h_cut8(h_mul(v[1], f2[1])), h_cut8(h_mul(v[2], f2[2])), h_cut8(h_mul(v[3], f2[3])));
            }
            fence_async();
            named_arrive(8, NTHREADS);
        }
    }
    uint32_t a[6][4], acc[24], rpar = 0, tile_off = here;
    const uint32_t bias_addr = sb + SM_BIASH + (lane & 3) * 96, lane16 = lane * 16, lane_off = ((lane >> 2) * CH + 8 * (lane & 3)) * 2;
    const uint32_t stage = sb + SM_RING + (spare + rank) % NSLOT * SLOT_BYTES + w4 * WARP_BYTES, bar_r = sb + BAR_R + warp_id * 8;
    auto load_bias = [&]() {
#pragma unroll
        for (int q = 0; q < 6; q++) lds128(acc[4 * q], acc[4 * q + 1], acc[4 * q + 2], acc[4 * q + 3], bias_addr + q * 16);
    };
    auto load_frags = [&]() {
#pragma unroll
        for (int s = 0; s < 6; s++) ldg128(a[s], reinterpret_cast<const char*>(out) + next_off + w4 * WARP_BYTES + lane16 + s * 512);
    };
    auto stage_x = [&]() {
        if (elect_one()) {
            mbar_expect_tx(bar_r, WARP_BYTES);
            bulk_load_stream(stage, reinterpret_cast<const char*>(x) + tile_off + w4 * WARP_BYTES, WARP_BYTES, bar_r);
        }
    };
    {
        named_bar(8 + rank, rank ? 256 : NTHREADS);
        if (rank == 0) PROF(4);
        load_bias();
        pin(k1); pin(k2); pin(k3);
        wg_fence();
        gemm2_chunk<288>(acc, k3, ds);
        wg_commit();
        gemm2_chunk<96>(acc, k1, ds);
        wg_commit();
        gemm2_chunk<192>(acc, k2, ds);
        wg_commit();
        stage_x();
        wg_wait<2>();
        uint32_t k0[24];
#pragma unroll
        for (int q = 0; q < 6; q++)
            lds128(k0[4 * q], k0[4 * q + 1], k0[4 * q + 2], k0[4 * q + 3], sb + SM_RING + cur.slot * SLOT_BYTES + w4 * REGION_BYTES + lane16 + q * 512);
        pin(k0);
        wg_fence();
        gemm2_chunk<0>(acc, k0, ds);
        wg_commit();
        if (rank < NCONS) named_arrive(9 + rank, 256);
        wg_wait<2>();
        load_frags();
        if (lane16 == 0) mbar_arrive(sb + BAR_PIN);
        mbar_wait(bar_r, rpar);
        wg_wait<0>();
    }
    auto lent = [&](uint32_t entry) { return &sc->lent[((wk.index * LENT + (entry & 3) - 1) * 4 + w4) * (24 * 32)]; };
    for (jt = rank - 4; jt < nrest; jt += 4) {
        if (jt >= zero) {
        tile_off = next_off;
        lds32(next_off, sb + SM_TILES + (jt + 4) * 4);
        if (tile_off & 3) {
            const uint4* src = lent(tile_off) + lane;
            tile_off &= ~3u;
            next_off = __shfl_sync(~0u, next_off, 0);
            stage_x();
            if (elect_one()) prefetch_l2(reinterpret_cast<const char*>(out) + next_off + w4 * WARP_BYTES, WARP_BYTES);
            load_bias();
#pragma unroll 1
            for (int half = 0; half < 2; half++, src += 12 * 32) {
                uint32_t gl[48];
#pragma unroll
                for (int s = 0; s < 12; s++) ldg128(reinterpret_cast<uint32_t (&)[4]>(gl[4 * s]), src + s * 32);
                if (!half) {
                    named_bar(4 + rank, 256);
                    named_arrive(4 + ((rank + 1) & 3), 256);
                }
                pin(gl);
                wg_fence();
#pragma unroll
                for (int s = 0; s < 12; s++) wgmma(acc, gl[4 * s], gl[4 * s + 1], gl[4 * s + 2], gl[4 * s + 3], ds.w2[12 * half + s], 1);
                wg_commit();
                wg_wait<0>();
            }
            load_frags();
            mbar_wait(bar_r, rpar);
        } else {
            uint32_t d0[12], d1[12], g0[12], g1[12];
            next_off = __shfl_sync(~0u, next_off, 0);
            const bool more = jt + 4 < nrest && !(next_off & 3);
            load_bias();
            wg_fence();
            gemm1_chunk<0>(d0, a, ds, 0);
            wg_commit();
            if (jt) named_bar(4 + rank, 256);
            gemm1_chunk<48>(d1, a, ds, 0);
            wg_commit();
            wg_wait<1>();
#define CNX_STEP(C, D, G)                                                   \
    gelu_to(G, D);                                                          \
    wg_fence();                                                             \
    if (C < 6) gemm1_chunk<48 * (C < 6 ? C + 2 : 0)>(D, a, ds, zero);      \
    gemm2_chunk<48 * C>(acc, G, ds);                                       \
    wg_commit();                                                            \
    if (C == 1 && jt + 1 < nrest) named_arrive(4 + ((rank + 1) & 3), 256); \
    wg_wait<(C < 7 ? 1 : 0)>();
            CNX_STEP(0, d0, g0)
            stage_x();
            if (elect_one()) {
                if (more) prefetch_l2(reinterpret_cast<const char*>(out) + next_off + w4 * WARP_BYTES, WARP_BYTES);
                else if (next_off & 3) prefetch_l2(lent(next_off), 24 * 32 * 16);
            }
            CNX_STEP(1, d1, g1)
            CNX_STEP(2, d0, g0)
            CNX_STEP(3, d1, g1)
            CNX_STEP(4, d0, g0)
            CNX_STEP(5, d1, g1)
            CNX_STEP(6, d0, g0)
#pragma unroll
            for (int s = 0; s < 6; s++) ldg128_if(more, a[s], reinterpret_cast<const char*>(out) + next_off + w4 * WARP_BYTES + lane16 + s * 512);
            if (lane16 == 0) mbar_arrive(sb + BAR_PIN);
            mbar_wait(bar_r, rpar);
            CNX_STEP(7, d1, g1)
#undef CNX_STEP
        }
        }
        {
            pin(acc);
            rpar ^= 1;
            uint4* op = reinterpret_cast<uint4*>(reinterpret_cast<char*>(out) + tile_off + w4 * WARP_BYTES + lane_off);
#pragma unroll
            for (int h = 0; h < 2; h++)
#pragma unroll
                for (int m = 0; m < 3; m++) {
                    uint32_t xin[4], o[4];
                    lds128(xin[0], xin[1], xin[2], xin[3], stage + lane_off + h * 1536 + m * 64);
#pragma unroll
                    for (int q = 0; q < 4; q++) {
                        const uint32_t v = acc[2 * (4 * m + q) + h];
                        o[q] = bf_fma(pack_bf2(h_lo(v), h_hi(v)), inv_rho2, xin[q]);
                    }
                    __stcs(op + h * 96 + m * 4, make_uint4(o[0], o[1], o[2], o[3]));
                }
            __syncwarp();
        }
    }
    PROF(5);
}

}

typedef CUresult (*EncodeTiledFn)(CUtensorMap*, CUtensorMapDataType, cuuint32_t, void*, const cuuint64_t*, const cuuint64_t*,
                                  const cuuint32_t*, const cuuint32_t*, CUtensorMapInterleave, CUtensorMapSwizzle,
                                  CUtensorMapL2promotion, CUtensorMapFloatOOBfill);

extern "C" void kernel_launch(void* const* d_in, const int* in_sizes, int n_in, void* d_out, int out_size) {
    using namespace cnx;
    static EncodeTiledFn encode = nullptr;
    static int num_sms = 0;
    static Scratch* scratch = nullptr;
    if (!encode) {
        void* fn = nullptr;
        cudaDriverEntryPointQueryResult qr;
        cudaGetDriverEntryPoint("cuTensorMapEncodeTiled", &fn, cudaEnableDefault, &qr);
        encode = (EncodeTiledFn)fn;
        cudaGetSymbolAddress((void**)&scratch, g_scratch);
        int dev = 0;
        cudaGetDevice(&dev);
        cudaDeviceGetAttribute(&num_sms, cudaDevAttrMultiProcessorCount, dev);
        if (num_sms > MAX_CTAS) num_sms = MAX_CTAS;
        cudaFuncSetAttribute(block_kernel, cudaFuncAttributeMaxDynamicSharedMemorySize, SM_TOTAL);
    }
    CUtensorMap tm;
    cuuint64_t dims[3] = {(cuuint64_t)CH, (cuuint64_t)IMG_W, (cuuint64_t)IMG_H};
    cuuint64_t strides[2] = {(cuuint64_t)CH * 2, (cuuint64_t)CH * 2 * IMG_W};
    cuuint32_t box[3] = {(cuuint32_t)CH, (cuuint32_t)REGION_PX, 1};
    cuuint32_t estr[3] = {1, 1, 1};
    encode(&tm, CU_TENSOR_MAP_DATA_TYPE_BFLOAT16, 3, d_in[0], dims, strides, box, estr, CU_TENSOR_MAP_INTERLEAVE_NONE,
           CU_TENSOR_MAP_SWIZZLE_NONE, CU_TENSOR_MAP_L2_PROMOTION_L2_128B, CU_TENSOR_MAP_FLOAT_OOB_FILL_NONE);
    Params pm = {};
    Descs& ds = pm.ds;
    for (int c = 0; c < 8; c++)
        for (int k = 0; k < 6; k++) ds.w1[c][k] = make_desc(SB + SM_W1 + c * 6 * 1536 + k * 256, 128, 1536);
    for (int k = 0; k < 24; k++) ds.w2[k] = make_desc(SB + SM_W2 + k * 256, 128, 6144);
    ds.ones = make_desc(SB + SM_ONES, 0, 0);
    CUtensorMap tw;
    cuuint64_t wdims[2] = {(cuuint64_t)EX, (cuuint64_t)CH};
    cuuint64_t wstrides[1] = {(cuuint64_t)EX * 2};
    cuuint32_t wbox[2] = {64, (cuuint32_t)CH};
    encode(&tw, CU_TENSOR_MAP_DATA_TYPE_BFLOAT16, 2, d_in[2], wdims, wstrides, wbox, estr, CU_TENSOR_MAP_INTERLEAVE_NONE,
           CU_TENSOR_MAP_SWIZZLE_128B, CU_TENSOR_MAP_L2_PROMOTION_L2_128B, CU_TENSOR_MAP_FLOAT_OOB_FILL_NONE);
    Split& sp = pm.sp;
    sp = {NTILES / num_sms, NTILES % num_sms, 1, 1 << 16, 0, {}};
    if (sp.per_cta + 9 > MAX_ROWS) return;
    if (sp.extra && sp.extra * (8 * LENT + 1) + W2_GROUPS / 2 <= num_sms && sp.per_cta >= 5 * LENT + 8) {
        sp.period = num_sms / sp.extra;
        sp.inv_period = 65535 / sp.period + 1;
        sp.lenders = sp.extra;
        for (int l = 0; l < sp.extra; l++) {
            const Work w = get_work((l + 1) * sp.period - sp.period / 2 - 1, sp);
            for (int e = 0; e < LENT; e++) sp.lent_off[l * LENT + e] = tile_offset(w.tile(e));
            if (w.nA < 2 * LENT) sp.lenders = 0;
        }
    }
    pm.x = (const __nv_bfloat16*)d_in[0];
    pm.dw = (const __nv_bfloat16*)d_in[1];
    pm.w2 = (const __nv_bfloat16*)d_in[3];
    pm.gamma = (const __nv_bfloat16*)d_in[4];
    pm.beta = (const __nv_bfloat16*)d_in[5];
    pm.out = (__nv_bfloat16*)d_out;
    pm.sc = scratch;
    block_kernel<<<num_sms, NTHREADS, SM_TOTAL>>>(tm, tw, pm);
}
```

```cpp
#include <cuda_runtime.h>
#include <cuda_bf16.h>
#include <cuda_fp16.h>
#include <cuda.h>
#include <stdint.h>

namespace cnx {

constexpr int IMG_H = 512, IMG_W = 512, CH = 96, EX = 384;
constexpr int TILE_W = 64;
constexpr int NTILES = (IMG_W / TILE_W) * IMG_H;
constexpr int NSLOT = 6;
constexpr int REGION_PX = 18;
constexpr int REGION_BYTES = REGION_PX * CH * 2;
constexpr int SLOT_BYTES = 4 * REGION_BYTES;
constexpr int A_LBO = 144, A_SBO = 12 * A_LBO;
constexpr int PREFETCH_ROWS = 3;
constexpr int NCONS = 3;
constexpr int CONS_THREADS = 128 * NCONS;
constexpr int NTHREADS = 128 + CONS_THREADS;
constexpr int MAX_ROWS = 52;
constexpr int TILE_BYTES = TILE_W * CH * 2, WARP_BYTES = TILE_BYTES / 4;
constexpr int ORDER_P = 3;
constexpr int W2_EARLY = 9;
static_assert(MAX_ROWS <= 128, "one table entry per producer thread");
static_assert(2 * A_SBO == REGION_BYTES && REGION_BYTES % 128 == 0, "region layout");

constexpr uint32_t SB = 1024;
constexpr int SM_W1 = 0;
constexpr int SM_W2 = SM_W1 + CH * EX * 2;
constexpr int SM_RING = SM_W2 + CH * EX * 2;
constexpr int SM_BIASH = SM_RING + NSLOT * SLOT_BYTES;
constexpr int SM_RED = SM_BIASH + 384;
constexpr int RED_MAX = 0, RED_LAUNCH = 48, RED_INV_RHO = 52, RED_JOB = 56;
constexpr int SM_TILES = SM_RED + 256;
constexpr int SM_ONES = SM_TILES + MAX_ROWS * 4;
constexpr int SM_BAR = SM_ONES + 128;
constexpr int BAR_X = SM_BAR;
constexpr int BAR_A = BAR_X + NSLOT * 4 * 8;
constexpr int BAR_E = BAR_A + NSLOT * 4 * 8;
constexpr int BAR_PIN = BAR_E + NSLOT * 4 * 8;
constexpr int BAR_W = BAR_PIN + 8;
constexpr int BAR_F = BAR_W + 6 * 8;
constexpr int BAR_R = BAR_F + 8;
constexpr int SM_TOTAL = BAR_R + 16 * 8;
constexpr int SM_FILTER = SM_RING + (NSLOT - 1) * SLOT_BYTES + 9 * 128;
constexpr int SM_SQ = SM_W2;
constexpr int SQ_ROW = 128 * 16, SQ_HALF = 6 * SQ_ROW;
static_assert(SM_ONES % 16 == 0 && SM_TOTAL <= 232448, "shared memory budget");

constexpr float KZ = 0.3292034911525734f;
constexpr uint32_t GELU_C2 = 0x40d940d9u;
constexpr float INV_2KZ = 0.5f / KZ;
constexpr uint32_t CONV_SCALE2 = 0x2f802f80u;
constexpr unsigned SPIN_LIMIT = 1u << 19;

constexpr int MAX_CTAS = 170;
constexpr int W2_GROUPS = EX / 8;
constexpr int LENT = 3, MAX_LENDERS = MAX_CTAS / (8 * LENT + 1);
struct Scratch {
    uint32_t w2h[EX * CH / 2];
    float w2max[EX];
    float bias[CH + 32];
    unsigned long long sums[EX / 4][32];
    __device__ __forceinline__ unsigned long long* sum(int e) { return &sums[e >> 2][e & 3]; }
    uint4 lent[MAX_LENDERS * LENT * 8 * 4 * 3 * 32];
    unsigned launch, pad0[31], early, pad1[31], prep, pad2[31], lent_out, pad3[31];
    unsigned job;
};
__device__ __align__(128) Scratch g_scratch;

#define PROF(k)

__device__ __forceinline__ uint32_t smem_u32(const void* p) { return (uint32_t)__cvta_generic_to_shared(p); }
__device__ __forceinline__ void mbar_init(uint32_t bar, uint32_t cnt) {
    asm volatile("mbarrier.init.shared::cta.b64 [%0], %1;" ::"r"(bar), "r"(cnt) : "memory");
}
__device__ __forceinline__ void mbar_arrive(uint32_t bar) {
    asm volatile("mbarrier.arrive.shared::cta.b64 _, [%0];" ::"r"(bar) : "memory");
}
__device__ __forceinline__ void mbar_expect_tx(uint32_t bar, uint32_t bytes) {
    asm volatile("mbarrier.arrive.expect_tx.shared::cta.b64 _, [%0], %1;" ::"r"(bar), "r"(bytes) : "memory");
}
__device__ __forceinline__ bool mbar_try(uint32_t bar, uint32_t par) {
    uint32_t ok;
    asm volatile("{\n.reg .pred p;\nmbarrier.try_wait.parity.shared::cta.b64 p, [%1], %2;\nselp.u32 %0, 1, 0, p;\n}\n"
                 : "=r"(ok) : "r"(bar), "r"(par) : "memory");
    return ok != 0;
}
__device__ __forceinline__ void mbar_wait(uint32_t bar, uint32_t par) {
    unsigned n = 0;
    while (!mbar_try(bar, par)) {
        if (++n > SPIN_LIMIT) __trap();
    }
}
__device__ __forceinline__ void mbar_wait_once(uint32_t bar, uint32_t par) {
    unsigned n = 0;
    bool ok;
#pragma unroll 1
    do {
        ok = mbar_try(bar, par);
        if (++n > SPIN_LIMIT) __trap();
    } while (!ok);
}
__device__ __forceinline__ bool elect_one() {
    uint32_t ok;
    asm volatile("{\n.reg .pred p;\nelect.sync _|p, 0xffffffff;\nselp.u32 %0, 1, 0, p;\n}\n" : "=r"(ok));
    return ok != 0;
}
__device__ __forceinline__ uint32_t opaque(uint32_t v) { return __shfl_sync(~0u, v, threadIdx.x & 31); }
__device__ __forceinline__ uint32_t lane_id() { uint32_t v; asm volatile("mov.u32 %0, %%laneid;" : "=r"(v)); return v; }
__device__ __forceinline__ uint32_t opaque_uniform(uint32_t v) { return __shfl_sync(~0u, v, 0); }
__device__ __forceinline__ void named_bar(int id, int n) { asm volatile("bar.sync %0, %1;" ::"r"(id), "r"(n) : "memory"); }
__device__ __forceinline__ void named_arrive(int id, int n) { asm volatile("bar.arrive %0, %1;" ::"r"(id), "r"(n) : "memory"); }
__device__ __forceinline__ void fence_async() { asm volatile("fence.proxy.async.shared::cta;" ::: "memory"); }
constexpr uint64_t EVICT_FIRST = 0x12F0000000000000ull;
__device__ __forceinline__ void tma_row(uint32_t dst, const CUtensorMap* tm, uint32_t bar, int x, int y) {
    asm volatile("cp.async.bulk.tensor.3d.shared::cluster.global.mbarrier::complete_tx::bytes.L2::cache_hint [%0], [%1, {%3, %4, %5}], [%2], %6;"
                 ::"r"(dst), "l"(tm), "r"(bar), "r"(0), "r"(x), "r"(y), "l"(EVICT_FIRST) : "memory");
}
__device__ __forceinline__ void bulk_load_stream(uint32_t dst, const void* src, uint32_t bytes, uint32_t bar) {
    asm volatile("cp.async.bulk.shared::cluster.global.mbarrier::complete_tx::bytes.L2::cache_hint [%0], [%1], %2, [%3], %4;"
                 ::"r"(dst), "l"(src), "r"(bytes), "r"(bar), "l"(EVICT_FIRST) : "memory");
}
__device__ __forceinline__ void prefetch_l2(const void* src, uint32_t bytes) {
    asm volatile("cp.async.bulk.prefetch.L2.global [%0], %1;" ::"l"(src), "r"(bytes) : "memory");
}
__device__ __forceinline__ void tma_2d(uint32_t dst, const CUtensorMap* tm, uint32_t bar, int x, int y) {
    asm volatile("cp.async.bulk.tensor.2d.shared::cluster.global.mbarrier::complete_tx::bytes [%0], [%1, {%3, %4}], [%2];"
                 ::"r"(dst), "l"(tm), "r"(bar), "r"(x), "r"(y) : "memory");
}
__device__ __forceinline__ void bulk_load(uint32_t dst, const void* src, uint32_t bytes, uint32_t bar) {
    asm volatile("cp.async.bulk.shared::cluster.global.mbarrier::complete_tx::bytes [%0], [%1], %2, [%3];"
                 ::"r"(dst), "l"(src), "r"(bytes), "r"(bar) : "memory");
}
__device__ __forceinline__ void wg_fence() { asm volatile("wgmma.fence.sync.aligned;" ::: "memory"); }
__device__ __forceinline__ void wg_commit() { asm volatile("wgmma.commit_group.sync.aligned;" ::: "memory"); }
template <int N> __device__ __forceinline__ void wg_wait() { asm volatile("wgmma.wait_group.sync.aligned %0;" ::"n"(N) : "memory"); }
template <int N> __device__ __forceinline__ void pin(uint32_t (&d)[N]) {
#pragma unroll
    for (int q = 0; q < N; q++) asm volatile("" : "+r"(d[q])::"memory");
}
__device__ __forceinline__ void stg128(void* p, const uint32_t (&v)[4]) {
    asm volatile("st.global.v4.u32 [%0], {%1, %2, %3, %4};" ::"l"(p), "r"(v[0]), "r"(v[1]), "r"(v[2]), "r"(v[3]) : "memory");
}
__device__ __forceinline__ void ldg128(uint32_t (&v)[4], const void* p) {
    asm volatile("ld.global.L1::no_allocate.v4.u32 {%0, %1, %2, %3}, [%4];" : "=r"(v[0]), "=r"(v[1]), "=r"(v[2]), "=r"(v[3]) : "l"(p) : "memory");
}
__device__ __forceinline__ void ldg128_if(bool on, uint32_t (&v)[4], const void* p) {
    asm volatile("{\n.reg .pred p;\nsetp.ne.b32 p, %5, 0;\n@p ld.global.L1::no_allocate.v4.u32 {%0, %1, %2, %3}, [%4];\n}\n"
                 : "+r"(v[0]), "+r"(v[1]), "+r"(v[2]), "+r"(v[3]) : "l"(p), "r"((int)on) : "memory");
}
__host__ __device__ constexpr uint64_t make_desc(uint32_t addr, uint32_t lbo, uint32_t sbo) {
    return (uint64_t)((addr & 0x3FFFF) >> 4) | ((uint64_t)(lbo >> 4) << 16) | ((uint64_t)(sbo >> 4) << 32);
}
__device__ __forceinline__ void wgmma(uint32_t (&d)[12], uint32_t a0, uint32_t a1, uint32_t a2, uint32_t a3, uint64_t db, int acc) {
    asm volatile("{\n.reg .pred p;\nsetp.ne.b32 p, %17, 0;\n"
                 "wgmma.mma_async.sync.aligned.m64n48k16.f16.f16.f16 "
                 "{%0, %1, %2, %3, %4, %5, %6, %7, %8, %9, %10, %11}, "
                 "{%12, %13, %14, %15}, %16, p, 1, 1, 0;\n}\n"
                 : "+r"(d[0]), "+r"(d[1]), "+r"(d[2]), "+r"(d[3]), "+r"(d[4]), "+r"(d[5]), "+r"(d[6]), "+r"(d[7]), "+r"(d[8]), "+r"(d[9]), "+r"(d[10]), "+r"(d[11])
                 : "r"(a0), "r"(a1), "r"(a2), "r"(a3), "l"(db), "r"(acc));
}
__device__ __forceinline__ void wgmma(uint32_t (&d)[24], uint32_t a0, uint32_t a1, uint32_t a2, uint32_t a3, uint64_t db, int acc) {
    asm volatile("{\n.reg .pred p;\nsetp.ne.b32 p, %29, 0;\n"
                 "wgmma.mma_async.sync.aligned.m64n96k16.f16.f16.f16 "
                 "{%0, %1, %2, %3, %4, %5, %6, %7, %8, %9, %10, %11, %12, %13, %14, %15, %16, %17, %18, %19, %20, %21, %22, %23}, "
                 "{%24, %25, %26, %27}, %28, p, 1, 1, 0;\n}\n"
                 : "+r"(d[0]), "+r"(d[1]), "+r"(d[2]), "+r"(d[3]), "+r"(d[4]), "+r"(d[5]), "+r"(d[6]), "+r"(d[7]), "+r"(d[8]), "+r"(d[9]), "+r"(d[10]), "+r"(d[11]), "+r"(d[12]), "+r"(d[13]), "+r"(d[14]), "+r"(d[15]), "+r"(d[16]), "+r"(d[17]), "+r"(d[18]), "+r"(d[19]), "+r"(d[20]), "+r"(d[21]), "+r"(d[22]), "+r"(d[23])
                 : "r"(a0), "r"(a1), "r"(a2), "r"(a3), "l"(db), "r"(acc));
}
template <int ACC>
__device__ __forceinline__ void wgmma_rowsum(float (&d)[4], const uint32_t (&a)[4], uint64_t ones) {
    asm volatile("{\n.reg .pred p;\nsetp.ne.b32 p, %9, 0;\n"
                 "wgmma.mma_async.sync.aligned.m64n8k16.f32.bf16.bf16 {%0, %1, %2, %3}, {%4, %5, %6, %7}, %8, p, 1, 1, 0;\n}\n"
                 : "+f"(d[0]), "+f"(d[1]), "+f"(d[2]), "+f"(d[3])
                 : "r"(a[0]), "r"(a[1]), "r"(a[2]), "r"(a[3]), "l"(ones), "n"(ACC));
}
__device__ __forceinline__ void ldsm4(uint32_t (&r)[4], uint32_t addr) {
    asm volatile("ldmatrix.sync.aligned.m8n8.x4.shared.b16 {%0, %1, %2, %3}, [%4];"
                 : "=r"(r[0]), "=r"(r[1]), "=r"(r[2]), "=r"(r[3]) : "r"(addr) : "memory");
}
__device__ __forceinline__ void ldsm4_t(uint32_t (&r)[4], uint32_t addr) {
    asm volatile("ldmatrix.sync.aligned.m8n8.x4.trans.shared.b16 {%0, %1, %2, %3}, [%4];"
                 : "=r"(r[0]), "=r"(r[1]), "=r"(r[2]), "=r"(r[3]) : "r"(addr) : "memory");
}
__device__ __forceinline__ void stsm4(uint32_t addr, uint32_t a, uint32_t b, uint32_t c, uint32_t d) {
    asm volatile("stmatrix.sync.aligned.m8n8.x4.shared.b16 [%0], {%1, %2, %3, %4};"
                 ::"r"(addr), "r"(a), "r"(b), "r"(c), "r"(d) : "memory");
}
__device__ __forceinline__ uint32_t transpose8x8(uint32_t v) {
    uint32_t d; asm volatile("movmatrix.sync.aligned.m8n8.trans.b16 %0, %1;" : "=r"(d) : "r"(v)); return d;
}
__device__ __forceinline__ void spin_until(const unsigned* counter, unsigned target) {
    unsigned n = 0, c;
    do {
        asm volatile("ld.acquire.gpu.global.u32 %0, [%1];" : "=r"(c) : "l"(counter) : "memory");
        if (++n > SPIN_LIMIT) __trap();
    } while ((int)(c - target) < 0);
}
__device__ __forceinline__ void signal(unsigned* counter) {
    __syncwarp();
    if (elect_one()) asm volatile("red.release.gpu.global.add.u32 [%0], 1;" ::"l"(counter) : "memory");
    __syncwarp();
}
__device__ __forceinline__ void lds128(uint32_t& a, uint32_t& b, uint32_t& c, uint32_t& d, uint32_t addr) {
    asm volatile("ld.shared.v4.u32 {%0, %1, %2, %3}, [%4];" : "=r"(a), "=r"(b), "=r"(c), "=r"(d) : "r"(addr) : "memory");
}
__device__ __forceinline__ void lds64(uint32_t& a, uint32_t& b, uint32_t addr) {
    asm volatile("ld.shared.v2.u32 {%0, %1}, [%2];" : "=r"(a), "=r"(b) : "r"(addr) : "memory");
}
__device__ __forceinline__ void lds32(uint32_t& a, uint32_t addr) {
    asm volatile("ld.shared.u32 %0, [%1];" : "=r"(a) : "r"(addr) : "memory");
}
__device__ __forceinline__ int ldsi(uint32_t addr) {
    uint32_t v;
    lds32(v, addr);
    return (int)v;
}
__device__ __forceinline__ float ldsf(uint32_t addr) {
    uint32_t v;
    lds32(v, addr);
    return __uint_as_float(v);
}
__device__ __forceinline__ void sts32(uint32_t addr, uint32_t a) {
    asm volatile("st.shared.u32 [%0], %1;" ::"r"(addr), "r"(a) : "memory");
}
__device__ __forceinline__ void sts128(uint32_t addr, uint32_t a, uint32_t b, uint32_t c, uint32_t d) {
    asm volatile("st.shared.v4.u32 [%0], {%1, %2, %3, %4};" ::"r"(addr), "r"(a), "r"(b), "r"(c), "r"(d) : "memory");
}
__device__ __forceinline__ void sts64(uint32_t addr, uint32_t a, uint32_t b) {
    asm volatile("st.shared.v2.u32 [%0], {%1, %2};" ::"r"(addr), "r"(a), "r"(b) : "memory");
}
__device__ __forceinline__ void anchor(uint32_t addr, uint32_t a, uint32_t b, uint32_t c, uint32_t d) {
    asm volatile("{\n.reg .pred p;\nsetp.eq.b32 p, %0, 0;\n@p st.shared.v4.u32 [%0], {%1, %2, %3, %4};\n}\n"
                 ::"r"(addr), "r"(a), "r"(b), "r"(c), "r"(d) : "memory");
}
__device__ __forceinline__ uint32_t bf_fma(uint32_t a, uint32_t b, uint32_t c) {
    uint32_t d; asm("fma.rn.bf16x2 %0, %1, %2, %3;" : "=r"(d) : "r"(a), "r"(b), "r"(c)); return d;
}
__device__ __forceinline__ uint32_t bf_mul(uint32_t a, uint32_t b) {
    uint32_t d; asm("mul.rn.bf16x2 %0, %1, %2;" : "=r"(d) : "r"(a), "r"(b)); return d;
}
__device__ __forceinline__ uint32_t bf_absmax(uint32_t a, uint32_t b) {
    uint32_t d; asm("max.xorsign.abs.bf16x2 %0, %1, %2;" : "=r"(d) : "r"(a), "r"(b)); return d;
}
__device__ __forceinline__ uint32_t h_fma(uint32_t a, uint32_t b, uint32_t c) {
    uint32_t d; asm("fma.rn.f16x2 %0, %1, %2, %3;" : "=r"(d) : "r"(a), "r"(b), "r"(c)); return d;
}
__device__ __forceinline__ uint32_t h_mul(uint32_t a, uint32_t b) {
    uint32_t d; asm("mul.rn.f16x2 %0, %1, %2;" : "=r"(d) : "r"(a), "r"(b)); return d;
}
__device__ __forceinline__ uint32_t h_cut8(uint32_t v) { return v & 0xfff8fff8u; }
constexpr float CUT_GAIN = 1.f + 0.4375f * 0.7213f / 128;
__device__ __forceinline__ uint32_t h_tanh(uint32_t a) {
    uint32_t d; asm("tanh.approx.f16x2 %0, %1;" : "=r"(d) : "r"(a)); return d;
}
__device__ __forceinline__ uint32_t pack_h2(float lo, float hi) {
    uint32_t d; asm("cvt.rn.f16x2.f32 %0, %1, %2;" : "=r"(d) : "f"(hi), "f"(lo)); return d;
}
__device__ __forceinline__ uint32_t pack_bf2(float lo, float hi) {
    uint32_t d; asm("cvt.rn.bf16x2.f32 %0, %1, %2;" : "=r"(d) : "f"(hi), "f"(lo)); return d;
}
__device__ __forceinline__ float bf_lo(uint32_t v) { return __uint_as_float(v << 16); }
__device__ __forceinline__ float bf_hi(uint32_t v) { return __uint_as_float(v & 0xffff0000u); }
__device__ __forceinline__ float h_lo(uint32_t v) { return __low2float(*reinterpret_cast<__half2*>(&v)); }
__device__ __forceinline__ float h_hi(uint32_t v) { return __high2float(*reinterpret_cast<__half2*>(&v)); }
__device__ __forceinline__ float warp_absmax(uint32_t v) {
    return __uint_as_float(__reduce_max_sync(~0u, max((v & 0x7fffu) << 16, v & 0x7fff0000u)));
}
__device__ __forceinline__ uint32_t gelu2(uint32_t z) {
    uint32_t p = h_fma(z, z, GELU_C2);
    uint32_t t = h_tanh(h_mul(z, p));
    return h_fma(z, t, z);
}
__device__ __forceinline__ float pow2i(int e) { return __uint_as_float((uint32_t)(e + 127) << 23); }
__device__ __forceinline__ int ilog2f(float v) {
    int e = (int)((__float_as_uint(v) >> 23) & 0xff) - 127;
    return max(-100, min(100, e));
}

__device__ __forceinline__ int bound_exp(float w1max) { return w1max > 0.f ? ilog2f(2.f * KZ * 96.f * w1max) : 0; }
__device__ __forceinline__ bool plain_squares(int e) { return (unsigned)(4 - e) <= 6; }
__device__ __forceinline__ int square_exp(int e) { return plain_squares(e) ? 0 : max(-14, min(4 - e, 14)); }
__device__ __forceinline__ int sum_exp(int e) { return max(-90, min(90, 33 - 2 * e)); }
__device__ __forceinline__ int row_exp(float m) { return 2 - ilog2f(m); }

struct Split {
    int per_cta, extra, period, inv_period, lenders;
    uint32_t lent_off[MAX_LENDERS * LENT];
    __host__ __device__ __forceinline__ int longer_before(int cta) const {
        const int n = (cta + period / 2) * inv_period >> 16;
        return n < extra ? n : extra;
    }
};
struct Work {
    int tA, tB, nA, nB, dir, rows, lent, index;
    __host__ __device__ __forceinline__ int tile(int j) const { return j < nA ? tA + dir * j : tB + dir * (j - nA); }
};
__host__ __device__ __forceinline__ Work get_work(int cta, const Split& sp) {
    Work w;
    const int before = sp.longer_before(cta), longer = sp.longer_before(cta + 1) - before;
    w.lent = longer && sp.lenders ? LENT : 0;
    w.index = before;
    const int t0 = cta * sp.per_cta + before, t1 = t0 + sp.per_cta + longer;
    const int tm = t1 < (t0 | 511) + 1 ? t1 : (t0 | 511) + 1;
    const bool swap = t1 > tm && t1 - tm < tm - t0, down = cta & 1;
    w.nA = swap ? t1 - tm : tm - t0;
    w.nB = t1 - t0 - w.nA;
    w.tA = down ? (swap ? tm : t0) : (swap ? t1 : tm) - 1;
    w.tB = down ? (swap ? t0 : tm) : (swap ? tm : t1) - 1;
    w.dir = down ? 1 : -1;
    w.rows = w.nA + 2 + (w.nB ? w.nB + 2 : 0);
    return w;
}
__device__ __forceinline__ int row_code(const Work& w, int i) {
    const bool in_a = i < w.nA + 2;
    const int t = in_a ? w.tA : w.tB;
    return ((t & 511) + w.dir * ((in_a ? i : i - (w.nA + 2)) - 1)) << 16 | (t >> 9) * TILE_W;
}
__host__ __device__ __forceinline__ uint32_t tile_offset(int tile) { return ((tile & 511) * IMG_W + (tile >> 9) * TILE_W) * (CH * 2); }
__device__ __forceinline__ int tile_order(int j, int n) {
    return j % ORDER_P == ORDER_P - 1 ? j / ORDER_P : n - 1 - (j - j / ORDER_P);
}
__device__ __forceinline__ void issue_region(const CUtensorMap* tm, uint32_t dst, uint32_t bar, int warp, int code) {
    mbar_expect_tx(bar, REGION_BYTES);
    tma_row(dst, tm, bar, (code & 0xffff) + (16 * warp - 1), code >> 16);
}

template <class Event>
__device__ __forceinline__ void conv_producer(const Work& wk, const CUtensorMap* tm, uint32_t sb, int warp, Event event) {
    const int lane = threadIdx.x & 31;
    const int j = lane & 15, grp = lane >> 4;
    const uint32_t reg0 = sb + SM_RING + warp * REGION_BYTES;
    const uint32_t bars = sb + SM_BAR + warp * 8;
    if (warp * 32 + lane < MAX_ROWS) {
        const int i = warp * 32 + lane, before = min(i / 5, wk.lent);
        const bool back = i % 5 == 0 && i > 0 && i / 5 <= wk.lent;
        sts32(sb + SM_TILES + i * 4, back ? tile_offset(wk.tile(before - 1)) | before
                                          : tile_offset(wk.tile(wk.lent + tile_order(i - before, wk.nA + wk.nB - 4 - wk.lent))));
    }
    const uint32_t ld64 = opaque(reg0 + grp * 8 * 192 + j * 8), ld32 = opaque(reg0 + grp * 8 * 192 + 128 + j * 4);
    const uint32_t st64 = opaque(reg0 + grp * A_SBO + (j >> 1) * A_LBO + (j & 1) * 8);
    const uint32_t st32 = opaque(reg0 + grp * A_SBO + (8 + (j >> 2)) * A_LBO + (j & 3) * 4);
    named_bar(0, NTHREADS);
    uint32_t w[3][3][3];
    mbar_wait_once(sb + BAR_F, 0);
#pragma unroll
    for (int tap = 0; tap < 9; tap++) {
        const uint32_t p = sb + SM_FILTER + (3 + wk.dir * 3 * (tap / 3 - 1) + tap % 3) * (CH * 2);
        lds64(w[tap / 3][tap % 3][0], w[tap / 3][tap % 3][1], p + 8 * j);
        lds32(w[tap / 3][tap % 3][2], p + 128 + 4 * j);
#pragma unroll
        for (int q = 0; q < 3; q++) w[tap / 3][tap % 3][q] = bf_mul(w[tap / 3][tap % 3][q], CONV_SCALE2);
    }
#pragma unroll
    for (int tap = 0; tap < 9; tap++) sts64(reg0 + (NSLOT - 1) * SLOT_BYTES + tap * 128 + j * 8, w[tap / 3][tap % 3][1], w[tap / 3][tap % 3][0]);
    named_bar(1, 128);
#pragma unroll
    for (int tap = 0; tap < 9; tap++) lds64(w[tap / 3][tap % 3][1], w[tap / 3][tap % 3][0], reg0 + (NSLOT - 1) * SLOT_BYTES + tap * 128 + j * 8);
    static_assert(2 * PREFETCH_ROWS == NSLOT && SLOT_BYTES % 32 == 0, "slot arithmetic");
    uint32_t bo = 0, par = 0, pbo = PREFETCH_ROWS * 32, ppar = 1;
    int px, py;
    auto request = [&]() {
        mbar_wait_once(bars + (BAR_E - SM_BAR) + pbo, ppar);
        if (elect_one()) {
            mbar_expect_tx(bars + pbo, REGION_BYTES);
            tma_row(reg0 + pbo * (SLOT_BYTES / 32), tm, bars + pbo, px, py);
        }
    };
    auto advance = [&]() {
        bo += 32;
        if (bo == NSLOT * 32) { bo = 0; par ^= 1; }
        pbo += 32;
        if (pbo == NSLOT * 32) { pbo = 0; ppar ^= 1; }
    };
    auto aim = [&](int row) {
        const int code = row_code(wk, row);
        px = (code & 0xffff) + (16 * warp - 1);
        py = code >> 16;
    };
    uint32_t accB[8][3], accC[8][3];
    int r = 0;
#pragma unroll 1
    while (r < wk.rows) {
        if (r == 0 || r == wk.nA + 2) {
            const uint32_t bo0 = bo;
            uint32_t bo1;
#pragma unroll 1
            for (int k = 0; k < 2; k++, r++) {
                mbar_wait_once(bars + bo, par);
                bo1 = bo;
                if (r >= 2) {
                    aim(r + PREFETCH_ROWS);
                    request();
                }
                advance();
            }
            const uint32_t so0 = bo0 * (SLOT_BYTES / 32), so1 = bo1 * (SLOT_BYTES / 32);
#pragma unroll
            for (int p = 0; p < 10; p++) {
                uint32_t u[3], v[3];
                lds64(u[0], u[1], so0 + ld64 + p * 192);
                lds32(u[2], so0 + ld32 + p * 192);
                lds64(v[0], v[1], so1 + ld64 + p * 192);
                lds32(v[2], so1 + ld32 + p * 192);
#pragma unroll
                for (int dx = 0; dx < 3; dx++) {
                    const int o = p - dx;
                    if (o < 0 || o > 7) continue;
#pragma unroll
                    for (int q = 0; q < 3; q++) {
                        accB[o][q] = bf_fma(v[q], w[1][dx][q], dx == 0 ? bf_mul(u[q], w[0][dx][q]) : bf_fma(u[q], w[0][dx][q], accB[o][q]));
                        accC[o][q] = dx == 0 ? bf_mul(v[q], w[0][dx][q]) : bf_fma(v[q], w[0][dx][q], accC[o][q]);
                    }
                }
            }
            anchor(ld64, accB[7][0], accB[7][1], accB[7][2], 0);
            __syncwarp();
            if (elect_one()) {
                mbar_arrive(bars + (BAR_A - SM_BAR) + bo0);
                mbar_arrive(bars + (BAR_E - SM_BAR) + bo0);
                mbar_arrive(bars + (BAR_A - SM_BAR) + bo1);
                mbar_arrive(bars + (BAR_E - SM_BAR) + bo1);
            }
        }
        int end = wk.rows;
        const int marks[4] = {wk.rows - PREFETCH_ROWS, wk.rows - 11, wk.nA + 2, wk.nA + 2 - PREFETCH_ROWS};
#pragma unroll
        for (int k = 0; k < 4; k++) end = marks[k] > r ? min(end, marks[k]) : end;
        const bool fetch = r < wk.rows - PREFETCH_ROWS;
        aim(r + PREFETCH_ROWS);
        px = opaque_uniform(px);
        const int py_end = opaque_uniform(py + wk.dir * (end - r));
        r = end;
#pragma unroll 1
        do {
            mbar_wait(bars + bo, par);
            const uint32_t so = bo * (SLOT_BYTES / 32);
            uint32_t out[8][3];
#pragma unroll
            for (int p = 0; p < 10; p++) {
                uint32_t xv[3];
                lds64(xv[0], xv[1], so + ld64 + p * 192);
                lds32(xv[2], so + ld32 + p * 192);
#pragma unroll
                for (int dx = 0; dx < 3; dx++) {
                    const int o = p - dx;
                    if (o < 0 || o > 7) continue;
#pragma unroll
                    for (int q = 0; q < 3; q++) {
                        out[o][q] = bf_fma(xv[q], w[2][dx][q], dx == 0 ? accB[o][q] : out[o][q]);
                        accB[o][q] = bf_fma(xv[q], w[1][dx][q], dx == 0 ? accC[o][q] : accB[o][q]);
                        accC[o][q] = dx == 0 ? bf_mul(xv[q], w[0][dx][q]) : bf_fma(xv[q], w[0][dx][q], accC[o][q]);
                    }
                }
            }
            __syncwarp();
#pragma unroll
            for (int o = 0; o < 8; o++) {
                sts64(so + st64 + o * 16, out[o][0], out[o][1]);
                sts32(so + st32 + o * 16, out[o][2]);
            }
            __syncwarp();
            if (elect_one()) mbar_arrive(bars + (BAR_A - SM_BAR) + bo);
            if (fetch) request();
            advance();
            py += wk.dir;
        } while (py != py_end);
        if (((wk.rows - r) & ~8) == PREFETCH_ROWS) event(wk.rows - r == PREFETCH_ROWS);
    }
}

template <bool SCALED, int K0 = 0, int K1 = 3>
__device__ __forceinline__ void gelu_sq(uint32_t (&d)[24], uint32_t (&keep)[24], uint32_t sq_addr, uint32_t scale2) {
    pin(d);
#pragma unroll
    for (int k = K0; k < K1; k++) {
        uint32_t hs[4];
        lds128(hs[0], hs[1], hs[2], hs[3], sq_addr + k * SQ_ROW);
#pragma unroll
        for (int q = 0; q < 4; q++) {
            uint32_t g0 = gelu2(d[8 * k + 2 * q]), g1 = gelu2(d[8 * k + 2 * q + 1]);
            keep[8 * k + 2 * q] = g0;
            keep[8 * k + 2 * q + 1] = g1;
            if (SCALED) { g0 = h_mul(g0, scale2); g1 = h_mul(g1, scale2); }
            hs[q] = h_fma(g1, g1, h_fma(g0, g0, hs[q]));
        }
        sts128(sq_addr + k * SQ_ROW, hs[0], hs[1], hs[2], hs[3]);
    }
}
__device__ __forceinline__ void gelu_sq_reg(uint32_t (&d)[24], uint32_t (&hs)[12]) {
    pin(d);
#pragma unroll
    for (int q = 0; q < 12; q++) {
        const uint32_t g0 = gelu2(d[2 * q]), g1 = gelu2(d[2 * q + 1]);
        hs[q] = h_fma(g1, g1, h_fma(g0, g0, hs[q]));
    }
}
__device__ __forceinline__ void gelu_to(uint32_t (&g)[12], uint32_t (&d)[12]) {
    pin(d);
#pragma unroll
    for (int q = 0; q < 12; q++) g[q] = gelu2(d[q]);
    pin(g);
}
__device__ __forceinline__ void load_tile(uint32_t (&raw)[6][4], uint32_t addr) {
#pragma unroll
    for (int s = 0; s < 6; s++) ldsm4(raw[s], addr + s * 2 * A_LBO);
}
template <class F>
__device__ __forceinline__ void layer_norm(uint32_t (&raw)[6][4], uint64_t ones, F meanwhile) {
    constexpr int NS = 2;
    uint32_t sq[NS][4];
#pragma unroll
    for (int s = 0; s < 6; s++)
#pragma unroll
        for (int q = 0; q < 4; q++) sq[s % NS][q] = s < NS ? bf_mul(raw[s][q], raw[s][q]) : bf_fma(raw[s][q], raw[s][q], sq[s % NS][q]);
    float sum[4], ssq[4];
    wg_fence();
    wgmma_rowsum<0>(sum, raw[0], ones);
#pragma unroll
    for (int s = 1; s < 6; s++) wgmma_rowsum<1>(sum, raw[s], ones);
    wgmma_rowsum<0>(ssq, sq[0], ones);
#pragma unroll
    for (int s = 1; s < NS; s++) wgmma_rowsum<1>(ssq, sq[s], ones);
    wg_commit();
    meanwhile();
    wg_wait<0>();
    uint32_t sc[2], sh[2];
#pragma unroll
    for (int h = 0; h < 2; h++) {
        asm volatile("" : "+f"(sum[2 * h]), "+f"(ssq[2 * h])::"memory");
        constexpr float EPS = 1e-5f / (KZ * KZ) * 0x1p-64f;
        const float m = sum[2 * h] * (1.f / (CH * KZ));
        float rstd;
        asm("rsqrt.approx.ftz.f32 %0, %1;" : "=f"(rstd) : "f"(fmaxf(fmaf(-m, m, fmaf(ssq[2 * h], 1.f / (CH * KZ * KZ), EPS)), EPS)));
        rstd *= 0x1p-112f;
        sc[h] = pack_bf2(rstd, rstd);
        const float shift = sum[2 * h] * (-1.f / CH) * bf_hi(sc[h]);
        sh[h] = pack_bf2(shift, shift);
    }
#pragma unroll
    for (int s = 0; s < 6; s++)
#pragma unroll
        for (int q = 0; q < 4; q++) {
            const uint32_t v = bf_fma(raw[s][q], sc[q & 1], sh[q & 1]);
            asm("lop3.b32 %0, %1, %2, 0x80008000, 0xd8;" : "=r"(raw[s][q]) : "r"(v << 3), "r"(v));
        }
}
struct Cursor {
    int slot;
    uint32_t par;
    __device__ __forceinline__ void advance(int n) {
        slot += n;
        if (slot >= NSLOT) { slot -= NSLOT; par ^= 1; }
    }
};
struct Descs {
    uint64_t w1[8][6];
    uint64_t w2[24];
    uint64_t ones;
};
template <int E0, int N>
__device__ __forceinline__ void gemm1_chunk(uint32_t (&d)[N], const uint32_t (&a)[6][4], const Descs& ds, int zero) {
#pragma unroll
    for (int s = 0; s < 6; s++) wgmma(d, a[s][0], a[s][1], a[s][2], a[s][3], ds.w1[E0 / 48][s], s ? 1 : zero);
}
template <int E0, int N>
__device__ __forceinline__ void gemm2_chunk(uint32_t (&acc)[24], const uint32_t (&g)[N], const Descs& ds) {
#pragma unroll
    for (int s = 0; s < N / 4; s++) wgmma(acc, g[4 * s], g[4 * s + 1], g[4 * s + 2], g[4 * s + 3], ds.w2[E0 / 16 + s], 1);
}

struct __align__(64) Params {
    Split sp;
    int zero;
    const __nv_bfloat16 *x, *dw, *w2, *gamma, *beta;
    __nv_bfloat16* out;
    Scratch* sc;
    Descs ds;
};

__global__ void __launch_bounds__(NTHREADS, 1)
block_kernel(const __grid_constant__ CUtensorMap tmap, const __grid_constant__ CUtensorMap tmap_w1, const __grid_constant__ Params pm) {
    const Split& sp = pm.sp;
    const Descs& ds = pm.ds;
    const int& zero = pm.zero;
    const __nv_bfloat16 *const &x = pm.x, *const &dw = pm.dw, *const &w2 = pm.w2, *const &gamma = pm.gamma, *const &beta = pm.beta;
    __nv_bfloat16* const& out = pm.out;
    Scratch* const& sc = pm.sc;
    extern __shared__ __align__(1024) uint8_t smem[];
    constexpr uint32_t sb = SB;
    const int tid = threadIdx.x;
    const Work wk = get_work(blockIdx.x, sp);
    constexpr uint32_t s_red = sb + SM_RED;
    if (smem_u32(smem) != SB) __trap();

    const int warp_id = __shfl_sync(~0u, tid >> 5, 0);
    PROF(0);
    const int cw = warp_id - 4, wgi = cw >> 2, w4 = warp_id & 3;
    if (elect_one()) {
        static_assert(3 * NSLOT * 4 == 8 + 4 * 16 && BAR_F == BAR_W + 48, "barrier shares");
        const int b = warp_id - 8;
        const uint32_t bar = b < 0 ? sb + BAR_X + warp_id * 8 : b < 7 ? sb + BAR_W + b * 8 : sb + BAR_PIN;
        mbar_init(bar, 1);
#pragma unroll
        for (int k = 0; k < 4; k++) mbar_init(sb + BAR_X + (8 + 4 * warp_id + k) * 8, 1);
        mbar_init(sb + BAR_R + warp_id * 8, 1);
        fence_async();
        if (b < 0) {
            issue_region(&tmap, sb + SM_RING + warp_id * REGION_BYTES, bar, w4, ((wk.tA & 511) + wk.dir * wgi) << 16 | (wk.tA >> 9) * TILE_W);
        } else if (b < 6) {
            mbar_expect_tx(bar, 64 * CH * 2);
            tma_2d(sb + SM_W2 + b * (64 * CH * 2), &tmap_w1, bar, 64 * b, 0);
        } else if (b == 6) {
            mbar_expect_tx(bar, 9 * CH * 2);
            bulk_load(sb + SM_FILTER, dw, 9 * CH * 2, bar);
        }
    }
    __syncwarp();
    const int ntiles = wk.nA + wk.nB;
    const int rank = (wgi + wk.lent + 2 * (ntiles - 1)) % NCONS | (wgi >> 2 & 3);
    const int spare = wk.rows % NSLOT, spare2 = spare == NSLOT - 1 ? 0 : spare + 1;
    const uint32_t sq_base = sb + (wgi < 0 ? SM_RING + spare * SLOT_BYTES : SM_SQ + rank * 2 * SQ_HALF);
    const uint32_t sq_upper = wgi < 0 ? (spare2 - spare) * SLOT_BYTES : SQ_HALF;
    const uint32_t bar_a = sb + BAR_A + w4 * 8, bar_e = sb + BAR_E + w4 * 8;
    auto max_w1 = [&](uint32_t lane) { return __uint_as_float(__reduce_max_sync(~0u, lane < 4 * NCONS ? ldsi(s_red + RED_MAX + lane * 4) : 0)); };
    auto square_scale = [&](uint32_t lane) {
        const float f = pow2i(square_exp(bound_exp(max_w1(lane))));
        return pack_h2(f, f);
    };
    uint32_t a_addr, sq;
    const uint32_t sq_warp = sq_base + w4 * 512;
    auto set_addresses = [&]() {
        a_addr = opaque(sb + SM_RING + w4 * REGION_BYTES + ((tid >> 3) & 1) * A_SBO + ((tid >> 4) & 1) * A_LBO + (tid & 7) * 16);
        sq = opaque(sq_base + (tid & 127) * 16);
    };
    uint32_t turn, turn_end, so, so_sum, bo, bo_sum, off;
    auto set_run = [&](int j, int stop, int row) {
        const int slot = row % NSLOT, both = 2 * (row % 3) + 3;
        turn = opaque_uniform(row / 3);
        turn_end = opaque_uniform(row / 3 + (stop - j + NCONS - 1) / NCONS);
        so = opaque_uniform(slot * SLOT_BYTES);
        so_sum = opaque_uniform(both * SLOT_BYTES);
        bo = opaque_uniform(bar_a + slot * 32);
        bo_sum = opaque_uniform(2 * bar_a + both * 32);
        off = opaque_uniform(tile_offset(wk.tile(j)) + w4 * WARP_BYTES - sq_warp);
    };
    const int nrest = ntiles - 4;
    int jt;
    Cursor cur;
    int fast_from;
    if (warp_id < 4) {
        conv_producer(wk, &tmap, sb, warp_id, [&](bool second) {
            if (!second) {
                if (tid == 0) sts32(s_red + RED_JOB, wk.lent ? NTILES : atomicAdd(&sc->job, 1));
                if (blockIdx.x == 0) {
#pragma unroll 1
                    for (int e = tid; e < EX; e += 128) *sc->sum(e) = 0;
                    sc->bias[tid] = 0.f;
                }
                if (blockIdx.x == 0 || wk.lent) signal(&sc->early);
                __syncwarp();
            } else {
                const int piece = opaque_uniform(ldsi(s_red + RED_JOB)) - W2_GROUPS / 2, q = 2 * piece + W2_GROUPS + (w4 >> 1);
                if (piece < 8 * LENT * sp.lenders) {
                    spin_until(&sc->early, (ldsi(s_red + RED_LAUNCH) + 1) * 4 * (sp.lenders + 1));
                    if (elect_one()) {
                        if (piece >= 0) prefetch_l2(reinterpret_cast<const char*>(out) + sp.lent_off[piece / 8] + w4 * WARP_BYTES, WARP_BYTES);
                        else { prefetch_l2(w2 + 8 * q * CH, 8 * CH * 2); prefetch_l2(beta + 8 * q, 16); }
                    }
                }
            }
        });
        const int piece = opaque_uniform(ldsi(s_red + RED_JOB)) - W2_GROUPS / 2, q = 2 * piece + W2_GROUPS + (w4 >> 1);
        const bool prepares = piece < 0, helps = piece < 8 * LENT * sp.lenders;
        set_addresses();
        const int lane = lane_id(), g = lane >> 2, t = lane & 3;
        uint32_t a[6][4];
        unsigned short bt_raw;
        if (prepares) {
#pragma unroll
            for (int m = 0; m < 3; m++) ldg128(a[m], w2 + (8 * q + g) * CH + 32 * m + 8 * t);
            asm volatile("ld.global.nc.u16 %0, [%1];" : "=h"(bt_raw) : "l"(beta + 8 * q + g) : "memory");
        } else if (helps) {
#pragma unroll
            for (int s = 0; s < 6; s++) ldg128(a[s], reinterpret_cast<const char*>(out) + sp.lent_off[piece / 8] + w4 * WARP_BYTES + lane * 16 + s * 512);
        }
        mbar_wait_once(bar_e + spare2 * 32, (wk.rows - 5) / NSLOT & 1);
        mbar_wait_once(bar_e + spare * 32, (wk.rows - 6) / NSLOT & 1);
        named_bar(1, 128);
#pragma unroll
        for (int k = 0; k < 6; k++) { sts128(sq + k * SQ_ROW, 0, 0, 0, 0); sts128(sq + sq_upper + k * SQ_ROW, 0, 0, 0, 0); }
        if (prepares) {
            const int half = w4 & 1;
            uint32_t rmax = 0;
#pragma unroll
            for (int m = 0; m < 3; m++) rmax = bf_absmax(bf_absmax(rmax, bf_absmax(a[m][0], a[m][1])), bf_absmax(a[m][2], a[m][3]));
            uint2 u = half ? make_uint2(a[0][2], a[0][3]) : make_uint2(a[0][0], a[0][1]), u1 = half ? make_uint2(a[1][2], a[1][3]) : make_uint2(a[1][0], a[1][1]);
            const uint2 u2 = half ? make_uint2(a[2][2], a[2][3]) : make_uint2(a[2][0], a[2][1]);
            const float bt = bf_lo(bt_raw);
            rmax = bf_absmax(rmax, __shfl_xor_sync(~0u, rmax, 1));
            rmax = bf_absmax(rmax, __shfl_xor_sync(~0u, rmax, 2));
            const float mx = fmaxf(fabsf(bf_lo(rmax)), fabsf(bf_hi(rmax))), rs = pow2i(row_exp(mx));
            if (t == 0 && !half) sc->w2max[8 * q + g] = mx;
#pragma unroll 1
            for (int m = 0; m < 3; m++, u = u1, u1 = u2) {
                float f[4];
#pragma unroll
                for (int k = 0; k < 2; k++) {
                    const float lo = bf_lo(k ? u.y : u.x), hi = bf_hi(k ? u.y : u.x);
                    sc->w2h[(4 * m + 2 * half + k) * 1536 + q * 32 + lane] = transpose8x8(pack_h2(lo * rs, hi * rs));
                    f[2 * k] = lo * bt;
                    f[2 * k + 1] = hi * bt;
                }
                const float r0 = (g & 2 ? f[2] : f[0]) + __shfl_xor_sync(~0u, g & 2 ? f[0] : f[2], 8);
                const float r1 = (g & 2 ? f[3] : f[1]) + __shfl_xor_sync(~0u, g & 2 ? f[1] : f[3], 8);
                float r = (g & 1 ? r1 : r0) + __shfl_xor_sync(~0u, g & 1 ? r0 : r1, 4);
                r += __shfl_xor_sync(~0u, r, 16);
                if (g < 4) atomicAdd(&sc->bias[32 * m + 8 * t + 4 * half + g], r);
            }
            asm volatile("fence.proxy.async.global;" ::: "memory");
            signal(&sc->prep);
        } else
        if (helps) {
            uint32_t d[12], gl[12];
            const uint32_t scale2 = square_scale(lane);
            wg_fence();
#pragma unroll
            for (int s = 0; s < 6; s++) wgmma(d, a[s][0], a[s][1], a[s][2], a[s][3], ds.w1[0][s] + piece % 8 * (6 * 1536 / 16), s ? 1 : 0);
            wg_commit();
            wg_wait<0>();
            gelu_to(gl, d);
#pragma unroll
            for (int s = 0; s < 3; s++) {
                sc->lent[((piece / 8 * 4 + w4) * 24 + piece % 8 * 3 + s) * 32 + lane] = make_uint4(gl[4 * s], gl[4 * s + 1], gl[4 * s + 2], gl[4 * s + 3]);
                uint32_t hs[2];
#pragma unroll
                for (int k = 0; k < 2; k++) {
                    const uint32_t g0 = h_mul(gl[4 * s + 2 * k], scale2), g1 = h_mul(gl[4 * s + 2 * k + 1], scale2);
                    hs[k] = h_fma(g1, g1, h_mul(g0, g0));
                }
                const int pair = piece % 4 * 3 + s;
                sts64(sq + (piece & 4 ? sq_upper : 0) + (pair >> 1) * SQ_ROW + (pair & 1) * 8, hs[0], hs[1]);
            }
        }
        jt = ntiles - 1;
        cur.slot = spare ? spare - 1 : NSLOT - 1;
        cur.par = (wk.rows - 1) / NSLOT & 1;
        fast_from = ntiles;
        turn = turn_end = so = so_sum = bo = bo_sum = off = rank;
    } else {
        set_addresses();
        if (wgi == NCONS - 1) named_arrive(4, 256);
        set_run(wk.lent + wgi, min(wk.nA, nrest), wk.lent + wgi + 2);
        jt = wgi < wk.lent ? wgi : wk.lent + wgi;
        cur = {2, 0};
        cur.advance(jt + (jt >= wk.nA ? 2 : 0));
        {
            const int ct = tid - 128, lane = tid & 31;
            const unsigned epoch = *reinterpret_cast<volatile unsigned*>(&sc->launch);
            const int r = lane & 7, mi = lane >> 3;
            const uint32_t src = sb + SM_W2 + (cw >> 1) * (64 * CH * 2) + r * 128 + ((((cw & 1) * 4 + mi) ^ r) * 16);
            const uint32_t dst = sb + SM_W1 + (4 * cw + mi) * 1536 + r * 16;
            const int code = row_code(wk, PREFETCH_ROWS - 1 + wgi);
            named_bar(0, NTHREADS);
            auto request = [&]() {
                if (elect_one())
                    issue_region(&tmap, sb + SM_RING + (PREFETCH_ROWS - 1 + wgi) * SLOT_BYTES + w4 * REGION_BYTES, sb + BAR_X + (cw + 8) * 8, w4, code);
                __syncwarp();
            };
#pragma unroll 1
            for (int k = 0; k < 2; k++) {
                if (wgi == k) request();
                mbar_wait_once(sb + BAR_W + (cw >> 1) * 8, 0);
            }
            uint32_t wmax[2] = {}, wsum[4] = {};
#pragma unroll 3
            for (int c = 0; c < 12; c++) {
                uint32_t u[4];
                ldsm4_t(u, src + c * 1024);
#pragma unroll
                for (int q = 0; q < 4; q++) {
                    wmax[q & 1] = bf_absmax(wmax[q & 1], u[q]);
                    wsum[q] = bf_fma(u[q], 0x3f803f80u, wsum[q]);
                    u[q] = pack_h2(__uint_as_float(u[q] * (65536 + zero)), bf_hi(u[q]));
                }
                stsm4(dst + c * 128, u[0], u[1], u[2], u[3]);
            }
            const float w1max = warp_absmax(bf_absmax(wmax[0], wmax[1]));
            if (lane == 0) sts32(s_red + RED_MAX + cw * 4, __float_as_uint(w1max));
            bool center = false;
#pragma unroll
            for (int q = 0; q < 4; q++) {
#pragma unroll
                for (int o = 1; o <= 2; o <<= 1) wsum[q] = bf_fma(__shfl_xor_sync(~0u, wsum[q], o), 0x3f803f80u, wsum[q]);
                center |= fabsf(bf_lo(wsum[q]) + bf_hi(wsum[q])) > (0.15f * CH) * w1max;
            }
            if (__builtin_expect(__any_sync(~0u, center), 0)) {
                float mean[4] = {};
#pragma unroll 1
                for (int pass = 0; pass < 2; pass++) {
                    float sum[4] = {};
#pragma unroll 1
                    for (int c = 0; c < 12; c++) {
                        uint32_t u[4];
                        ldsm4_t(u, src + c * 1024);
#pragma unroll
                        for (int q = 0; q < 4; q++) {
                            sum[q] += bf_lo(u[q]) + bf_hi(u[q]);
                            u[q] = pack_h2(bf_lo(u[q]) - mean[q], bf_hi(u[q]) - mean[q]);
                        }
                        stsm4(dst + c * 128, u[0], u[1], u[2], u[3]);
                    }
#pragma unroll
                    for (int q = 0; q < 4; q++) {
                        sum[q] += __shfl_xor_sync(~0u, sum[q], 1);
                        sum[q] += __shfl_xor_sync(~0u, sum[q], 2);
                        mean[q] = sum[q] * (1.f / CH);
                    }
                }
            }
            if (!(cw & 2)) {
#pragma unroll
                for (int c = 0; c < 12; c++) sts128(src + c * 1024, 0, 0, 0, 0);
            }
            if (ct < 32) sts32(sb + SM_ONES + ct * 4, 0x3f803f80u);
            if (ct == 0) sts32(s_red + RED_LAUNCH, epoch);
            fence_async();
            named_bar(2, CONS_THREADS);
            if (wgi == 2) request();
        }
        PROF(1);
        if (cur.par) mbar_wait_once(bar_a, 0);
        fast_from = wk.lent;
        if (!__all_sync(~0u, plain_squares(bound_exp(max_w1(lane_id()))))) {
            fast_from = ntiles;
#pragma unroll 1
            for (int q = 0; q < 6; q++) sts128(sq + SQ_HALF + q * SQ_ROW, 0, 0, 0, 0);
        }
    }
    uint32_t k1[24], k2[24], k3[24];
    uint32_t here;
    constexpr int SQC = 3 * SQ_ROW;
    auto store_at = [&](const uint32_t (&a)[6][4], uint32_t off) {
        char* ap = reinterpret_cast<char*>(out) + (off + sq);
#pragma unroll
        for (int s = 0; s < 6; s++) stg128(ap + s * 512, a[s]);
    };
    const uint32_t own_bar = 4 + wgi, next_bar = 4 + (wgi == NCONS - 1 ? 0 : wgi + 1);
    for (;;) {
        if (jt >= fast_from) {
            uint32_t hs2[12] = {}, hs3[12] = {};
            const uint32_t step = wk.dir * (NCONS * IMG_W * CH * 2);
            int second = wk.nB;
#pragma unroll 1
            for (;;) {
#pragma unroll 1
                while (turn != turn_end) {
                    uint32_t a[6][4], d0[24], d1[24], unused[24];
                    mbar_wait(bo, turn >> 1 & 1);
                    load_tile(a, a_addr + so);
                    layer_norm(a, ds.ones, [&]() { named_bar(own_bar, 256); });
                    wg_fence();
                    gemm1_chunk<0>(d0, a, ds, 0);
                    wg_commit();
                    gemm1_chunk<96>(d1, a, ds, 0);
                    wg_commit();
                    wg_wait<1>();
                    gelu_sq<false, 0, 1>(d0, unused, sq, 0);
                    gelu_sq<false, 1, 2>(d0, unused, sq, 0);
                    store_at(a, off);
                    gelu_sq<false, 2, 3>(d0, unused, sq, 0);
                    if (elect_one()) mbar_arrive(bo + (BAR_E - BAR_A));
                    wg_fence();
                    gemm1_chunk<192>(d0, a, ds, zero);
                    wg_commit();
                    named_arrive(next_bar, 256);
                    wg_wait<1>();
                    gelu_sq<false, 0, 1>(d1, unused, sq + SQC, 0);
                    gelu_sq<false, 1, 3>(d1, unused, sq + SQC, 0);
                    wg_fence();
                    gemm1_chunk<288>(d1, a, ds, zero);
                    wg_commit();
                    wg_wait<1>();
                    gelu_sq_reg(d0, hs2);
                    anchor(sq, hs2[8], hs2[9], hs2[10], hs2[11]);
                    wg_wait<0>();
                    gelu_sq_reg(d1, hs3);
                    so = so_sum - so;
                    bo = bo_sum - bo;
                    off += step;
                    turn++;
                }
                if (!second) break;
                const int j = ntiles - second + (rank + second + 2) % NCONS;
                second = 0;
                set_run(j, nrest, j + 4);
            }
            jt = nrest + rank;
            cur.slot = (bo - bar_a) >> 5;
            cur.par = turn >> 1 & 1;
#pragma unroll
            for (int k = 0; k < 3; k++) {
                sts128(sq + SQ_HALF + k * SQ_ROW, hs2[4 * k], hs2[4 * k + 1], hs2[4 * k + 2], hs2[4 * k + 3]);
                sts128(sq + SQ_HALF + SQC + k * SQ_ROW, hs3[4 * k], hs3[4 * k + 1], hs3[4 * k + 2], hs3[4 * k + 3]);
            }
        }
        const bool last = jt >= nrest;
        here = tile_offset(wk.tile(jt));
        if (last) {
            const uint32_t next = ldsi(sb + SM_TILES + rank * 4);
            if (elect_one()) {
                prefetch_l2(reinterpret_cast<const char*>(x) + here + w4 * WARP_BYTES, WARP_BYTES);
                if (rank == ORDER_P - 1) prefetch_l2(reinterpret_cast<const char*>(out) + next + w4 * WARP_BYTES, WARP_BYTES);
            }
        }
        uint32_t a[6][4], d0[24], d1[24], d3[24], k0[24];
        mbar_wait_once(bar_a + cur.slot * 32, cur.par);
        load_tile(a, a_addr + cur.slot * SLOT_BYTES);
        layer_norm(a, ds.ones, [&]() { if (jt >= wk.lent && wgi >= 0) named_bar(own_bar, 256); });
        if (!last) {
            store_at(a, here + w4 * WARP_BYTES - sq_warp);
            __syncwarp();
            if (elect_one()) mbar_arrive(bar_e + cur.slot * 32);
            if (jt < wk.lent) {
                jt += LENT;
                cur.advance(LENT);
                continue;
            }
        }
        wg_fence();
        gemm1_chunk<0>(d0, a, ds, 0);
        wg_commit();
        gemm1_chunk<96>(d1, a, ds, 0);
        wg_commit();
        const uint32_t scale2 = square_scale(lane_id());
        wg_wait<1>();
        gelu_sq<true>(d0, k0, sq, scale2);
        if (last) {
#pragma unroll
            for (int q = 0; q < 6; q++)
                sts128(sb + SM_RING + cur.slot * SLOT_BYTES + w4 * REGION_BYTES - sq_warp + sq + q * 512, k0[4 * q], k0[4 * q + 1], k0[4 * q + 2], k0[4 * q + 3]);
        }
        wg_fence();
        gemm1_chunk<192>(d0, a, ds, zero);
        wg_commit();
        if (jt + 2 < ntiles) named_arrive(next_bar, 256);
        wg_wait<1>();
        gelu_sq<true>(d1, k1, sq + SQC, scale2);
        wg_fence();
        gemm1_chunk<288>(d3, a, ds, 0);
        wg_commit();
        wg_wait<1>();
        gelu_sq<true>(d0, k2, sq + sq_upper, scale2);
        wg_wait<0>();
        gelu_sq<true>(d3, k3, sq + sq_upper + SQC, scale2);
        if (last) break;
        cur.advance(NCONS + ((jt < wk.nA && jt + NCONS >= wk.nA) ? 2 : 0));
        jt += NCONS;
    }
    const uint32_t lane = lane_id();
    uint32_t next_off = opaque_uniform(ldsi(sb + SM_TILES + rank * 4));
    const uint32_t s_fac = sb + SM_RING + spare * SLOT_BYTES + SQ_HALF;
    uint32_t inv_rho2;
    {
        if (rank == 0) {
            const int g = lane >> 2, t = lane & 3, i0 = w4 * 32 + lane;
            const bool leader = i0 == 0;
            const uint32_t pick = (g & 1) == (t & 1) ? (g & 2 ? 0x3c000000u : 0x00003c00u) : 0;
            const int be = bound_exp(max_w1(lane));
            const float to_fixed = pow2i(sum_exp(be) - 2 * square_exp(be));
            const uint32_t two_rows = sb + (w4 * 3 + (lane >> 3 & 1)) * SQ_ROW + ((lane >> 4) * 8 + (lane & 7)) * 16;
            const uint32_t third_row = sb + (w4 * 3 + 2) * SQ_ROW + lane * 16;
            unsigned short gam_raw[3];
            float rmax[3], f[3][4] = {};
            float2 bpair = make_float2(0.f, 0.f);
#pragma unroll 1
            for (int i = 0; i < 4; i++) {
                if (i == 1 && leader) {
                    spin_until(&sc->prep, (ldsi(s_red + RED_LAUNCH) + 1) * (W2_GROUPS * 2));
                    asm volatile("fence.proxy.async.global;" ::: "memory");
                    mbar_expect_tx(sb + BAR_W, 6 * SQ_HALF);
                }
                __syncwarp();
                named_bar(2, 128);
                if (i && leader) {
                    fence_async();
                    bulk_load(sb + SM_W2 + (i - 1) * 2 * SQ_HALF, reinterpret_cast<const char*>(sc->w2h) + (i - 1) * 2 * SQ_HALF, 2 * SQ_HALF, sb + BAR_W);
                }
                if (i == 1) {
#pragma unroll
                    for (int m = 0; m < 3; m++) {
                        asm volatile("ld.global.nc.u16 %0, [%1];" : "=h"(gam_raw[m]) : "l"(gamma + i0 + 128 * m) : "memory");
                        asm volatile("ld.global.cg.f32 %0, [%1];" : "=f"(rmax[m]) : "l"(&sc->w2max[i0 + 128 * m]) : "memory");
                    }
                    if (i0 < 96)
                        asm volatile("ld.global.cg.v2.f32 {%0, %1}, [%2];" : "=f"(bpair.x), "=f"(bpair.y)
                                     : "l"(&sc->bias[32 * (i0 % 24 >> 3) + 8 * (i0 / 24) + (i0 % 24 & 6)]) : "memory");
                }
                __syncwarp();
                const uint32_t from = i < NCONS ? SM_SQ + i * 2 * SQ_HALF : w4 < 2 ? SM_RING + spare * SLOT_BYTES : SM_RING + spare2 * SLOT_BYTES - SQ_HALF;
                if (i) named_bar(12 + i, 256);
#pragma unroll
                for (int r = 0; r < 12; r++) {
                    uint32_t u[4];
                    ldsm4_t(u, from + (r % 3 == 2 ? third_row + r / 3 * 512 : two_rows + (r / 3 * 2 + r % 3) * 256));
                    asm volatile("mma.sync.aligned.m16n8k16.row.col.f32.f16.f16.f32 {%0, %1, %2, %3}, {%4, %5, %6, %7}, {%8, %8}, {%0, %1, %2, %3};"
                                 : "+f"(f[r % 3][0]), "+f"(f[r % 3][1]), "+f"(f[r % 3][2]), "+f"(f[r % 3][3])
                                 : "r"(u[0]), "r"(u[1]), "r"(u[2]), "r"(u[3]), "r"(pick));
                }
            }
            unsigned long long* dst = sc->sum(96 * w4 + 8 * (g >> 1) + 2 * (t & 1) + (g & 1));
#pragma unroll
            for (int r = 0; r < 3; r++) {
                const float tot = r < 2 ? (t < 2 ? f[0][r & 1] + f[1][r & 1] : f[0][r + 2 & 3] + f[1][r + 2 & 3]) : (t < 2 ? f[2][0] + f[2][2] : f[2][1] + f[2][3]);
                atomicAdd(dst + (r < 2 ? (t >> 1) * 8 + r : 16 + (t >> 1)) * 32, __float2ull_rn(fminf(tot * to_fixed, 0x1p47f)) << 8 | 1);
            }
            PROF(2);
            float base[3], slope[3], reach[3];
            const float w1max = max_w1(lane);
            const float gbound = fmaxf(2.f * KZ * 9.7979590f * 192.f * w1max, 1.f) * 19.5959180f * INV_2KZ;
            const unsigned fixed = __reduce_max_sync(~0u, __float_as_uint(fmaf(gbound, fmaxf(fmaxf(rmax[0], rmax[1]), rmax[2]), fmaxf(fabsf(bpair.x), fabsf(bpair.y)))));
            if (lane == 0) sts32(s_red + 96 + w4 * 4, fixed);
#pragma unroll
            for (int m = 0; m < 3; m++) {
                base[m] = rmax[m] > 0.f ? pow2i(-row_exp(rmax[m])) * (INV_2KZ * CUT_GAIN) : 0.f;
                slope[m] = base[m] * bf_lo(gam_raw[m]);
                reach[m] = fabsf(bf_lo(gam_raw[m])) * rmax[m] * gbound;
            }
            const float to_square = pow2i(-sum_exp(bound_exp(w1max))) * (INV_2KZ * INV_2KZ / 256);
#pragma unroll
            for (int m = 0; m < 3; m++) anchor(sq, __float_as_uint(base[m]), __float_as_uint(slope[m]), __float_as_uint(reach[m]), __float_as_uint(to_square));
            const unsigned epoch = ldsi(s_red + RED_LAUNCH);
            const uint32_t own_sum = (i0 >> 2) * 256 + (i0 & 3) * 8, own_fac = s_fac + i0 * 2;
            auto peek = [&](const void* p) {
                unsigned long long v;
                asm volatile("ld.relaxed.gpu.global.u64 %0, [%1];" : "=l"(v) : "l"(p) : "memory");
                return v;
            };
            const char* mine = reinterpret_cast<const char*>(sc->sums) + own_sum;
            unsigned n = 0;
            while (((unsigned)peek(sc->sum((blockIdx.x * 4 + w4) % (EX / 4) * 4)) & 255u) != gridDim.x)
                if (++n > SPIN_LIMIT) __trap();
            unsigned long long sum[3];
            for (;;) {
                bool all = true;
#pragma unroll
                for (int m = 0; m < 3; m++) {
                    sum[m] = peek(mine + m * (32 * 256));
                    all &= ((unsigned)sum[m] & 255u) == gridDim.x;
                }
                if (__all_sync(~0u, all)) break;
                if (++n > SPIN_LIMIT) __trap();
            }
            PROF(3);
            float gx[3];
#pragma unroll
            for (int m = 0; m < 3; m++) asm("sqrt.approx.ftz.f32 %0, %1;" : "=f"(gx[m]) : "f"(fmaf(__ull2float_rn(sum[m]), to_square, 1e-6f)));
            float tot = gx[0] + gx[1] + gx[2];
#pragma unroll
            for (int o = 16; o >= 1; o >>= 1) tot += __shfl_xor_sync(~0u, tot, o);
            const unsigned vwarp = __reduce_max_sync(~0u, __float_as_uint(fmaxf(fmaxf(reach[0] * gx[0], reach[1] * gx[1]), reach[2] * gx[2])));
            if (lane == 0) { sts32(s_red + 64 + w4 * 4, __float_as_uint(tot)); sts32(s_red + 80 + w4 * 4, vwarp); }
            named_bar(2, 128);
            uint32_t u[4], v[4], w[4];
            lds128(u[0], u[1], u[2], u[3], s_red + 64);
            lds128(v[0], v[1], v[2], v[3], s_red + 80);
            lds128(w[0], w[1], w[2], w[3], s_red + 96);
            tot = (__uint_as_float(u[0]) + __uint_as_float(u[1])) + (__uint_as_float(u[2]) + __uint_as_float(u[3]));
            const float vmax = __uint_as_float(max(max(v[0], v[1]), max(v[2], v[3]))), fmax2 = __uint_as_float(max(max(w[0], w[1]), max(w[2], w[3])));
            float inv_mean;
            asm("rcp.approx.ftz.f32 %0, %1;" : "=f"(inv_mean) : "f"(fmaf(tot, 1.f / EX, 1e-6f)));
            const int rho_e = 14 - ilog2f(fmaf(vmax, inv_mean, 2.f * fmax2));
            const float rho = pow2i(rho_e), inv_rho = pow2i(-rho_e);
            inv_rho2 = pack_bf2(inv_rho, inv_rho);
#pragma unroll
            for (int m = 0; m < 3; m++) {
                const float f = fmaf(slope[m] * gx[m], inv_mean, base[m]) * rho;
                asm volatile("st.shared.u16 [%0], %1;" ::"r"(own_fac + 256 * m), "h"((unsigned short)pack_h2(f, 0.f)) : "memory");
            }
            if (i0 < 96) sts32(sb + SM_BIASH + i0 * 4, pack_h2(bpair.x * rho, bpair.y * rho));
            if (i0 == 96) sts32(s_red + RED_INV_RHO, inv_rho2);
            named_arrive(12, NTHREADS);
            if (blockIdx.x == 0 && leader) { sc->launch = epoch + 1; sc->job = 0; }
            if (wk.lent) spin_until(&sc->lent_out, (epoch + 1) * 32 * LENT * sp.lenders);
        } else {
            named_arrive(12 + rank, 256);
            if (rank == NCONS && (unsigned)(ldsi(s_red + RED_JOB) - W2_GROUPS / 2) < 8 * LENT * sp.lenders) signal(&sc->lent_out);
            const int rw = rank * 4 - 4 + w4;
            const uint32_t row = sb + SM_W2 + rw * 512 + lane * 16;
            uint32_t u[W2_EARLY][4], f2[4];
            mbar_wait_once(sb + BAR_W, 1);
#pragma unroll
            for (int nb = 0; nb < W2_EARLY; nb++) {
                lds128(u[nb][0], u[nb][1], u[nb][2], u[nb][3], row + nb * 6144);
            }
            named_bar(12, NTHREADS);
            PROF(3);
            lds128(f2[0], f2[1], f2[2], f2[3], s_fac + rw * 64 + (lane >> 3) * 16);
            lds32(inv_rho2, s_red + RED_INV_RHO);
#pragma unroll
            for (int nb = 0; nb < 12; nb++) {
                uint32_t v[4];
                if (nb < W2_EARLY) { v[0] = u[nb % W2_EARLY][0]; v[1] = u[nb % W2_EARLY][1]; v[2] = u[nb % W2_EARLY][2]; v[3] = u[nb % W2_EARLY][3]; }
                else lds128(v[0], v[1], v[2], v[3], row + nb * 6144);
                sts128(row + nb * 6144, h_cut8(h_mul(v[0], f2[0])), h_cut8(h_mul(v[1], f2[1])), h_cut8(h_mul(v[2], f2[2])), h_cut8(h_mul(v[3], f2[3])));
            }
            fence_async();
            named_arrive(8, NTHREADS);
        }
    }
    uint32_t a[6][4], acc[24], rpar = 0, tile_off = here;
    const uint32_t bias_addr = sb + SM_BIASH + (lane & 3) * 96, lane16 = lane * 16, lane_off = ((lane >> 2) * CH + 8 * (lane & 3)) * 2;
    const uint32_t stage = sb + SM_RING + (spare + rank) % NSLOT * SLOT_BYTES + w4 * WARP_BYTES, bar_r = sb + BAR_R + warp_id * 8;
    auto load_bias = [&]() {
#pragma unroll
        for (int q = 0; q < 6; q++) lds128(acc[4 * q], acc[4 * q + 1], acc[4 * q + 2], acc[4 * q + 3], bias_addr + q * 16);
    };
    auto load_frags = [&]() {
#pragma unroll
        for (int s = 0; s < 6; s++) ldg128(a[s], reinterpret_cast<const char*>(out) + next_off + w4 * WARP_BYTES + lane16 + s * 512);
    };
    auto stage_x = [&]() {
        if (elect_one()) {
            mbar_expect_tx(bar_r, WARP_BYTES);
            bulk_load_stream(stage, reinterpret_cast<const char*>(x) + tile_off + w4 * WARP_BYTES, WARP_BYTES, bar_r);
        }
    };
    {
        named_bar(8 + rank, rank ? 256 : NTHREADS);
        if (rank == 0) PROF(4);
        load_bias();
        pin(k1); pin(k2); pin(k3);
        wg_fence();
        gemm2_chunk<288>(acc, k3, ds);
        wg_commit();
        gemm2_chunk<96>(acc, k1, ds);
        wg_commit();
        gemm2_chunk<192>(acc, k2, ds);
        wg_commit();
        stage_x();
        wg_wait<2>();
        uint32_t k0[24];
#pragma unroll
        for (int q = 0; q < 6; q++)
            lds128(k0[4 * q], k0[4 * q + 1], k0[4 * q + 2], k0[4 * q + 3], sb + SM_RING + cur.slot * SLOT_BYTES + w4 * REGION_BYTES + lane16 + q * 512);
        pin(k0);
        wg_fence();
        gemm2_chunk<0>(acc, k0, ds);
        wg_commit();
        if (rank < NCONS) named_arrive(9 + rank, 256);
        wg_wait<2>();
        load_frags();
        if (lane16 == 0) mbar_arrive(sb + BAR_PIN);
        mbar_wait(bar_r, rpar);
        wg_wait<0>();
    }
    auto lent = [&](uint32_t entry) { return &sc->lent[((wk.index * LENT + (entry & 3) - 1) * 4 + w4) * (24 * 32)]; };
    for (jt = rank - 4; jt < nrest; jt += 4) {
        if (jt >= zero) {
        tile_off = next_off;
        lds32(next_off, sb + SM_TILES + (jt + 4) * 4);
        if (tile_off & 3) {
            const uint4* src = lent(tile_off) + lane;
            tile_off &= ~3u;
            next_off = __shfl_sync(~0u, next_off, 0);
            stage_x();
            if (elect_one()) prefetch_l2(reinterpret_cast<const char*>(out) + next_off + w4 * WARP_BYTES, WARP_BYTES);
            load_bias();
#pragma unroll 1
            for (int half = 0; half < 2; half++, src += 12 * 32) {
                uint32_t gl[48];
#pragma unroll
                for (int s = 0; s < 12; s++) ldg128(reinterpret_cast<uint32_t (&)[4]>(gl[4 * s]), src + s * 32);
                if (!half) {
                    named_bar(4 + rank, 256);
                    named_arrive(4 + ((rank + 1) & 3), 256);
                }
                pin(gl);
                wg_fence();
#pragma unroll
                for (int s = 0; s < 12; s++) wgmma(acc, gl[4 * s], gl[4 * s + 1], gl[4 * s + 2], gl[4 * s + 3], ds.w2[12 * half + s], 1);
                wg_commit();
                wg_wait<0>();
            }
            load_frags();
            mbar_wait(bar_r, rpar);
        } else {
            uint32_t d0[12], d1[12], g0[12], g1[12];
            next_off = __shfl_sync(~0u, next_off, 0);
            const bool more = jt + 4 < nrest && !(next_off & 3);
            load_bias();
            wg_fence();
            gemm1_chunk<0>(d0, a, ds, 0);
            wg_commit();
            if (jt) named_bar(4 + rank, 256);
            gemm1_chunk<48>(d1, a, ds, 0);
            wg_commit();
            wg_wait<1>();
#define CNX_STEP(C, D, G)                                                   \
    gelu_to(G, D);                                                          \
    wg_fence();                                                             \
    if (C < 6) gemm1_chunk<48 * (C < 6 ? C + 2 : 0)>(D, a, ds, zero);      \
    gemm2_chunk<48 * C>(acc, G, ds);                                       \
    wg_commit();                                                            \
    if (C == 1 && jt + 1 < nrest) named_arrive(4 + ((rank + 1) & 3), 256); \
    wg_wait<(C < 7 ? 1 : 0)>();
            CNX_STEP(0, d0, g0)
            stage_x();
            if (elect_one()) {
                if (more) prefetch_l2(reinterpret_cast<const char*>(out) + next_off + w4 * WARP_BYTES, WARP_BYTES);
                else if (next_off & 3) prefetch_l2(lent(next_off), 24 * 32 * 16);
            }
            CNX_STEP(1, d1, g1)
            CNX_STEP(2, d0, g0)
            CNX_STEP(3, d1, g1)
            CNX_STEP(4, d0, g0)
            CNX_STEP(5, d1, g1)
            CNX_STEP(6, d0, g0)
#pragma unroll
            for (int s = 0; s < 6; s++) ldg128_if(more, a[s], reinterpret_cast<const char*>(out) + next_off + w4 * WARP_BYTES + lane16 + s * 512);
            if (lane16 == 0) mbar_arrive(sb + BAR_PIN);
            mbar_wait(bar_r, rpar);
            CNX_STEP(7, d1, g1)
#undef CNX_STEP
        }
        }
        {
            pin(acc);
            rpar ^= 1;
            uint4* op = reinterpret_cast<uint4*>(reinterpret_cast<char*>(out) + tile_off + w4 * WARP_BYTES + lane_off);
#pragma unroll
            for (int h = 0; h < 2; h++)
#pragma unroll
                for (int m = 0; m < 3; m++) {
                    uint32_t xin[4], o[4];
                    lds128(xin[0], xin[1], xin[2], xin[3], stage + lane_off + h * 1536 + m * 64);
#pragma unroll
                    for (int q = 0; q < 4; q++) {
                        const uint32_t v = acc[2 * (4 * m + q) + h];
                        o[q] = bf_fma(pack_bf2(h_lo(v), h_hi(v)), inv_rho2, xin[q]);
                    }
                    __stcs(op + h * 96 + m * 4, make_uint4(o[0], o[1], o[2], o[3]));
                }
            __syncwarp();
        }
    }
    PROF(5);
}

}

typedef CUresult (*EncodeTiledFn)(CUtensorMap*, CUtensorMapDataType, cuuint32_t, void*, const cuuint64_t*, const cuuint64_t*,
                                  const cuuint32_t*, const cuuint32_t*, CUtensorMapInterleave, CUtensorMapSwizzle,
                                  CUtensorMapL2promotion, CUtensorMapFloatOOBfill);

extern "C" void kernel_launch(void* const* d_in, const int* in_sizes, int n_in, void* d_out, int out_size) {
    using namespace cnx;
    static EncodeTiledFn encode = nullptr;
    static int num_sms = 0;
    static Scratch* scratch = nullptr;
    if (!encode) {
        void* fn = nullptr;
        cudaDriverEntryPointQueryResult qr;
        cudaGetDriverEntryPoint("cuTensorMapEncodeTiled", &fn, cudaEnableDefault, &qr);
        encode = (EncodeTiledFn)fn;
        cudaGetSymbolAddress((void**)&scratch, g_scratch);
        int dev = 0;
        cudaGetDevice(&dev);
        cudaDeviceGetAttribute(&num_sms, cudaDevAttrMultiProcessorCount, dev);
        if (num_sms > MAX_CTAS) num_sms = MAX_CTAS;
        cudaFuncSetAttribute(block_kernel, cudaFuncAttributeMaxDynamicSharedMemorySize, SM_TOTAL);
    }
    CUtensorMap tm;
    cuuint64_t dims[3] = {(cuuint64_t)CH, (cuuint64_t)IMG_W, (cuuint64_t)IMG_H};
    cuuint64_t strides[2] = {(cuuint64_t)CH * 2, (cuuint64_t)CH * 2 * IMG_W};
    cuuint32_t box[3] = {(cuuint32_t)CH, (cuuint32_t)REGION_PX, 1};
    cuuint32_t estr[3] = {1, 1, 1};
    encode(&tm, CU_TENSOR_MAP_DATA_TYPE_BFLOAT16, 3, d_in[0], dims, strides, box, estr, CU_TENSOR_MAP_INTERLEAVE_NONE,
           CU_TENSOR_MAP_SWIZZLE_NONE, CU_TENSOR_MAP_L2_PROMOTION_L2_128B, CU_TENSOR_MAP_FLOAT_OOB_FILL_NONE);
    Params pm = {};
    Descs& ds = pm.ds;
    for (int c = 0; c < 8; c++)
        for (int k = 0; k < 6; k++) ds.w1[c][k] = make_desc(SB + SM_W1 + c * 6 * 1536 + k * 256, 128, 1536);
    for (int k = 0; k < 24; k++) ds.w2[k] = make_desc(SB + SM_W2 + k * 256, 128, 6144);
    ds.ones = make_desc(SB + SM_ONES, 0, 0);
    CUtensorMap tw;
    cuuint64_t wdims[2] = {(cuuint64_t)EX, (cuuint64_t)CH};
    cuuint64_t wstrides[1] = {(cuuint64_t)EX * 2};
    cuuint32_t wbox[2] = {64, (cuuint32_t)CH};
    encode(&tw, CU_TENSOR_MAP_DATA_TYPE_BFLOAT16, 2, d_in[2], wdims, wstrides, wbox, estr, CU_TENSOR_MAP_INTERLEAVE_NONE,
           CU_TENSOR_MAP_SWIZZLE_128B, CU_TENSOR_MAP_L2_PROMOTION_L2_128B, CU_TENSOR_MAP_FLOAT_OOB_FILL_NONE);
    Split& sp = pm.sp;
    sp = {NTILES / num_sms, NTILES % num_sms, 1, 1 << 16, 0, {}};
    if (sp.per_cta + 9 > MAX_ROWS) return;
    if (sp.extra && sp.extra * (8 * LENT + 1) + W2_GROUPS / 2 <= num_sms && sp.per_cta >= 5 * LENT + 8) {
        sp.period = num_sms / sp.extra;
        sp.inv_period = 65535 / sp.period + 1;
        sp.lenders = sp.extra;
        for (int l = 0; l < sp.extra; l++) {
            const Work w = get_work((l + 1) * sp.period - sp.period / 2 - 1, sp);
            for (int e = 0; e < LENT; e++) sp.lent_off[l * LENT + e] = tile_offset(w.tile(e));
            if (w.nA < 2 * LENT) sp.lenders = 0;
        }
    }
    pm.x = (const __nv_bfloat16*)d_in[0];
    pm.dw = (const __nv_bfloat16*)d_in[1];
    pm.w2 = (const __nv_bfloat16*)d_in[3];
    pm.gamma = (const __nv_bfloat16*)d_in[4];
    pm.beta = (const __nv_bfloat16*)d_in[5];
    pm.out = (__nv_bfloat16*)d_out;
    pm.sc = scratch;
    block_kernel<<<num_sms, NTHREADS, SM_TOTAL>>>(tm, tw, pm);
}
```

```cpp
#include <cuda_runtime.h>
#include <cuda_bf16.h>
#include <cuda_fp16.h>
#include <cuda.h>
#include <stdint.h>

namespace cnx {

constexpr int IMG_H = 512, IMG_W = 512, CH = 96, EX = 384;
constexpr int TILE_W = 64;
constexpr int NTILES = (IMG_W / TILE_W) * IMG_H;
constexpr int NSLOT = 6;
constexpr int REGION_PX = 18;
constexpr int REGION_BYTES = REGION_PX * CH * 2;
constexpr int SLOT_BYTES = 4 * REGION_BYTES;
constexpr int A_LBO = 144, A_SBO = 12 * A_LBO;
constexpr int PREFETCH_ROWS = 3;
constexpr int NCONS = 3;
constexpr int CONS_THREADS = 128 * NCONS;
constexpr int NTHREADS = 128 + CONS_THREADS;
constexpr int MAX_ROWS = 52;
constexpr int TILE_BYTES = TILE_W * CH * 2, WARP_BYTES = TILE_BYTES / 4;
constexpr int ORDER_P = 3;
constexpr int W2_EARLY = 9;
static_assert(MAX_ROWS <= 128, "one table entry per producer thread");
static_assert(2 * A_SBO == REGION_BYTES && REGION_BYTES % 128 == 0, "region layout");

constexpr uint32_t SB = 1024;
constexpr int SM_W1 = 0;
constexpr int SM_W2 = SM_W1 + CH * EX * 2;
constexpr int SM_RING = SM_W2 + CH * EX * 2;
constexpr int SM_BIASH = SM_RING + NSLOT * SLOT_BYTES;
constexpr int SM_RED = SM_BIASH + 384;
constexpr int RED_MAX = 0, RED_LAUNCH = 48, RED_INV_RHO = 52, RED_JOB = 56;
constexpr int SM_TILES = SM_RED + 256;
constexpr int SM_ONES = SM_TILES + MAX_ROWS * 4;
constexpr int SM_BAR = SM_ONES + 128;
constexpr int BAR_X = SM_BAR;
constexpr int BAR_A = BAR_X + NSLOT * 4 * 8;
constexpr int BAR_E = BAR_A + NSLOT * 4 * 8;
constexpr int BAR_PIN = BAR_E + NSLOT * 4 * 8;
constexpr int BAR_W = BAR_PIN + 8;
constexpr int BAR_F = BAR_W + 6 * 8;
constexpr int BAR_R = BAR_F + 8;
constexpr int SM_TOTAL = BAR_R + 16 * 8;
constexpr int SM_FILTER = SM_RING + (NSLOT - 1) * SLOT_BYTES + 9 * 128;
constexpr int SM_SQ = SM_W2;
constexpr int SQ_ROW = 128 * 16, SQ_HALF = 6 * SQ_ROW;
static_assert(SM_ONES % 16 == 0 && SM_TOTAL <= 232448, "shared memory budget");

constexpr float KZ = 0.3292034911525734f;
constexpr uint32_t GELU_C2 = 0x40d940d9u;
constexpr float INV_2KZ = 0.5f / KZ;
constexpr uint32_t CONV_SCALE2 = 0x2f802f80u;
constexpr unsigned SPIN_LIMIT = 1u << 19;

constexpr int MAX_CTAS = 170;
constexpr int W2_GROUPS = EX / 8;
constexpr int LENT = 3, MAX_LENDERS = MAX_CTAS / (8 * LENT + 1);
struct Scratch {
    uint32_t w2h[EX * CH / 2];
    float w2max[EX];
    float bias[CH + 32];
    unsigned long long sums[EX / 4][32];
    __device__ __forceinline__ unsigned long long* sum(int e) { return &sums[e >> 2][e & 3]; }
    uint4 lent[MAX_LENDERS * LENT * 8 * 4 * 3 * 32];
    unsigned launch, pad0[31], early, pad1[31], prep, pad2[31], lent_out, pad3[31];
    unsigned job;
};
__device__ __align__(128) Scratch g_scratch;

#define PROF(k)

__device__ __forceinline__ uint32_t smem_u32(const void* p) { return (uint32_t)__cvta_generic_to_shared(p); }
__device__ __forceinline__ void mbar_init(uint32_t bar, uint32_t cnt) {
    asm volatile("mbarrier.init.shared::cta.b64 [%0], %1;" ::"r"(bar), "r"(cnt) : "memory");
}
__device__ __forceinline__ void mbar_arrive(uint32_t bar) {
    asm volatile("mbarrier.arrive.shared::cta.b64 _, [%0];" ::"r"(bar) : "memory");
}
__device__ __forceinline__ void mbar_expect_tx(uint32_t bar, uint32_t bytes) {
    asm volatile("mbarrier.arrive.expect_tx.shared::cta.b64 _, [%0], %1;" ::"r"(bar), "r"(bytes) : "memory");
}
__device__ __forceinline__ bool mbar_try(uint32_t bar, uint32_t par) {
    uint32_t ok;
    asm volatile("{\n.reg .pred p;\nmbarrier.try_wait.parity.shared::cta.b64 p, [%1], %2;\nselp.u32 %0, 1, 0, p;\n}\n"
                 : "=r"(ok) : "r"(bar), "r"(par) : "memory");
    return ok != 0;
}
__device__ __forceinline__ void mbar_wait(uint32_t bar, uint32_t par) {
    unsigned n = 0;
    while (!mbar_try(bar, par)) {
        if (++n > SPIN_LIMIT) __trap();
    }
}
__device__ __forceinline__ void mbar_wait_once(uint32_t bar, uint32_t par) {
    unsigned n = 0;
    bool ok;
#pragma unroll 1
    do {
        ok = mbar_try(bar, par);
        if (++n > SPIN_LIMIT) __trap();
    } while (!ok);
}
__device__ __forceinline__ bool elect_one() {
    uint32_t ok;
    asm volatile("{\n.reg .pred p;\nelect.sync _|p, 0xffffffff;\nselp.u32 %0, 1, 0, p;\n}\n" : "=r"(ok));
    return ok != 0;
}
__device__ __forceinline__ uint32_t opaque(uint32_t v) { return __shfl_sync(~0u, v, threadIdx.x & 31); }
__device__ __forceinline__ uint32_t lane_id() { uint32_t v; asm volatile("mov.u32 %0, %%laneid;" : "=r"(v)); return v; }
__device__ __forceinline__ uint32_t opaque_uniform(uint32_t v) { return __shfl_sync(~0u, v, 0); }
__device__ __forceinline__ void named_bar(int id, int n) { asm volatile("bar.sync %0, %1;" ::"r"(id), "r"(n) : "memory"); }
__device__ __forceinline__ void named_arrive(int id, int n) { asm volatile("bar.arrive %0, %1;" ::"r"(id), "r"(n) : "memory"); }
__device__ __forceinline__ void fence_async() { asm volatile("fence.proxy.async.shared::cta;" ::: "memory"); }
constexpr uint64_t EVICT_FIRST = 0x12F0000000000000ull;
__device__ __forceinline__ void tma_row(uint32_t dst, const CUtensorMap* tm, uint32_t bar, int x, int y) {
    asm volatile("cp.async.bulk.tensor.3d.shared::cluster.global.mbarrier::complete_tx::bytes.L2::cache_hint [%0], [%1, {%3, %4, %5}], [%2], %6;"
                 ::"r"(dst), "l"(tm), "r"(bar), "r"(0), "r"(x), "r"(y), "l"(EVICT_FIRST) : "memory");
}
__device__ __forceinline__ void bulk_load_stream(uint32_t dst, const void* src, uint32_t bytes, uint32_t bar) {
    asm volatile("cp.async.bulk.shared::cluster.global.mbarrier::complete_tx::bytes.L2::cache_hint [%0], [%1], %2, [%3], %4;"
                 ::"r"(dst), "l"(src), "r"(bytes), "r"(bar), "l"(EVICT_FIRST) : "memory");
}
__device__ __forceinline__ void prefetch_l2(const void* src, uint32_t bytes) {
    asm volatile("cp.async.bulk.prefetch.L2.global [%0], %1;" ::"l"(src), "r"(bytes) : "memory");
}
__device__ __forceinline__ void tma_2d(uint32_t dst, const CUtensorMap* tm, uint32_t bar, int x, int y) {
    asm volatile("cp.async.bulk.tensor.2d.shared::cluster.global.mbarrier::complete_tx::bytes [%0], [%1, {%3, %4}], [%2];"
                 ::"r"(dst), "l"(tm), "r"(bar), "r"(x), "r"(y) : "memory");
}
__device__ __forceinline__ void bulk_load(uint32_t dst, const void* src, uint32_t bytes, uint32_t bar) {
    asm volatile("cp.async.bulk.shared::cluster.global.mbarrier::complete_tx::bytes [%0], [%1], %2, [%3];"
                 ::"r"(dst), "l"(src), "r"(bytes), "r"(bar) : "memory");
}
__device__ __forceinline__ void wg_fence() { asm volatile("wgmma.fence.sync.aligned;" ::: "memory"); }
__device__ __forceinline__ void wg_commit() { asm volatile("wgmma.commit_group.sync.aligned;" ::: "memory"); }
template <int N> __device__ __forceinline__ void wg_wait() { asm volatile("wgmma.wait_group.sync.aligned %0;" ::"n"(N) : "memory"); }
template <int N> __device__ __forceinline__ void pin(uint32_t (&d)[N]) {
#pragma unroll
    for (int q = 0; q < N; q++) asm volatile("" : "+r"(d[q])::"memory");
}
__device__ __forceinline__ void stg128(void* p, const uint32_t (&v)[4]) {
    asm volatile("st.global.v4.u32 [%0], {%1, %2, %3, %4};" ::"l"(p), "r"(v[0]), "r"(v[1]), "r"(v[2]), "r"(v[3]) : "memory");
}
__device__ __forceinline__ void ldg128(uint32_t (&v)[4], const void* p) {
    asm volatile("ld.global.L1::no_allocate.v4.u32 {%0, %1, %2, %3}, [%4];" : "=r"(v[0]), "=r"(v[1]), "=r"(v[2]), "=r"(v[3]) : "l"(p) : "memory");
}
__device__ __forceinline__ void ldg128_if(bool on, uint32_t (&v)[4], const void* p) {
    asm volatile("{\n.reg .pred p;\nsetp.ne.b32 p, %5, 0;\n@p ld.global.L1::no_allocate.v4.u32 {%0, %1, %2, %3}, [%4];\n}\n"
                 : "+r"(v[0]), "+r"(v[1]), "+r"(v[2]), "+r"(v[3]) : "l"(p), "r"((int)on) : "memory");
}
__host__ __device__ constexpr uint64_t make_desc(uint32_t addr, uint32_t lbo, uint32_t sbo) {
    return (uint64_t)((addr & 0x3FFFF) >> 4) | ((uint64_t)(lbo >> 4) << 16) | ((uint64_t)(sbo >> 4) << 32);
}
__device__ __forceinline__ void wgmma(uint32_t (&d)[12], uint32_t a0, uint32_t a1, uint32_t a2, uint32_t a3, uint64_t db, int acc) {
    asm volatile("{\n.reg .pred p;\nsetp.ne.b32 p, %17, 0;\n"
                 "wgmma.mma_async.sync.aligned.m64n48k16.f16.f16.f16 "
                 "{%0, %1, %2, %3, %4, %5, %6, %7, %8, %9, %10, %11}, "
                 "{%12, %13, %14, %15}, %16, p, 1, 1, 0;\n}\n"
                 : "+r"(d[0]), "+r"(d[1]), "+r"(d[2]), "+r"(d[3]), "+r"(d[4]), "+r"(d[5]), "+r"(d[6]), "+r"(d[7]), "+r"(d[8]), "+r"(d[9]), "+r"(d[10]), "+r"(d[11])
                 : "r"(a0), "r"(a1), "r"(a2), "r"(a3), "l"(db), "r"(acc));
}
__device__ __forceinline__ void wgmma(uint32_t (&d)[24], uint32_t a0, uint32_t a1, uint32_t a2, uint32_t a3, uint64_t db, int acc) {
    asm volatile("{\n.reg .pred p;\nsetp.ne.b32 p, %29, 0;\n"
                 "wgmma.mma_async.sync.aligned.m64n96k16.f16.f16.f16 "
                 "{%0, %1, %2, %3, %4, %5, %6, %7, %8, %9, %10, %11, %12, %13, %14, %15, %16, %17, %18, %19, %20, %21, %22, %23}, "
                 "{%24, %25, %26, %27}, %28, p, 1, 1, 0;\n}\n"
                 : "+r"(d[0]), "+r"(d[1]), "+r"(d[2]), "+r"(d[3]), "+r"(d[4]), "+r"(d[5]), "+r"(d[6]), "+r"(d[7]), "+r"(d[8]), "+r"(d[9]), "+r"(d[10]), "+r"(d[11]), "+r"(d[12]), "+r"(d[13]), "+r"(d[14]), "+r"(d[15]), "+r"(d[16]), "+r"(d[17]), "+r"(d[18]), "+r"(d[19]), "+r"(d[20]), "+r"(d[21]), "+r"(d[22]), "+r"(d[23])
                 : "r"(a0), "r"(a1), "r"(a2), "r"(a3), "l"(db), "r"(acc));
}
template <int ACC>
__device__ __forceinline__ void wgmma_rowsum(float (&d)[4], const uint32_t (&a)[4], uint64_t ones) {
    asm volatile("{\n.reg .pred p;\nsetp.ne.b32 p, %9, 0;\n"
                 "wgmma.mma_async.sync.aligned.m64n8k16.f32.bf16.bf16 {%0, %1, %2, %3}, {%4, %5, %6, %7}, %8, p, 1, 1, 0;\n}\n"
                 : "+f"(d[0]), "+f"(d[1]), "+f"(d[2]), "+f"(d[3])
                 : "r"(a[0]), "r"(a[1]), "r"(a[2]), "r"(a[3]), "l"(ones), "n"(ACC));
}
__device__ __forceinline__ void ldsm4(uint32_t (&r)[4], uint32_t addr) {
    asm volatile("ldmatrix.sync.aligned.m8n8.x4.shared.b16 {%0, %1, %2, %3}, [%4];"
                 : "=r"(r[0]), "=r"(r[1]), "=r"(r[2]), "=r"(r[3]) : "r"(addr) : "memory");
}
__device__ __forceinline__ void ldsm4_t(uint32_t (&r)[4], uint32_t addr) {
    asm volatile("ldmatrix.sync.aligned.m8n8.x4.trans.shared.b16 {%0, %1, %2, %3}, [%4];"
                 : "=r"(r[0]), "=r"(r[1]), "=r"(r[2]), "=r"(r[3]) : "r"(addr) : "memory");
}
__device__ __forceinline__ void stsm4(uint32_t addr, uint32_t a, uint32_t b, uint32_t c, uint32_t d) {
    asm volatile("stmatrix.sync.aligned.m8n8.x4.shared.b16 [%0], {%1, %2, %3, %4};"
                 ::"r"(addr), "r"(a), "r"(b), "r"(c), "r"(d) : "memory");
}
__device__ __forceinline__ uint32_t transpose8x8(uint32_t v) {
    uint32_t d; asm volatile("movmatrix.sync.aligned.m8n8.trans.b16 %0, %1;" : "=r"(d) : "r"(v)); return d;
}
__device__ __forceinline__ void spin_until(const unsigned* counter, unsigned target) {
    unsigned n = 0, c;
    do {
        asm volatile("ld.acquire.gpu.global.u32 %0, [%1];" : "=r"(c) : "l"(counter) : "memory");
        if (++n > SPIN_LIMIT) __trap();
    } while ((int)(c - target) < 0);
}
__device__ __forceinline__ void signal(unsigned* counter) {
    __syncwarp();
    if (elect_one()) asm volatile("red.release.gpu.global.add.u32 [%0], 1;" ::"l"(counter) : "memory");
    __syncwarp();
}
__device__ __forceinline__ void lds128(uint32_t& a, uint32_t& b, uint32_t& c, uint32_t& d, uint32_t addr) {
    asm volatile("ld.shared.v4.u32 {%0, %1, %2, %3}, [%4];" : "=r"(a), "=r"(b), "=r"(c), "=r"(d) : "r"(addr) : "memory");
}
__device__ __forceinline__ void lds64(uint32_t& a, uint32_t& b, uint32_t addr) {
    asm volatile("ld.shared.v2.u32 {%0, %1}, [%2];" : "=r"(a), "=r"(b) : "r"(addr) : "memory");
}
__device__ __forceinline__ void lds32(uint32_t& a, uint32_t addr) {
    asm volatile("ld.shared.u32 %0, [%1];" : "=r"(a) : "r"(addr) : "memory");
}
__device__ __forceinline__ int ldsi(uint32_t addr) {
    uint32_t v;
    lds32(v, addr);
    return (int)v;
}
__device__ __forceinline__ float ldsf(uint32_t addr) {
    uint32_t v;
    lds32(v, addr);
    return __uint_as_float(v);
}
__device__ __forceinline__ void sts32(uint32_t addr, uint32_t a) {
    asm volatile("st.shared.u32 [%0], %1;" ::"r"(addr), "r"(a) : "memory");
}
__device__ __forceinline__ void sts128(uint32_t addr, uint32_t a, uint32_t b, uint32_t c, uint32_t d) {
    asm volatile("st.shared.v4.u32 [%0], {%1, %2, %3, %4};" ::"r"(addr), "r"(a), "r"(b), "r"(c), "r"(d) : "memory");
}
__device__ __forceinline__ void sts64(uint32_t addr, uint32_t a, uint32_t b) {
    asm volatile("st.shared.v2.u32 [%0], {%1, %2};" ::"r"(addr), "r"(a), "r"(b) : "memory");
}
__device__ __forceinline__ void anchor(uint32_t addr, uint32_t a, uint32_t b, uint32_t c, uint32_t d) {
    asm volatile("{\n.reg .pred p;\nsetp.eq.b32 p, %0, 0;\n@p st.shared.v4.u32 [%0], {%1, %2, %3, %4};\n}\n"
                 ::"r"(addr), "r"(a), "r"(b), "r"(c), "r"(d) : "memory");
}
__device__ __forceinline__ uint32_t bf_fma(uint32_t a, uint32_t b, uint32_t c) {
    uint32_t d; asm("fma.rn.bf16x2 %0, %1, %2, %3;" : "=r"(d) : "r"(a), "r"(b), "r"(c)); return d;
}
__device__ __forceinline__ uint32_t bf_mul(uint32_t a, uint32_t b) {
    uint32_t d; asm("mul.rn.bf16x2 %0, %1, %2;" : "=r"(d) : "r"(a), "r"(b)); return d;
}
__device__ __forceinline__ uint32_t bf_absmax(uint32_t a, uint32_t b) {
    uint32_t d; asm("max.xorsign.abs.bf16x2 %0, %1, %2;" : "=r"(d) : "r"(a), "r"(b)); return d;
}
__device__ __forceinline__ uint32_t h_fma(uint32_t a, uint32_t b, uint32_t c) {
    uint32_t d; asm("fma.rn.f16x2 %0, %1, %2, %3;" : "=r"(d) : "r"(a), "r"(b), "r"(c)); return d;
}
__device__ __forceinline__ uint32_t h_mul(uint32_t a, uint32_t b) {
    uint32_t d; asm("mul.rn.f16x2 %0, %1, %2;" : "=r"(d) : "r"(a), "r"(b)); return d;
}
__device__ __forceinline__ uint32_t h_cut8(uint32_t v) { return v & 0xfff8fff8u; }
constexpr float CUT_GAIN = 1.f + 0.4375f * 0.7213f / 128;
__device__ __forceinline__ uint32_t h_tanh(uint32_t a) {
    uint32_t d; asm("tanh.approx.f16x2 %0, %1;" : "=r"(d) : "r"(a)); return d;
}
__device__ __forceinline__ uint32_t pack_h2(float lo, float hi) {
    uint32_t d; asm("cvt.rn.f16x2.f32 %0, %1, %2;" : "=r"(d) : "f"(hi), "f"(lo)); return d;
}
__device__ __forceinline__ uint32_t pack_bf2(float lo, float hi) {
    uint32_t d; asm("cvt.rn.bf16x2.f32 %0, %1, %2;" : "=r"(d) : "f"(hi), "f"(lo)); return d;
}
__device__ __forceinline__ float bf_lo(uint32_t v) { return __uint_as_float(v << 16); }
__device__ __forceinline__ float bf_hi(uint32_t v) { return __uint_as_float(v & 0xffff0000u); }
__device__ __forceinline__ float h_lo(uint32_t v) { return __low2float(*reinterpret_cast<__half2*>(&v)); }
__device__ __forceinline__ float h_hi(uint32_t v) { return __high2float(*reinterpret_cast<__half2*>(&v)); }
__device__ __forceinline__ float warp_absmax(uint32_t v) {
    return __uint_as_float(__reduce_max_sync(~0u, max((v & 0x7fffu) << 16, v & 0x7fff0000u)));
}
__device__ __forceinline__ uint32_t gelu2(uint32_t z) {
    uint32_t p = h_fma(z, z, GELU_C2);
    uint32_t t = h_tanh(h_mul(z, p));
    return h_fma(z, t, z);
}
__device__ __forceinline__ float pow2i(int e) { return __uint_as_float((uint32_t)(e + 127) << 23); }
__device__ __forceinline__ int ilog2f(float v) {
    int e = (int)((__float_as_uint(v) >> 23) & 0xff) - 127;
    return max(-100, min(100, e));
}

__device__ __forceinline__ int bound_exp(float w1max) { return w1max > 0.f ? ilog2f(2.f * KZ * 96.f * w1max) : 0; }
__device__ __forceinline__ bool plain_squares(int e) { return (unsigned)(4 - e) <= 6; }
__device__ __forceinline__ int square_exp(int e) { return plain_squares(e) ? 0 : max(-14, min(4 - e, 14)); }
__device__ __forceinline__ int sum_exp(int e) { return max(-90, min(90, 33 - 2 * e)); }
__device__ __forceinline__ int row_exp(float m) { return 2 - ilog2f(m); }

struct Split {
    int per_cta, extra, period, inv_period, lenders;
    uint32_t lent_off[MAX_LENDERS * LENT];
    __host__ __device__ __forceinline__ int longer_before(int cta) const {
        const int n = (cta + period / 2) * inv_period >> 16;
        return n < extra ? n : extra;
    }
};
struct Work {
    int tA, tB, nA, nB, dir, rows, lent, index;
    __host__ __device__ __forceinline__ int tile(int j) const { return j < nA ? tA + dir * j : tB + dir * (j - nA); }
};
__host__ __device__ __forceinline__ Work get_work(int cta, const Split& sp) {
    Work w;
    const int before = sp.longer_before(cta), longer = sp.longer_before(cta + 1) - before;
    w.lent = longer && sp.lenders ? LENT : 0;
    w.index = before;
    const int t0 = cta * sp.per_cta + before, t1 = t0 + sp.per_cta + longer;
    const int tm = t1 < (t0 | 511) + 1 ? t1 : (t0 | 511) + 1;
    const bool swap = t1 > tm && t1 - tm < tm - t0, down = cta & 1;
    w.nA = swap ? t1 - tm : tm - t0;
    w.nB = t1 - t0 - w.nA;
    w.tA = down ? (swap ? tm : t0) : (swap ? t1 : tm) - 1;
    w.tB = down ? (swap ? t0 : tm) : (swap ? tm : t1) - 1;
    w.dir = down ? 1 : -1;
    w.rows = w.nA + 2 + (w.nB ? w.nB + 2 : 0);
    return w;
}
__device__ __forceinline__ int row_code(const Work& w, int i) {
    const bool in_a = i < w.nA + 2;
    const int t = in_a ? w.tA : w.tB;
    return ((t & 511) + w.dir * ((in_a ? i : i - (w.nA + 2)) - 1)) << 16 | (t >> 9) * TILE_W;
}
__host__ __device__ __forceinline__ uint32_t tile_offset(int tile) { return ((tile & 511) * IMG_W + (tile >> 9) * TILE_W) * (CH * 2); }
__device__ __forceinline__ int tile_order(int j, int n) {
    return j % ORDER_P == ORDER_P - 1 ? j / ORDER_P : n - 1 - (j - j / ORDER_P);
}
__device__ __forceinline__ void issue_region(const CUtensorMap* tm, uint32_t dst, uint32_t bar, int warp, int code) {
    mbar_expect_tx(bar, REGION_BYTES);
    tma_row(dst, tm, bar, (code & 0xffff) + (16 * warp - 1), code >> 16);
}

template <class Event>
__device__ __forceinline__ void conv_producer(const Work& wk, const CUtensorMap* tm, uint32_t sb, int warp, Event event) {
    const int lane = threadIdx.x & 31;
    const int j = lane & 15, grp = lane >> 4;
    const uint32_t reg0 = sb + SM_RING + warp * REGION_BYTES;
    const uint32_t bars = sb + SM_BAR + warp * 8;
    if (warp * 32 + lane < MAX_ROWS) {
        const int i = warp * 32 + lane, before = min(i / 5, wk.lent);
        const bool back = i % 5 == 0 && i > 0 && i / 5 <= wk.lent;
        sts32(sb + SM_TILES + i * 4, back ? tile_offset(wk.tile(before - 1)) | before
                                          : tile_offset(wk.tile(wk.lent + tile_order(i - before, wk.nA + wk.nB - 4 - wk.lent))));
    }
    const uint32_t ld64 = opaque(reg0 + grp * 8 * 192 + j * 8), ld32 = opaque(reg0 + grp * 8 * 192 + 128 + j * 4);
    const uint32_t st64 = opaque(reg0 + grp * A_SBO + (j >> 1) * A_LBO + (j & 1) * 8);
    const uint32_t st32 = opaque(reg0 + grp * A_SBO + (8 + (j >> 2)) * A_LBO + (j & 3) * 4);
    named_bar(0, NTHREADS);
    uint32_t w[3][3][3];
    mbar_wait_once(sb + BAR_F, 0);
#pragma unroll
    for (int tap = 0; tap < 9; tap++) {
        const uint32_t p = sb + SM_FILTER + (3 + wk.dir * 3 * (tap / 3 - 1) + tap % 3) * (CH * 2);
        lds64(w[tap / 3][tap % 3][0], w[tap / 3][tap % 3][1], p + 8 * j);
        lds32(w[tap / 3][tap % 3][2], p + 128 + 4 * j);
#pragma unroll
        for (int q = 0; q < 3; q++) w[tap / 3][tap % 3][q] = bf_mul(w[tap / 3][tap % 3][q], CONV_SCALE2);
    }
#pragma unroll
    for (int tap = 0; tap < 9; tap++) sts64(reg0 + (NSLOT - 1) * SLOT_BYTES + tap * 128 + j * 8, w[tap / 3][tap % 3][1], w[tap / 3][tap % 3][0]);
    named_bar(1, 128);
#pragma unroll
    for (int tap = 0; tap < 9; tap++) lds64(w[tap / 3][tap % 3][1], w[tap / 3][tap % 3][0], reg0 + (NSLOT - 1) * SLOT_BYTES + tap * 128 + j * 8);
    static_assert(2 * PREFETCH_ROWS == NSLOT && SLOT_BYTES % 32 == 0, "slot arithmetic");
    uint32_t bo = 0, par = 0, pbo = PREFETCH_ROWS * 32, ppar = 1;
    int px, py;
    auto request = [&]() {
        mbar_wait_once(bars + (BAR_E - SM_BAR) + pbo, ppar);
        if (elect_one()) {
            mbar_expect_tx(bars + pbo, REGION_BYTES);
            tma_row(reg0 + pbo * (SLOT_BYTES / 32), tm, bars + pbo, px, py);
        }
    };
    auto advance = [&]() {
        bo += 32;
        if (bo == NSLOT * 32) { bo = 0; par ^= 1; }
        pbo += 32;
        if (pbo == NSLOT * 32) { pbo = 0; ppar ^= 1; }
    };
    auto aim = [&](int row) {
        const int code = row_code(wk, row);
        px = (code & 0xffff) + (16 * warp - 1);
        py = code >> 16;
    };
    uint32_t accB[8][3], accC[8][3];
    int r = 0;
#pragma unroll 1
    while (r < wk.rows) {
        if (r == 0 || r == wk.nA + 2) {
            const uint32_t bo0 = bo;
            uint32_t bo1;
#pragma unroll 1
            for (int k = 0; k < 2; k++, r++) {
                mbar_wait_once(bars + bo, par);
                bo1 = bo;
                if (r >= 2) {
                    aim(r + PREFETCH_ROWS);
                    request();
                }
                advance();
            }
            const uint32_t so0 = bo0 * (SLOT_BYTES / 32), so1 = bo1 * (SLOT_BYTES / 32);
#pragma unroll
            for (int p = 0; p < 10; p++) {
                uint32_t u[3], v[3];
                lds64(u[0], u[1], so0 + ld64 + p * 192);
                lds32(u[2], so0 + ld32 + p * 192);
                lds64(v[0], v[1], so1 + ld64 + p * 192);
                lds32(v[2], so1 + ld32 + p * 192);
#pragma unroll
                for (int dx = 0; dx < 3; dx++) {
                    const int o = p - dx;
                    if (o < 0 || o > 7) continue;
#pragma unroll
                    for (int q = 0; q < 3; q++) {
                        accB[o][q] = bf_fma(v[q], w[1][dx][q], dx == 0 ? bf_mul(u[q], w[0][dx][q]) : bf_fma(u[q], w[0][dx][q], accB[o][q]));
                        accC[o][q] = dx == 0 ? bf_mul(v[q], w[0][dx][q]) : bf_fma(v[q], w[0][dx][q], accC[o][q]);
                    }
                }
            }
            anchor(ld64, accB[7][0], accB[7][1], accB[7][2], 0);
            __syncwarp();
            if (elect_one()) {
                mbar_arrive(bars + (BAR_A - SM_BAR) + bo0);
                mbar_arrive(bars + (BAR_E - SM_BAR) + bo0);
                mbar_arrive(bars + (BAR_A - SM_BAR) + bo1);
                mbar_arrive(bars + (BAR_E - SM_BAR) + bo1);
            }
        }
        int end = wk.rows;
        const int marks[4] = {wk.rows - PREFETCH_ROWS, wk.rows - 11, wk.nA + 2, wk.nA + 2 - PREFETCH_ROWS};
#pragma unroll
        for (int k = 0; k < 4; k++) end = marks[k] > r ? min(end, marks[k]) : end;
        const bool fetch = r < wk.rows - PREFETCH_ROWS;
        aim(r + PREFETCH_ROWS);
        px = opaque_uniform(px);
        const int py_end = opaque_uniform(py + wk.dir * (end - r));
        r = end;
#pragma unroll 1
        do {
            mbar_wait(bars + bo, par);
            const uint32_t so = bo * (SLOT_BYTES / 32);
            uint32_t out[8][3];
#pragma unroll
            for (int p = 0; p < 10; p++) {
                uint32_t xv[3];
                lds64(xv[0], xv[1], so + ld64 + p * 192);
                lds32(xv[2], so + ld32 + p * 192);
#pragma unroll
                for (int dx = 0; dx < 3; dx++) {
                    const int o = p - dx;
                    if (o < 0 || o > 7) continue;
#pragma unroll
                    for (int q = 2; q >= 0; q--) {
                        out[o][q] = bf_fma(xv[q], w[2][dx][q], dx == 0 ? accB[o][q] : out[o][q]);
                        accB[o][q] = bf_fma(xv[q], w[1][dx][q], dx == 0 ? accC[o][q] : accB[o][q]);
                        accC[o][q] = dx == 0 ? bf_mul(xv[q], w[0][dx][q]) : bf_fma(xv[q], w[0][dx][q], accC[o][q]);
                    }
                }
            }
            __syncwarp();
#pragma unroll
            for (int o = 0; o < 8; o++) {
                sts64(so + st64 + o * 16, out[o][0], out[o][1]);
                sts32(so + st32 + o * 16, out[o][2]);
            }
            __syncwarp();
            if (elect_one()) mbar_arrive(bars + (BAR_A - SM_BAR) + bo);
            if (fetch) request();
            advance();
            py += wk.dir;
        } while (py != py_end);
        if (((wk.rows - r) & ~8) == PREFETCH_ROWS) event(wk.rows - r == PREFETCH_ROWS);
    }
}

template <bool SCALED, int K0 = 0, int K1 = 3>
__device__ __forceinline__ void gelu_sq(uint32_t (&d)[24], uint32_t (&keep)[24], uint32_t sq_addr, uint32_t scale2) {
    pin(d);
#pragma unroll
    for (int k = K0; k < K1; k++) {
        uint32_t hs[4];
        lds128(hs[0], hs[1], hs[2], hs[3], sq_addr + k * SQ_ROW);
#pragma unroll
        for (int q = 0; q < 4; q++) {
            uint32_t g0 = gelu2(d[8 * k + 2 * q]), g1 = gelu2(d[8 * k + 2 * q + 1]);
            keep[8 * k + 2 * q] = g0;
            keep[8 * k + 2 * q + 1] = g1;
            if (SCALED) { g0 = h_mul(g0, scale2); g1 = h_mul(g1, scale2); }
            hs[q] = h_fma(g1, g1, h_fma(g0, g0, hs[q]));
        }
        sts128(sq_addr + k * SQ_ROW, hs[0], hs[1], hs[2], hs[3]);
    }
}
__device__ __forceinline__ void gelu_sq_reg(uint32_t (&d)[24], uint32_t (&hs)[12]) {
    pin(d);
#pragma unroll
    for (int q = 0; q < 12; q++) {
        const uint32_t g0 = gelu2(d[2 * q]), g1 = gelu2(d[2 * q + 1]);
        hs[q] = h_fma(g1, g1, h_fma(g0, g0, hs[q]));
    }
}
__device__ __forceinline__ void gelu_to(uint32_t (&g)[12], uint32_t (&d)[12]) {
    pin(d);
#pragma unroll
    for (int q = 0; q < 12; q++) g[q] = gelu2(d[q]);
    pin(g);
}
__device__ __forceinline__ void load_tile(uint32_t (&raw)[6][4], uint32_t addr) {
#pragma unroll
    for (int s = 0; s < 6; s++) ldsm4(raw[s], addr + s * 2 * A_LBO);
}
template <class F>
__device__ __forceinline__ void layer_norm(uint32_t (&raw)[6][4], uint64_t ones, F meanwhile) {
    uint32_t sq[2][4];
#pragma unroll
    for (int s = 0; s < 6; s++)
#pragma unroll
        for (int q = 0; q < 4; q++) sq[s / 3][q] = s % 3 == 0 ? bf_mul(raw[s][q], raw[s][q]) : bf_fma(raw[s][q], raw[s][q], sq[s / 3][q]);
    float sum[4], ssq[4];
    wg_fence();
    wgmma_rowsum<0>(sum, raw[0], ones);
#pragma unroll
    for (int s = 1; s < 6; s++) wgmma_rowsum<1>(sum, raw[s], ones);
    wgmma_rowsum<0>(ssq, sq[0], ones);
    wgmma_rowsum<1>(ssq, sq[1], ones);
    wg_commit();
    meanwhile();
    wg_wait<0>();
    uint32_t sc[2], sh[2];
#pragma unroll
    for (int h = 0; h < 2; h++) {
        asm volatile("" : "+f"(sum[2 * h]), "+f"(ssq[2 * h])::"memory");
        constexpr float EPS = 1e-5f / (KZ * KZ) * 0x1p-64f;
        const float m = sum[2 * h] * (1.f / (CH * KZ));
        float rstd;
        asm("rsqrt.approx.ftz.f32 %0, %1;" : "=f"(rstd) : "f"(fmaxf(fmaf(-m, m, fmaf(ssq[2 * h], 1.f / (CH * KZ * KZ), EPS)), EPS)));
        rstd *= 0x1p-112f;
        sc[h] = pack_bf2(rstd, rstd);
        const float shift = sum[2 * h] * (-1.f / CH) * bf_hi(sc[h]);
        sh[h] = pack_bf2(shift, shift);
    }
#pragma unroll
    for (int s = 0; s < 6; s++)
#pragma unroll
        for (int q = 0; q < 4; q++) {
            const uint32_t v = bf_fma(raw[s][q], sc[q & 1], sh[q & 1]);
            asm("lop3.b32 %0, %1, %2, 0x80008000, 0xd8;" : "=r"(raw[s][q]) : "r"(v << 3), "r"(v));
        }
}
struct Cursor {
    int slot;
    uint32_t par;
    __device__ __forceinline__ void advance(int n) {
        slot += n;
        if (slot >= NSLOT) { slot -= NSLOT; par ^= 1; }
    }
};
struct Descs {
    uint64_t w1[8][6];
    uint64_t w2[24];
    uint64_t ones;
};
template <int E0, int N>
__device__ __forceinline__ void gemm1_chunk(uint32_t (&d)[N], const uint32_t (&a)[6][4], const Descs& ds, int zero) {
#pragma unroll
    for (int s = 0; s < 6; s++) wgmma(d, a[s][0], a[s][1], a[s][2], a[s][3], ds.w1[E0 / 48][s], s ? 1 : zero);
}
template <int E0, int N>
__device__ __forceinline__ void gemm2_chunk(uint32_t (&acc)[24], const uint32_t (&g)[N], const Descs& ds) {
#pragma unroll
    for (int s = 0; s < N / 4; s++) wgmma(acc, g[4 * s], g[4 * s + 1], g[4 * s + 2], g[4 * s + 3], ds.w2[E0 / 16 + s], 1);
}

struct __align__(64) Params {
    Split sp;
    int zero;
    const __nv_bfloat16 *x, *dw, *w2, *gamma, *beta;
    __nv_bfloat16* out;
    Scratch* sc;
    Descs ds;
};

__global__ void __launch_bounds__(NTHREADS, 1)
block_kernel(const __grid_constant__ CUtensorMap tmap, const __grid_constant__ CUtensorMap tmap_w1, const __grid_constant__ Params pm) {
    const Split& sp = pm.sp;
    const Descs& ds = pm.ds;
    const int& zero = pm.zero;
    const __nv_bfloat16 *const &x = pm.x, *const &dw = pm.dw, *const &w2 = pm.w2, *const &gamma = pm.gamma, *const &beta = pm.beta;
    __nv_bfloat16* const& out = pm.out;
    Scratch* const& sc = pm.sc;
    extern __shared__ __align__(1024) uint8_t smem[];
    constexpr uint32_t sb = SB;
    const int tid = threadIdx.x;
    const Work wk = get_work(blockIdx.x, sp);
    constexpr uint32_t s_red = sb + SM_RED;
    if (smem_u32(smem) != SB) __trap();

    const int warp_id = __shfl_sync(~0u, tid >> 5, 0);
    PROF(0);
    const int cw = warp_id - 4, wgi = cw >> 2, w4 = warp_id & 3;
    if (elect_one()) {
        static_assert(3 * NSLOT * 4 == 8 + 4 * 16 && BAR_F == BAR_W + 48, "barrier shares");
        const int b = warp_id - 8;
        const uint32_t bar = b < 0 ? sb + BAR_X + warp_id * 8 : b < 7 ? sb + BAR_W + b * 8 : sb + BAR_PIN;
        mbar_init(bar, 1);
#pragma unroll
        for (int k = 0; k < 4; k++) mbar_init(sb + BAR_X + (8 + 4 * warp_id + k) * 8, 1);
        mbar_init(sb + BAR_R + warp_id * 8, 1);
        fence_async();
        if (b < 0) {
            issue_region(&tmap, sb + SM_RING + warp_id * REGION_BYTES, bar, w4, ((wk.tA & 511) + wk.dir * wgi) << 16 | (wk.tA >> 9) * TILE_W);
        } else if (b < 6) {
            mbar_expect_tx(bar, 64 * CH * 2);
            tma_2d(sb + SM_W2 + b * (64 * CH * 2), &tmap_w1, bar, 64 * b, 0);
        } else if (b == 6) {
            mbar_expect_tx(bar, 9 * CH * 2);
            bulk_load(sb + SM_FILTER, dw, 9 * CH * 2, bar);
        }
    }
    __syncwarp();
    const int ntiles = wk.nA + wk.nB;
    const int rank = (wgi + wk.lent + 2 * (ntiles - 1)) % NCONS | (wgi >> 2 & 3);
    const int spare = wk.rows % NSLOT, spare2 = spare == NSLOT - 1 ? 0 : spare + 1;
    const uint32_t sq_base = sb + (wgi < 0 ? SM_RING + spare * SLOT_BYTES : SM_SQ + rank * 2 * SQ_HALF);
    const uint32_t sq_upper = wgi < 0 ? (spare2 - spare) * SLOT_BYTES : SQ_HALF;
    const uint32_t bar_a = sb + BAR_A + w4 * 8, bar_e = sb + BAR_E + w4 * 8;
    auto max_w1 = [&](uint32_t lane) { return __uint_as_float(__reduce_max_sync(~0u, lane < 4 * NCONS ? ldsi(s_red + RED_MAX + lane * 4) : 0)); };
    auto square_scale = [&](uint32_t lane) {
        const float f = pow2i(square_exp(bound_exp(max_w1(lane))));
        return pack_h2(f, f);
    };
    uint32_t a_addr, sq;
    const uint32_t sq_warp = sq_base + w4 * 512;
    auto set_addresses = [&]() {
        a_addr = opaque(sb + SM_RING + w4 * REGION_BYTES + ((tid >> 3) & 1) * A_SBO + ((tid >> 4) & 1) * A_LBO + (tid & 7) * 16);
        sq = opaque(sq_base + (tid & 127) * 16);
    };
    uint32_t turn, turn_end, so, so_sum, bo, bo_sum, off;
    auto set_run = [&](int j, int stop, int row) {
        const int slot = row % NSLOT, both = 2 * (row % 3) + 3;
        turn = opaque_uniform(row / 3);
        turn_end = opaque_uniform(row / 3 + (stop - j + NCONS - 1) / NCONS);
        so = opaque_uniform(slot * SLOT_BYTES);
        so_sum = opaque_uniform(both * SLOT_BYTES);
        bo = opaque_uniform(bar_a + slot * 32);
        bo_sum = opaque_uniform(2 * bar_a + both * 32);
        off = opaque_uniform(tile_offset(wk.tile(j)) + w4 * WARP_BYTES - sq_warp);
    };
    const int nrest = ntiles - 4;
    int jt;
    Cursor cur;
    int fast_from;
    if (warp_id < 4) {
        conv_producer(wk, &tmap, sb, warp_id, [&](bool second) {
            if (!second) {
                if (tid == 0) sts32(s_red + RED_JOB, wk.lent ? NTILES : atomicAdd(&sc->job, 1));
                if (blockIdx.x == 0) {
#pragma unroll 1
                    for (int e = tid; e < EX; e += 128) *sc->sum(e) = 0;
                    sc->bias[tid] = 0.f;
                }
                if (blockIdx.x == 0 || wk.lent) signal(&sc->early);
                __syncwarp();
            } else {
                const int piece = opaque_uniform(ldsi(s_red + RED_JOB)) - W2_GROUPS / 2, q = 2 * piece + W2_GROUPS + (w4 >> 1);
                if (piece < 8 * LENT * sp.lenders) {
                    spin_until(&sc->early, (ldsi(s_red + RED_LAUNCH) + 1) * 4 * (sp.lenders + 1));
                    if (elect_one()) {
                        if (piece >= 0) prefetch_l2(reinterpret_cast<const char*>(out) + sp.lent_off[piece / 8] + w4 * WARP_BYTES, WARP_BYTES);
                        else { prefetch_l2(w2 + 8 * q * CH, 8 * CH * 2); prefetch_l2(beta + 8 * q, 16); }
                    }
                }
            }
        });
        const int piece = opaque_uniform(ldsi(s_red + RED_JOB)) - W2_GROUPS / 2, q = 2 * piece + W2_GROUPS + (w4 >> 1);
        const bool prepares = piece < 0, helps = piece < 8 * LENT * sp.lenders;
        set_addresses();
        const int lane = lane_id(), g = lane >> 2, t = lane & 3;
        uint32_t a[6][4];
        unsigned short bt_raw;
        if (prepares) {
#pragma unroll
            for (int m = 0; m < 3; m++) ldg128(a[m], w2 + (8 * q + g) * CH + 32 * m + 8 * t);
            asm volatile("ld.global.nc.u16 %0, [%1];" : "=h"(bt_raw) : "l"(beta + 8 * q + g) : "memory");
        } else if (helps) {
#pragma unroll
            for (int s = 0; s < 6; s++) ldg128(a[s], reinterpret_cast<const char*>(out) + sp.lent_off[piece / 8] + w4 * WARP_BYTES + lane * 16 + s * 512);
        }
        mbar_wait_once(bar_e + spare2 * 32, (wk.rows - 5) / NSLOT & 1);
        mbar_wait_once(bar_e + spare * 32, (wk.rows - 6) / NSLOT & 1);
        named_bar(1, 128);
#pragma unroll
        for (int k = 0; k < 6; k++) { sts128(sq + k * SQ_ROW, 0, 0, 0, 0); sts128(sq + sq_upper + k * SQ_ROW, 0, 0, 0, 0); }
        if (prepares) {
            const int half = w4 & 1;
            uint32_t rmax = 0;
#pragma unroll
            for (int m = 0; m < 3; m++) rmax = bf_absmax(bf_absmax(rmax, bf_absmax(a[m][0], a[m][1])), bf_absmax(a[m][2], a[m][3]));
            uint2 u = half ? make_uint2(a[0][2], a[0][3]) : make_uint2(a[0][0], a[0][1]), u1 = half ? make_uint2(a[1][2], a[1][3]) : make_uint2(a[1][0], a[1][1]);
            const uint2 u2 = half ? make_uint2(a[2][2], a[2][3]) : make_uint2(a[2][0], a[2][1]);
            const float bt = bf_lo(bt_raw);
            rmax = bf_absmax(rmax, __shfl_xor_sync(~0u, rmax, 1));
            rmax = bf_absmax(rmax, __shfl_xor_sync(~0u, rmax, 2));
            const float mx = fmaxf(fabsf(bf_lo(rmax)), fabsf(bf_hi(rmax))), rs = pow2i(row_exp(mx));
            if (t == 0 && !half) sc->w2max[8 * q + g] = mx;
#pragma unroll 1
            for (int m = 0; m < 3; m++, u = u1, u1 = u2) {
                float f[4];
#pragma unroll
                for (int k = 0; k < 2; k++) {
                    const float lo = bf_lo(k ? u.y : u.x), hi = bf_hi(k ? u.y : u.x);
                    sc->w2h[(4 * m + 2 * half + k) * 1536 + q * 32 + lane] = transpose8x8(pack_h2(lo * rs, hi * rs));
                    f[2 * k] = lo * bt;
                    f[2 * k + 1] = hi * bt;
                }
                const float r0 = (g & 2 ? f[2] : f[0]) + __shfl_xor_sync(~0u, g & 2 ? f[0] : f[2], 8);
                const float r1 = (g & 2 ? f[3] : f[1]) + __shfl_xor_sync(~0u, g & 2 ? f[1] : f[3], 8);
                float r = (g & 1 ? r1 : r0) + __shfl_xor_sync(~0u, g & 1 ? r0 : r1, 4);
                r += __shfl_xor_sync(~0u, r, 16);
                if (g < 4) atomicAdd(&sc->bias[32 * m + 8 * t + 4 * half + g], r);
            }
            asm volatile("fence.proxy.async.global;" ::: "memory");
            signal(&sc->prep);
        } else
        if (helps) {
            uint32_t d[12], gl[12];
            const uint32_t scale2 = square_scale(lane);
            wg_fence();
#pragma unroll
            for (int s = 0; s < 6; s++) wgmma(d, a[s][0], a[s][1], a[s][2], a[s][3], ds.w1[0][s] + piece % 8 * (6 * 1536 / 16), s ? 1 : 0);
            wg_commit();
            wg_wait<0>();
            gelu_to(gl, d);
#pragma unroll
            for (int s = 0; s < 3; s++) {
                sc->lent[((piece / 8 * 4 + w4) * 24 + piece % 8 * 3 + s) * 32 + lane] = make_uint4(gl[4 * s], gl[4 * s + 1], gl[4 * s + 2], gl[4 * s + 3]);
                uint32_t hs[2];
#pragma unroll
                for (int k = 0; k < 2; k++) {
                    const uint32_t g0 = h_mul(gl[4 * s + 2 * k], scale2), g1 = h_mul(gl[4 * s + 2 * k + 1], scale2);
                    hs[k] = h_fma(g1, g1, h_mul(g0, g0));
                }
                const int pair = piece % 4 * 3 + s;
                sts64(sq + (piece & 4 ? sq_upper : 0) + (pair >> 1) * SQ_ROW + (pair & 1) * 8, hs[0], hs[1]);
            }
        }
        jt = ntiles - 1;
        cur.slot = spare ? spare - 1 : NSLOT - 1;
        cur.par = (wk.rows - 1) / NSLOT & 1;
        fast_from = ntiles;
        turn = turn_end = so = so_sum = bo = bo_sum = off = rank;
    } else {
        set_addresses();
        if (wgi == NCONS - 1) named_arrive(4, 256);
        set_run(wk.lent + wgi, min(wk.nA, nrest), wk.lent + wgi + 2);
        jt = wgi < wk.lent ? wgi : wk.lent + wgi;
        cur = {2, 0};
        cur.advance(jt + (jt >= wk.nA ? 2 : 0));
        {
            const int ct = tid - 128, lane = tid & 31;
            const unsigned epoch = *reinterpret_cast<volatile unsigned*>(&sc->launch);
            const int r = lane & 7, mi = lane >> 3;
            const uint32_t src = sb + SM_W2 + (cw >> 1) * (64 * CH * 2) + r * 128 + ((((cw & 1) * 4 + mi) ^ r) * 16);
            const uint32_t dst = sb + SM_W1 + (4 * cw + mi) * 1536 + r * 16;
            const int code = row_code(wk, PREFETCH_ROWS - 1 + wgi);
            named_bar(0, NTHREADS);
            auto request = [&]() {
                if (elect_one())
                    issue_region(&tmap, sb + SM_RING + (PREFETCH_ROWS - 1 + wgi) * SLOT_BYTES + w4 * REGION_BYTES, sb + BAR_X + (cw + 8) * 8, w4, code);
                __syncwarp();
            };
#pragma unroll 1
            for (int k = 0; k < 2; k++) {
                if (wgi == k) request();
                mbar_wait_once(sb + BAR_W + (cw >> 1) * 8, 0);
            }
            uint32_t wmax[2] = {}, wsum[4] = {};
#pragma unroll 3
            for (int c = 0; c < 12; c++) {
                uint32_t u[4];
                ldsm4_t(u, src + c * 1024);
#pragma unroll
                for (int q = 0; q < 4; q++) {
                    wmax[q & 1] = bf_absmax(wmax[q & 1], u[q]);
                    wsum[q] = bf_fma(u[q], 0x3f803f80u, wsum[q]);
                    u[q] = pack_h2(__uint_as_float(u[q] * (65536 + zero)), bf_hi(u[q]));
                }
                stsm4(dst + c * 128, u[0], u[1], u[2], u[3]);
            }
            const float w1max = warp_absmax(bf_absmax(wmax[0], wmax[1]));
            if (lane == 0) sts32(s_red + RED_MAX + cw * 4, __float_as_uint(w1max));
            bool center = false;
#pragma unroll
            for (int q = 0; q < 4; q++) {
#pragma unroll
                for (int o = 1; o <= 2; o <<= 1) wsum[q] = bf_fma(__shfl_xor_sync(~0u, wsum[q], o), 0x3f803f80u, wsum[q]);
                center |= fabsf(bf_lo(wsum[q]) + bf_hi(wsum[q])) > (0.15f * CH) * w1max;
            }
            if (__builtin_expect(__any_sync(~0u, center), 0)) {
                float mean[4] = {};
#pragma unroll 1
                for (int pass = 0; pass < 2; pass++) {
                    float sum[4] = {};
#pragma unroll 1
                    for (int c = 0; c < 12; c++) {
                        uint32_t u[4];
                        ldsm4_t(u, src + c * 1024);
#pragma unroll
                        for (int q = 0; q < 4; q++) {
                            sum[q] += bf_lo(u[q]) + bf_hi(u[q]);
                            u[q] = pack_h2(bf_lo(u[q]) - mean[q], bf_hi(u[q]) - mean[q]);
                        }
                        stsm4(dst + c * 128, u[0], u[1], u[2], u[3]);
                    }
#pragma unroll
                    for (int q = 0; q < 4; q++) {
                        sum[q] += __shfl_xor_sync(~0u, sum[q], 1);
                        sum[q] += __shfl_xor_sync(~0u, sum[q], 2);
                        mean[q] = sum[q] * (1.f / CH);
                    }
                }
            }
            if (!(cw & 2)) {
#pragma unroll
                for (int c = 0; c < 12; c++) sts128(src + c * 1024, 0, 0, 0, 0);
            }
            if (ct < 32) sts32(sb + SM_ONES + ct * 4, 0x3f803f80u);
            if (ct == 0) sts32(s_red + RED_LAUNCH, epoch);
            fence_async();
            named_bar(2, CONS_THREADS);
            if (wgi == 2) request();
        }
        PROF(1);
        if (cur.par) mbar_wait_once(bar_a, 0);
        fast_from = wk.lent;
        if (!__all_sync(~0u, plain_squares(bound_exp(max_w1(lane_id()))))) {
            fast_from = ntiles;
#pragma unroll 1
            for (int q = 0; q < 6; q++) sts128(sq + SQ_HALF + q * SQ_ROW, 0, 0, 0, 0);
        }
    }
    uint32_t k1[24], k2[24], k3[24];
    uint32_t here;
    constexpr int SQC = 3 * SQ_ROW;
    auto store_at = [&](const uint32_t (&a)[6][4], uint32_t off) {
        char* ap = reinterpret_cast<char*>(out) + (off + sq);
#pragma unroll
        for (int s = 0; s < 6; s++) stg128(ap + s * 512, a[s]);
    };
    const uint32_t own_bar = 4 + wgi, next_bar = 4 + (wgi == NCONS - 1 ? 0 : wgi + 1);
    for (;;) {
        if (jt >= fast_from) {
            uint32_t hs2[12] = {}, hs3[12] = {};
            const uint32_t step = wk.dir * (NCONS * IMG_W * CH * 2);
            int second = wk.nB;
#pragma unroll 1
            for (;;) {
#pragma unroll 1
                while (turn != turn_end) {
                    uint32_t a[6][4], d0[24], d1[24], unused[24];
                    mbar_wait(bo, turn >> 1 & 1);
                    load_tile(a, a_addr + so);
                    layer_norm(a, ds.ones, [&]() { named_bar(own_bar, 256); });
                    wg_fence();
                    gemm1_chunk<0>(d0, a, ds, 0);
                    wg_commit();
                    gemm1_chunk<96>(d1, a, ds, 0);
                    wg_commit();
                    wg_wait<1>();
                    gelu_sq<false, 0, 1>(d0, unused, sq, 0);
                    gelu_sq<false, 1, 2>(d0, unused, sq, 0);
                    store_at(a, off);
                    gelu_sq<false, 2, 3>(d0, unused, sq, 0);
                    if (elect_one()) mbar_arrive(bo + (BAR_E - BAR_A));
                    wg_fence();
                    gemm1_chunk<192>(d0, a, ds, zero);
                    wg_commit();
                    named_arrive(next_bar, 256);
                    wg_wait<1>();
                    gelu_sq<false, 0, 1>(d1, unused, sq + SQC, 0);
                    gelu_sq<false, 1, 3>(d1, unused, sq + SQC, 0);
                    wg_fence();
                    gemm1_chunk<288>(d1, a, ds, zero);
                    wg_commit();
                    wg_wait<1>();
                    gelu_sq_reg(d0, hs2);
                    anchor(sq, hs2[8], hs2[9], hs2[10], hs2[11]);
                    wg_wait<0>();
                    gelu_sq_reg(d1, hs3);
                    so = so_sum - so;
                    bo = bo_sum - bo;
                    off += step;
                    turn++;
                }
                if (!second) break;
                const int j = ntiles - second + (rank + second + 2) % NCONS;
                second = 0;
                set_run(j, nrest, j + 4);
            }
            jt = nrest + rank;
            cur.slot = (bo - bar_a) >> 5;
            cur.par = turn >> 1 & 1;
#pragma unroll
            for (int k = 0; k < 3; k++) {
                sts128(sq + SQ_HALF + k * SQ_ROW, hs2[4 * k], hs2[4 * k + 1], hs2[4 * k + 2], hs2[4 * k + 3]);
                sts128(sq + SQ_HALF + SQC + k * SQ_ROW, hs3[4 * k], hs3[4 * k + 1], hs3[4 * k + 2], hs3[4 * k + 3]);
            }
        }
        const bool last = jt >= nrest;
        here = tile_offset(wk.tile(jt));
        if (last) {
            const uint32_t next = ldsi(sb + SM_TILES + rank * 4);
            if (elect_one()) {
                prefetch_l2(reinterpret_cast<const char*>(x) + here + w4 * WARP_BYTES, WARP_BYTES);
                if (rank == ORDER_P - 1) prefetch_l2(reinterpret_cast<const char*>(out) + next + w4 * WARP_BYTES, WARP_BYTES);
            }
        }
        uint32_t a[6][4], d0[24], d1[24], d3[24], k0[24];
        mbar_wait_once(bar_a + cur.slot * 32, cur.par);
        load_tile(a, a_addr + cur.slot * SLOT_BYTES);
        layer_norm(a, ds.ones, [&]() { if (jt >= wk.lent && wgi >= 0) named_bar(own_bar, 256); });
        if (!last) {
            store_at(a, here + w4 * WARP_BYTES - sq_warp);
            __syncwarp();
            if (elect_one()) mbar_arrive(bar_e + cur.slot * 32);
            if (jt < wk.lent) {
                jt += LENT;
                cur.advance(LENT);
                continue;
            }
        }
        wg_fence();
        gemm1_chunk<0>(d0, a, ds, 0);
        wg_commit();
        gemm1_chunk<96>(d1, a, ds, 0);
        wg_commit();
        const uint32_t scale2 = square_scale(lane_id());
        wg_wait<1>();
        gelu_sq<true>(d0, k0, sq, scale2);
        if (last) {
#pragma unroll
            for (int q = 0; q < 6; q++)
                sts128(sb + SM_RING + cur.slot * SLOT_BYTES + w4 * REGION_BYTES - sq_warp + sq + q * 512, k0[4 * q], k0[4 * q + 1], k0[4 * q + 2], k0[4 * q + 3]);
        }
        wg_fence();
        gemm1_chunk<192>(d0, a, ds, zero);
        wg_commit();
        if (jt + 2 < ntiles) named_arrive(next_bar, 256);
        wg_wait<1>();
        gelu_sq<true>(d1, k1, sq + SQC, scale2);
        wg_fence();
        gemm1_chunk<288>(d3, a, ds, 0);
        wg_commit();
        wg_wait<1>();
        gelu_sq<true>(d0, k2, sq + sq_upper, scale2);
        wg_wait<0>();
        gelu_sq<true>(d3, k3, sq + sq_upper + SQC, scale2);
        if (last) break;
        cur.advance(NCONS + ((jt < wk.nA && jt + NCONS >= wk.nA) ? 2 : 0));
        jt += NCONS;
    }
    const uint32_t lane = lane_id();
    uint32_t next_off = opaque_uniform(ldsi(sb + SM_TILES + rank * 4));
    const uint32_t s_fac = sb + SM_RING + spare * SLOT_BYTES + SQ_HALF;
    uint32_t inv_rho2;
    {
        if (rank == 0) {
            const int g = lane >> 2, t = lane & 3, i0 = w4 * 32 + lane;
            const bool leader = i0 == 0;
            const uint32_t pick = (g & 1) == (t & 1) ? (g & 2 ? 0x3c000000u : 0x00003c00u) : 0;
            const int be = bound_exp(max_w1(lane));
            const float to_fixed = pow2i(sum_exp(be) - 2 * square_exp(be));
            const uint32_t two_rows = sb + (w4 * 3 + (lane >> 3 & 1)) * SQ_ROW + ((lane >> 4) * 8 + (lane & 7)) * 16;
            const uint32_t third_row = sb + (w4 * 3 + 2) * SQ_ROW + lane * 16;
            unsigned short gam_raw[3];
            float rmax[3], f[3][4] = {};
            float2 bpair = make_float2(0.f, 0.f);
#pragma unroll 1
            for (int i = 0; i < 4; i++) {
                if (i == 1 && leader) {
                    spin_until(&sc->prep, (ldsi(s_red + RED_LAUNCH) + 1) * (W2_GROUPS * 2));
                    asm volatile("fence.proxy.async.global;" ::: "memory");
                    mbar_expect_tx(sb + BAR_W, 6 * SQ_HALF);
                }
                __syncwarp();
                named_bar(2, 128);
                if (i && leader) {
                    fence_async();
                    bulk_load(sb + SM_W2 + (i - 1) * 2 * SQ_HALF, reinterpret_cast<const char*>(sc->w2h) + (i - 1) * 2 * SQ_HALF, 2 * SQ_HALF, sb + BAR_W);
                }
                if (i == 1) {
#pragma unroll
                    for (int m = 0; m < 3; m++) {
                        asm volatile("ld.global.nc.u16 %0, [%1];" : "=h"(gam_raw[m]) : "l"(gamma + i0 + 128 * m) : "memory");
                        asm volatile("ld.global.cg.f32 %0, [%1];" : "=f"(rmax[m]) : "l"(&sc->w2max[i0 + 128 * m]) : "memory");
                    }
                    if (i0 < 96)
                        asm volatile("ld.global.cg.v2.f32 {%0, %1}, [%2];" : "=f"(bpair.x), "=f"(bpair.y)
                                     : "l"(&sc->bias[32 * (i0 % 24 >> 3) + 8 * (i0 / 24) + (i0 % 24 & 6)]) : "memory");
                }
                __syncwarp();
                const uint32_t from = i < NCONS ? SM_SQ + i * 2 * SQ_HALF : w4 < 2 ? SM_RING + spare * SLOT_BYTES : SM_RING + spare2 * SLOT_BYTES - SQ_HALF;
                if (i) named_bar(12 + i, 256);
#pragma unroll
                for (int r = 0; r < 12; r++) {
                    uint32_t u[4];
                    ldsm4_t(u, from + (r % 3 == 2 ? third_row + r / 3 * 512 : two_rows + (r / 3 * 2 + r % 3) * 256));
                    asm volatile("mma.sync.aligned.m16n8k16.row.col.f32.f16.f16.f32 {%0, %1, %2, %3}, {%4, %5, %6, %7}, {%8, %8}, {%0, %1, %2, %3};"
                                 : "+f"(f[r % 3][0]), "+f"(f[r % 3][1]), "+f"(f[r % 3][2]), "+f"(f[r % 3][3])
                                 : "r"(u[0]), "r"(u[1]), "r"(u[2]), "r"(u[3]), "r"(pick));
                }
            }
            unsigned long long* dst = sc->sum(96 * w4 + 8 * (g >> 1) + 2 * (t & 1) + (g & 1));
#pragma unroll
            for (int r = 0; r < 3; r++) {
                const float tot = r < 2 ? (t < 2 ? f[0][r & 1] + f[1][r & 1] : f[0][r + 2 & 3] + f[1][r + 2 & 3]) : (t < 2 ? f[2][0] + f[2][2] : f[2][1] + f[2][3]);
                atomicAdd(dst + (r < 2 ? (t >> 1) * 8 + r : 16 + (t >> 1)) * 32, __float2ull_rn(fminf(tot * to_fixed, 0x1p47f)) << 8 | 1);
            }
            PROF(2);
            float base[3], slope[3], reach[3];
            const float w1max = max_w1(lane);
            const float gbound = fmaxf(2.f * KZ * 9.7979590f * 192.f * w1max, 1.f) * 19.5959180f * INV_2KZ;
            const unsigned fixed = __reduce_max_sync(~0u, __float_as_uint(fmaf(gbound, fmaxf(fmaxf(rmax[0], rmax[1]), rmax[2]), fmaxf(fabsf(bpair.x), fabsf(bpair.y)))));
            if (lane == 0) sts32(s_red + 96 + w4 * 4, fixed);
#pragma unroll
            for (int m = 0; m < 3; m++) {
                base[m] = rmax[m] > 0.f ? pow2i(-row_exp(rmax[m])) * (INV_2KZ * CUT_GAIN) : 0.f;
                slope[m] = base[m] * bf_lo(gam_raw[m]);
                reach[m] = fabsf(bf_lo(gam_raw[m])) * rmax[m] * gbound;
            }
            const float to_square = pow2i(-sum_exp(bound_exp(w1max))) * (INV_2KZ * INV_2KZ / 256);
#pragma unroll
            for (int m = 0; m < 3; m++) anchor(sq, __float_as_uint(base[m]), __float_as_uint(slope[m]), __float_as_uint(reach[m]), __float_as_uint(to_square));
            const unsigned epoch = ldsi(s_red + RED_LAUNCH);
            const uint32_t own_sum = (i0 >> 2) * 256 + (i0 & 3) * 8, own_fac = s_fac + i0 * 2;
            auto peek = [&](const void* p) {
                unsigned long long v;
                asm volatile("ld.relaxed.gpu.global.u64 %0, [%1];" : "=l"(v) : "l"(p) : "memory");
                return v;
            };
            const char* mine = reinterpret_cast<const char*>(sc->sums) + own_sum;
            unsigned n = 0;
            while (((unsigned)peek(sc->sum((blockIdx.x * 4 + w4) % (EX / 4) * 4)) & 255u) != gridDim.x)
                if (++n > SPIN_LIMIT) __trap();
            unsigned long long sum[3];
            for (;;) {
                bool all = true;
#pragma unroll
                for (int m = 0; m < 3; m++) {
                    sum[m] = peek(mine + m * (32 * 256));
                    all &= ((unsigned)sum[m] & 255u) == gridDim.x;
                }
                if (__all_sync(~0u, all)) break;
                if (++n > SPIN_LIMIT) __trap();
            }
            PROF(3);
            float gx[3];
#pragma unroll
            for (int m = 0; m < 3; m++) asm("sqrt.approx.ftz.f32 %0, %1;" : "=f"(gx[m]) : "f"(fmaf(__ull2float_rn(sum[m]), to_square, 1e-6f)));
            float tot = gx[0] + gx[1] + gx[2];
#pragma unroll
            for (int o = 16; o >= 1; o >>= 1) tot += __shfl_xor_sync(~0u, tot, o);
            const unsigned vwarp = __reduce_max_sync(~0u, __float_as_uint(fmaxf(fmaxf(reach[0] * gx[0], reach[1] * gx[1]), reach[2] * gx[2])));
            if (lane == 0) { sts32(s_red + 64 + w4 * 4, __float_as_uint(tot)); sts32(s_red + 80 + w4 * 4, vwarp); }
            named_bar(2, 128);
            uint32_t u[4], v[4], w[4];
            lds128(u[0], u[1], u[2], u[3], s_red + 64);
            lds128(v[0], v[1], v[2], v[3], s_red + 80);
            lds128(w[0], w[1], w[2], w[3], s_red + 96);
            tot = (__uint_as_float(u[0]) + __uint_as_float(u[1])) + (__uint_as_float(u[2]) + __uint_as_float(u[3]));
            const float vmax = __uint_as_float(max(max(v[0], v[1]), max(v[2], v[3]))), fmax2 = __uint_as_float(max(max(w[0], w[1]), max(w[2], w[3])));
            float inv_mean;
            asm("rcp.approx.ftz.f32 %0, %1;" : "=f"(inv_mean) : "f"(fmaf(tot, 1.f / EX, 1e-6f)));
            const int rho_e = 14 - ilog2f(fmaf(vmax, inv_mean, 2.f * fmax2));
            const float rho = pow2i(rho_e), inv_rho = pow2i(-rho_e);
            inv_rho2 = pack_bf2(inv_rho, inv_rho);
#pragma unroll
            for (int m = 0; m < 3; m++) {
                const float f = fmaf(slope[m] * gx[m], inv_mean, base[m]) * rho;
                asm volatile("st.shared.u16 [%0], %1;" ::"r"(own_fac + 256 * m), "h"((unsigned short)pack_h2(f, 0.f)) : "memory");
            }
            if (i0 < 96) sts32(sb + SM_BIASH + i0 * 4, pack_h2(bpair.x * rho, bpair.y * rho));
            if (i0 == 96) sts32(s_red + RED_INV_RHO, inv_rho2);
            named_arrive(12, NTHREADS);
            if (blockIdx.x == 0 && leader) { sc->launch = epoch + 1; sc->job = 0; }
            if (wk.lent) spin_until(&sc->lent_out, (epoch + 1) * 32 * LENT * sp.lenders);
        } else {
            named_arrive(12 + rank, 256);
            if (rank == NCONS && (unsigned)(ldsi(s_red + RED_JOB) - W2_GROUPS / 2) < 8 * LENT * sp.lenders) signal(&sc->lent_out);
            const int rw = rank * 4 - 4 + w4;
            const uint32_t row = sb + SM_W2 + rw * 512 + lane * 16;
            uint32_t u[W2_EARLY][4], f2[4];
            mbar_wait_once(sb + BAR_W, 1);
#pragma unroll
            for (int nb = 0; nb < W2_EARLY; nb++) {
                lds128(u[nb][0], u[nb][1], u[nb][2], u[nb][3], row + nb * 6144);
            }
            named_bar(12, NTHREADS);
            PROF(3);
            lds128(f2[0], f2[1], f2[2], f2[3], s_fac + rw * 64 + (lane >> 3) * 16);
            lds32(inv_rho2, s_red + RED_INV_RHO);
#pragma unroll
            for (int nb = 0; nb < 12; nb++) {
                uint32_t v[4];
                if (nb < W2_EARLY) { v[0] = u[nb % W2_EARLY][0]; v[1] = u[nb % W2_EARLY][1]; v[2] = u[nb % W2_EARLY][2]; v[3] = u[nb % W2_EARLY][3]; }
                else lds128(v[0], v[1], v[2], v[3], row + nb * 6144);
                sts128(row + nb * 6144, h_cut8(h_mul(v[0], f2[0])), h_cut8(h_mul(v[1], f2[1])), h_cut8(h_mul(v[2], f2[2])), h_cut8(h_mul(v[3], f2[3])));
            }
            fence_async();
            named_arrive(8, NTHREADS);
        }
    }
    uint32_t a[6][4], acc[24], rpar = 0, tile_off = here;
    const uint32_t bias_addr = sb + SM_BIASH + (lane & 3) * 96, lane16 = lane * 16, lane_off = ((lane >> 2) * CH + 8 * (lane & 3)) * 2;
    const uint32_t stage = sb + SM_RING + (spare + rank) % NSLOT * SLOT_BYTES + w4 * WARP_BYTES, bar_r = sb + BAR_R + warp_id * 8;
    auto load_bias = [&]() {
#pragma unroll
        for (int q = 0; q < 6; q++) lds128(acc[4 * q], acc[4 * q + 1], acc[4 * q + 2], acc[4 * q + 3], bias_addr + q * 16);
    };
    auto load_frags = [&]() {
#pragma unroll
        for (int s = 0; s < 6; s++) ldg128(a[s], reinterpret_cast<const char*>(out) + next_off + w4 * WARP_BYTES + lane16 + s * 512);
    };
    auto stage_x = [&]() {
        if (elect_one()) {
            mbar_expect_tx(bar_r, WARP_BYTES);
            bulk_load_stream(stage, reinterpret_cast<const char*>(x) + tile_off + w4 * WARP_BYTES, WARP_BYTES, bar_r);
        }
    };
    {
        named_bar(8 + rank, rank ? 256 : NTHREADS);
        if (rank == 0) PROF(4);
        load_bias();
        pin(k1); pin(k2); pin(k3);
        wg_fence();
        gemm2_chunk<288>(acc, k3, ds);
        wg_commit();
        gemm2_chunk<96>(acc, k1, ds);
        wg_commit();
        gemm2_chunk<192>(acc, k2, ds);
        wg_commit();
        stage_x();
        wg_wait<2>();
        uint32_t k0[24];
#pragma unroll
        for (int q = 0; q < 6; q++)
            lds128(k0[4 * q], k0[4 * q + 1], k0[4 * q + 2], k0[4 * q + 3], sb + SM_RING + cur.slot * SLOT_BYTES + w4 * REGION_BYTES + lane16 + q * 512);
        pin(k0);
        wg_fence();
        gemm2_chunk<0>(acc, k0, ds);
        wg_commit();
        if (rank < NCONS) named_arrive(9 + rank, 256);
        wg_wait<2>();
        load_frags();
        if (lane16 == 0) mbar_arrive(sb + BAR_PIN);
        mbar_wait(bar_r, rpar);
        wg_wait<0>();
    }
    auto lent = [&](uint32_t entry) { return &sc->lent[((wk.index * LENT + (entry & 3) - 1) * 4 + w4) * (24 * 32)]; };
    for (jt = rank - 4; jt < nrest; jt += 4) {
        if (jt >= zero) {
        tile_off = next_off;
        lds32(next_off, sb + SM_TILES + (jt + 4) * 4);
        if (tile_off & 3) {
            const uint4* src = lent(tile_off) + lane;
            tile_off &= ~3u;
            next_off = __shfl_sync(~0u, next_off, 0);
            stage_x();
            if (elect_one()) prefetch_l2(reinterpret_cast<const char*>(out) + next_off + w4 * WARP_BYTES, WARP_BYTES);
            load_bias();
#pragma unroll 1
            for (int half = 0; half < 2; half++, src += 12 * 32) {
                uint32_t gl[48];
#pragma unroll
                for (int s = 0; s < 12; s++) ldg128(reinterpret_cast<uint32_t (&)[4]>(gl[4 * s]), src + s * 32);
                if (!half) {
                    named_bar(4 + rank, 256);
                    named_arrive(4 + ((rank + 1) & 3), 256);
                }
                pin(gl);
                wg_fence();
#pragma unroll
                for (int s = 0; s < 12; s++) wgmma(acc, gl[4 * s], gl[4 * s + 1], gl[4 * s + 2], gl[4 * s + 3], ds.w2[12 * half + s], 1);
                wg_commit();
                wg_wait<0>();
            }
            load_frags();
            mbar_wait(bar_r, rpar);
        } else {
            uint32_t d0[12], d1[12], g0[12], g1[12];
            next_off = __shfl_sync(~0u, next_off, 0);
            const bool more = jt + 4 < nrest && !(next_off & 3);
            load_bias();
            wg_fence();
            gemm1_chunk<0>(d0, a, ds, 0);
            wg_commit();
            if (jt) named_bar(4 + rank, 256);
            gemm1_chunk<48>(d1, a, ds, 0);
            wg_commit();
            wg_wait<1>();
#define CNX_STEP(C, D, G)                                                   \
    gelu_to(G, D);                                                          \
    wg_fence();                                                             \
    if (C < 6) gemm1_chunk<48 * (C < 6 ? C + 2 : 0)>(D, a, ds, zero);      \
    gemm2_chunk<48 * C>(acc, G, ds);                                       \
    wg_commit();                                                            \
    if (C == 1 && jt + 1 < nrest) named_arrive(4 + ((rank + 1) & 3), 256); \
    wg_wait<(C < 7 ? 1 : 0)>();
            CNX_STEP(0, d0, g0)
            stage_x();
            if (elect_one()) {
                if (more) prefetch_l2(reinterpret_cast<const char*>(out) + next_off + w4 * WARP_BYTES, WARP_BYTES);
                else if (next_off & 3) prefetch_l2(lent(next_off), 24 * 32 * 16);
            }
            CNX_STEP(1, d1, g1)
            CNX_STEP(2, d0, g0)
            CNX_STEP(3, d1, g1)
            CNX_STEP(4, d0, g0)
            CNX_STEP(5, d1, g1)
            CNX_STEP(6, d0, g0)
#pragma unroll
            for (int s = 0; s < 6; s++) ldg128_if(more, a[s], reinterpret_cast<const char*>(out) + next_off + w4 * WARP_BYTES + lane16 + s * 512);
            if (lane16 == 0) mbar_arrive(sb + BAR_PIN);
            mbar_wait(bar_r, rpar);
            CNX_STEP(7, d1, g1)
#undef CNX_STEP
        }
        }
        {
            pin(acc);
            rpar ^= 1;
            uint4* op = reinterpret_cast<uint4*>(reinterpret_cast<char*>(out) + tile_off + w4 * WARP_BYTES + lane_off);
#pragma unroll
            for (int h = 0; h < 2; h++)
#pragma unroll
                for (int m = 0; m < 3; m++) {
                    uint32_t xin[4], o[4];
                    lds128(xin[0], xin[1], xin[2], xin[3], stage + lane_off + h * 1536 + m * 64);
#pragma unroll
                    for (int q = 0; q < 4; q++) {
                        const uint32_t v = acc[2 * (4 * m + q) + h];
                        o[q] = bf_fma(pack_bf2(h_lo(v), h_hi(v)), inv_rho2, xin[q]);
                    }
                    __stcs(op + h * 96 + m * 4, make_uint4(o[0], o[1], o[2], o[3]));
                }
            __syncwarp();
        }
    }
    PROF(5);
}

}

typedef CUresult (*EncodeTiledFn)(CUtensorMap*, CUtensorMapDataType, cuuint32_t, void*, const cuuint64_t*, const cuuint64_t*,
                                  const cuuint32_t*, const cuuint32_t*, CUtensorMapInterleave, CUtensorMapSwizzle,
                                  CUtensorMapL2promotion, CUtensorMapFloatOOBfill);

extern "C" void kernel_launch(void* const* d_in, const int* in_sizes, int n_in, void* d_out, int out_size) {
    using namespace cnx;
    static EncodeTiledFn encode = nullptr;
    static int num_sms = 0;
    static Scratch* scratch = nullptr;
    if (!encode) {
        void* fn = nullptr;
        cudaDriverEntryPointQueryResult qr;
        cudaGetDriverEntryPoint("cuTensorMapEncodeTiled", &fn, cudaEnableDefault, &qr);
        encode = (EncodeTiledFn)fn;
        cudaGetSymbolAddress((void**)&scratch, g_scratch);
        int dev = 0;
        cudaGetDevice(&dev);
        cudaDeviceGetAttribute(&num_sms, cudaDevAttrMultiProcessorCount, dev);
        if (num_sms > MAX_CTAS) num_sms = MAX_CTAS;
        cudaFuncSetAttribute(block_kernel, cudaFuncAttributeMaxDynamicSharedMemorySize, SM_TOTAL);
    }
    CUtensorMap tm;
    cuuint64_t dims[3] = {(cuuint64_t)CH, (cuuint64_t)IMG_W, (cuuint64_t)IMG_H};
    cuuint64_t strides[2] = {(cuuint64_t)CH * 2, (cuuint64_t)CH * 2 * IMG_W};
    cuuint32_t box[3] = {(cuuint32_t)CH, (cuuint32_t)REGION_PX, 1};
    cuuint32_t estr[3] = {1, 1, 1};
    encode(&tm, CU_TENSOR_MAP_DATA_TYPE_BFLOAT16, 3, d_in[0], dims, strides, box, estr, CU_TENSOR_MAP_INTERLEAVE_NONE,
           CU_TENSOR_MAP_SWIZZLE_NONE, CU_TENSOR_MAP_L2_PROMOTION_L2_128B, CU_TENSOR_MAP_FLOAT_OOB_FILL_NONE);
    Params pm = {};
    Descs& ds = pm.ds;
    for (int c = 0; c < 8; c++)
        for (int k = 0; k < 6; k++) ds.w1[c][k] = make_desc(SB + SM_W1 + c * 6 * 1536 + k * 256, 128, 1536);
    for (int k = 0; k < 24; k++) ds.w2[k] = make_desc(SB + SM_W2 + k * 256, 128, 6144);
    ds.ones = make_desc(SB + SM_ONES, 0, 0);
    CUtensorMap tw;
    cuuint64_t wdims[2] = {(cuuint64_t)EX, (cuuint64_t)CH};
    cuuint64_t wstrides[1] = {(cuuint64_t)EX * 2};
    cuuint32_t wbox[2] = {64, (cuuint32_t)CH};
    encode(&tw, CU_TENSOR_MAP_DATA_TYPE_BFLOAT16, 2, d_in[2], wdims, wstrides, wbox, estr, CU_TENSOR_MAP_INTERLEAVE_NONE,
           CU_TENSOR_MAP_SWIZZLE_128B, CU_TENSOR_MAP_L2_PROMOTION_L2_128B, CU_TENSOR_MAP_FLOAT_OOB_FILL_NONE);
    Split& sp = pm.sp;
    sp = {NTILES / num_sms, NTILES % num_sms, 1, 1 << 16, 0, {}};
    if (sp.per_cta + 9 > MAX_ROWS) return;
    if (sp.extra && sp.extra * (8 * LENT + 1) + W2_GROUPS / 2 <= num_sms && sp.per_cta >= 5 * LENT + 8) {
        sp.period = num_sms / sp.extra;
        sp.inv_period = 65535 / sp.period + 1;
        sp.lenders = sp.extra;
        for (int l = 0; l < sp.extra; l++) {
            const Work w = get_work((l + 1) * sp.period - sp.period / 2 - 1, sp);
            for (int e = 0; e < LENT; e++) sp.lent_off[l * LENT + e] = tile_offset(w.tile(e));
            if (w.nA < 2 * LENT) sp.lenders = 0;
        }
    }
    pm.x = (const __nv_bfloat16*)d_in[0];
    pm.dw = (const __nv_bfloat16*)d_in[1];
    pm.w2 = (const __nv_bfloat16*)d_in[3];
    pm.gamma = (const __nv_bfloat16*)d_in[4];
    pm.beta = (const __nv_bfloat16*)d_in[5];
    pm.out = (__nv_bfloat16*)d_out;
    pm.sc = scratch;
    block_kernel<<<num_sms, NTHREADS, SM_TOTAL>>>(tm, tw, pm);
}
```

```cpp
#include <cuda_runtime.h>
#include <cuda_bf16.h>
#include <cuda_fp16.h>
#include <cuda.h>
#include <stdint.h>

namespace cnx {

constexpr int IMG_H = 512, IMG_W = 512, CH = 96, EX = 384;
constexpr int TILE_W = 64;
constexpr int NTILES = (IMG_W / TILE_W) * IMG_H;
constexpr int NSLOT = 6;
constexpr int REGION_PX = 18;
constexpr int REGION_BYTES = REGION_PX * CH * 2;
constexpr int SLOT_BYTES = 4 * REGION_BYTES;
constexpr int A_LBO = 144, A_SBO = 12 * A_LBO;
constexpr int PREFETCH_ROWS = 3;
constexpr int NCONS = 3;
constexpr int CONS_THREADS = 128 * NCONS;
constexpr int NTHREADS = 128 + CONS_THREADS;
constexpr int MAX_ROWS = 52;
constexpr int TILE_BYTES = TILE_W * CH * 2, WARP_BYTES = TILE_BYTES / 4;
constexpr int ORDER_P = 3;
constexpr int W2_EARLY = 9;
static_assert(MAX_ROWS <= 128, "one table entry per producer thread");
static_assert(2 * A_SBO == REGION_BYTES && REGION_BYTES % 128 == 0, "region layout");

constexpr uint32_t SB = 1024;
constexpr int SM_W1 = 0;
constexpr int SM_W2 = SM_W1 + CH * EX * 2;
constexpr int SM_RING = SM_W2 + CH * EX * 2;
constexpr int SM_BIASH = SM_RING + NSLOT * SLOT_BYTES;
constexpr int SM_RED = SM_BIASH + 384;
constexpr int RED_MAX = 0, RED_LAUNCH = 48, RED_INV_RHO = 52, RED_JOB = 56;
constexpr int SM_TILES = SM_RED + 256;
constexpr int SM_ONES = SM_TILES + MAX_ROWS * 4;
constexpr int SM_BAR = SM_ONES + 128;
constexpr int BAR_X = SM_BAR;
constexpr int BAR_A = BAR_X + NSLOT * 4 * 8;
constexpr int BAR_E = BAR_A + NSLOT * 4 * 8;
constexpr int BAR_PIN = BAR_E + NSLOT * 4 * 8;
constexpr int BAR_W = BAR_PIN + 8;
constexpr int BAR_F = BAR_W + 6 * 8;
constexpr int BAR_R = BAR_F + 8;
constexpr int SM_TOTAL = BAR_R + 16 * 8;
constexpr int SM_FILTER = SM_RING + (NSLOT - 1) * SLOT_BYTES + 9 * 128;
constexpr int SM_SQ = SM_W2;
constexpr int SQ_ROW = 128 * 16, SQ_HALF = 6 * SQ_ROW;
static_assert(SM_ONES % 16 == 0 && SM_TOTAL <= 232448, "shared memory budget");

constexpr float KZ = 0.3292034911525734f;
constexpr uint32_t GELU_C2 = 0x40d940d9u;
constexpr float INV_2KZ = 0.5f / KZ;
constexpr uint32_t CONV_SCALE2 = 0x2f802f80u;
constexpr unsigned SPIN_LIMIT = 1u << 19;

constexpr int MAX_CTAS = 170;
constexpr int W2_GROUPS = EX / 8;
constexpr int LENT = 3, MAX_LENDERS = MAX_CTAS / (8 * LENT + 1);
struct Scratch {
    uint32_t w2h[EX * CH / 2];
    float w2max[EX];
    float bias[CH + 32];
    unsigned long long sums[EX / 4][32];
    __device__ __forceinline__ unsigned long long* sum(int e) { return &sums[e >> 2][e & 3]; }
    uint4 lent[MAX_LENDERS * LENT * 8 * 4 * 3 * 32];
    unsigned launch, pad0[31], early, pad1[31], prep, pad2[31], lent_out, pad3[31];
    unsigned job;
};
__device__ __align__(128) Scratch g_scratch;

#define PROF(k)

__device__ __forceinline__ uint32_t smem_u32(const void* p) { return (uint32_t)__cvta_generic_to_shared(p); }
__device__ __forceinline__ void mbar_init(uint32_t bar, uint32_t cnt) {
    asm volatile("mbarrier.init.shared::cta.b64 [%0], %1;" ::"r"(bar), "r"(cnt) : "memory");
}
__device__ __forceinline__ void mbar_arrive(uint32_t bar) {
    asm volatile("mbarrier.arrive.shared::cta.b64 _, [%0];" ::"r"(bar) : "memory");
}
__device__ __forceinline__ void mbar_expect_tx(uint32_t bar, uint32_t bytes) {
    asm volatile("mbarrier.arrive.expect_tx.shared::cta.b64 _, [%0], %1;" ::"r"(bar), "r"(bytes) : "memory");
}
__device__ __forceinline__ bool mbar_try(uint32_t bar, uint32_t par) {
    uint32_t ok;
    asm volatile("{\n.reg .pred p;\nmbarrier.try_wait.parity.shared::cta.b64 p, [%1], %2;\nselp.u32 %0, 1, 0, p;\n}\n"
                 : "=r"(ok) : "r"(bar), "r"(par) : "memory");
    return ok != 0;
}
__device__ __forceinline__ void mbar_wait(uint32_t bar, uint32_t par) {
    unsigned n = 0;
    while (!mbar_try(bar, par)) {
        if (++n > SPIN_LIMIT) __trap();
    }
}
__device__ __forceinline__ void mbar_wait_once(uint32_t bar, uint32_t par) {
    unsigned n = 0;
    bool ok;
#pragma unroll 1
    do {
        ok = mbar_try(bar, par);
        if (++n > SPIN_LIMIT) __trap();
    } while (!ok);
}
__device__ __forceinline__ bool elect_one() {
    uint32_t ok;
    asm volatile("{\n.reg .pred p;\nelect.sync _|p, 0xffffffff;\nselp.u32 %0, 1, 0, p;\n}\n" : "=r"(ok));
    return ok != 0;
}
__device__ __forceinline__ uint32_t opaque(uint32_t v) { return __shfl_sync(~0u, v, threadIdx.x & 31); }
__device__ __forceinline__ uint32_t lane_id() { uint32_t v; asm volatile("mov.u32 %0, %%laneid;" : "=r"(v)); return v; }
__device__ __forceinline__ uint32_t opaque_uniform(uint32_t v) { return __shfl_sync(~0u, v, 0); }
__device__ __forceinline__ void named_bar(int id, int n) { asm volatile("bar.sync %0, %1;" ::"r"(id), "r"(n) : "memory"); }
__device__ __forceinline__ void named_arrive(int id, int n) { asm volatile("bar.arrive %0, %1;" ::"r"(id), "r"(n) : "memory"); }
__device__ __forceinline__ void fence_async() { asm volatile("fence.proxy.async.shared::cta;" ::: "memory"); }
constexpr uint64_t EVICT_FIRST = 0x12F0000000000000ull;
__device__ __forceinline__ void tma_row(uint32_t dst, const CUtensorMap* tm, uint32_t bar, int x, int y) {
    asm volatile("cp.async.bulk.tensor.3d.shared::cluster.global.mbarrier::complete_tx::bytes.L2::cache_hint [%0], [%1, {%3, %4, %5}], [%2], %6;"
                 ::"r"(dst), "l"(tm), "r"(bar), "r"(0), "r"(x), "r"(y), "l"(EVICT_FIRST) : "memory");
}
__device__ __forceinline__ void bulk_load_stream(uint32_t dst, const void* src, uint32_t bytes, uint32_t bar) {
    asm volatile("cp.async.bulk.shared::cluster.global.mbarrier::complete_tx::bytes.L2::cache_hint [%0], [%1], %2, [%3], %4;"
                 ::"r"(dst), "l"(src), "r"(bytes), "r"(bar), "l"(EVICT_FIRST) : "memory");
}
__device__ __forceinline__ void prefetch_l2(const void* src, uint32_t bytes) {
    asm volatile("cp.async.bulk.prefetch.L2.global [%0], %1;" ::"l"(src), "r"(bytes) : "memory");
}
__device__ __forceinline__ void tma_2d(uint32_t dst, const CUtensorMap* tm, uint32_t bar, int x, int y) {
    asm volatile("cp.async.bulk.tensor.2d.shared::cluster.global.mbarrier::complete_tx::bytes [%0], [%1, {%3, %4}], [%2];"
                 ::"r"(dst), "l"(tm), "r"(bar), "r"(x), "r"(y) : "memory");
}
__device__ __forceinline__ void bulk_load(uint32_t dst, const void* src, uint32_t bytes, uint32_t bar) {
    asm volatile("cp.async.bulk.shared::cluster.global.mbarrier::complete_tx::bytes [%0], [%1], %2, [%3];"
                 ::"r"(dst), "l"(src), "r"(bytes), "r"(bar) : "memory");
}
__device__ __forceinline__ void wg_fence() { asm volatile("wgmma.fence.sync.aligned;" ::: "memory"); }
__device__ __forceinline__ void wg_commit() { asm volatile("wgmma.commit_group.sync.aligned;" ::: "memory"); }
template <int N> __device__ __forceinline__ void wg_wait() { asm volatile("wgmma.wait_group.sync.aligned %0;" ::"n"(N) : "memory"); }
template <int N> __device__ __forceinline__ void pin(uint32_t (&d)[N]) {
#pragma unroll
    for (int q = 0; q < N; q++) asm volatile("" : "+r"(d[q])::"memory");
}
__device__ __forceinline__ void stg128(void* p, const uint32_t (&v)[4]) {
    asm volatile("st.global.v4.u32 [%0], {%1, %2, %3, %4};" ::"l"(p), "r"(v[0]), "r"(v[1]), "r"(v[2]), "r"(v[3]) : "memory");
}
__device__ __forceinline__ void ldg128(uint32_t (&v)[4], const void* p) {
    asm volatile("ld.global.L1::no_allocate.v4.u32 {%0, %1, %2, %3}, [%4];" : "=r"(v[0]), "=r"(v[1]), "=r"(v[2]), "=r"(v[3]) : "l"(p) : "memory");
}
__device__ __forceinline__ void ldg128_if(bool on, uint32_t (&v)[4], const void* p) {
    asm volatile("{\n.reg .pred p;\nsetp.ne.b32 p, %5, 0;\n@p ld.global.L1::no_allocate.v4.u32 {%0, %1, %2, %3}, [%4];\n}\n"
                 : "+r"(v[0]), "+r"(v[1]), "+r"(v[2]), "+r"(v[3]) : "l"(p), "r"((int)on) : "memory");
}
__host__ __device__ constexpr uint64_t make_desc(uint32_t addr, uint32_t lbo, uint32_t sbo) {
    return (uint64_t)((addr & 0x3FFFF) >> 4) | ((uint64_t)(lbo >> 4) << 16) | ((uint64_t)(sbo >> 4) << 32);
}
__device__ __forceinline__ void wgmma(uint32_t (&d)[12], uint32_t a0, uint32_t a1, uint32_t a2, uint32_t a3, uint64_t db, int acc) {
    asm volatile("{\n.reg .pred p;\nsetp.ne.b32 p, %17, 0;\n"
                 "wgmma.mma_async.sync.aligned.m64n48k16.f16.f16.f16 "
                 "{%0, %1, %2, %3, %4, %5, %6, %7, %8, %9, %10, %11}, "
                 "{%12, %13, %14, %15}, %16, p, 1, 1, 0;\n}\n"
                 : "+r"(d[0]), "+r"(d[1]), "+r"(d[2]), "+r"(d[3]), "+r"(d[4]), "+r"(d[5]), "+r"(d[6]), "+r"(d[7]), "+r"(d[8]), "+r"(d[9]), "+r"(d[10]), "+r"(d[11])
                 : "r"(a0), "r"(a1), "r"(a2), "r"(a3), "l"(db), "r"(acc));
}
__device__ __forceinline__ void wgmma(uint32_t (&d)[24], uint32_t a0, uint32_t a1, uint32_t a2, uint32_t a3, uint64_t db, int acc) {
    asm volatile("{\n.reg .pred p;\nsetp.ne.b32 p, %29, 0;\n"
                 "wgmma.mma_async.sync.aligned.m64n96k16.f16.f16.f16 "
                 "{%0, %1, %2, %3, %4, %5, %6, %7, %8, %9, %10, %11, %12, %13, %14, %15, %16, %17, %18, %19, %20, %21, %22, %23}, "
                 "{%24, %25, %26, %27}, %28, p, 1, 1, 0;\n}\n"
                 : "+r"(d[0]), "+r"(d[1]), "+r"(d[2]), "+r"(d[3]), "+r"(d[4]), "+r"(d[5]), "+r"(d[6]), "+r"(d[7]), "+r"(d[8]), "+r"(d[9]), "+r"(d[10]), "+r"(d[11]), "+r"(d[12]), "+r"(d[13]), "+r"(d[14]), "+r"(d[15]), "+r"(d[16]), "+r"(d[17]), "+r"(d[18]), "+r"(d[19]), "+r"(d[20]), "+r"(d[21]), "+r"(d[22]), "+r"(d[23])
                 : "r"(a0), "r"(a1), "r"(a2), "r"(a3), "l"(db), "r"(acc));
}
template <int ACC>
__device__ __forceinline__ void wgmma_rowsum(float (&d)[4], const uint32_t (&a)[4], uint64_t ones) {
    asm volatile("{\n.reg .pred p;\nsetp.ne.b32 p, %9, 0;\n"
                 "wgmma.mma_async.sync.aligned.m64n8k16.f32.bf16.bf16 {%0, %1, %2, %3}, {%4, %5, %6, %7}, %8, p, 1, 1, 0;\n}\n"
                 : "+f"(d[0]), "+f"(d[1]), "+f"(d[2]), "+f"(d[3])
                 : "r"(a[0]), "r"(a[1]), "r"(a[2]), "r"(a[3]), "l"(ones), "n"(ACC));
}
__device__ __forceinline__ void ldsm4(uint32_t (&r)[4], uint32_t addr) {
    asm volatile("ldmatrix.sync.aligned.m8n8.x4.shared.b16 {%0, %1, %2, %3}, [%4];"
                 : "=r"(r[0]), "=r"(r[1]), "=r"(r[2]), "=r"(r[3]) : "r"(addr) : "memory");
}
__device__ __forceinline__ void ldsm4_t(uint32_t (&r)[4], uint32_t addr) {
    asm volatile("ldmatrix.sync.aligned.m8n8.x4.trans.shared.b16 {%0, %1, %2, %3}, [%4];"
                 : "=r"(r[0]), "=r"(r[1]), "=r"(r[2]), "=r"(r[3]) : "r"(addr) : "memory");
}
__device__ __forceinline__ void stsm4(uint32_t addr, uint32_t a, uint32_t b, uint32_t c, uint32_t d) {
    asm volatile("stmatrix.sync.aligned.m8n8.x4.shared.b16 [%0], {%1, %2, %3, %4};"
                 ::"r"(addr), "r"(a), "r"(b), "r"(c), "r"(d) : "memory");
}
__device__ __forceinline__ uint32_t transpose8x8(uint32_t v) {
    uint32_t d; asm volatile("movmatrix.sync.aligned.m8n8.trans.b16 %0, %1;" : "=r"(d) : "r"(v)); return d;
}
__device__ __forceinline__ void spin_until(const unsigned* counter, unsigned target) {
    unsigned n = 0, c;
    do {
        asm volatile("ld.acquire.gpu.global.u32 %0, [%1];" : "=r"(c) : "l"(counter) : "memory");
        if (++n > SPIN_LIMIT) __trap();
    } while ((int)(c - target) < 0);
}
__device__ __forceinline__ void signal(unsigned* counter) {
    __syncwarp();
    if (elect_one()) asm volatile("red.release.gpu.global.add.u32 [%0], 1;" ::"l"(counter) : "memory");
    __syncwarp();
}
__device__ __forceinline__ void lds128(uint32_t& a, uint32_t& b, uint32_t& c, uint32_t& d, uint32_t addr) {
    asm volatile("ld.shared.v4.u32 {%0, %1, %2, %3}, [%4];" : "=r"(a), "=r"(b), "=r"(c), "=r"(d) : "r"(addr) : "memory");
}
__device__ __forceinline__ void lds64(uint32_t& a, uint32_t& b, uint32_t addr) {
    asm volatile("ld.shared.v2.u32 {%0, %1}, [%2];" : "=r"(a), "=r"(b) : "r"(addr) : "memory");
}
__device__ __forceinline__ void lds32(uint32_t& a, uint32_t addr) {
    asm volatile("ld.shared.u32 %0, [%1];" : "=r"(a) : "r"(addr) : "memory");
}
__device__ __forceinline__ int ldsi(uint32_t addr) {
    uint32_t v;
    lds32(v, addr);
    return (int)v;
}
__device__ __forceinline__ float ldsf(uint32_t addr) {
    uint32_t v;
    lds32(v, addr);
    return __uint_as_float(v);
}
__device__ __forceinline__ void sts32(uint32_t addr, uint32_t a) {
    asm volatile("st.shared.u32 [%0], %1;" ::"r"(addr), "r"(a) : "memory");
}
__device__ __forceinline__ void sts128(uint32_t addr, uint32_t a, uint32_t b, uint32_t c, uint32_t d) {
    asm volatile("st.shared.v4.u32 [%0], {%1, %2, %3, %4};" ::"r"(addr), "r"(a), "r"(b), "r"(c), "r"(d) : "memory");
}
__device__ __forceinline__ void sts64(uint32_t addr, uint32_t a, uint32_t b) {
    asm volatile("st.shared.v2.u32 [%0], {%1, %2};" ::"r"(addr), "r"(a), "r"(b) : "memory");
}
__device__ __forceinline__ void anchor(uint32_t addr, uint32_t a, uint32_t b, uint32_t c, uint32_t d) {
    asm volatile("{\n.reg .pred p;\nsetp.eq.b32 p, %0, 0;\n@p st.shared.v4.u32 [%0], {%1, %2, %3, %4};\n}\n"
                 ::"r"(addr), "r"(a), "r"(b), "r"(c), "r"(d) : "memory");
}
__device__ __forceinline__ uint32_t bf_fma(uint32_t a, uint32_t b, uint32_t c) {
    uint32_t d; asm("fma.rn.bf16x2 %0, %1, %2, %3;" : "=r"(d) : "r"(a), "r"(b), "r"(c)); return d;
}
__device__ __forceinline__ uint32_t bf_mul(uint32_t a, uint32_t b) {
    uint32_t d; asm("mul.rn.bf16x2 %0, %1, %2;" : "=r"(d) : "r"(a), "r"(b)); return d;
}
__device__ __forceinline__ uint32_t bf_absmax(uint32_t a, uint32_t b) {
    uint32_t d; asm("max.xorsign.abs.bf16x2 %0, %1, %2;" : "=r"(d) : "r"(a), "r"(b)); return d;
}
__device__ __forceinline__ uint32_t h_fma(uint32_t a, uint32_t b, uint32_t c) {
    uint32_t d; asm("fma.rn.f16x2 %0, %1, %2, %3;" : "=r"(d) : "r"(a), "r"(b), "r"(c)); return d;
}
__device__ __forceinline__ uint32_t h_mul(uint32_t a, uint32_t b) {
    uint32_t d; asm("mul.rn.f16x2 %0, %1, %2;" : "=r"(d) : "r"(a), "r"(b)); return d;
}
__device__ __forceinline__ uint32_t h_cut8(uint32_t v) { return v & 0xfff8fff8u; }
constexpr float CUT_GAIN = 1.f + 0.4375f * 0.7213f / 128;
__device__ __forceinline__ uint32_t h_tanh(uint32_t a) {
    uint32_t d; asm("tanh.approx.f16x2 %0, %1;" : "=r"(d) : "r"(a)); return d;
}
__device__ __forceinline__ uint32_t pack_h2(float lo, float hi) {
    uint32_t d; asm("cvt.rn.f16x2.f32 %0, %1, %2;" : "=r"(d) : "f"(hi), "f"(lo)); return d;
}
__device__ __forceinline__ uint32_t pack_bf2(float lo, float hi) {
    uint32_t d; asm("cvt.rn.bf16x2.f32 %0, %1, %2;" : "=r"(d) : "f"(hi), "f"(lo)); return d;
}
__device__ __forceinline__ float bf_lo(uint32_t v) { return __uint_as_float(v << 16); }
__device__ __forceinline__ float bf_hi(uint32_t v) { return __uint_as_float(v & 0xffff0000u); }
__device__ __forceinline__ float h_lo(uint32_t v) { return __low2float(*reinterpret_cast<__half2*>(&v)); }
__device__ __forceinline__ float h_hi(uint32_t v) { return __high2float(*reinterpret_cast<__half2*>(&v)); }
__device__ __forceinline__ float warp_absmax(uint32_t v) {
    return __uint_as_float(__reduce_max_sync(~0u, max((v & 0x7fffu) << 16, v & 0x7fff0000u)));
}
__device__ __forceinline__ uint32_t gelu2(uint32_t z) {
    uint32_t p = h_fma(z, z, GELU_C2);
    uint32_t t = h_tanh(h_mul(z, p));
    return h_fma(z, t, z);
}
__device__ __forceinline__ float pow2i(int e) { return __uint_as_float((uint32_t)(e + 127) << 23); }
__device__ __forceinline__ int ilog2f(float v) {
    int e = (int)((__float_as_uint(v) >> 23) & 0xff) - 127;
    return max(-100, min(100, e));
}

__device__ __forceinline__ int bound_exp(float w1max) { return w1max > 0.f ? ilog2f(2.f * KZ * 96.f * w1max) : 0; }
__device__ __forceinline__ bool plain_squares(int e) { return (unsigned)(4 - e) <= 6; }
__device__ __forceinline__ int square_exp(int e) { return plain_squares(e) ? 0 : max(-14, min(4 - e, 14)); }
__device__ __forceinline__ int sum_exp(int e) { return max(-90, min(90, 33 - 2 * e)); }
__device__ __forceinline__ int row_exp(float m) { return 2 - ilog2f(m); }

struct Split {
    int per_cta, extra, period, inv_period, lenders;
    uint32_t lent_off[MAX_LENDERS * LENT];
    __host__ __device__ __forceinline__ int longer_before(int cta) const {
        const int n = (cta + period / 2) * inv_period >> 16;
        return n < extra ? n : extra;
    }
};
struct Work {
    int tA, tB, nA, nB, dir, rows, lent, index;
    __host__ __device__ __forceinline__ int tile(int j) const { return j < nA ? tA + dir * j : tB + dir * (j - nA); }
};
__host__ __device__ __forceinline__ Work get_work(int cta, const Split& sp) {
    Work w;
    const int before = sp.longer_before(cta), longer = sp.longer_before(cta + 1) - before;
    w.lent = longer && sp.lenders ? LENT : 0;
    w.index = before;
    const int t0 = cta * sp.per_cta + before, t1 = t0 + sp.per_cta + longer;
    const int tm = t1 < (t0 | 511) + 1 ? t1 : (t0 | 511) + 1;
    const bool swap = t1 > tm && t1 - tm < tm - t0, down = cta & 1;
    w.nA = swap ? t1 - tm : tm - t0;
    w.nB = t1 - t0 - w.nA;
    w.tA = down ? (swap ? tm : t0) : (swap ? t1 : tm) - 1;
    w.tB = down ? (swap ? t0 : tm) : (swap ? tm : t1) - 1;
    w.dir = down ? 1 : -1;
    w.rows = w.nA + 2 + (w.nB ? w.nB + 2 : 0);
    return w;
}
__device__ __forceinline__ int row_code(const Work& w, int i) {
    const bool in_a = i < w.nA + 2;
    const int t = in_a ? w.tA : w.tB;
    return ((t & 511) + w.dir * ((in_a ? i : i - (w.nA + 2)) - 1)) << 16 | (t >> 9) * TILE_W;
}
__host__ __device__ __forceinline__ uint32_t tile_offset(int tile) { return ((tile & 511) * IMG_W + (tile >> 9) * TILE_W) * (CH * 2); }
__device__ __forceinline__ int tile_order(int j, int n) {
    return j % ORDER_P == ORDER_P - 1 ? j / ORDER_P : n - 1 - (j - j / ORDER_P);
}
__device__ __forceinline__ void issue_region(const CUtensorMap* tm, uint32_t dst, uint32_t bar, int warp, int code) {
    mbar_expect_tx(bar, REGION_BYTES);
    tma_row(dst, tm, bar, (code & 0xffff) + (16 * warp - 1), code >> 16);
}

template <class Event>
__device__ __forceinline__ void conv_producer(const Work& wk, const CUtensorMap* tm, uint32_t sb, int warp, Event event) {
    const int lane = threadIdx.x & 31;
    const int j = lane & 15, grp = lane >> 4;
    const uint32_t reg0 = sb + SM_RING + warp * REGION_BYTES;
    const uint32_t bars = sb + SM_BAR + warp * 8;
    if (warp * 32 + lane < MAX_ROWS) {
        const int i = warp * 32 + lane, before = min(i / 5, wk.lent);
        const bool back = i % 5 == 0 && i > 0 && i / 5 <= wk.lent;
        sts32(sb + SM_TILES + i * 4, back ? tile_offset(wk.tile(before - 1)) | before
                                          : tile_offset(wk.tile(wk.lent + tile_order(i - before, wk.nA + wk.nB - 4 - wk.lent))));
    }
    const uint32_t ld64 = opaque(reg0 + grp * 8 * 192 + j * 8), ld32 = opaque(reg0 + grp * 8 * 192 + 128 + j * 4);
    const uint32_t st64 = opaque(reg0 + grp * A_SBO + (j >> 1) * A_LBO + (j & 1) * 8);
    const uint32_t st32 = opaque(reg0 + grp * A_SBO + (8 + (j >> 2)) * A_LBO + (j & 3) * 4);
    named_bar(0, NTHREADS);
    uint32_t w[3][3][3];
    mbar_wait_once(sb + BAR_F, 0);
#pragma unroll
    for (int tap = 0; tap < 9; tap++) {
        const uint32_t p = sb + SM_FILTER + (3 + wk.dir * 3 * (tap / 3 - 1) + tap % 3) * (CH * 2);
        lds64(w[tap / 3][tap % 3][0], w[tap / 3][tap % 3][1], p + 8 * j);
        lds32(w[tap / 3][tap % 3][2], p + 128 + 4 * j);
#pragma unroll
        for (int q = 0; q < 3; q++) w[tap / 3][tap % 3][q] = bf_mul(w[tap / 3][tap % 3][q], CONV_SCALE2);
    }
#pragma unroll
    for (int tap = 0; tap < 9; tap++) sts64(reg0 + (NSLOT - 1) * SLOT_BYTES + tap * 128 + j * 8, w[tap / 3][tap % 3][1], w[tap / 3][tap % 3][0]);
    named_bar(1, 128);
#pragma unroll
    for (int tap = 0; tap < 9; tap++) lds64(w[tap / 3][tap % 3][1], w[tap / 3][tap % 3][0], reg0 + (NSLOT - 1) * SLOT_BYTES + tap * 128 + j * 8);
    static_assert(2 * PREFETCH_ROWS == NSLOT && SLOT_BYTES % 32 == 0, "slot arithmetic");
    uint32_t bo = 0, so = 0, par = 0, pbo = PREFETCH_ROWS * 32, ppar = 1;
    int px, py;
    auto request = [&]() {
        mbar_wait_once(bars + (BAR_E - SM_BAR) + pbo, ppar);
        if (elect_one()) {
            mbar_expect_tx(bars + pbo, REGION_BYTES);
            tma_row(reg0 + pbo * (SLOT_BYTES / 32), tm, bars + pbo, px, py);
        }
    };
    auto advance = [&]() {
        bo += 32;
        so += SLOT_BYTES;
        if (bo == NSLOT * 32) { bo = 0; so = 0; par ^= 1; }
        pbo += 32;
        if (pbo == NSLOT * 32) { pbo = 0; ppar ^= 1; }
    };
    auto aim = [&](int row) {
        const int code = row_code(wk, row);
        px = (code & 0xffff) + (16 * warp - 1);
        py = code >> 16;
    };
    uint32_t accB[8][3], accC[8][3];
    int r = 0;
#pragma unroll 1
    while (r < wk.rows) {
        if (r == 0 || r == wk.nA + 2) {
            const uint32_t bo0 = bo;
            uint32_t bo1;
#pragma unroll 1
            for (int k = 0; k < 2; k++, r++) {
                mbar_wait_once(bars + bo, par);
                bo1 = bo;
                if (r >= 2) {
                    aim(r + PREFETCH_ROWS);
                    request();
                }
                advance();
            }
            const uint32_t so0 = bo0 * (SLOT_BYTES / 32), so1 = bo1 * (SLOT_BYTES / 32);
#pragma unroll
            for (int p = 0; p < 10; p++) {
                uint32_t u[3], v[3];
                lds64(u[0], u[1], so0 + ld64 + p * 192);
                lds32(u[2], so0 + ld32 + p * 192);
                lds64(v[0], v[1], so1 + ld64 + p * 192);
                lds32(v[2], so1 + ld32 + p * 192);
#pragma unroll
                for (int dx = 0; dx < 3; dx++) {
                    const int o = p - dx;
                    if (o < 0 || o > 7) continue;
#pragma unroll
                    for (int q = 0; q < 3; q++) {
                        accB[o][q] = bf_fma(v[q], w[1][dx][q], dx == 0 ? bf_mul(u[q], w[0][dx][q]) : bf_fma(u[q], w[0][dx][q], accB[o][q]));
                        accC[o][q] = dx == 0 ? bf_mul(v[q], w[0][dx][q]) : bf_fma(v[q], w[0][dx][q], accC[o][q]);
                    }
                }
            }
            anchor(ld64, accB[7][0], accB[7][1], accB[7][2], 0);
            __syncwarp();
            if (elect_one()) {
                mbar_arrive(bars + (BAR_A - SM_BAR) + bo0);
                mbar_arrive(bars + (BAR_E - SM_BAR) + bo0);
                mbar_arrive(bars + (BAR_A - SM_BAR) + bo1);
                mbar_arrive(bars + (BAR_E - SM_BAR) + bo1);
            }
        }
        int end = wk.rows;
        const int marks[4] = {wk.rows - PREFETCH_ROWS, wk.rows - 11, wk.nA + 2, wk.nA + 2 - PREFETCH_ROWS};
#pragma unroll
        for (int k = 0; k < 4; k++) end = marks[k] > r ? min(end, marks[k]) : end;
        const int fetch = opaque_uniform(end - wk.rows);
        aim(r + PREFETCH_ROWS);
        px = opaque_uniform(px);
        const int py_end = opaque_uniform(py + wk.dir * (end - r));
        r = end;
#pragma unroll 1
        do {
            mbar_wait(bars + bo, par);
            uint32_t out[8][3];
#pragma unroll
            for (int p = 0; p < 10; p++) {
                uint32_t xv[3];
                lds64(xv[0], xv[1], so + ld64 + p * 192);
                lds32(xv[2], so + ld32 + p * 192);
#pragma unroll
                for (int dx = 0; dx < 3; dx++) {
                    const int o = p - dx;
                    if (o < 0 || o > 7) continue;
#pragma unroll
                    for (int q = 2; q >= 0; q--) {
                        out[o][q] = bf_fma(xv[q], w[2][dx][q], dx == 0 ? accB[o][q] : out[o][q]);
                        accB[o][q] = bf_fma(xv[q], w[1][dx][q], dx == 0 ? accC[o][q] : accB[o][q]);
                        accC[o][q] = dx == 0 ? bf_mul(xv[q], w[0][dx][q]) : bf_fma(xv[q], w[0][dx][q], accC[o][q]);
                    }
                }
            }
            __syncwarp();
#pragma unroll
            for (int o = 7; o >= 0; o--) {
                sts64(so + st64 + o * 16, out[o][0], out[o][1]);
                sts32(so + st32 + o * 16, out[o][2]);
            }
            __syncwarp();
            if (elect_one()) mbar_arrive(bars + (BAR_A - SM_BAR) + bo);
            if (fetch) request();
            advance();
            py += wk.dir;
        } while (py != py_end);
        if (((wk.rows - r) & ~8) == PREFETCH_ROWS) event(wk.rows - r == PREFETCH_ROWS);
    }
}

template <bool SCALED, int K0 = 0, int K1 = 3>
__device__ __forceinline__ void gelu_sq(uint32_t (&d)[24], uint32_t (&keep)[24], uint32_t sq_addr, uint32_t scale2) {
    pin(d);
#pragma unroll
    for (int k = K0; k < K1; k++) {
        uint32_t hs[4];
        lds128(hs[0], hs[1], hs[2], hs[3], sq_addr + k * SQ_ROW);
#pragma unroll
        for (int q = 0; q < 4; q++) {
            uint32_t g0 = gelu2(d[8 * k + 2 * q]), g1 = gelu2(d[8 * k + 2 * q + 1]);
            keep[8 * k + 2 * q] = g0;
            keep[8 * k + 2 * q + 1] = g1;
            if (SCALED) { g0 = h_mul(g0, scale2); g1 = h_mul(g1, scale2); }
            hs[q] = h_fma(g1, g1, h_fma(g0, g0, hs[q]));
        }
        sts128(sq_addr + k * SQ_ROW, hs[0], hs[1], hs[2], hs[3]);
    }
}
__device__ __forceinline__ void gelu_sq_reg(uint32_t (&d)[24], uint32_t (&hs)[12]) {
    pin(d);
#pragma unroll
    for (int q = 0; q < 12; q++) {
        const uint32_t g0 = gelu2(d[2 * q]), g1 = gelu2(d[2 * q + 1]);
        hs[q] = h_fma(g1, g1, h_fma(g0, g0, hs[q]));
    }
}
__device__ __forceinline__ void gelu_to(uint32_t (&g)[12], uint32_t (&d)[12]) {
    pin(d);
#pragma unroll
    for (int q = 0; q < 12; q++) g[q] = gelu2(d[q]);
    pin(g);
}
__device__ __forceinline__ void load_tile(uint32_t (&raw)[6][4], uint32_t addr) {
#pragma unroll
    for (int s = 0; s < 6; s++) ldsm4(raw[s], addr + s * 2 * A_LBO);
}
template <class F>
__device__ __forceinline__ void layer_norm(uint32_t (&raw)[6][4], uint64_t ones, F meanwhile) {
    uint32_t sq[2][4];
#pragma unroll
    for (int s = 0; s < 6; s++)
#pragma unroll
        for (int q = 0; q < 4; q++) sq[s / 3][q] = s % 3 == 0 ? bf_mul(raw[s][q], raw[s][q]) : bf_fma(raw[s][q], raw[s][q], sq[s / 3][q]);
    float sum[4], ssq[4];
    wg_fence();
    wgmma_rowsum<0>(sum, raw[0], ones);
#pragma unroll
    for (int s = 1; s < 6; s++) wgmma_rowsum<1>(sum, raw[s], ones);
    wgmma_rowsum<0>(ssq, sq[0], ones);
    wgmma_rowsum<1>(ssq, sq[1], ones);
    wg_commit();
    meanwhile();
    wg_wait<0>();
    uint32_t sc[2], sh[2];
#pragma unroll
    for (int h = 0; h < 2; h++) {
        asm volatile("" : "+f"(sum[2 * h]), "+f"(ssq[2 * h])::"memory");
        constexpr float EPS = 1e-5f / (KZ * KZ) * 0x1p-64f;
        const float m = sum[2 * h] * (1.f / (CH * KZ));
        float rstd;
        asm("rsqrt.approx.ftz.f32 %0, %1;" : "=f"(rstd) : "f"(fmaxf(fmaf(-m, m, fmaf(ssq[2 * h], 1.f / (CH * KZ * KZ), EPS)), EPS)));
        rstd *= 0x1p-112f;
        sc[h] = pack_bf2(rstd, rstd);
        const float shift = sum[2 * h] * (-1.f / CH) * bf_hi(sc[h]);
        sh[h] = pack_bf2(shift, shift);
    }
#pragma unroll
    for (int s = 0; s < 6; s++)
#pragma unroll
        for (int q = 0; q < 4; q++) {
            const uint32_t v = bf_fma(raw[s][q], sc[q & 1], sh[q & 1]);
            asm("lop3.b32 %0, %1, %2, 0x80008000, 0xd8;" : "=r"(raw[s][q]) : "r"(v << 3), "r"(v));
        }
}
struct Cursor {
    int slot;
    uint32_t par;
    __device__ __forceinline__ void advance(int n) {
        slot += n;
        if (slot >= NSLOT) { slot -= NSLOT; par ^= 1; }
    }
};
struct Descs {
    uint64_t w1[8][6];
    uint64_t w2[24];
    uint64_t ones;
};
template <int E0, int N>
__device__ __forceinline__ void gemm1_chunk(uint32_t (&d)[N], const uint32_t (&a)[6][4], const Descs& ds, int zero) {
#pragma unroll
    for (int s = 0; s < 6; s++) wgmma(d, a[s][0], a[s][1], a[s][2], a[s][3], ds.w1[E0 / 48][s], s ? 1 : zero);
}
template <int E0, int N>
__device__ __forceinline__ void gemm2_chunk(uint32_t (&acc)[24], const uint32_t (&g)[N], const Descs& ds) {
#pragma unroll
    for (int s = 0; s < N / 4; s++) wgmma(acc, g[4 * s], g[4 * s + 1], g[4 * s + 2], g[4 * s + 3], ds.w2[E0 / 16 + s], 1);
}

struct __align__(64) Params {
    Split sp;
    int zero;
    const __nv_bfloat16 *x, *dw, *w2, *gamma, *beta;
    __nv_bfloat16* out;
    Scratch* sc;
    Descs ds;
};

__global__ void __launch_bounds__(NTHREADS, 1)
block_kernel(const __grid_constant__ CUtensorMap tmap, const __grid_constant__ CUtensorMap tmap_w1, const __grid_constant__ Params pm) {
    const Split& sp = pm.sp;
    const Descs& ds = pm.ds;
    const int& zero = pm.zero;
    const __nv_bfloat16 *const &x = pm.x, *const &dw = pm.dw, *const &w2 = pm.w2, *const &gamma = pm.gamma, *const &beta = pm.beta;
    __nv_bfloat16* const& out = pm.out;
    Scratch* const& sc = pm.sc;
    extern __shared__ __align__(1024) uint8_t smem[];
    constexpr uint32_t sb = SB;
    const int tid = threadIdx.x;
    const Work wk = get_work(blockIdx.x, sp);
    constexpr uint32_t s_red = sb + SM_RED;
    if (smem_u32(smem) != SB) __trap();

    const int warp_id = __shfl_sync(~0u, tid >> 5, 0);
    PROF(0);
    const int cw = warp_id - 4, wgi = cw >> 2, w4 = warp_id & 3;
    if (elect_one()) {
        static_assert(3 * NSLOT * 4 == 8 + 4 * 16 && BAR_F == BAR_W + 48, "barrier shares");
        const int b = warp_id - 8;
        const uint32_t bar = b < 0 ? sb + BAR_X + warp_id * 8 : b < 7 ? sb + BAR_W + b * 8 : sb + BAR_PIN;
        mbar_init(bar, 1);
#pragma unroll
        for (int k = 0; k < 4; k++) mbar_init(sb + BAR_X + (8 + 4 * warp_id + k) * 8, 1);
        mbar_init(sb + BAR_R + warp_id * 8, 1);
        fence_async();
        if (b < 0) {
            issue_region(&tmap, sb + SM_RING + warp_id * REGION_BYTES, bar, w4, ((wk.tA & 511) + wk.dir * wgi) << 16 | (wk.tA >> 9) * TILE_W);
        } else if (b < 6) {
            mbar_expect_tx(bar, 64 * CH * 2);
            tma_2d(sb + SM_W2 + b * (64 * CH * 2), &tmap_w1, bar, 64 * b, 0);
        } else if (b == 6) {
            mbar_expect_tx(bar, 9 * CH * 2);
            bulk_load(sb + SM_FILTER, dw, 9 * CH * 2, bar);
        }
    }
    __syncwarp();
    const int ntiles = wk.nA + wk.nB;
    const int rank = (wgi + wk.lent + 2 * (ntiles - 1)) % NCONS | (wgi >> 2 & 3);
    const int spare = wk.rows % NSLOT, spare2 = spare == NSLOT - 1 ? 0 : spare + 1;
    const uint32_t sq_base = sb + (wgi < 0 ? SM_RING + spare * SLOT_BYTES : SM_SQ + rank * 2 * SQ_HALF);
    const uint32_t sq_upper = wgi < 0 ? (spare2 - spare) * SLOT_BYTES : SQ_HALF;
    const uint32_t bar_a = sb + BAR_A + w4 * 8, bar_e = sb + BAR_E + w4 * 8;
    auto max_w1 = [&](uint32_t lane) { return __uint_as_float(__reduce_max_sync(~0u, lane < 4 * NCONS ? ldsi(s_red + RED_MAX + lane * 4) : 0)); };
    auto square_scale = [&](uint32_t lane) {
        const float f = pow2i(square_exp(bound_exp(max_w1(lane))));
        return pack_h2(f, f);
    };
    uint32_t a_addr, sq;
    const uint32_t sq_warp = sq_base + w4 * 512;
    auto set_addresses = [&]() {
        a_addr = opaque(sb + SM_RING + w4 * REGION_BYTES + ((tid >> 3) & 1) * A_SBO + ((tid >> 4) & 1) * A_LBO + (tid & 7) * 16);
        sq = opaque(sq_base + (tid & 127) * 16);
    };
    uint32_t turn, turn_end, so, so_sum, bo, bo_sum, off;
    auto set_run = [&](int j, int stop, int row) {
        const int slot = row % NSLOT, both = 2 * (row % 3) + 3;
        turn = opaque_uniform(row / 3);
        turn_end = opaque_uniform(row / 3 + (stop - j + NCONS - 1) / NCONS);
        so = opaque_uniform(slot * SLOT_BYTES);
        so_sum = opaque_uniform(both * SLOT_BYTES);
        bo = opaque_uniform(bar_a + slot * 32);
        bo_sum = opaque_uniform(2 * bar_a + both * 32);
        off = opaque_uniform(tile_offset(wk.tile(j)) + w4 * WARP_BYTES - sq_warp);
    };
    const int nrest = ntiles - 4;
    int jt;
    Cursor cur;
    int fast_from;
    if (warp_id < 4) {
        conv_producer(wk, &tmap, sb, warp_id, [&](bool second) {
            if (!second) {
                if (tid == 0) sts32(s_red + RED_JOB, wk.lent ? NTILES : atomicAdd(&sc->job, 1));
                if (blockIdx.x == 0) {
#pragma unroll 1
                    for (int e = tid; e < EX; e += 128) *sc->sum(e) = 0;
                    sc->bias[tid] = 0.f;
                }
                if (blockIdx.x == 0 || wk.lent) signal(&sc->early);
                __syncwarp();
            } else {
                const int piece = opaque_uniform(ldsi(s_red + RED_JOB)) - W2_GROUPS / 2, q = 2 * piece + W2_GROUPS + (w4 >> 1);
                if (piece < 8 * LENT * sp.lenders) {
                    spin_until(&sc->early, (ldsi(s_red + RED_LAUNCH) + 1) * 4 * (sp.lenders + 1));
                    if (elect_one()) {
                        if (piece >= 0) prefetch_l2(reinterpret_cast<const char*>(out) + sp.lent_off[piece / 8] + w4 * WARP_BYTES, WARP_BYTES);
                        else { prefetch_l2(w2 + 8 * q * CH, 8 * CH * 2); prefetch_l2(beta + 8 * q, 16); }
                    }
                }
            }
        });
        const int piece = opaque_uniform(ldsi(s_red + RED_JOB)) - W2_GROUPS / 2, q = 2 * piece + W2_GROUPS + (w4 >> 1);
        const bool prepares = piece < 0, helps = piece < 8 * LENT * sp.lenders;
        set_addresses();
        const int lane = lane_id(), g = lane >> 2, t = lane & 3;
        uint32_t a[6][4];
        unsigned short bt_raw;
        if (prepares) {
#pragma unroll
            for (int m = 0; m < 3; m++) ldg128(a[m], w2 + (8 * q + g) * CH + 32 * m + 8 * t);
            asm volatile("ld.global.nc.u16 %0, [%1];" : "=h"(bt_raw) : "l"(beta + 8 * q + g) : "memory");
        } else if (helps) {
#pragma unroll
            for (int s = 0; s < 6; s++) ldg128(a[s], reinterpret_cast<const char*>(out) + sp.lent_off[piece / 8] + w4 * WARP_BYTES + lane * 16 + s * 512);
        }
        mbar_wait_once(bar_e + spare2 * 32, (wk.rows - 5) / NSLOT & 1);
        mbar_wait_once(bar_e + spare * 32, (wk.rows - 6) / NSLOT & 1);
        named_bar(1, 128);
#pragma unroll
        for (int k = 0; k < 6; k++) { sts128(sq + k * SQ_ROW, 0, 0, 0, 0); sts128(sq + sq_upper + k * SQ_ROW, 0, 0, 0, 0); }
        if (prepares) {
            const int half = w4 & 1;
            uint32_t rmax = 0;
#pragma unroll
            for (int m = 0; m < 3; m++) rmax = bf_absmax(bf_absmax(rmax, bf_absmax(a[m][0], a[m][1])), bf_absmax(a[m][2], a[m][3]));
            uint2 u = half ? make_uint2(a[0][2], a[0][3]) : make_uint2(a[0][0], a[0][1]), u1 = half ? make_uint2(a[1][2], a[1][3]) : make_uint2(a[1][0], a[1][1]);
            const uint2 u2 = half ? make_uint2(a[2][2], a[2][3]) : make_uint2(a[2][0], a[2][1]);
            const float bt = bf_lo(bt_raw);
            rmax = bf_absmax(rmax, __shfl_xor_sync(~0u, rmax, 1));
            rmax = bf_absmax(rmax, __shfl_xor_sync(~0u, rmax, 2));
            const float mx = fmaxf(fabsf(bf_lo(rmax)), fabsf(bf_hi(rmax))), rs = pow2i(row_exp(mx));
            if (t == 0 && !half) sc->w2max[8 * q + g] = mx;
#pragma unroll 1
            for (int m = 0; m < 3; m++, u = u1, u1 = u2) {
                float f[4];
#pragma unroll
                for (int k = 0; k < 2; k++) {
                    const float lo = bf_lo(k ? u.y : u.x), hi = bf_hi(k ? u.y : u.x);
                    sc->w2h[(4 * m + 2 * half + k) * 1536 + q * 32 + lane] = transpose8x8(pack_h2(lo * rs, hi * rs));
                    f[2 * k] = lo * bt;
                    f[2 * k + 1] = hi * bt;
                }
                const float r0 = (g & 2 ? f[2] : f[0]) + __shfl_xor_sync(~0u, g & 2 ? f[0] : f[2], 8);
                const float r1 = (g & 2 ? f[3] : f[1]) + __shfl_xor_sync(~0u, g & 2 ? f[1] : f[3], 8);
                float r = (g & 1 ? r1 : r0) + __shfl_xor_sync(~0u, g & 1 ? r0 : r1, 4);
                r += __shfl_xor_sync(~0u, r, 16);
                if (g < 4) atomicAdd(&sc->bias[32 * m + 8 * t + 4 * half + g], r);
            }
            asm volatile("fence.proxy.async.global;" ::: "memory");
            signal(&sc->prep);
        } else
        if (helps) {
            uint32_t d[12], gl[12];
            const uint32_t scale2 = square_scale(lane);
            wg_fence();
#pragma unroll
            for (int s = 0; s < 6; s++) wgmma(d, a[s][0], a[s][1], a[s][2], a[s][3], ds.w1[0][s] + piece % 8 * (6 * 1536 / 16), s ? 1 : 0);
            wg_commit();
            wg_wait<0>();
            gelu_to(gl, d);
#pragma unroll
            for (int s = 0; s < 3; s++) {
                sc->lent[((piece / 8 * 4 + w4) * 24 + piece % 8 * 3 + s) * 32 + lane] = make_uint4(gl[4 * s], gl[4 * s + 1], gl[4 * s + 2], gl[4 * s + 3]);
                uint32_t hs[2];
#pragma unroll
                for (int k = 0; k < 2; k++) {
                    const uint32_t g0 = h_mul(gl[4 * s + 2 * k], scale2), g1 = h_mul(gl[4 * s + 2 * k + 1], scale2);
                    hs[k] = h_fma(g1, g1, h_mul(g0, g0));
                }
                const int pair = piece % 4 * 3 + s;
                sts64(sq + (piece & 4 ? sq_upper : 0) + (pair >> 1) * SQ_ROW + (pair & 1) * 8, hs[0], hs[1]);
            }
        }
        jt = ntiles - 1;
        cur.slot = spare ? spare - 1 : NSLOT - 1;
        cur.par = (wk.rows - 1) / NSLOT & 1;
        fast_from = ntiles;
        turn = turn_end = so = so_sum = bo = bo_sum = off = rank;
    } else {
        set_addresses();
        if (wgi == NCONS - 1) named_arrive(4, 256);
        set_run(wk.lent + wgi, min(wk.nA, nrest), wk.lent + wgi + 2);
        jt = wgi < wk.lent ? wgi : wk.lent + wgi;
        cur = {2, 0};
        cur.advance(jt + (jt >= wk.nA ? 2 : 0));
        {
            const int ct = tid - 128, lane = tid & 31;
            const unsigned epoch = *reinterpret_cast<volatile unsigned*>(&sc->launch);
            const int r = lane & 7, mi = lane >> 3;
            const uint32_t src = sb + SM_W2 + (cw >> 1) * (64 * CH * 2) + r * 128 + ((((cw & 1) * 4 + mi) ^ r) * 16);
            const uint32_t dst = sb + SM_W1 + (4 * cw + mi) * 1536 + r * 16;
            const int code = row_code(wk, PREFETCH_ROWS - 1 + wgi);
            named_bar(0, NTHREADS);
            auto request = [&]() {
                if (elect_one())
                    issue_region(&tmap, sb + SM_RING + (PREFETCH_ROWS - 1 + wgi) * SLOT_BYTES + w4 * REGION_BYTES, sb + BAR_X + (cw + 8) * 8, w4, code);
                __syncwarp();
            };
#pragma unroll 1
            for (int k = 0; k < 2; k++) {
                if (wgi == k) request();
                mbar_wait_once(sb + BAR_W + (cw >> 1) * 8, 0);
            }
            uint32_t wmax[2] = {}, wsum[4] = {};
#pragma unroll 3
            for (int c = 0; c < 12; c++) {
                uint32_t u[4];
                ldsm4_t(u, src + c * 1024);
#pragma unroll
                for (int q = 0; q < 4; q++) {
                    wmax[q & 1] = bf_absmax(wmax[q & 1], u[q]);
                    wsum[q] = bf_fma(u[q], 0x3f803f80u, wsum[q]);
                    u[q] = pack_h2(__uint_as_float(u[q] * (65536 + zero)), bf_hi(u[q]));
                }
                stsm4(dst + c * 128, u[0], u[1], u[2], u[3]);
            }
            const float w1max = warp_absmax(bf_absmax(wmax[0], wmax[1]));
            if (lane == 0) sts32(s_red + RED_MAX + cw * 4, __float_as_uint(w1max));
            bool center = false;
#pragma unroll
            for (int q = 0; q < 4; q++) {
#pragma unroll
                for (int o = 1; o <= 2; o <<= 1) wsum[q] = bf_fma(__shfl_xor_sync(~0u, wsum[q], o), 0x3f803f80u, wsum[q]);
                center |= fabsf(bf_lo(wsum[q]) + bf_hi(wsum[q])) > (0.15f * CH) * w1max;
            }
            if (__builtin_expect(__any_sync(~0u, center), 0)) {
                float mean[4] = {};
#pragma unroll 1
                for (int pass = 0; pass < 2; pass++) {
                    float sum[4] = {};
#pragma unroll 1
                    for (int c = 0; c < 12; c++) {
                        uint32_t u[4];
                        ldsm4_t(u, src + c * 1024);
#pragma unroll
                        for (int q = 0; q < 4; q++) {
                            sum[q] += bf_lo(u[q]) + bf_hi(u[q]);
                            u[q] = pack_h2(bf_lo(u[q]) - mean[q], bf_hi(u[q]) - mean[q]);
                        }
                        stsm4(dst + c * 128, u[0], u[1], u[2], u[3]);
                    }
#pragma unroll
                    for (int q = 0; q < 4; q++) {
                        sum[q] += __shfl_xor_sync(~0u, sum[q], 1);
                        sum[q] += __shfl_xor_sync(~0u, sum[q], 2);
                        mean[q] = sum[q] * (1.f / CH);
                    }
                }
            }
            if (!(cw & 2)) {
#pragma unroll
                for (int c = 0; c < 12; c++) sts128(src + c * 1024, 0, 0, 0, 0);
            }
            if (ct < 32) sts32(sb + SM_ONES + ct * 4, 0x3f803f80u);
            if (ct == 0) sts32(s_red + RED_LAUNCH, epoch);
            fence_async();
            named_bar(2, CONS_THREADS);
            if (wgi == 2) request();
        }
        PROF(1);
        if (cur.par) mbar_wait_once(bar_a, 0);
        fast_from = wk.lent;
        if (!__all_sync(~0u, plain_squares(bound_exp(max_w1(lane_id()))))) {
            fast_from = ntiles;
#pragma unroll 1
            for (int q = 0; q < 6; q++) sts128(sq + SQ_HALF + q * SQ_ROW, 0, 0, 0, 0);
        }
    }
    uint32_t k1[24], k2[24], k3[24];
    uint32_t here;
    constexpr int SQC = 3 * SQ_ROW;
    auto store_at = [&](const uint32_t (&a)[6][4], uint32_t off) {
        char* ap = reinterpret_cast<char*>(out) + (off + sq);
#pragma unroll
        for (int s = 0; s < 6; s++) stg128(ap + s * 512, a[s]);
    };
    const uint32_t own_bar = 4 + wgi, next_bar = 4 + (wgi == NCONS - 1 ? 0 : wgi + 1);
    for (;;) {
        if (jt >= fast_from) {
            uint32_t hs2[12] = {}, hs3[12] = {};
            const uint32_t step = wk.dir * (NCONS * IMG_W * CH * 2);
            int second = wk.nB;
#pragma unroll 1
            for (;;) {
#pragma unroll 1
                while (turn != turn_end) {
                    uint32_t a[6][4], d0[24], d1[24], unused[24];
                    mbar_wait(bo, turn >> 1 & 1);
                    load_tile(a, a_addr + so);
                    layer_norm(a, ds.ones, [&]() { named_bar(own_bar, 256); });
                    wg_fence();
                    gemm1_chunk<0>(d0, a, ds, 0);
                    wg_commit();
                    gemm1_chunk<96>(d1, a, ds, 0);
                    wg_commit();
                    wg_wait<1>();
                    gelu_sq<false, 0, 1>(d0, unused, sq, 0);
                    gelu_sq<false, 1, 2>(d0, unused, sq, 0);
                    store_at(a, off);
                    gelu_sq<false, 2, 3>(d0, unused, sq, 0);
                    if (elect_one()) mbar_arrive(bo + (BAR_E - BAR_A));
                    wg_fence();
                    gemm1_chunk<192>(d0, a, ds, zero);
                    wg_commit();
                    named_arrive(next_bar, 256);
                    wg_wait<1>();
                    gelu_sq<false, 0, 1>(d1, unused, sq + SQC, 0);
                    gelu_sq<false, 1, 3>(d1, unused, sq + SQC, 0);
                    wg_fence();
                    gemm1_chunk<288>(d1, a, ds, zero);
                    wg_commit();
                    wg_wait<1>();
                    gelu_sq_reg(d0, hs2);
                    anchor(sq, hs2[8], hs2[9], hs2[10], hs2[11]);
                    wg_wait<0>();
                    gelu_sq_reg(d1, hs3);
                    so = so_sum - so;
                    bo = bo_sum - bo;
                    off += step;
                    turn++;
                }
                if (!second) break;
                const int j = ntiles - second + (rank + second + 2) % NCONS;
                second = 0;
                set_run(j, nrest, j + 4);
            }
            jt = nrest + rank;
            cur.slot = (bo - bar_a) >> 5;
            cur.par = turn >> 1 & 1;
#pragma unroll
            for (int k = 0; k < 3; k++) {
                sts128(sq + SQ_HALF + k * SQ_ROW, hs2[4 * k], hs2[4 * k + 1], hs2[4 * k + 2], hs2[4 * k + 3]);
                sts128(sq + SQ_HALF + SQC + k * SQ_ROW, hs3[4 * k], hs3[4 * k + 1], hs3[4 * k + 2], hs3[4 * k + 3]);
            }
        }
        const bool last = jt >= nrest;
        here = tile_offset(wk.tile(jt));
        if (last) {
            const uint32_t next = ldsi(sb + SM_TILES + rank * 4);
            if (elect_one()) {
                prefetch_l2(reinterpret_cast<const char*>(x) + here + w4 * WARP_BYTES, WARP_BYTES);
                if (rank == ORDER_P - 1) prefetch_l2(reinterpret_cast<const char*>(out) + next + w4 * WARP_BYTES, WARP_BYTES);
            }
        }
        uint32_t a[6][4], d0[24], d1[24], d3[24], k0[24];
        mbar_wait_once(bar_a + cur.slot * 32, cur.par);
        load_tile(a, a_addr + cur.slot * SLOT_BYTES);
        layer_norm(a, ds.ones, [&]() { if (jt >= wk.lent && wgi >= 0) named_bar(own_bar, 256); });
        if (!last) {
            store_at(a, here + w4 * WARP_BYTES - sq_warp);
            __syncwarp();
            if (elect_one()) mbar_arrive(bar_e + cur.slot * 32);
            if (jt < wk.lent) {
                jt += LENT;
                cur.advance(LENT);
                continue;
            }
        }
        wg_fence();
        gemm1_chunk<0>(d0, a, ds, 0);
        wg_commit();
        gemm1_chunk<96>(d1, a, ds, 0);
        wg_commit();
        const uint32_t scale2 = square_scale(lane_id());
        wg_wait<1>();
        gelu_sq<true>(d0, k0, sq, scale2);
        if (last) {
#pragma unroll
            for (int q = 0; q < 6; q++)
                sts128(sb + SM_RING + cur.slot * SLOT_BYTES + w4 * REGION_BYTES - sq_warp + sq + q * 512, k0[4 * q], k0[4 * q + 1], k0[4 * q + 2], k0[4 * q + 3]);
        }
        wg_fence();
        gemm1_chunk<192>(d0, a, ds, zero);
        wg_commit();
        if (jt + 2 < ntiles) named_arrive(next_bar, 256);
        wg_wait<1>();
        gelu_sq<true>(d1, k1, sq + SQC, scale2);
        wg_fence();
        gemm1_chunk<288>(d3, a, ds, 0);
        wg_commit();
        wg_wait<1>();
        gelu_sq<true>(d0, k2, sq + sq_upper, scale2);
        wg_wait<0>();
        gelu_sq<true>(d3, k3, sq + sq_upper + SQC, scale2);
        if (last) break;
        cur.advance(NCONS + ((jt < wk.nA && jt + NCONS >= wk.nA) ? 2 : 0));
        jt += NCONS;
    }
    const uint32_t lane = lane_id();
    uint32_t next_off = opaque_uniform(ldsi(sb + SM_TILES + rank * 4));
    const uint32_t s_fac = sb + SM_RING + spare * SLOT_BYTES + SQ_HALF;
    uint32_t inv_rho2;
    {
        if (rank == 0) {
            const int g = lane >> 2, t = lane & 3, i0 = w4 * 32 + lane;
            const bool leader = i0 == 0;
            const uint32_t pick = (g & 1) == (t & 1) ? (g & 2 ? 0x3c000000u : 0x00003c00u) : 0;
            const int be = bound_exp(max_w1(lane));
            const float to_fixed = pow2i(sum_exp(be) - 2 * square_exp(be));
            const uint32_t two_rows = sb + (w4 * 3 + (lane >> 3 & 1)) * SQ_ROW + ((lane >> 4) * 8 + (lane & 7)) * 16;
            const uint32_t third_row = sb + (w4 * 3 + 2) * SQ_ROW + lane * 16;
            unsigned short gam_raw[3];
            float rmax[3], f[3][4] = {};
            float2 bpair = make_float2(0.f, 0.f);
#pragma unroll 1
            for (int i = 0; i < 4; i++) {
                if (i == 1 && leader) {
                    spin_until(&sc->prep, (ldsi(s_red + RED_LAUNCH) + 1) * (W2_GROUPS * 2));
                    asm volatile("fence.proxy.async.global;" ::: "memory");
                    mbar_expect_tx(sb + BAR_W, 6 * SQ_HALF);
                }
                __syncwarp();
                named_bar(2, 128);
                if (i && leader) {
                    fence_async();
                    bulk_load(sb + SM_W2 + (i - 1) * 2 * SQ_HALF, reinterpret_cast<const char*>(sc->w2h) + (i - 1) * 2 * SQ_HALF, 2 * SQ_HALF, sb + BAR_W);
                }
                if (i == 1) {
#pragma unroll
                    for (int m = 0; m < 3; m++) {
                        asm volatile("ld.global.nc.u16 %0, [%1];" : "=h"(gam_raw[m]) : "l"(gamma + i0 + 128 * m) : "memory");
                        asm volatile("ld.global.cg.f32 %0, [%1];" : "=f"(rmax[m]) : "l"(&sc->w2max[i0 + 128 * m]) : "memory");
                    }
                    if (i0 < 96)
                        asm volatile("ld.global.cg.v2.f32 {%0, %1}, [%2];" : "=f"(bpair.x), "=f"(bpair.y)
                                     : "l"(&sc->bias[32 * (i0 % 24 >> 3) + 8 * (i0 / 24) + (i0 % 24 & 6)]) : "memory");
                }
                __syncwarp();
                const uint32_t from = i < NCONS ? SM_SQ + i * 2 * SQ_HALF : w4 < 2 ? SM_RING + spare * SLOT_BYTES : SM_RING + spare2 * SLOT_BYTES - SQ_HALF;
                if (i) named_bar(12 + i, 256);
#pragma unroll
                for (int r = 0; r < 12; r++) {
                    uint32_t u[4];
                    ldsm4_t(u, from + (r % 3 == 2 ? third_row + r / 3 * 512 : two_rows + (r / 3 * 2 + r % 3) * 256));
                    asm volatile("mma.sync.aligned.m16n8k16.row.col.f32.f16.f16.f32 {%0, %1, %2, %3}, {%4, %5, %6, %7}, {%8, %8}, {%0, %1, %2, %3};"
                                 : "+f"(f[r % 3][0]), "+f"(f[r % 3][1]), "+f"(f[r % 3][2]), "+f"(f[r % 3][3])
                                 : "r"(u[0]), "r"(u[1]), "r"(u[2]), "r"(u[3]), "r"(pick));
                }
            }
            unsigned long long* dst = sc->sum(96 * w4 + 8 * (g >> 1) + 2 * (t & 1) + (g & 1));
#pragma unroll
            for (int r = 0; r < 3; r++) {
                const float tot = r < 2 ? (t < 2 ? f[0][r & 1] + f[1][r & 1] : f[0][r + 2 & 3] + f[1][r + 2 & 3]) : (t < 2 ? f[2][0] + f[2][2] : f[2][1] + f[2][3]);
                atomicAdd(dst + (r < 2 ? (t >> 1) * 8 + r : 16 + (t >> 1)) * 32, __float2ull_rn(fminf(tot * to_fixed, 0x1p47f)) << 8 | 1);
            }
            PROF(2);
            float base[3], slope[3], reach[3];
            const float w1max = max_w1(lane);
            const float gbound = fmaxf(2.f * KZ * 9.7979590f * 192.f * w1max, 1.f) * 19.5959180f * INV_2KZ;
            const unsigned fixed = __reduce_max_sync(~0u, __float_as_uint(fmaf(gbound, fmaxf(fmaxf(rmax[0], rmax[1]), rmax[2]), fmaxf(fabsf(bpair.x), fabsf(bpair.y)))));
            if (lane == 0) sts32(s_red + 96 + w4 * 4, fixed);
#pragma unroll
            for (int m = 0; m < 3; m++) {
                base[m] = rmax[m] > 0.f ? pow2i(-row_exp(rmax[m])) * (INV_2KZ * CUT_GAIN) : 0.f;
                slope[m] = base[m] * bf_lo(gam_raw[m]);
                reach[m] = fabsf(bf_lo(gam_raw[m])) * rmax[m] * gbound;
            }
            const float to_square = pow2i(-sum_exp(bound_exp(w1max))) * (INV_2KZ * INV_2KZ / 256);
#pragma unroll
            for (int m = 0; m < 3; m++) anchor(sq, __float_as_uint(base[m]), __float_as_uint(slope[m]), __float_as_uint(reach[m]), __float_as_uint(to_square));
            const unsigned epoch = ldsi(s_red + RED_LAUNCH);
            const uint32_t own_sum = (i0 >> 2) * 256 + (i0 & 3) * 8, own_fac = s_fac + i0 * 2;
            auto peek = [&](const void* p) {
                unsigned long long v;
                asm volatile("ld.relaxed.gpu.global.u64 %0, [%1];" : "=l"(v) : "l"(p) : "memory");
                return v;
            };
            const char* mine = reinterpret_cast<const char*>(sc->sums) + own_sum;
            unsigned n = 0;
            while (((unsigned)peek(sc->sum((blockIdx.x * 4 + w4) % (EX / 4) * 4)) & 255u) != gridDim.x)
                if (++n > SPIN_LIMIT) __trap();
            unsigned long long sum[3];
            for (;;) {
                bool all = true;
#pragma unroll
                for (int m = 0; m < 3; m++) {
                    sum[m] = peek(mine + m * (32 * 256));
                    all &= ((unsigned)sum[m] & 255u) == gridDim.x;
                }
                if (__all_sync(~0u, all)) break;
                if (++n > SPIN_LIMIT) __trap();
            }
            PROF(3);
            float gx[3];
#pragma unroll
            for (int m = 0; m < 3; m++) asm("sqrt.approx.ftz.f32 %0, %1;" : "=f"(gx[m]) : "f"(fmaf(__ull2float_rn(sum[m]), to_square, 1e-6f)));
            float tot = gx[0] + gx[1] + gx[2];
#pragma unroll
            for (int o = 16; o >= 1; o >>= 1) tot += __shfl_xor_sync(~0u, tot, o);
            const unsigned vwarp = __reduce_max_sync(~0u, __float_as_uint(fmaxf(fmaxf(reach[0] * gx[0], reach[1] * gx[1]), reach[2] * gx[2])));
            if (lane == 0) { sts32(s_red + 64 + w4 * 4, __float_as_uint(tot)); sts32(s_red + 80 + w4 * 4, vwarp); }
            named_bar(2, 128);
            uint32_t u[4], v[4], w[4];
            lds128(u[0], u[1], u[2], u[3], s_red + 64);
            lds128(v[0], v[1], v[2], v[3], s_red + 80);
            lds128(w[0], w[1], w[2], w[3], s_red + 96);
            tot = (__uint_as_float(u[0]) + __uint_as_float(u[1])) + (__uint_as_float(u[2]) + __uint_as_float(u[3]));
            const float vmax = __uint_as_float(max(max(v[0], v[1]), max(v[2], v[3]))), fmax2 = __uint_as_float(max(max(w[0], w[1]), max(w[2], w[3])));
            float inv_mean;
            asm("rcp.approx.ftz.f32 %0, %1;" : "=f"(inv_mean) : "f"(fmaf(tot, 1.f / EX, 1e-6f)));
            const int rho_e = 14 - ilog2f(fmaf(vmax, inv_mean, 2.f * fmax2));
            const float rho = pow2i(rho_e), inv_rho = pow2i(-rho_e);
            inv_rho2 = pack_bf2(inv_rho, inv_rho);
#pragma unroll
            for (int m = 0; m < 3; m++) {
                const float f = fmaf(slope[m] * gx[m], inv_mean, base[m]) * rho;
                asm volatile("st.shared.u16 [%0], %1;" ::"r"(own_fac + 256 * m), "h"((unsigned short)pack_h2(f, 0.f)) : "memory");
            }
            if (i0 < 96) sts32(sb + SM_BIASH + i0 * 4, pack_h2(bpair.x * rho, bpair.y * rho));
            if (i0 == 96) sts32(s_red + RED_INV_RHO, inv_rho2);
            named_arrive(12, NTHREADS);
            if (blockIdx.x == 0 && leader) { sc->launch = epoch + 1; sc->job = 0; }
            if (wk.lent) spin_until(&sc->lent_out, (epoch + 1) * 32 * LENT * sp.lenders);
        } else {
            named_arrive(12 + rank, 256);
            if (rank == NCONS && (unsigned)(ldsi(s_red + RED_JOB) - W2_GROUPS / 2) < 8 * LENT * sp.lenders) signal(&sc->lent_out);
            const int rw = rank * 4 - 4 + w4;
            const uint32_t row = sb + SM_W2 + rw * 512 + lane * 16;
            uint32_t u[W2_EARLY][4], f2[4];
            mbar_wait_once(sb + BAR_W, 1);
#pragma unroll
            for (int nb = 0; nb < W2_EARLY; nb++) {
                lds128(u[nb][0], u[nb][1], u[nb][2], u[nb][3], row + nb * 6144);
            }
            named_bar(12, NTHREADS);
            PROF(3);
            lds128(f2[0], f2[1], f2[2], f2[3], s_fac + rw * 64 + (lane >> 3) * 16);
            lds32(inv_rho2, s_red + RED_INV_RHO);
#pragma unroll
            for (int nb = 0; nb < 12; nb++) {
                uint32_t v[4];
                if (nb < W2_EARLY) { v[0] = u[nb % W2_EARLY][0]; v[1] = u[nb % W2_EARLY][1]; v[2] = u[nb % W2_EARLY][2]; v[3] = u[nb % W2_EARLY][3]; }
                else lds128(v[0], v[1], v[2], v[3], row + nb * 6144);
                sts128(row + nb * 6144, h_cut8(h_mul(v[0], f2[0])), h_cut8(h_mul(v[1], f2[1])), h_cut8(h_mul(v[2], f2[2])), h_cut8(h_mul(v[3], f2[3])));
            }
            fence_async();
            named_arrive(8, NTHREADS);
        }
    }
    uint32_t a[6][4], acc[24], rpar = 0, tile_off = here;
    const uint32_t bias_addr = sb + SM_BIASH + (lane & 3) * 96, lane16 = lane * 16, lane_off = ((lane >> 2) * CH + 8 * (lane & 3)) * 2;
    const uint32_t stage = sb + SM_RING + (spare + rank) % NSLOT * SLOT_BYTES + w4 * WARP_BYTES, bar_r = sb + BAR_R + warp_id * 8;
    auto load_bias = [&]() {
#pragma unroll
        for (int q = 0; q < 6; q++) lds128(acc[4 * q], acc[4 * q + 1], acc[4 * q + 2], acc[4 * q + 3], bias_addr + q * 16);
    };
    auto load_frags = [&]() {
#pragma unroll
        for (int s = 0; s < 6; s++) ldg128(a[s], reinterpret_cast<const char*>(out) + next_off + w4 * WARP_BYTES + lane16 + s * 512);
    };
    auto stage_x = [&]() {
        if (elect_one()) {
            mbar_expect_tx(bar_r, WARP_BYTES);
            bulk_load_stream(stage, reinterpret_cast<const char*>(x) + tile_off + w4 * WARP_BYTES, WARP_BYTES, bar_r);
        }
    };
    {
        named_bar(8 + rank, rank ? 256 : NTHREADS);
        if (rank == 0) PROF(4);
        load_bias();
        pin(k1); pin(k2); pin(k3);
        wg_fence();
        gemm2_chunk<288>(acc, k3, ds);
        wg_commit();
        gemm2_chunk<96>(acc, k1, ds);
        wg_commit();
        gemm2_chunk<192>(acc, k2, ds);
        wg_commit();
        stage_x();
        wg_wait<2>();
        uint32_t k0[24];
#pragma unroll
        for (int q = 0; q < 6; q++)
            lds128(k0[4 * q], k0[4 * q + 1], k0[4 * q + 2], k0[4 * q + 3], sb + SM_RING + cur.slot * SLOT_BYTES + w4 * REGION_BYTES + lane16 + q * 512);
        pin(k0);
        wg_fence();
        gemm2_chunk<0>(acc, k0, ds);
        wg_commit();
        if (rank < NCONS) named_arrive(9 + rank, 256);
        wg_wait<2>();
        load_frags();
        if (lane16 == 0) mbar_arrive(sb + BAR_PIN);
        mbar_wait(bar_r, rpar);
        wg_wait<0>();
    }
    auto lent = [&](uint32_t entry) { return &sc->lent[((wk.index * LENT + (entry & 3) - 1) * 4 + w4) * (24 * 32)]; };
    for (jt = rank - 4; jt < nrest; jt += 4) {
        if (jt >= zero) {
        tile_off = next_off;
        lds32(next_off, sb + SM_TILES + (jt + 4) * 4);
        if (tile_off & 3) {
            const uint4* src = lent(tile_off) + lane;
            tile_off &= ~3u;
            next_off = __shfl_sync(~0u, next_off, 0);
            stage_x();
            if (elect_one()) prefetch_l2(reinterpret_cast<const char*>(out) + next_off + w4 * WARP_BYTES, WARP_BYTES);
            load_bias();
#pragma unroll 1
            for (int half = 0; half < 2; half++, src += 12 * 32) {
                uint32_t gl[48];
#pragma unroll
                for (int s = 0; s < 12; s++) ldg128(reinterpret_cast<uint32_t (&)[4]>(gl[4 * s]), src + s * 32);
                if (!half) {
                    named_bar(4 + rank, 256);
                    named_arrive(4 + ((rank + 1) & 3), 256);
                }
                pin(gl);
                wg_fence();
#pragma unroll
                for (int s = 0; s < 12; s++) wgmma(acc, gl[4 * s], gl[4 * s + 1], gl[4 * s + 2], gl[4 * s + 3], ds.w2[12 * half + s], 1);
                wg_commit();
                wg_wait<0>();
            }
            load_frags();
            mbar_wait(bar_r, rpar);
        } else {
            uint32_t d0[12], d1[12], g0[12], g1[12];
            next_off = __shfl_sync(~0u, next_off, 0);
            const bool more = jt + 4 < nrest && !(next_off & 3);
            load_bias();
            wg_fence();
            gemm1_chunk<0>(d0, a, ds, 0);
            wg_commit();
            if (jt) named_bar(4 + rank, 256);
            gemm1_chunk<48>(d1, a, ds, 0);
            wg_commit();
            wg_wait<1>();
#define CNX_STEP(C, D, G)                                                   \
    gelu_to(G, D);                                                          \
    wg_fence();                                                             \
    if (C < 6) gemm1_chunk<48 * (C < 6 ? C + 2 : 0)>(D, a, ds, zero);      \
    gemm2_chunk<48 * C>(acc, G, ds);                                       \
    wg_commit();                                                            \
    if (C == 1 && jt + 1 < nrest) named_arrive(4 + ((rank + 1) & 3), 256); \
    wg_wait<(C < 7 ? 1 : 0)>();
            CNX_STEP(0, d0, g0)
            stage_x();
            if (elect_one()) {
                if (more) prefetch_l2(reinterpret_cast<const char*>(out) + next_off + w4 * WARP_BYTES, WARP_BYTES);
                else if (next_off & 3) prefetch_l2(lent(next_off), 24 * 32 * 16);
            }
            CNX_STEP(1, d1, g1)
            CNX_STEP(2, d0, g0)
            CNX_STEP(3, d1, g1)
            CNX_STEP(4, d0, g0)
            CNX_STEP(5, d1, g1)
            CNX_STEP(6, d0, g0)
#pragma unroll
            for (int s = 0; s < 6; s++) ldg128_if(more, a[s], reinterpret_cast<const char*>(out) + next_off + w4 * WARP_BYTES + lane16 + s * 512);
            if (lane16 == 0) mbar_arrive(sb + BAR_PIN);
            mbar_wait(bar_r, rpar);
            CNX_STEP(7, d1, g1)
#undef CNX_STEP
        }
        }
        {
            pin(acc);
            rpar ^= 1;
            uint4* op = reinterpret_cast<uint4*>(reinterpret_cast<char*>(out) + tile_off + w4 * WARP_BYTES + lane_off);
#pragma unroll
            for (int h = 0; h < 2; h++)
#pragma unroll
                for (int m = 0; m < 3; m++) {
                    uint32_t xin[4], o[4];
                    lds128(xin[0], xin[1], xin[2], xin[3], stage + lane_off + h * 1536 + m * 64);
#pragma unroll
                    for (int q = 0; q < 4; q++) {
                        const uint32_t v = acc[2 * (4 * m + q) + h];
                        o[q] = bf_fma(pack_bf2(h_lo(v), h_hi(v)), inv_rho2, xin[q]);
                    }
                    __stcs(op + h * 96 + m * 4, make_uint4(o[0], o[1], o[2], o[3]));
                }
            __syncwarp();
        }
    }
    PROF(5);
}

}

typedef CUresult (*EncodeTiledFn)(CUtensorMap*, CUtensorMapDataType, cuuint32_t, void*, const cuuint64_t*, const cuuint64_t*,
                                  const cuuint32_t*, const cuuint32_t*, CUtensorMapInterleave, CUtensorMapSwizzle,
                                  CUtensorMapL2promotion, CUtensorMapFloatOOBfill);

extern "C" void kernel_launch(void* const* d_in, const int* in_sizes, int n_in, void* d_out, int out_size) {
    using namespace cnx;
    static EncodeTiledFn encode = nullptr;
    static int num_sms = 0;
    static Scratch* scratch = nullptr;
    if (!encode) {
        void* fn = nullptr;
        cudaDriverEntryPointQueryResult qr;
        cudaGetDriverEntryPoint("cuTensorMapEncodeTiled", &fn, cudaEnableDefault, &qr);
        encode = (EncodeTiledFn)fn;
        cudaGetSymbolAddress((void**)&scratch, g_scratch);
        int dev = 0;
        cudaGetDevice(&dev);
        cudaDeviceGetAttribute(&num_sms, cudaDevAttrMultiProcessorCount, dev);
        if (num_sms > MAX_CTAS) num_sms = MAX_CTAS;
        cudaFuncSetAttribute(block_kernel, cudaFuncAttributeMaxDynamicSharedMemorySize, SM_TOTAL);
    }
    CUtensorMap tm;
    cuuint64_t dims[3] = {(cuuint64_t)CH, (cuuint64_t)IMG_W, (cuuint64_t)IMG_H};
    cuuint64_t strides[2] = {(cuuint64_t)CH * 2, (cuuint64_t)CH * 2 * IMG_W};
    cuuint32_t box[3] = {(cuuint32_t)CH, (cuuint32_t)REGION_PX, 1};
    cuuint32_t estr[3] = {1, 1, 1};
    encode(&tm, CU_TENSOR_MAP_DATA_TYPE_BFLOAT16, 3, d_in[0], dims, strides, box, estr, CU_TENSOR_MAP_INTERLEAVE_NONE,
           CU_TENSOR_MAP_SWIZZLE_NONE, CU_TENSOR_MAP_L2_PROMOTION_L2_128B, CU_TENSOR_MAP_FLOAT_OOB_FILL_NONE);
    Params pm = {};
    Descs& ds = pm.ds;
    for (int c = 0; c < 8; c++)
        for (int k = 0; k < 6; k++) ds.w1[c][k] = make_desc(SB + SM_W1 + c * 6 * 1536 + k * 256, 128, 1536);
    for (int k = 0; k < 24; k++) ds.w2[k] = make_desc(SB + SM_W2 + k * 256, 128, 6144);
    ds.ones = make_desc(SB + SM_ONES, 0, 0);
    CUtensorMap tw;
    cuuint64_t wdims[2] = {(cuuint64_t)EX, (cuuint64_t)CH};
    cuuint64_t wstrides[1] = {(cuuint64_t)EX * 2};
    cuuint32_t wbox[2] = {64, (cuuint32_t)CH};
    encode(&tw, CU_TENSOR_MAP_DATA_TYPE_BFLOAT16, 2, d_in[2], wdims, wstrides, wbox, estr, CU_TENSOR_MAP_INTERLEAVE_NONE,
           CU_TENSOR_MAP_SWIZZLE_128B, CU_TENSOR_MAP_L2_PROMOTION_L2_128B, CU_TENSOR_MAP_FLOAT_OOB_FILL_NONE);
    Split& sp = pm.sp;
    sp = {NTILES / num_sms, NTILES % num_sms, 1, 1 << 16, 0, {}};
    if (sp.per_cta + 9 > MAX_ROWS) return;
    if (sp.extra && sp.extra * (8 * LENT + 1) + W2_GROUPS / 2 <= num_sms && sp.per_cta >= 5 * LENT + 8) {
        sp.period = num_sms / sp.extra;
        sp.inv_period = 65535 / sp.period + 1;
        sp.lenders = sp.extra;
        for (int l = 0; l < sp.extra; l++) {
            const Work w = get_work((l + 1) * sp.period - sp.period / 2 - 1, sp);
            for (int e = 0; e < LENT; e++) sp.lent_off[l * LENT + e] = tile_offset(w.tile(e));
            if (w.nA < 2 * LENT) sp.lenders = 0;
        }
    }
    pm.x = (const __nv_bfloat16*)d_in[0];
    pm.dw = (const __nv_bfloat16*)d_in[1];
    pm.w2 = (const __nv_bfloat16*)d_in[3];
    pm.gamma = (const __nv_bfloat16*)d_in[4];
    pm.beta = (const __nv_bfloat16*)d_in[5];
    pm.out = (__nv_bfloat16*)d_out;
    pm.sc = scratch;
    block_kernel<<<num_sms, NTHREADS, SM_TOTAL>>>(tm, tw, pm);
}
```

```cpp
#include <cuda_runtime.h>
#include <cuda_bf16.h>
#include <cuda_fp16.h>
#include <cuda.h>
#include <stdint.h>

namespace cnx {

constexpr int IMG_H = 512, IMG_W = 512, CH = 96, EX = 384;
constexpr int TILE_W = 64;
constexpr int NTILES = (IMG_W / TILE_W) * IMG_H;
constexpr int NSLOT = 6;
constexpr int REGION_PX = 18;
constexpr int REGION_BYTES = REGION_PX * CH * 2;
constexpr int SLOT_BYTES = 4 * REGION_BYTES;
constexpr int A_LBO = 144, A_SBO = 12 * A_LBO;
constexpr int PREFETCH_ROWS = 3;
constexpr int NCONS = 3;
constexpr int CONS_THREADS = 128 * NCONS;
constexpr int NTHREADS = 128 + CONS_THREADS;
constexpr int MAX_ROWS = 52;
constexpr int TILE_BYTES = TILE_W * CH * 2, WARP_BYTES = TILE_BYTES / 4;
constexpr int ORDER_P = 3;
constexpr int W2_EARLY = 10;
static_assert(MAX_ROWS <= 128, "one table entry per producer thread");
static_assert(2 * A_SBO == REGION_BYTES && REGION_BYTES % 128 == 0, "region layout");

constexpr uint32_t SB = 1024;
constexpr int SM_W1 = 0;
constexpr int SM_W2 = SM_W1 + CH * EX * 2;
constexpr int SM_RING = SM_W2 + CH * EX * 2;
constexpr int SM_BIASH = SM_RING + NSLOT * SLOT_BYTES;
constexpr int SM_RED = SM_BIASH + 384;
constexpr int RED_MAX = 0, RED_LAUNCH = 48, RED_INV_RHO = 52, RED_JOB = 56;
constexpr int SM_TILES = SM_RED + 256;
constexpr int SM_ONES = SM_TILES + MAX_ROWS * 4;
constexpr int SM_BAR = SM_ONES + 128;
constexpr int BAR_X = SM_BAR;
constexpr int BAR_A = BAR_X + NSLOT * 4 * 8;
constexpr int BAR_E = BAR_A + NSLOT * 4 * 8;
constexpr int BAR_PIN = BAR_E + NSLOT * 4 * 8;
constexpr int BAR_W = BAR_PIN + 8;
constexpr int BAR_F = BAR_W + 6 * 8;
constexpr int BAR_R = BAR_F + 8;
constexpr int SM_TOTAL = BAR_R + 16 * 8;
constexpr int SM_FILTER = SM_RING + (NSLOT - 1) * SLOT_BYTES + 9 * 128;
constexpr int SM_SQ = SM_W2;
constexpr int SQ_ROW = 128 * 16, SQ_HALF = 6 * SQ_ROW;
static_assert(SM_ONES % 16 == 0 && SM_TOTAL <= 232448, "shared memory budget");

constexpr float KZ = 0.3292034911525734f;
constexpr uint32_t GELU_C2 = 0x40d940d9u;
constexpr float INV_2KZ = 0.5f / KZ;
constexpr uint32_t CONV_SCALE2 = 0x2f802f80u;
constexpr unsigned SPIN_LIMIT = 1u << 19;

constexpr int MAX_CTAS = 170;
constexpr int W2_GROUPS = EX / 8;
constexpr int LENT = 3, MAX_LENDERS = MAX_CTAS / (8 * LENT + 1);
struct Scratch {
    uint32_t w2h[EX * CH / 2];
    float w2max[EX];
    float bias[CH + 32];
    unsigned long long sums[EX / 4][32];
    __device__ __forceinline__ unsigned long long* sum(int e) { return &sums[e >> 2][e & 3]; }
    uint4 lent[MAX_LENDERS * LENT * 8 * 4 * 3 * 32];
    unsigned launch, pad0[31], early, pad1[31], prep, pad2[31], lent_out, pad3[31];
    unsigned job;
};
__device__ __align__(128) Scratch g_scratch;

#define PROF(k)

__device__ __forceinline__ uint32_t smem_u32(const void* p) { return (uint32_t)__cvta_generic_to_shared(p); }
__device__ __forceinline__ void mbar_init(uint32_t bar, uint32_t cnt) {
    asm volatile("mbarrier.init.shared::cta.b64 [%0], %1;" ::"r"(bar), "r"(cnt) : "memory");
}
__device__ __forceinline__ void mbar_arrive(uint32_t bar) {
    asm volatile("mbarrier.arrive.shared::cta.b64 _, [%0];" ::"r"(bar) : "memory");
}
__device__ __forceinline__ void mbar_expect_tx(uint32_t bar, uint32_t bytes) {
    asm volatile("mbarrier.arrive.expect_tx.shared::cta.b64 _, [%0], %1;" ::"r"(bar), "r"(bytes) : "memory");
}
__device__ __forceinline__ bool mbar_try(uint32_t bar, uint32_t par) {
    uint32_t ok;
    asm volatile("{\n.reg .pred p;\nmbarrier.try_wait.parity.shared::cta.b64 p, [%1], %2;\nselp.u32 %0, 1, 0, p;\n}\n"
                 : "=r"(ok) : "r"(bar), "r"(par) : "memory");
    return ok != 0;
}
__device__ __forceinline__ void mbar_wait(uint32_t bar, uint32_t par) {
    unsigned n = 0;
    while (!mbar_try(bar, par)) {
        if (++n > SPIN_LIMIT) __trap();
    }
}
__device__ __forceinline__ void mbar_wait_once(uint32_t bar, uint32_t par) {
    unsigned n = 0;
    bool ok;
#pragma unroll 1
    do {
        ok = mbar_try(bar, par);
        if (++n > SPIN_LIMIT) __trap();
    } while (!ok);
}
__device__ __forceinline__ bool elect_one() {
    uint32_t ok;
    asm volatile("{\n.reg .pred p;\nelect.sync _|p, 0xffffffff;\nselp.u32 %0, 1, 0, p;\n}\n" : "=r"(ok));
    return ok != 0;
}
__device__ __forceinline__ uint32_t opaque(uint32_t v) { return __shfl_sync(~0u, v, threadIdx.x & 31); }
__device__ __forceinline__ uint32_t lane_id() { uint32_t v; asm volatile("mov.u32 %0, %%laneid;" : "=r"(v)); return v; }
__device__ __forceinline__ uint32_t opaque_uniform(uint32_t v) { return __shfl_sync(~0u, v, 0); }
__device__ __forceinline__ void named_bar(int id, int n) { asm volatile("bar.sync %0, %1;" ::"r"(id), "r"(n) : "memory"); }
__device__ __forceinline__ void named_arrive(int id, int n) { asm volatile("bar.arrive %0, %1;" ::"r"(id), "r"(n) : "memory"); }
__device__ __forceinline__ void fence_async() { asm volatile("fence.proxy.async.shared::cta;" ::: "memory"); }
constexpr uint64_t EVICT_FIRST = 0x12F0000000000000ull;
__device__ __forceinline__ void tma_row(uint32_t dst, const CUtensorMap* tm, uint32_t bar, int x, int y) {
    asm volatile("cp.async.bulk.tensor.3d.shared::cluster.global.mbarrier::complete_tx::bytes.L2::cache_hint [%0], [%1, {%3, %4, %5}], [%2], %6;"
                 ::"r"(dst), "l"(tm), "r"(bar), "r"(0), "r"(x), "r"(y), "l"(EVICT_FIRST) : "memory");
}
__device__ __forceinline__ void bulk_load_stream(uint32_t dst, const void* src, uint32_t bytes, uint32_t bar) {
    asm volatile("cp.async.bulk.shared::cluster.global.mbarrier::complete_tx::bytes.L2::cache_hint [%0], [%1], %2, [%3], %4;"
                 ::"r"(dst), "l"(src), "r"(bytes), "r"(bar), "l"(EVICT_FIRST) : "memory");
}
__device__ __forceinline__ void prefetch_l2(const void* src, uint32_t bytes) {
    asm volatile("cp.async.bulk.prefetch.L2.global [%0], %1;" ::"l"(src), "r"(bytes) : "memory");
}
__device__ __forceinline__ void tma_2d(uint32_t dst, const CUtensorMap* tm, uint32_t bar, int x, int y) {
    asm volatile("cp.async.bulk.tensor.2d.shared::cluster.global.mbarrier::complete_tx::bytes [%0], [%1, {%3, %4}], [%2];"
                 ::"r"(dst), "l"(tm), "r"(bar), "r"(x), "r"(y) : "memory");
}
__device__ __forceinline__ void bulk_load(uint32_t dst, const void* src, uint32_t bytes, uint32_t bar) {
    asm volatile("cp.async.bulk.shared::cluster.global.mbarrier::complete_tx::bytes [%0], [%1], %2, [%3];"
                 ::"r"(dst), "l"(src), "r"(bytes), "r"(bar) : "memory");
}
__device__ __forceinline__ void wg_fence() { asm volatile("wgmma.fence.sync.aligned;" ::: "memory"); }
__device__ __forceinline__ void wg_commit() { asm volatile("wgmma.commit_group.sync.aligned;" ::: "memory"); }
template <int N> __device__ __forceinline__ void wg_wait() { asm volatile("wgmma.wait_group.sync.aligned %0;" ::"n"(N) : "memory"); }
template <int N> __device__ __forceinline__ void pin(uint32_t (&d)[N]) {
#pragma unroll
    for (int q = 0; q < N; q++) asm volatile("" : "+r"(d[q])::"memory");
}
__device__ __forceinline__ void stg128(void* p, const uint32_t (&v)[4]) {
    asm volatile("st.global.v4.u32 [%0], {%1, %2, %3, %4};" ::"l"(p), "r"(v[0]), "r"(v[1]), "r"(v[2]), "r"(v[3]) : "memory");
}
__device__ __forceinline__ void ldg128(uint32_t (&v)[4], const void* p) {
    asm volatile("ld.global.L1::no_allocate.v4.u32 {%0, %1, %2, %3}, [%4];" : "=r"(v[0]), "=r"(v[1]), "=r"(v[2]), "=r"(v[3]) : "l"(p) : "memory");
}
__device__ __forceinline__ void ldg128_if(bool on, uint32_t (&v)[4], const void* p) {
    asm volatile("{\n.reg .pred p;\nsetp.ne.b32 p, %5, 0;\n@p ld.global.L1::no_allocate.v4.u32 {%0, %1, %2, %3}, [%4];\n}\n"
                 : "+r"(v[0]), "+r"(v[1]), "+r"(v[2]), "+r"(v[3]) : "l"(p), "r"((int)on) : "memory");
}
__host__ __device__ constexpr uint64_t make_desc(uint32_t addr, uint32_t lbo, uint32_t sbo) {
    return (uint64_t)((addr & 0x3FFFF) >> 4) | ((uint64_t)(lbo >> 4) << 16) | ((uint64_t)(sbo >> 4) << 32);
}
__device__ __forceinline__ void wgmma(uint32_t (&d)[12], uint32_t a0, uint32_t a1, uint32_t a2, uint32_t a3, uint64_t db, int acc) {
    asm volatile("{\n.reg .pred p;\nsetp.ne.b32 p, %17, 0;\n"
                 "wgmma.mma_async.sync.aligned.m64n48k16.f16.f16.f16 "
                 "{%0, %1, %2, %3, %4, %5, %6, %7, %8, %9, %10, %11}, "
                 "{%12, %13, %14, %15}, %16, p, 1, 1, 0;\n}\n"
                 : "+r"(d[0]), "+r"(d[1]), "+r"(d[2]), "+r"(d[3]), "+r"(d[4]), "+r"(d[5]), "+r"(d[6]), "+r"(d[7]), "+r"(d[8]), "+r"(d[9]), "+r"(d[10]), "+r"(d[11])
                 : "r"(a0), "r"(a1), "r"(a2), "r"(a3), "l"(db), "r"(acc));
}
__device__ __forceinline__ void wgmma(uint32_t (&d)[24], uint32_t a0, uint32_t a1, uint32_t a2, uint32_t a3, uint64_t db, int acc) {
    asm volatile("{\n.reg .pred p;\nsetp.ne.b32 p, %29, 0;\n"
                 "wgmma.mma_async.sync.aligned.m64n96k16.f16.f16.f16 "
                 "{%0, %1, %2, %3, %4, %5, %6, %7, %8, %9, %10, %11, %12, %13, %14, %15, %16, %17, %18, %19, %20, %21, %22, %23}, "
                 "{%24, %25, %26, %27}, %28, p, 1, 1, 0;\n}\n"
                 : "+r"(d[0]), "+r"(d[1]), "+r"(d[2]), "+r"(d[3]), "+r"(d[4]), "+r"(d[5]), "+r"(d[6]), "+r"(d[7]), "+r"(d[8]), "+r"(d[9]), "+r"(d[10]), "+r"(d[11]), "+r"(d[12]), "+r"(d[13]), "+r"(d[14]), "+r"(d[15]), "+r"(d[16]), "+r"(d[17]), "+r"(d[18]), "+r"(d[19]), "+r"(d[20]), "+r"(d[21]), "+r"(d[22]), "+r"(d[23])
                 : "r"(a0), "r"(a1), "r"(a2), "r"(a3), "l"(db), "r"(acc));
}
template <int ACC>
__device__ __forceinline__ void wgmma_rowsum(float (&d)[4], const uint32_t (&a)[4], uint64_t ones) {
    asm volatile("{\n.reg .pred p;\nsetp.ne.b32 p, %9, 0;\n"
                 "wgmma.mma_async.sync.aligned.m64n8k16.f32.bf16.bf16 {%0, %1, %2, %3}, {%4, %5, %6, %7}, %8, p, 1, 1, 0;\n}\n"
                 : "+f"(d[0]), "+f"(d[1]), "+f"(d[2]), "+f"(d[3])
                 : "r"(a[0]), "r"(a[1]), "r"(a[2]), "r"(a[3]), "l"(ones), "n"(ACC));
}
__device__ __forceinline__ void ldsm4(uint32_t (&r)[4], uint32_t addr) {
    asm volatile("ldmatrix.sync.aligned.m8n8.x4.shared.b16 {%0, %1, %2, %3}, [%4];"
                 : "=r"(r[0]), "=r"(r[1]), "=r"(r[2]), "=r"(r[3]) : "r"(addr) : "memory");
}
__device__ __forceinline__ void ldsm4_t(uint32_t (&r)[4], uint32_t addr) {
    asm volatile("ldmatrix.sync.aligned.m8n8.x4.trans.shared.b16 {%0, %1, %2, %3}, [%4];"
                 : "=r"(r[0]), "=r"(r[1]), "=r"(r[2]), "=r"(r[3]) : "r"(addr) : "memory");
}
__device__ __forceinline__ void stsm4(uint32_t addr, uint32_t a, uint32_t b, uint32_t c, uint32_t d) {
    asm volatile("stmatrix.sync.aligned.m8n8.x4.shared.b16 [%0], {%1, %2, %3, %4};"
                 ::"r"(addr), "r"(a), "r"(b), "r"(c), "r"(d) : "memory");
}
__device__ __forceinline__ uint32_t transpose8x8(uint32_t v) {
    uint32_t d; asm volatile("movmatrix.sync.aligned.m8n8.trans.b16 %0, %1;" : "=r"(d) : "r"(v)); return d;
}
__device__ __forceinline__ void spin_until(const unsigned* counter, unsigned target) {
    unsigned n = 0, c;
    do {
        asm volatile("ld.acquire.gpu.global.u32 %0, [%1];" : "=r"(c) : "l"(counter) : "memory");
        if (++n > SPIN_LIMIT) __trap();
    } while ((int)(c - target) < 0);
}
__device__ __forceinline__ void signal(unsigned* counter) {
    __syncwarp();
    if (elect_one()) asm volatile("red.release.gpu.global.add.u32 [%0], 1;" ::"l"(counter) : "memory");
    __syncwarp();
}
__device__ __forceinline__ void lds128(uint32_t& a, uint32_t& b, uint32_t& c, uint32_t& d, uint32_t addr) {
    asm volatile("ld.shared.v4.u32 {%0, %1, %2, %3}, [%4];" : "=r"(a), "=r"(b), "=r"(c), "=r"(d) : "r"(addr) : "memory");
}
__device__ __forceinline__ void lds64(uint32_t& a, uint32_t& b, uint32_t addr) {
    asm volatile("ld.shared.v2.u32 {%0, %1}, [%2];" : "=r"(a), "=r"(b) : "r"(addr) : "memory");
}
__device__ __forceinline__ void lds32(uint32_t& a, uint32_t addr) {
    asm volatile("ld.shared.u32 %0, [%1];" : "=r"(a) : "r"(addr) : "memory");
}
__device__ __forceinline__ int ldsi(uint32_t addr) {
    uint32_t v;
    lds32(v, addr);
    return (int)v;
}
__device__ __forceinline__ float ldsf(uint32_t addr) {
    uint32_t v;
    lds32(v, addr);
    return __uint_as_float(v);
}
__device__ __forceinline__ void sts32(uint32_t addr, uint32_t a) {
    asm volatile("st.shared.u32 [%0], %1;" ::"r"(addr), "r"(a) : "memory");
}
__device__ __forceinline__ void sts128(uint32_t addr, uint32_t a, uint32_t b, uint32_t c, uint32_t d) {
    asm volatile("st.shared.v4.u32 [%0], {%1, %2, %3, %4};" ::"r"(addr), "r"(a), "r"(b), "r"(c), "r"(d) : "memory");
}
__device__ __forceinline__ void sts64(uint32_t addr, uint32_t a, uint32_t b) {
    asm volatile("st.shared.v2.u32 [%0], {%1, %2};" ::"r"(addr), "r"(a), "r"(b) : "memory");
}
__device__ __forceinline__ void anchor(uint32_t addr, uint32_t a, uint32_t b, uint32_t c, uint32_t d) {
    asm volatile("{\n.reg .pred p;\nsetp.eq.b32 p, %0, 0;\n@p st.shared.v4.u32 [%0], {%1, %2, %3, %4};\n}\n"
                 ::"r"(addr), "r"(a), "r"(b), "r"(c), "r"(d) : "memory");
}
__device__ __forceinline__ uint32_t bf_fma(uint32_t a, uint32_t b, uint32_t c) {
    uint32_t d; asm("fma.rn.bf16x2 %0, %1, %2, %3;" : "=r"(d) : "r"(a), "r"(b), "r"(c)); return d;
}
__device__ __forceinline__ uint32_t bf_mul(uint32_t a, uint32_t b) {
    uint32_t d; asm("mul.rn.bf16x2 %0, %1, %2;" : "=r"(d) : "r"(a), "r"(b)); return d;
}
__device__ __forceinline__ uint32_t bf_absmax(uint32_t a, uint32_t b) {
    uint32_t d; asm("max.xorsign.abs.bf16x2 %0, %1, %2;" : "=r"(d) : "r"(a), "r"(b)); return d;
}
__device__ __forceinline__ uint32_t h_fma(uint32_t a, uint32_t b, uint32_t c) {
    uint32_t d; asm("fma.rn.f16x2 %0, %1, %2, %3;" : "=r"(d) : "r"(a), "r"(b), "r"(c)); return d;
}
__device__ __forceinline__ uint32_t h_mul(uint32_t a, uint32_t b) {
    uint32_t d; asm("mul.rn.f16x2 %0, %1, %2;" : "=r"(d) : "r"(a), "r"(b)); return d;
}
__device__ __forceinline__ uint32_t h_tanh(uint32_t a) {
    uint32_t d; asm("tanh.approx.f16x2 %0, %1;" : "=r"(d) : "r"(a)); return d;
}
__device__ __forceinline__ uint32_t pack_h2(float lo, float hi) {
    uint32_t d; asm("cvt.rn.f16x2.f32 %0, %1, %2;" : "=r"(d) : "f"(hi), "f"(lo)); return d;
}
__device__ __forceinline__ uint32_t pack_bf2(float lo, float hi) {
    uint32_t d; asm("cvt.rn.bf16x2.f32 %0, %1, %2;" : "=r"(d) : "f"(hi), "f"(lo)); return d;
}
__device__ __forceinline__ float bf_lo(uint32_t v) { return __uint_as_float(v << 16); }
__device__ __forceinline__ float bf_hi(uint32_t v) { return __uint_as_float(v & 0xffff0000u); }
__device__ __forceinline__ float h_lo(uint32_t v) { return __low2float(*reinterpret_cast<__half2*>(&v)); }
__device__ __forceinline__ float h_hi(uint32_t v) { return __high2float(*reinterpret_cast<__half2*>(&v)); }
__device__ __forceinline__ float warp_absmax(uint32_t v) {
    return __uint_as_float(__reduce_max_sync(~0u, max((v & 0x7fffu) << 16, v & 0x7fff0000u)));
}
__device__ __forceinline__ uint32_t gelu2(uint32_t z) {
    uint32_t p = h_fma(z, z, GELU_C2);
    uint32_t t = h_tanh(h_mul(z, p));
    return h_fma(z, t, z);
}
__device__ __forceinline__ float pow2i(int e) { return __uint_as_float((uint32_t)(e + 127) << 23); }
__device__ __forceinline__ int ilog2f(float v) {
    int e = (int)((__float_as_uint(v) >> 23) & 0xff) - 127;
    return max(-100, min(100, e));
}

__device__ __forceinline__ int bound_exp(float w1max) { return w1max > 0.f ? ilog2f(2.f * KZ * 96.f * w1max) : 0; }
__device__ __forceinline__ bool plain_squares(int e) { return (unsigned)(4 - e) <= 6; }
__device__ __forceinline__ int square_exp(int e) { return plain_squares(e) ? 0 : max(-14, min(4 - e, 14)); }
__device__ __forceinline__ int sum_exp(int e) { return max(-90, min(90, 33 - 2 * e)); }
__device__ __forceinline__ int row_exp(float m) { return 2 - ilog2f(m); }

struct Split {
    int per_cta, extra, period, inv_period, lenders;
    uint32_t lent_off[MAX_LENDERS * LENT];
    __host__ __device__ __forceinline__ int longer_before(int cta) const {
        const int n = (cta + period / 2) * inv_period >> 16;
        return n < extra ? n : extra;
    }
};
struct Work {
    int tA, tB, nA, nB, dir, rows, lent, index;
    __host__ __device__ __forceinline__ int tile(int j) const { return j < nA ? tA + dir * j : tB + dir * (j - nA); }
};
__host__ __device__ __forceinline__ Work get_work(int cta, const Split& sp) {
    Work w;
    const int before = sp.longer_before(cta), longer = sp.longer_before(cta + 1) - before;
    w.lent = longer && sp.lenders ? LENT : 0;
    w.index = before;
    const int t0 = cta * sp.per_cta + before, t1 = t0 + sp.per_cta + longer;
    const int tm = t1 < (t0 | 511) + 1 ? t1 : (t0 | 511) + 1;
    const bool swap = t1 > tm && t1 - tm < tm - t0, down = cta & 1;
    w.nA = swap ? t1 - tm : tm - t0;
    w.nB = t1 - t0 - w.nA;
    w.tA = down ? (swap ? tm : t0) : (swap ? t1 : tm) - 1;
    w.tB = down ? (swap ? t0 : tm) : (swap ? tm : t1) - 1;
    w.dir = down ? 1 : -1;
    w.rows = w.nA + 2 + (w.nB ? w.nB + 2 : 0);
    return w;
}
__device__ __forceinline__ int row_code(const Work& w, int i) {
    const bool in_a = i < w.nA + 2;
    const int t = in_a ? w.tA : w.tB;
    return ((t & 511) + w.dir * ((in_a ? i : i - (w.nA + 2)) - 1)) << 16 | (t >> 9) * TILE_W;
}
__host__ __device__ __forceinline__ uint32_t tile_offset(int tile) { return ((tile & 511) * IMG_W + (tile >> 9) * TILE_W) * (CH * 2); }
__device__ __forceinline__ int tile_order(int j, int n) {
    return j % ORDER_P == ORDER_P - 1 ? j / ORDER_P : n - 1 - (j - j / ORDER_P);
}
__device__ __forceinline__ void issue_region(const CUtensorMap* tm, uint32_t dst, uint32_t bar, int warp, int code) {
    mbar_expect_tx(bar, REGION_BYTES);
    tma_row(dst, tm, bar, (code & 0xffff) + (16 * warp - 1), code >> 16);
}

template <class Event>
__device__ __forceinline__ void conv_producer(const Work& wk, const CUtensorMap* tm, uint32_t sb, int warp, Event event) {
    const int lane = threadIdx.x & 31;
    const int j = lane & 15, grp = lane >> 4;
    const uint32_t reg0 = sb + SM_RING + warp * REGION_BYTES;
    const uint32_t bars = sb + SM_BAR + warp * 8;
    if (warp * 32 + lane < MAX_ROWS) {
        const int i = warp * 32 + lane, before = min(i / 5, wk.lent);
        const bool back = i % 5 == 0 && i > 0 && i / 5 <= wk.lent;
        sts32(sb + SM_TILES + i * 4, back ? tile_offset(wk.tile(before - 1)) | before
                                          : tile_offset(wk.tile(wk.lent + tile_order(i - before, wk.nA + wk.nB - 4 - wk.lent))));
    }
    const uint32_t ld64 = opaque(reg0 + grp * 8 * 192 + j * 8), ld32 = opaque(reg0 + grp * 8 * 192 + 128 + j * 4);
    const uint32_t st64 = opaque(reg0 + grp * A_SBO + (j >> 1) * A_LBO + (j & 1) * 8);
    const uint32_t st32 = opaque(reg0 + grp * A_SBO + (8 + (j >> 2)) * A_LBO + (j & 3) * 4);
    named_bar(0, NTHREADS);
    uint32_t w[3][3][3];
    mbar_wait_once(sb + BAR_F, 0);
#pragma unroll
    for (int tap = 0; tap < 9; tap++) {
        const uint32_t p = sb + SM_FILTER + (3 + wk.dir * 3 * (tap / 3 - 1) + tap % 3) * (CH * 2);
        lds64(w[tap / 3][tap % 3][0], w[tap / 3][tap % 3][1], p + 8 * j);
        lds32(w[tap / 3][tap % 3][2], p + 128 + 4 * j);
#pragma unroll
        for (int q = 0; q < 3; q++) w[tap / 3][tap % 3][q] = bf_mul(w[tap / 3][tap % 3][q], CONV_SCALE2);
    }
#pragma unroll
    for (int tap = 0; tap < 9; tap++) sts64(reg0 + (NSLOT - 1) * SLOT_BYTES + tap * 128 + j * 8, w[tap / 3][tap % 3][1], w[tap / 3][tap % 3][0]);
    named_bar(1, 128);
#pragma unroll
    for (int tap = 0; tap < 9; tap++) lds64(w[tap / 3][tap % 3][1], w[tap / 3][tap % 3][0], reg0 + (NSLOT - 1) * SLOT_BYTES + tap * 128 + j * 8);
    static_assert(2 * PREFETCH_ROWS == NSLOT && SLOT_BYTES % 32 == 0, "slot arithmetic");
    uint32_t bo = 0, so = 0, par = 0, pbo = PREFETCH_ROWS * 32, ppar = 1;
    int px, py;
    auto request = [&]() {
        mbar_wait_once(bars + (BAR_E - SM_BAR) + pbo, ppar);
        if (elect_one()) {
            mbar_expect_tx(bars + pbo, REGION_BYTES);
            tma_row(reg0 + pbo * (SLOT_BYTES / 32), tm, bars + pbo, px, py);
        }
    };
    auto advance = [&]() {
        bo += 32;
        so += SLOT_BYTES;
        if (bo == NSLOT * 32) { bo = 0; so = 0; par ^= 1; }
        pbo += 32;
        if (pbo == NSLOT * 32) { pbo = 0; ppar ^= 1; }
    };
    auto aim = [&](int row) {
        const int code = row_code(wk, row);
        px = (code & 0xffff) + (16 * warp - 1);
        py = code >> 16;
    };
    uint32_t accB[8][3], accC[8][3];
    int r = 0;
#pragma unroll 1
    while (r < wk.rows) {
        if (r == 0 || r == wk.nA + 2) {
            const uint32_t bo0 = bo;
            uint32_t bo1;
#pragma unroll 1
            for (int k = 0; k < 2; k++, r++) {
                mbar_wait_once(bars + bo, par);
                bo1 = bo;
                if (r >= 2) {
                    aim(r + PREFETCH_ROWS);
                    request();
                }
                advance();
            }
            const uint32_t so0 = bo0 * (SLOT_BYTES / 32), so1 = bo1 * (SLOT_BYTES / 32);
#pragma unroll
            for (int p = 0; p < 10; p++) {
                uint32_t u[3], v[3];
                lds64(u[0], u[1], so0 + ld64 + p * 192);
                lds32(u[2], so0 + ld32 + p * 192);
                lds64(v[0], v[1], so1 + ld64 + p * 192);
                lds32(v[2], so1 + ld32 + p * 192);
#pragma unroll
                for (int dx = 0; dx < 3; dx++) {
                    const int o = p - dx;
                    if (o < 0 || o > 7) continue;
#pragma unroll
                    for (int q = 0; q < 3; q++) {
                        accB[o][q] = bf_fma(v[q], w[1][dx][q], dx == 0 ? bf_mul(u[q], w[0][dx][q]) : bf_fma(u[q], w[0][dx][q], accB[o][q]));
                        accC[o][q] = dx == 0 ? bf_mul(v[q], w[0][dx][q]) : bf_fma(v[q], w[0][dx][q], accC[o][q]);
                    }
                }
            }
            anchor(ld64, accB[7][0], accB[7][1], accB[7][2], 0);
            __syncwarp();
            if (elect_one()) {
                mbar_arrive(bars + (BAR_A - SM_BAR) + bo0);
                mbar_arrive(bars + (BAR_E - SM_BAR) + bo0);
                mbar_arrive(bars + (BAR_A - SM_BAR) + bo1);
                mbar_arrive(bars + (BAR_E - SM_BAR) + bo1);
            }
        }
        int end = wk.rows;
        const int marks[4] = {wk.rows - PREFETCH_ROWS, wk.rows - 11, wk.nA + 2, wk.nA + 2 - PREFETCH_ROWS};
#pragma unroll
        for (int k = 0; k < 4; k++) end = marks[k] > r ? min(end, marks[k]) : end;
        const int fetch = opaque_uniform(end - wk.rows);
        aim(r + PREFETCH_ROWS);
        px = opaque_uniform(px);
        const int py_end = opaque_uniform(py + wk.dir * (end - r));
        r = end;
#pragma unroll 1
        do {
            mbar_wait(bars + bo, par);
            uint32_t out[8][3];
#pragma unroll
            for (int p = 0; p < 10; p++) {
                uint32_t xv[3];
                lds64(xv[0], xv[1], so + ld64 + p * 192);
                lds32(xv[2], so + ld32 + p * 192);
#pragma unroll
                for (int dx = 0; dx < 3; dx++) {
                    const int o = p - dx;
                    if (o < 0 || o > 7) continue;
#pragma unroll
                    for (int q = 2; q >= 0; q--) {
                        out[o][q] = bf_fma(xv[q], w[2][dx][q], dx == 0 ? accB[o][q] : out[o][q]);
                        accB[o][q] = bf_fma(xv[q], w[1][dx][q], dx == 0 ? accC[o][q] : accB[o][q]);
                        accC[o][q] = dx == 0 ? bf_mul(xv[q], w[0][dx][q]) : bf_fma(xv[q], w[0][dx][q], accC[o][q]);
                    }
                }
            }
            __syncwarp();
#pragma unroll
            for (int o = 7; o >= 0; o--) {
                sts64(so + st64 + o * 16, out[o][0], out[o][1]);
                sts32(so + st32 + o * 16, out[o][2]);
            }
            __syncwarp();
            if (elect_one()) mbar_arrive(bars + (BAR_A - SM_BAR) + bo);
            if (fetch) request();
            advance();
            py += wk.dir;
        } while (py != py_end);
        if (((wk.rows - r) & ~8) == PREFETCH_ROWS) event(wk.rows - r == PREFETCH_ROWS);
    }
}

template <bool SCALED, int K0 = 0, int K1 = 3>
__device__ __forceinline__ void gelu_sq(uint32_t (&d)[24], uint32_t (&keep)[24], uint32_t sq_addr, uint32_t scale2) {
    pin(d);
#pragma unroll
    for (int k = K0; k < K1; k++) {
        uint32_t hs[4];
        lds128(hs[0], hs[1], hs[2], hs[3], sq_addr + k * SQ_ROW);
#pragma unroll
        for (int q = 0; q < 4; q++) {
            uint32_t g0 = gelu2(d[8 * k + 2 * q]), g1 = gelu2(d[8 * k + 2 * q + 1]);
            keep[8 * k + 2 * q] = g0;
            keep[8 * k + 2 * q + 1] = g1;
            if (SCALED) { g0 = h_mul(g0, scale2); g1 = h_mul(g1, scale2); }
            hs[q] = h_fma(g1, g1, h_fma(g0, g0, hs[q]));
        }
        sts128(sq_addr + k * SQ_ROW, hs[0], hs[1], hs[2], hs[3]);
    }
}
__device__ __forceinline__ void gelu_sq_reg(uint32_t (&d)[24], uint32_t (&hs)[12]) {
    pin(d);
#pragma unroll
    for (int q = 0; q < 12; q++) {
        const uint32_t g0 = gelu2(d[2 * q]), g1 = gelu2(d[2 * q + 1]);
        hs[q] = h_fma(g1, g1, h_fma(g0, g0, hs[q]));
    }
}
__device__ __forceinline__ void gelu_to(uint32_t (&g)[12], uint32_t (&d)[12]) {
    pin(d);
#pragma unroll
    for (int q = 0; q < 12; q++) g[q] = gelu2(d[q]);
    pin(g);
}
__device__ __forceinline__ void load_tile(uint32_t (&raw)[6][4], uint32_t addr) {
#pragma unroll
    for (int s = 0; s < 6; s++) ldsm4(raw[s], addr + s * 2 * A_LBO);
}
template <class F>
__device__ __forceinline__ void layer_norm(uint32_t (&raw)[6][4], uint64_t ones, F meanwhile) {
    uint32_t sq[2][4];
#pragma unroll
    for (int s = 0; s < 6; s++)
#pragma unroll
        for (int q = 0; q < 4; q++) sq[s / 3][q] = s % 3 == 0 ? bf_mul(raw[s][q], raw[s][q]) : bf_fma(raw[s][q], raw[s][q], sq[s / 3][q]);
    float sum[4], ssq[4];
    wg_fence();
    wgmma_rowsum<0>(sum, raw[0], ones);
#pragma unroll
    for (int s = 1; s < 6; s++) wgmma_rowsum<1>(sum, raw[s], ones);
    wgmma_rowsum<0>(ssq, sq[0], ones);
    wgmma_rowsum<1>(ssq, sq[1], ones);
    wg_commit();
    meanwhile();
    wg_wait<0>();
    uint32_t sc[2], sh[2];
#pragma unroll
    for (int h = 0; h < 2; h++) {
        asm volatile("" : "+f"(sum[2 * h]), "+f"(ssq[2 * h])::"memory");
        constexpr float EPS = 1e-5f / (KZ * KZ) * 0x1p-64f;
        const float m = sum[2 * h] * (1.f / (CH * KZ));
        float rstd;
        asm("rsqrt.approx.ftz.f32 %0, %1;" : "=f"(rstd) : "f"(fmaxf(fmaf(-m, m, fmaf(ssq[2 * h], 1.f / (CH * KZ * KZ), EPS)), EPS)));
        rstd *= 0x1p-112f;
        sc[h] = pack_bf2(rstd, rstd);
        const float shift = sum[2 * h] * (-1.f / CH) * bf_hi(sc[h]);
        sh[h] = pack_bf2(shift, shift);
    }
#pragma unroll
    for (int s = 0; s < 6; s++)
#pragma unroll
        for (int q = 0; q < 4; q++) {
            const uint32_t v = bf_fma(raw[s][q], sc[q & 1], sh[q & 1]);
            asm("lop3.b32 %0, %1, %2, 0x80008000, 0xd8;" : "=r"(raw[s][q]) : "r"(v << 3), "r"(v));
        }
}
struct Cursor {
    int slot;
    uint32_t par;
    __device__ __forceinline__ void advance(int n) {
        slot += n;
        if (slot >= NSLOT) { slot -= NSLOT; par ^= 1; }
    }
};
struct Descs {
    uint64_t w1[8][6];
    uint64_t w2[24];
    uint64_t ones;
};
template <int E0, int N>
__device__ __forceinline__ void gemm1_chunk(uint32_t (&d)[N], const uint32_t (&a)[6][4], const Descs& ds, int zero) {
#pragma unroll
    for (int s = 0; s < 6; s++) wgmma(d, a[s][0], a[s][1], a[s][2], a[s][3], ds.w1[E0 / 48][s], s ? 1 : zero);
}
template <int E0, int N>
__device__ __forceinline__ void gemm2_chunk(uint32_t (&acc)[24], const uint32_t (&g)[N], const Descs& ds) {
#pragma unroll
    for (int s = 0; s < N / 4; s++) wgmma(acc, g[4 * s], g[4 * s + 1], g[4 * s + 2], g[4 * s + 3], ds.w2[E0 / 16 + s], 1);
}

struct __align__(64) Params {
    Split sp;
    int zero;
    const __nv_bfloat16 *x, *dw, *w2, *gamma, *beta;
    __nv_bfloat16* out;
    Scratch* sc;
    Descs ds;
};

__global__ void __launch_bounds__(NTHREADS, 1)
block_kernel(const __grid_constant__ CUtensorMap tmap, const __grid_constant__ CUtensorMap tmap_w1, const __grid_constant__ Params pm) {
    const Split& sp = pm.sp;
    const Descs& ds = pm.ds;
    const int& zero = pm.zero;
    const __nv_bfloat16 *const &x = pm.x, *const &dw = pm.dw, *const &w2 = pm.w2, *const &gamma = pm.gamma, *const &beta = pm.beta;
    __nv_bfloat16* const& out = pm.out;
    Scratch* const& sc = pm.sc;
    extern __shared__ __align__(1024) uint8_t smem[];
    constexpr uint32_t sb = SB;
    const int tid = threadIdx.x;
    const Work wk = get_work(blockIdx.x, sp);
    constexpr uint32_t s_red = sb + SM_RED;
    if (smem_u32(smem) != SB) __trap();

    const int warp_id = __shfl_sync(~0u, tid >> 5, 0);
    PROF(0);
    const int cw = warp_id - 4, wgi = cw >> 2, w4 = warp_id & 3;
    if (elect_one()) {
        static_assert(3 * NSLOT * 4 == 8 + 4 * 16 && BAR_F == BAR_W + 48, "barrier shares");
        const int b = warp_id - 8;
        const uint32_t bar = b < 0 ? sb + BAR_X + warp_id * 8 : b < 7 ? sb + BAR_W + b * 8 : sb + BAR_PIN;
        mbar_init(bar, 1);
#pragma unroll
        for (int k = 0; k < 4; k++) mbar_init(sb + BAR_X + (8 + 4 * warp_id + k) * 8, 1);
        mbar_init(sb + BAR_R + warp_id * 8, 1);
        fence_async();
        if (b < 0) {
            issue_region(&tmap, sb + SM_RING + warp_id * REGION_BYTES, bar, w4, ((wk.tA & 511) + wk.dir * wgi) << 16 | (wk.tA >> 9) * TILE_W);
        } else if (b < 6) {
            mbar_expect_tx(bar, 64 * CH * 2);
            tma_2d(sb + SM_W2 + b * (64 * CH * 2), &tmap_w1, bar, 64 * b, 0);
        } else if (b == 6) {
            mbar_expect_tx(bar, 9 * CH * 2);
            bulk_load(sb + SM_FILTER, dw, 9 * CH * 2, bar);
        }
    }
    __syncwarp();
    const int ntiles = wk.nA + wk.nB;
    const int rank = (wgi + wk.lent + 2 * (ntiles - 1)) % NCONS | (wgi >> 2 & 3);
    const int spare = wk.rows % NSLOT, spare2 = spare == NSLOT - 1 ? 0 : spare + 1;
    const uint32_t sq_base = sb + (wgi < 0 ? SM_RING + spare * SLOT_BYTES : SM_SQ + rank * 2 * SQ_HALF);
    const uint32_t sq_upper = wgi < 0 ? (spare2 - spare) * SLOT_BYTES : SQ_HALF;
    const uint32_t bar_a = sb + BAR_A + w4 * 8, bar_e = sb + BAR_E + w4 * 8;
    auto max_w1 = [&](uint32_t lane) { return __uint_as_float(__reduce_max_sync(~0u, lane < 4 * NCONS ? ldsi(s_red + RED_MAX + lane * 4) : 0)); };
    auto square_scale = [&](uint32_t lane) {
        const float f = pow2i(square_exp(bound_exp(max_w1(lane))));
        return pack_h2(f, f);
    };
    uint32_t a_addr, sq;
    const uint32_t sq_warp = sq_base + w4 * 512;
    auto set_addresses = [&]() {
        a_addr = opaque(sb + SM_RING + w4 * REGION_BYTES + ((tid >> 3) & 1) * A_SBO + ((tid >> 4) & 1) * A_LBO + (tid & 7) * 16);
        sq = opaque(sq_base + (tid & 127) * 16);
    };
    uint32_t turn, turn_end, so, so_sum, bo, bo_sum, off;
    auto set_run = [&](int j, int stop, int row) {
        const int slot = row % NSLOT, both = 2 * (row % 3) + 3;
        turn = opaque_uniform(row / 3);
        turn_end = opaque_uniform(row / 3 + (stop - j + NCONS - 1) / NCONS);
        so = opaque_uniform(slot * SLOT_BYTES);
        so_sum = opaque_uniform(both * SLOT_BYTES);
        bo = opaque_uniform(bar_a + slot * 32);
        bo_sum = opaque_uniform(2 * bar_a + both * 32);
        off = opaque_uniform(tile_offset(wk.tile(j)) + w4 * WARP_BYTES - sq_warp);
    };
    const int nrest = ntiles - 4;
    int jt;
    Cursor cur;
    int fast_from;
    if (warp_id < 4) {
        conv_producer(wk, &tmap, sb, warp_id, [&](bool second) {
            if (!second) {
                if (tid == 0) sts32(s_red + RED_JOB, wk.lent ? NTILES : atomicAdd(&sc->job, 1));
                if (blockIdx.x == 0) {
#pragma unroll 1
                    for (int e = tid; e < EX; e += 128) *sc->sum(e) = 0;
                    sc->bias[tid] = 0.f;
                }
                if (blockIdx.x == 0 || wk.lent) signal(&sc->early);
                __syncwarp();
            } else {
                const int piece = opaque_uniform(ldsi(s_red + RED_JOB)) - W2_GROUPS / 2, q = 2 * piece + W2_GROUPS + (w4 >> 1);
                if (piece < 8 * LENT * sp.lenders) {
                    spin_until(&sc->early, (ldsi(s_red + RED_LAUNCH) + 1) * 4 * (sp.lenders + 1));
                    if (elect_one()) {
                        if (piece >= 0) prefetch_l2(reinterpret_cast<const char*>(out) + sp.lent_off[piece / 8] + w4 * WARP_BYTES, WARP_BYTES);
                        else { prefetch_l2(w2 + 8 * q * CH, 8 * CH * 2); prefetch_l2(beta + 8 * q, 16); }
                    }
                }
            }
        });
        const int piece = opaque_uniform(ldsi(s_red + RED_JOB)) - W2_GROUPS / 2, q = 2 * piece + W2_GROUPS + (w4 >> 1);
        const bool prepares = piece < 0, helps = piece < 8 * LENT * sp.lenders;
        set_addresses();
        const int lane = lane_id(), g = lane >> 2, t = lane & 3;
        uint32_t a[6][4];
        unsigned short bt_raw;
        if (prepares) {
#pragma unroll
            for (int m = 0; m < 3; m++) ldg128(a[m], w2 + (8 * q + g) * CH + 32 * m + 8 * t);
            asm volatile("ld.global.nc.u16 %0, [%1];" : "=h"(bt_raw) : "l"(beta + 8 * q + g) : "memory");
        } else if (helps) {
#pragma unroll
            for (int s = 0; s < 6; s++) ldg128(a[s], reinterpret_cast<const char*>(out) + sp.lent_off[piece / 8] + w4 * WARP_BYTES + lane * 16 + s * 512);
        }
        mbar_wait_once(bar_e + spare2 * 32, (wk.rows - 5) / NSLOT & 1);
        mbar_wait_once(bar_e + spare * 32, (wk.rows - 6) / NSLOT & 1);
        named_bar(1, 128);
#pragma unroll
        for (int k = 0; k < 6; k++) { sts128(sq + k * SQ_ROW, 0, 0, 0, 0); sts128(sq + sq_upper + k * SQ_ROW, 0, 0, 0, 0); }
        if (prepares) {
            const int half = w4 & 1;
            uint32_t rmax = 0;
#pragma unroll
            for (int m = 0; m < 3; m++) rmax = bf_absmax(bf_absmax(rmax, bf_absmax(a[m][0], a[m][1])), bf_absmax(a[m][2], a[m][3]));
            uint2 u = half ? make_uint2(a[0][2], a[0][3]) : make_uint2(a[0][0], a[0][1]), u1 = half ? make_uint2(a[1][2], a[1][3]) : make_uint2(a[1][0], a[1][1]);
            const uint2 u2 = half ? make_uint2(a[2][2], a[2][3]) : make_uint2(a[2][0], a[2][1]);
            const float bt = bf_lo(bt_raw);
            rmax = bf_absmax(rmax, __shfl_xor_sync(~0u, rmax, 1));
            rmax = bf_absmax(rmax, __shfl_xor_sync(~0u, rmax, 2));
            const float mx = fmaxf(fabsf(bf_lo(rmax)), fabsf(bf_hi(rmax))), rs = pow2i(row_exp(mx));
            if (t == 0 && !half) sc->w2max[8 * q + g] = mx;
#pragma unroll 1
            for (int m = 0; m < 3; m++, u = u1, u1 = u2) {
                float f[4];
#pragma unroll
                for (int k = 0; k < 2; k++) {
                    const float lo = bf_lo(k ? u.y : u.x), hi = bf_hi(k ? u.y : u.x);
                    sc->w2h[(4 * m + 2 * half + k) * 1536 + q * 32 + lane] = transpose8x8(pack_h2(lo * rs, hi * rs));
                    f[2 * k] = lo * bt;
                    f[2 * k + 1] = hi * bt;
                }
                const float r0 = (g & 2 ? f[2] : f[0]) + __shfl_xor_sync(~0u, g & 2 ? f[0] : f[2], 8);
                const float r1 = (g & 2 ? f[3] : f[1]) + __shfl_xor_sync(~0u, g & 2 ? f[1] : f[3], 8);
                float r = (g & 1 ? r1 : r0) + __shfl_xor_sync(~0u, g & 1 ? r0 : r1, 4);
                r += __shfl_xor_sync(~0u, r, 16);
                if (g < 4) atomicAdd(&sc->bias[32 * m + 8 * t + 4 * half + g], r);
            }
            asm volatile("fence.proxy.async.global;" ::: "memory");
            signal(&sc->prep);
        } else
        if (helps) {
            uint32_t d[12], gl[12];
            const uint32_t scale2 = square_scale(lane);
            wg_fence();
#pragma unroll
            for (int s = 0; s < 6; s++) wgmma(d, a[s][0], a[s][1], a[s][2], a[s][3], ds.w1[0][s] + piece % 8 * (6 * 1536 / 16), s ? 1 : 0);
            wg_commit();
            wg_wait<0>();
            gelu_to(gl, d);
#pragma unroll
            for (int s = 0; s < 3; s++) {
                sc->lent[((piece / 8 * 4 + w4) * 24 + piece % 8 * 3 + s) * 32 + lane] = make_uint4(gl[4 * s], gl[4 * s + 1], gl[4 * s + 2], gl[4 * s + 3]);
                uint32_t hs[2];
#pragma unroll
                for (int k = 0; k < 2; k++) {
                    const uint32_t g0 = h_mul(gl[4 * s + 2 * k], scale2), g1 = h_mul(gl[4 * s + 2 * k + 1], scale2);
                    hs[k] = h_fma(g1, g1, h_mul(g0, g0));
                }
                const int pair = piece % 4 * 3 + s;
                sts64(sq + (piece & 4 ? sq_upper : 0) + (pair >> 1) * SQ_ROW + (pair & 1) * 8, hs[0], hs[1]);
            }
        }
        jt = ntiles - 1;
        cur.slot = spare ? spare - 1 : NSLOT - 1;
        cur.par = (wk.rows - 1) / NSLOT & 1;
        fast_from = ntiles;
        turn = turn_end = so = so_sum = bo = bo_sum = off = rank;
    } else {
        set_addresses();
        if (wgi == NCONS - 1) named_arrive(4, 256);
        set_run(wk.lent + wgi, min(wk.nA, nrest), wk.lent + wgi + 2);
        jt = wgi < wk.lent ? wgi : wk.lent + wgi;
        cur = {2, 0};
        cur.advance(jt + (jt >= wk.nA ? 2 : 0));
        {
            const int ct = tid - 128, lane = tid & 31;
            const unsigned epoch = *reinterpret_cast<volatile unsigned*>(&sc->launch);
            const int r = lane & 7, mi = lane >> 3;
            const uint32_t src = sb + SM_W2 + (cw >> 1) * (64 * CH * 2) + r * 128 + ((((cw & 1) * 4 + mi) ^ r) * 16);
            const uint32_t dst = sb + SM_W1 + (4 * cw + mi) * 1536 + r * 16;
            const int code = row_code(wk, PREFETCH_ROWS - 1 + wgi);
            named_bar(0, NTHREADS);
            auto request = [&]() {
                if (elect_one())
                    issue_region(&tmap, sb + SM_RING + (PREFETCH_ROWS - 1 + wgi) * SLOT_BYTES + w4 * REGION_BYTES, sb + BAR_X + (cw + 8) * 8, w4, code);
                __syncwarp();
            };
#pragma unroll 1
            for (int k = 0; k < 2; k++) {
                if (wgi == k) request();
                mbar_wait_once(sb + BAR_W + (cw >> 1) * 8, 0);
            }
            uint32_t wmax[2] = {}, wsum[4] = {};
#pragma unroll 3
            for (int c = 0; c < 12; c++) {
                uint32_t u[4];
                ldsm4_t(u, src + c * 1024);
#pragma unroll
                for (int q = 0; q < 4; q++) {
                    wmax[q & 1] = bf_absmax(wmax[q & 1], u[q]);
                    wsum[q] = bf_fma(u[q], 0x3f803f80u, wsum[q]);
                    u[q] = pack_h2(__uint_as_float(u[q] * (65536 + zero)), bf_hi(u[q]));
                }
                stsm4(dst + c * 128, u[0], u[1], u[2], u[3]);
            }
            const float w1max = warp_absmax(bf_absmax(wmax[0], wmax[1]));
            if (lane == 0) sts32(s_red + RED_MAX + cw * 4, __float_as_uint(w1max));
            bool center = false;
#pragma unroll
            for (int q = 0; q < 4; q++) {
#pragma unroll
                for (int o = 1; o <= 2; o <<= 1) wsum[q] = bf_fma(__shfl_xor_sync(~0u, wsum[q], o), 0x3f803f80u, wsum[q]);
                center |= fabsf(bf_lo(wsum[q]) + bf_hi(wsum[q])) > (0.15f * CH) * w1max;
            }
            if (__builtin_expect(__any_sync(~0u, center), 0)) {
                float mean[4] = {};
#pragma unroll 1
                for (int pass = 0; pass < 2; pass++) {
                    float sum[4] = {};
#pragma unroll 1
                    for (int c = 0; c < 12; c++) {
                        uint32_t u[4];
                        ldsm4_t(u, src + c * 1024);
#pragma unroll
                        for (int q = 0; q < 4; q++) {
                            sum[q] += bf_lo(u[q]) + bf_hi(u[q]);
                            u[q] = pack_h2(bf_lo(u[q]) - mean[q], bf_hi(u[q]) - mean[q]);
                        }
                        stsm4(dst + c * 128, u[0], u[1], u[2], u[3]);
                    }
#pragma unroll
                    for (int q = 0; q < 4; q++) {
                        sum[q] += __shfl_xor_sync(~0u, sum[q], 1);
                        sum[q] += __shfl_xor_sync(~0u, sum[q], 2);
                        mean[q] = sum[q] * (1.f / CH);
                    }
                }
            }
            if (!(cw & 2)) {
#pragma unroll
                for (int c = 0; c < 12; c++) sts128(src + c * 1024, 0, 0, 0, 0);
            }
            if (ct < 32) sts32(sb + SM_ONES + ct * 4, 0x3f803f80u);
            if (ct == 0) sts32(s_red + RED_LAUNCH, epoch);
            fence_async();
            named_bar(2, CONS_THREADS);
            if (wgi == 2) request();
        }
        PROF(1);
        if (cur.par) mbar_wait_once(bar_a, 0);
        fast_from = wk.lent;
        if (!__all_sync(~0u, plain_squares(bound_exp(max_w1(lane_id()))))) {
            fast_from = ntiles;
#pragma unroll 1
            for (int q = 0; q < 6; q++) sts128(sq + SQ_HALF + q * SQ_ROW, 0, 0, 0, 0);
        }
    }
    uint32_t k1[24], k2[24], k3[24];
    uint32_t here;
    constexpr int SQC = 3 * SQ_ROW;
    auto store_at = [&](const uint32_t (&a)[6][4], uint32_t off) {
        char* ap = reinterpret_cast<char*>(out) + (off + sq);
#pragma unroll
        for (int s = 0; s < 6; s++) stg128(ap + s * 512, a[s]);
    };
    const uint32_t own_bar = 4 + wgi, next_bar = 4 + (wgi == NCONS - 1 ? 0 : wgi + 1);
    for (;;) {
        if (jt >= fast_from) {
            uint32_t hs2[12] = {}, hs3[12] = {};
            const uint32_t step = wk.dir * (NCONS * IMG_W * CH * 2);
            int second = wk.nB;
#pragma unroll 1
            for (;;) {
#pragma unroll 1
                while (turn != turn_end) {
                    uint32_t a[6][4], d0[24], d1[24], unused[24];
                    mbar_wait(bo, turn >> 1 & 1);
                    load_tile(a, a_addr + so);
                    layer_norm(a, ds.ones, [&]() { named_bar(own_bar, 256); });
                    wg_fence();
                    gemm1_chunk<0>(d0, a, ds, 0);
                    wg_commit();
                    gemm1_chunk<96>(d1, a, ds, 0);
                    wg_commit();
                    wg_wait<1>();
                    gelu_sq<false, 0, 1>(d0, unused, sq, 0);
                    gelu_sq<false, 1, 2>(d0, unused, sq, 0);
                    store_at(a, off);
                    gelu_sq<false, 2, 3>(d0, unused, sq, 0);
                    if (elect_one()) mbar_arrive(bo + (BAR_E - BAR_A));
                    wg_fence();
                    gemm1_chunk<192>(d0, a, ds, zero);
                    wg_commit();
                    named_arrive(next_bar, 256);
                    wg_wait<1>();
                    gelu_sq<false, 0, 1>(d1, unused, sq + SQC, 0);
                    gelu_sq<false, 1, 3>(d1, unused, sq + SQC, 0);
                    wg_fence();
                    gemm1_chunk<288>(d1, a, ds, zero);
                    wg_commit();
                    wg_wait<1>();
                    gelu_sq_reg(d0, hs2);
                    anchor(sq, hs2[8], hs2[9], hs2[10], hs2[11]);
                    wg_wait<0>();
                    gelu_sq_reg(d1, hs3);
                    so = so_sum - so;
                    bo = bo_sum - bo;
                    off += step;
                    turn++;
                }
                if (!second) break;
                const int j = ntiles - second + (rank + second + 2) % NCONS;
                second = 0;
                set_run(j, nrest, j + 4);
            }
            jt = nrest + rank;
            cur.slot = (bo - bar_a) >> 5;
            cur.par = turn >> 1 & 1;
#pragma unroll
            for (int k = 0; k < 3; k++) {
                sts128(sq + SQ_HALF + k * SQ_ROW, hs2[4 * k], hs2[4 * k + 1], hs2[4 * k + 2], hs2[4 * k + 3]);
                sts128(sq + SQ_HALF + SQC + k * SQ_ROW, hs3[4 * k], hs3[4 * k + 1], hs3[4 * k + 2], hs3[4 * k + 3]);
            }
        }
        const bool last = jt >= nrest;
        here = tile_offset(wk.tile(jt));
        if (last) {
            const uint32_t next = ldsi(sb + SM_TILES + rank * 4);
            if (elect_one()) {
                prefetch_l2(reinterpret_cast<const char*>(x) + here + w4 * WARP_BYTES, WARP_BYTES);
                if (rank == ORDER_P - 1) prefetch_l2(reinterpret_cast<const char*>(out) + next + w4 * WARP_BYTES, WARP_BYTES);
            }
        }
        uint32_t a[6][4], d0[24], d1[24], d3[24], k0[24];
        mbar_wait_once(bar_a + cur.slot * 32, cur.par);
        load_tile(a, a_addr + cur.slot * SLOT_BYTES);
        layer_norm(a, ds.ones, [&]() { if (jt >= wk.lent && wgi >= 0) named_bar(own_bar, 256); });
        if (!last) {
            store_at(a, here + w4 * WARP_BYTES - sq_warp);
            __syncwarp();
            if (elect_one()) mbar_arrive(bar_e + cur.slot * 32);
            if (jt < wk.lent) {
                jt += LENT;
                cur.advance(LENT);
                continue;
            }
        }
        wg_fence();
        gemm1_chunk<0>(d0, a, ds, 0);
        wg_commit();
        gemm1_chunk<96>(d1, a, ds, 0);
        wg_commit();
        const uint32_t scale2 = square_scale(lane_id());
        wg_wait<1>();
        gelu_sq<true>(d0, k0, sq, scale2);
        if (last) {
#pragma unroll
            for (int q = 0; q < 6; q++)
                sts128(sb + SM_RING + cur.slot * SLOT_BYTES + w4 * REGION_BYTES - sq_warp + sq + q * 512, k0[4 * q], k0[4 * q + 1], k0[4 * q + 2], k0[4 * q + 3]);
        }
        wg_fence();
        gemm1_chunk<192>(d0, a, ds, zero);
        wg_commit();
        if (jt + 2 < ntiles) named_arrive(next_bar, 256);
        wg_wait<1>();
        gelu_sq<true>(d1, k1, sq + SQC, scale2);
        wg_fence();
        gemm1_chunk<288>(d3, a, ds, 0);
        wg_commit();
        wg_wait<1>();
        gelu_sq<true>(d0, k2, sq + sq_upper, scale2);
        wg_wait<0>();
        gelu_sq<true>(d3, k3, sq + sq_upper + SQC, scale2);
        if (last) break;
        cur.advance(NCONS + ((jt < wk.nA && jt + NCONS >= wk.nA) ? 2 : 0));
        jt += NCONS;
    }
    const uint32_t lane = lane_id();
    uint32_t next_off = opaque_uniform(ldsi(sb + SM_TILES + rank * 4));
    const uint32_t s_fac = sb + SM_RING + spare * SLOT_BYTES + SQ_HALF;
    uint32_t inv_rho2;
    {
        if (rank == 0) {
            const int g = lane >> 2, t = lane & 3, i0 = w4 * 32 + lane;
            const bool leader = i0 == 0;
            const uint32_t pick = (g & 1) == (t & 1) ? (g & 2 ? 0x3c000000u : 0x00003c00u) : 0;
            const int be = bound_exp(max_w1(lane));
            const float to_fixed = pow2i(sum_exp(be) - 2 * square_exp(be));
            const uint32_t two_rows = sb + (w4 * 3 + (lane >> 3 & 1)) * SQ_ROW + ((lane >> 4) * 8 + (lane & 7)) * 16;
            const uint32_t third_row = sb + (w4 * 3 + 2) * SQ_ROW + lane * 16;
            unsigned short gam_raw[3];
            float rmax[3], f[3][4] = {};
            float2 bpair = make_float2(0.f, 0.f);
#pragma unroll 1
            for (int i = 0; i < 4; i++) {
                if (i == 1 && leader) {
                    spin_until(&sc->prep, (ldsi(s_red + RED_LAUNCH) + 1) * (W2_GROUPS * 2));
                    asm volatile("fence.proxy.async.global;" ::: "memory");
                    mbar_expect_tx(sb + BAR_W, 6 * SQ_HALF);
                }
                __syncwarp();
                named_bar(2, 128);
                if (i && leader) {
                    fence_async();
                    bulk_load(sb + SM_W2 + (i - 1) * 2 * SQ_HALF, reinterpret_cast<const char*>(sc->w2h) + (i - 1) * 2 * SQ_HALF, 2 * SQ_HALF, sb + BAR_W);
                }
                if (i == 1) {
#pragma unroll
                    for (int m = 0; m < 3; m++) {
                        asm volatile("ld.global.nc.u16 %0, [%1];" : "=h"(gam_raw[m]) : "l"(gamma + i0 + 128 * m) : "memory");
                        asm volatile("ld.global.cg.f32 %0, [%1];" : "=f"(rmax[m]) : "l"(&sc->w2max[i0 + 128 * m]) : "memory");
                    }
                    if (i0 < 96)
                        asm volatile("ld.global.cg.v2.f32 {%0, %1}, [%2];" : "=f"(bpair.x), "=f"(bpair.y)
                                     : "l"(&sc->bias[32 * (i0 % 24 >> 3) + 8 * (i0 / 24) + (i0 % 24 & 6)]) : "memory");
                }
                __syncwarp();
                const uint32_t from = i < NCONS ? SM_SQ + i * 2 * SQ_HALF : w4 < 2 ? SM_RING + spare * SLOT_BYTES : SM_RING + spare2 * SLOT_BYTES - SQ_HALF;
                if (i) named_bar(12 + i, 256);
#pragma unroll
                for (int r = 0; r < 12; r++) {
                    uint32_t u[4];
                    ldsm4_t(u, from + (r % 3 == 2 ? third_row + r / 3 * 512 : two_rows + (r / 3 * 2 + r % 3) * 256));
                    asm volatile("mma.sync.aligned.m16n8k16.row.col.f32.f16.f16.f32 {%0, %1, %2, %3}, {%4, %5, %6, %7}, {%8, %8}, {%0, %1, %2, %3};"
                                 : "+f"(f[r % 3][0]), "+f"(f[r % 3][1]), "+f"(f[r % 3][2]), "+f"(f[r % 3][3])
                                 : "r"(u[0]), "r"(u[1]), "r"(u[2]), "r"(u[3]), "r"(pick));
                }
            }
            unsigned long long* dst = sc->sum(96 * w4 + 8 * (g >> 1) + 2 * (t & 1) + (g & 1));
#pragma unroll
            for (int r = 0; r < 3; r++) {
                const float tot = r < 2 ? (t < 2 ? f[0][r & 1] + f[1][r & 1] : f[0][r + 2 & 3] + f[1][r + 2 & 3]) : (t < 2 ? f[2][0] + f[2][2] : f[2][1] + f[2][3]);
                atomicAdd(dst + (r < 2 ? (t >> 1) * 8 + r : 16 + (t >> 1)) * 32, __float2ull_rn(fminf(tot * to_fixed, 0x1p47f)) << 8 | 1);
            }
            PROF(2);
            float base[3], slope[3], reach[3];
            const float w1max = max_w1(lane);
            const float gbound = fmaxf(2.f * KZ * 9.7979590f * 192.f * w1max, 1.f) * 19.5959180f * INV_2KZ;
            const unsigned fixed = __reduce_max_sync(~0u, __float_as_uint(fmaf(gbound, fmaxf(fmaxf(rmax[0], rmax[1]), rmax[2]), fmaxf(fabsf(bpair.x), fabsf(bpair.y)))));
            if (lane == 0) sts32(s_red + 96 + w4 * 4, fixed);
#pragma unroll
            for (int m = 0; m < 3; m++) {
                base[m] = rmax[m] > 0.f ? pow2i(-row_exp(rmax[m])) * INV_2KZ : 0.f;
                slope[m] = base[m] * bf_lo(gam_raw[m]);
                reach[m] = fabsf(bf_lo(gam_raw[m])) * rmax[m] * gbound;
            }
            const float to_square = pow2i(-sum_exp(bound_exp(w1max))) * (INV_2KZ * INV_2KZ / 256);
#pragma unroll
            for (int m = 0; m < 3; m++) anchor(sq, __float_as_uint(base[m]), __float_as_uint(slope[m]), __float_as_uint(reach[m]), __float_as_uint(to_square));
            const unsigned epoch = ldsi(s_red + RED_LAUNCH);
            const uint32_t own_sum = (i0 >> 2) * 256 + (i0 & 3) * 8, own_fac = s_fac + i0 * 2;
            auto peek = [&](const void* p) {
                unsigned long long v;
                asm volatile("ld.relaxed.gpu.global.u64 %0, [%1];" : "=l"(v) : "l"(p) : "memory");
                return v;
            };
            const char* mine = reinterpret_cast<const char*>(sc->sums) + own_sum;
            unsigned n = 0;
            while (((unsigned)peek(sc->sum((blockIdx.x * 4 + w4) % (EX / 4) * 4)) & 255u) != gridDim.x)
                if (++n > SPIN_LIMIT) __trap();
            unsigned long long sum[3];
            for (;;) {
                bool all = true;
#pragma unroll
                for (int m = 0; m < 3; m++) {
                    sum[m] = peek(mine + m * (32 * 256));
                    all &= ((unsigned)sum[m] & 255u) == gridDim.x;
                }
                if (__all_sync(~0u, all)) break;
                if (++n > SPIN_LIMIT) __trap();
            }
            PROF(3);
            float gx[3];
#pragma unroll
            for (int m = 0; m < 3; m++) asm("sqrt.approx.ftz.f32 %0, %1;" : "=f"(gx[m]) : "f"(fmaf(__ull2float_rn(sum[m]), to_square, 1e-6f)));
            float tot = gx[0] + gx[1] + gx[2];
#pragma unroll
            for (int o = 16; o >= 1; o >>= 1) tot += __shfl_xor_sync(~0u, tot, o);
            const unsigned vwarp = __reduce_max_sync(~0u, __float_as_uint(fmaxf(fmaxf(reach[0] * gx[0], reach[1] * gx[1]), reach[2] * gx[2])));
            if (lane == 0) { sts32(s_red + 64 + w4 * 4, __float_as_uint(tot)); sts32(s_red + 80 + w4 * 4, vwarp); }
            named_bar(2, 128);
            uint32_t u[4], v[4], w[4];
            lds128(u[0], u[1], u[2], u[3], s_red + 64);
            lds128(v[0], v[1], v[2], v[3], s_red + 80);
            lds128(w[0], w[1], w[2], w[3], s_red + 96);
            tot = (__uint_as_float(u[0]) + __uint_as_float(u[1])) + (__uint_as_float(u[2]) + __uint_as_float(u[3]));
            const float vmax = __uint_as_float(max(max(v[0], v[1]), max(v[2], v[3]))), fmax2 = __uint_as_float(max(max(w[0], w[1]), max(w[2], w[3])));
            float inv_mean;
            asm("rcp.approx.ftz.f32 %0, %1;" : "=f"(inv_mean) : "f"(fmaf(tot, 1.f / EX, 1e-6f)));
            const int rho_e = 14 - ilog2f(fmaf(vmax, inv_mean, 2.f * fmax2));
            const float rho = pow2i(rho_e), inv_rho = pow2i(-rho_e);
            inv_rho2 = pack_bf2(inv_rho, inv_rho);
#pragma unroll
            for (int m = 0; m < 3; m++) {
                const float f = fmaf(slope[m] * gx[m], inv_mean, base[m]) * rho;
                asm volatile("st.shared.u16 [%0], %1;" ::"r"(own_fac + 256 * m), "h"((unsigned short)pack_h2(f, 0.f)) : "memory");
            }
            if (i0 < 96) sts32(sb + SM_BIASH + i0 * 4, pack_h2(bpair.x * rho, bpair.y * rho));
            if (i0 == 96) sts32(s_red + RED_INV_RHO, inv_rho2);
            named_arrive(12, NTHREADS);
            if (blockIdx.x == 0 && leader) { sc->launch = epoch + 1; sc->job = 0; }
            if (wk.lent) spin_until(&sc->lent_out, (epoch + 1) * 32 * LENT * sp.lenders);
        } else {
            named_arrive(12 + rank, 256);
            if (rank == NCONS && (unsigned)(ldsi(s_red + RED_JOB) - W2_GROUPS / 2) < 8 * LENT * sp.lenders) signal(&sc->lent_out);
            const int rw = rank * 4 - 4 + w4;
            const uint32_t row = sb + SM_W2 + rw * 512 + lane * 16;
            uint32_t u[W2_EARLY][4], f2[4];
            mbar_wait_once(sb + BAR_W, 1);
#pragma unroll
            for (int nb = 0; nb < W2_EARLY; nb++) {
                lds128(u[nb][0], u[nb][1], u[nb][2], u[nb][3], row + nb * 6144);
            }
            named_bar(12, NTHREADS);
            PROF(3);
            lds128(f2[0], f2[1], f2[2], f2[3], s_fac + rw * 64 + (lane >> 3) * 16);
            lds32(inv_rho2, s_red + RED_INV_RHO);
#pragma unroll
            for (int nb = 0; nb < 12; nb++) {
                uint32_t v[4];
                if (nb < W2_EARLY) { v[0] = u[nb % W2_EARLY][0]; v[1] = u[nb % W2_EARLY][1]; v[2] = u[nb % W2_EARLY][2]; v[3] = u[nb % W2_EARLY][3]; }
                else lds128(v[0], v[1], v[2], v[3], row + nb * 6144);
                sts128(row + nb * 6144, h_mul(v[0], f2[0]), h_mul(v[1], f2[1]), h_mul(v[2], f2[2]), h_mul(v[3], f2[3]));
            }
            fence_async();
            named_arrive(8, NTHREADS);
        }
    }
    uint32_t a[6][4], acc[24], rpar = 0, tile_off = here;
    const uint32_t bias_addr = sb + SM_BIASH + (lane & 3) * 96, lane16 = lane * 16, lane_off = ((lane >> 2) * CH + 8 * (lane & 3)) * 2;
    const uint32_t stage = sb + SM_RING + (spare + rank) % NSLOT * SLOT_BYTES + w4 * WARP_BYTES, bar_r = sb + BAR_R + warp_id * 8;
    auto load_bias = [&]() {
#pragma unroll
        for (int q = 0; q < 6; q++) lds128(acc[4 * q], acc[4 * q + 1], acc[4 * q + 2], acc[4 * q + 3], bias_addr + q * 16);
    };
    auto load_frags = [&]() {
#pragma unroll
        for (int s = 0; s < 6; s++) ldg128(a[s], reinterpret_cast<const char*>(out) + next_off + w4 * WARP_BYTES + lane16 + s * 512);
    };
    auto stage_x = [&]() {
        if (elect_one()) {
            mbar_expect_tx(bar_r, WARP_BYTES);
            bulk_load_stream(stage, reinterpret_cast<const char*>(x) + tile_off + w4 * WARP_BYTES, WARP_BYTES, bar_r);
        }
    };
    {
        named_bar(8 + rank, rank ? 256 : NTHREADS);
        if (rank == 0) PROF(4);
        load_bias();
        pin(k1); pin(k2); pin(k3);
        wg_fence();
        gemm2_chunk<288>(acc, k3, ds);
        wg_commit();
        gemm2_chunk<96>(acc, k1, ds);
        wg_commit();
        gemm2_chunk<192>(acc, k2, ds);
        wg_commit();
        stage_x();
        wg_wait<2>();
        uint32_t k0[24];
#pragma unroll
        for (int q = 0; q < 6; q++)
            lds128(k0[4 * q], k0[4 * q + 1], k0[4 * q + 2], k0[4 * q + 3], sb + SM_RING + cur.slot * SLOT_BYTES + w4 * REGION_BYTES + lane16 + q * 512);
        pin(k0);
        wg_fence();
        gemm2_chunk<0>(acc, k0, ds);
        wg_commit();
        if (rank < NCONS) named_arrive(9 + rank, 256);
        wg_wait<2>();
        load_frags();
        if (lane16 == 0) mbar_arrive(sb + BAR_PIN);
        mbar_wait(bar_r, rpar);
        wg_wait<0>();
    }
    auto lent = [&](uint32_t entry) { return &sc->lent[((wk.index * LENT + (entry & 3) - 1) * 4 + w4) * (24 * 32)]; };
    for (jt = rank - 4; jt < nrest; jt += 4) {
        if (jt >= zero) {
        tile_off = next_off;
        lds32(next_off, sb + SM_TILES + (jt + 4) * 4);
        if (tile_off & 3) {
            const uint4* src = lent(tile_off) + lane;
            tile_off &= ~3u;
            next_off = __shfl_sync(~0u, next_off, 0);
            stage_x();
            if (elect_one()) prefetch_l2(reinterpret_cast<const char*>(out) + next_off + w4 * WARP_BYTES, WARP_BYTES);
            load_bias();
#pragma unroll 1
            for (int half = 0; half < 2; half++, src += 12 * 32) {
                uint32_t gl[48];
#pragma unroll
                for (int s = 0; s < 12; s++) ldg128(reinterpret_cast<uint32_t (&)[4]>(gl[4 * s]), src + s * 32);
                if (!half) {
                    named_bar(4 + rank, 256);
                    named_arrive(4 + ((rank + 1) & 3), 256);
                }
                pin(gl);
                wg_fence();
#pragma unroll
                for (int s = 0; s < 12; s++) wgmma(acc, gl[4 * s], gl[4 * s + 1], gl[4 * s + 2], gl[4 * s + 3], ds.w2[12 * half + s], 1);
                wg_commit();
                wg_wait<0>();
            }
            load_frags();
            mbar_wait(bar_r, rpar);
        } else {
            uint32_t d0[12], d1[12], g0[12], g1[12];
            next_off = __shfl_sync(~0u, next_off, 0);
            const bool more = jt + 4 < nrest && !(next_off & 3);
            load_bias();
            wg_fence();
            gemm1_chunk<0>(d0, a, ds, 0);
            wg_commit();
            if (jt && jt + 1 < nrest) named_bar(4 + rank, 256);
            gemm1_chunk<48>(d1, a, ds, 0);
            wg_commit();
            wg_wait<1>();
#define CNX_STEP(C, D, G)                                                   \
    gelu_to(G, D);                                                          \
    wg_fence();                                                             \
    if (C < 6) gemm1_chunk<48 * (C < 6 ? C + 2 : 0)>(D, a, ds, zero);      \
    gemm2_chunk<48 * C>(acc, G, ds);                                       \
    wg_commit();                                                            \
    if (C == 1 && jt + 2 < nrest) named_arrive(4 + ((rank + 1) & 3), 256); \
    wg_wait<(C < 7 ? 1 : 0)>();
            CNX_STEP(0, d0, g0)
            stage_x();
            if (elect_one()) {
                if (more) prefetch_l2(reinterpret_cast<const char*>(out) + next_off + w4 * WARP_BYTES, WARP_BYTES);
                else if (next_off & 3) prefetch_l2(lent(next_off), 24 * 32 * 16);
            }
            CNX_STEP(1, d1, g1)
            CNX_STEP(2, d0, g0)
            CNX_STEP(3, d1, g1)
            CNX_STEP(4, d0, g0)
            CNX_STEP(5, d1, g1)
            CNX_STEP(6, d0, g0)
#pragma unroll
            for (int s = 0; s < 6; s++) ldg128_if(more, a[s], reinterpret_cast<const char*>(out) + next_off + w4 * WARP_BYTES + lane16 + s * 512);
            if (lane16 == 0) mbar_arrive(sb + BAR_PIN);
            mbar_wait(bar_r, rpar);
            CNX_STEP(7, d1, g1)
#undef CNX_STEP
        }
        }
        {
            pin(acc);
            rpar ^= 1;
            uint4* op = reinterpret_cast<uint4*>(reinterpret_cast<char*>(out) + tile_off + w4 * WARP_BYTES + lane_off);
#pragma unroll
            for (int h = 0; h < 2; h++)
#pragma unroll
                for (int m = 0; m < 3; m++) {
                    uint32_t xin[4], o[4];
                    lds128(xin[0], xin[1], xin[2], xin[3], stage + lane_off + h * 1536 + m * 64);
#pragma unroll
                    for (int q = 0; q < 4; q++) {
                        const uint32_t v = acc[2 * (4 * m + q) + h];
                        o[q] = bf_fma(pack_bf2(h_lo(v), h_hi(v)), inv_rho2, xin[q]);
                    }
                    __stcs(op + h * 96 + m * 4, make_uint4(o[0], o[1], o[2], o[3]));
                }
            __syncwarp();
        }
    }
    PROF(5);
}

}

typedef CUresult (*EncodeTiledFn)(CUtensorMap*, CUtensorMapDataType, cuuint32_t, void*, const cuuint64_t*, const cuuint64_t*,
                                  const cuuint32_t*, const cuuint32_t*, CUtensorMapInterleave, CUtensorMapSwizzle,
                                  CUtensorMapL2promotion, CUtensorMapFloatOOBfill);

extern "C" void kernel_launch(void* const* d_in, const int* in_sizes, int n_in, void* d_out, int out_size) {
    using namespace cnx;
    static EncodeTiledFn encode = nullptr;
    static int num_sms = 0;
    static Scratch* scratch = nullptr;
    if (!encode) {
        void* fn = nullptr;
        cudaDriverEntryPointQueryResult qr;
        cudaGetDriverEntryPoint("cuTensorMapEncodeTiled", &fn, cudaEnableDefault, &qr);
        encode = (EncodeTiledFn)fn;
        cudaGetSymbolAddress((void**)&scratch, g_scratch);
        int dev = 0;
        cudaGetDevice(&dev);
        cudaDeviceGetAttribute(&num_sms, cudaDevAttrMultiProcessorCount, dev);
        if (num_sms > MAX_CTAS) num_sms = MAX_CTAS;
        cudaFuncSetAttribute(block_kernel, cudaFuncAttributeMaxDynamicSharedMemorySize, SM_TOTAL);
    }
    CUtensorMap tm;
    cuuint64_t dims[3] = {(cuuint64_t)CH, (cuuint64_t)IMG_W, (cuuint64_t)IMG_H};
    cuuint64_t strides[2] = {(cuuint64_t)CH * 2, (cuuint64_t)CH * 2 * IMG_W};
    cuuint32_t box[3] = {(cuuint32_t)CH, (cuuint32_t)REGION_PX, 1};
    cuuint32_t estr[3] = {1, 1, 1};
    encode(&tm, CU_TENSOR_MAP_DATA_TYPE_BFLOAT16, 3, d_in[0], dims, strides, box, estr, CU_TENSOR_MAP_INTERLEAVE_NONE,
           CU_TENSOR_MAP_SWIZZLE_NONE, CU_TENSOR_MAP_L2_PROMOTION_L2_128B, CU_TENSOR_MAP_FLOAT_OOB_FILL_NONE);
    Params pm = {};
    Descs& ds = pm.ds;
    for (int c = 0; c < 8; c++)
        for (int k = 0; k < 6; k++) ds.w1[c][k] = make_desc(SB + SM_W1 + c * 6 * 1536 + k * 256, 128, 1536);
    for (int k = 0; k < 24; k++) ds.w2[k] = make_desc(SB + SM_W2 + k * 256, 128, 6144);
    ds.ones = make_desc(SB + SM_ONES, 0, 0);
    CUtensorMap tw;
    cuuint64_t wdims[2] = {(cuuint64_t)EX, (cuuint64_t)CH};
    cuuint64_t wstrides[1] = {(cuuint64_t)EX * 2};
    cuuint32_t wbox[2] = {64, (cuuint32_t)CH};
    encode(&tw, CU_TENSOR_MAP_DATA_TYPE_BFLOAT16, 2, d_in[2], wdims, wstrides, wbox, estr, CU_TENSOR_MAP_INTERLEAVE_NONE,
           CU_TENSOR_MAP_SWIZZLE_128B, CU_TENSOR_MAP_L2_PROMOTION_L2_128B, CU_TENSOR_MAP_FLOAT_OOB_FILL_NONE);
    Split& sp = pm.sp;
    sp = {NTILES / num_sms, NTILES % num_sms, 1, 1 << 16, 0, {}};
    if (sp.per_cta + 9 > MAX_ROWS) return;
    if (sp.extra && sp.extra * (8 * LENT + 1) + W2_GROUPS / 2 <= num_sms && sp.per_cta >= 5 * LENT + 8) {
        sp.period = num_sms / sp.extra;
        sp.inv_period = 65535 / sp.period + 1;
        sp.lenders = sp.extra;
        for (int l = 0; l < sp.extra; l++) {
            const Work w = get_work((l + 1) * sp.period - sp.period / 2 - 1, sp);
            for (int e = 0; e < LENT; e++) sp.lent_off[l * LENT + e] = tile_offset(w.tile(e));
            if (w.nA < 2 * LENT) sp.lenders = 0;
        }
    }
    pm.x = (const __nv_bfloat16*)d_in[0];
    pm.dw = (const __nv_bfloat16*)d_in[1];
    pm.w2 = (const __nv_bfloat16*)d_in[3];
    pm.gamma = (const __nv_bfloat16*)d_in[4];
    pm.beta = (const __nv_bfloat16*)d_in[5];
    pm.out = (__nv_bfloat16*)d_out;
    pm.sc = scratch;
    block_kernel<<<num_sms, NTHREADS, SM_TOTAL>>>(tm, tw, pm);
}
```

```cpp
#include <cuda_runtime.h>
#include <cuda_bf16.h>
#include <cuda_fp16.h>
#include <cuda.h>
#include <stdint.h>

namespace cnx {

constexpr int IMG_H = 512, IMG_W = 512, CH = 96, EX = 384;
constexpr int TILE_W = 64;
constexpr int NTILES = (IMG_W / TILE_W) * IMG_H;
constexpr int NSLOT = 6;
constexpr int REGION_PX = 18;
constexpr int REGION_BYTES = REGION_PX * CH * 2;
constexpr int SLOT_BYTES = 4 * REGION_BYTES;
constexpr int A_LBO = 144, A_SBO = 12 * A_LBO;
constexpr int PREFETCH_ROWS = 3;
constexpr int NCONS = 3;
constexpr int CONS_THREADS = 128 * NCONS;
constexpr int NTHREADS = 128 + CONS_THREADS;
constexpr int MAX_ROWS = 52;
constexpr int TILE_BYTES = TILE_W * CH * 2, WARP_BYTES = TILE_BYTES / 4;
constexpr int ORDER_P = 3;
constexpr int W2_EARLY = 10;
static_assert(MAX_ROWS <= 128, "one table entry per producer thread");
static_assert(2 * A_SBO == REGION_BYTES && REGION_BYTES % 128 == 0, "region layout");

constexpr uint32_t SB = 1024;
constexpr int SM_W1 = 0;
constexpr int SM_W2 = SM_W1 + CH * EX * 2;
constexpr int SM_RING = SM_W2 + CH * EX * 2;
constexpr int SM_BIASH = SM_RING + NSLOT * SLOT_BYTES;
constexpr int SM_RED = SM_BIASH + 384;
constexpr int RED_MAX = 0, RED_LAUNCH = 48, RED_INV_RHO = 52, RED_JOB = 56;
constexpr int SM_TILES = SM_RED + 256;
constexpr int SM_ONES = SM_TILES + MAX_ROWS * 4;
constexpr int SM_BAR = SM_ONES + 128;
constexpr int BAR_X = SM_BAR;
constexpr int BAR_A = BAR_X + NSLOT * 4 * 8;
constexpr int BAR_E = BAR_A + NSLOT * 4 * 8;
constexpr int BAR_PIN = BAR_E + NSLOT * 4 * 8;
constexpr int BAR_W = BAR_PIN + 8;
constexpr int BAR_F = BAR_W + 6 * 8;
constexpr int BAR_R = BAR_F + 8;
constexpr int SM_TOTAL = BAR_R + 16 * 8;
constexpr int SM_FILTER = SM_RING + (NSLOT - 1) * SLOT_BYTES + 9 * 128;
constexpr int SM_SQ = SM_W2;
constexpr int SQ_ROW = 128 * 16, SQ_HALF = 6 * SQ_ROW;
static_assert(SM_ONES % 16 == 0 && SM_TOTAL <= 232448, "shared memory budget");

constexpr float KZ = 0.3292034911525734f;
constexpr uint32_t GELU_C2 = 0x40d940d9u;
constexpr float INV_2KZ = 0.5f / KZ;
constexpr uint32_t CONV_SCALE2 = 0x2f802f80u;
constexpr unsigned SPIN_LIMIT = 1u << 19;

constexpr int MAX_CTAS = 170;
constexpr int W2_GROUPS = EX / 8;
constexpr int LENT = 3, MAX_LENDERS = MAX_CTAS / (8 * LENT + 1);
struct Scratch {
    uint32_t w2h[EX * CH / 2];
    float w2max[EX];
    float bias[CH + 32];
    unsigned long long sums[EX / 4][32];
    __device__ __forceinline__ unsigned long long* sum(int e) { return &sums[e >> 2][e & 3]; }
    uint4 lent[MAX_LENDERS * LENT * 8 * 4 * 3 * 32];
    unsigned launch, pad0[31], early, pad1[31], prep, pad2[31], lent_out, pad3[31];
    unsigned job;
};
__device__ __align__(128) Scratch g_scratch;

#define PROF(k)

__device__ __forceinline__ uint32_t smem_u32(const void* p) { return (uint32_t)__cvta_generic_to_shared(p); }
__device__ __forceinline__ void mbar_init(uint32_t bar, uint32_t cnt) {
    asm volatile("mbarrier.init.shared::cta.b64 [%0], %1;" ::"r"(bar), "r"(cnt) : "memory");
}
__device__ __forceinline__ void mbar_arrive(uint32_t bar) {
    asm volatile("mbarrier.arrive.shared::cta.b64 _, [%0];" ::"r"(bar) : "memory");
}
__device__ __forceinline__ void mbar_expect_tx(uint32_t bar, uint32_t bytes) {
    asm volatile("mbarrier.arrive.expect_tx.shared::cta.b64 _, [%0], %1;" ::"r"(bar), "r"(bytes) : "memory");
}
__device__ __forceinline__ bool mbar_try(uint32_t bar, uint32_t par) {
    uint32_t ok;
    asm volatile("{\n.reg .pred p;\nmbarrier.try_wait.parity.shared::cta.b64 p, [%1], %2;\nselp.u32 %0, 1, 0, p;\n}\n"
                 : "=r"(ok) : "r"(bar), "r"(par) : "memory");
    return ok != 0;
}
__device__ __forceinline__ void mbar_wait(uint32_t bar, uint32_t par) {
    unsigned n = 0;
    while (!mbar_try(bar, par)) {
        if (++n > SPIN_LIMIT) __trap();
    }
}
__device__ __forceinline__ void mbar_wait_once(uint32_t bar, uint32_t par) {
    unsigned n = 0;
    bool ok;
#pragma unroll 1
    do {
        ok = mbar_try(bar, par);
        if (++n > SPIN_LIMIT) __trap();
    } while (!ok);
}
__device__ __forceinline__ bool elect_one() {
    uint32_t ok;
    asm volatile("{\n.reg .pred p;\nelect.sync _|p, 0xffffffff;\nselp.u32 %0, 1, 0, p;\n}\n" : "=r"(ok));
    return ok != 0;
}
__device__ __forceinline__ uint32_t opaque(uint32_t v) { return __shfl_sync(~0u, v, threadIdx.x & 31); }
__device__ __forceinline__ uint32_t lane_id() { uint32_t v; asm volatile("mov.u32 %0, %%laneid;" : "=r"(v)); return v; }
__device__ __forceinline__ uint32_t opaque_uniform(uint32_t v) { return __shfl_sync(~0u, v, 0); }
__device__ __forceinline__ void named_bar(int id, int n) { asm volatile("bar.sync %0, %1;" ::"r"(id), "r"(n) : "memory"); }
__device__ __forceinline__ void named_arrive(int id, int n) { asm volatile("bar.arrive %0, %1;" ::"r"(id), "r"(n) : "memory"); }
__device__ __forceinline__ void fence_async() { asm volatile("fence.proxy.async.shared::cta;" ::: "memory"); }
constexpr uint64_t EVICT_FIRST = 0x12F0000000000000ull;
__device__ __forceinline__ void tma_row(uint32_t dst, const CUtensorMap* tm, uint32_t bar, int x, int y) {
    asm volatile("cp.async.bulk.tensor.3d.shared::cluster.global.mbarrier::complete_tx::bytes.L2::cache_hint [%0], [%1, {%3, %4, %5}], [%2], %6;"
                 ::"r"(dst), "l"(tm), "r"(bar), "r"(0), "r"(x), "r"(y), "l"(EVICT_FIRST) : "memory");
}
__device__ __forceinline__ void bulk_load_stream(uint32_t dst, const void* src, uint32_t bytes, uint32_t bar) {
    asm volatile("cp.async.bulk.shared::cluster.global.mbarrier::complete_tx::bytes.L2::cache_hint [%0], [%1], %2, [%3], %4;"
                 ::"r"(dst), "l"(src), "r"(bytes), "r"(bar), "l"(EVICT_FIRST) : "memory");
}
__device__ __forceinline__ void prefetch_l2(const void* src, uint32_t bytes) {
    asm volatile("cp.async.bulk.prefetch.L2.global [%0], %1;" ::"l"(src), "r"(bytes) : "memory");
}
__device__ __forceinline__ void tma_2d(uint32_t dst, const CUtensorMap* tm, uint32_t bar, int x, int y) {
    asm volatile("cp.async.bulk.tensor.2d.shared::cluster.global.mbarrier::complete_tx::bytes [%0], [%1, {%3, %4}], [%2];"
                 ::"r"(dst), "l"(tm), "r"(bar), "r"(x), "r"(y) : "memory");
}
__device__ __forceinline__ void bulk_load(uint32_t dst, const void* src, uint32_t bytes, uint32_t bar) {
    asm volatile("cp.async.bulk.shared::cluster.global.mbarrier::complete_tx::bytes [%0], [%1], %2, [%3];"
                 ::"r"(dst), "l"(src), "r"(bytes), "r"(bar) : "memory");
}
__device__ __forceinline__ void wg_fence() { asm volatile("wgmma.fence.sync.aligned;" ::: "memory"); }
__device__ __forceinline__ void wg_commit() { asm volatile("wgmma.commit_group.sync.aligned;" ::: "memory"); }
template <int N> __device__ __forceinline__ void wg_wait() { asm volatile("wgmma.wait_group.sync.aligned %0;" ::"n"(N) : "memory"); }
template <int N> __device__ __forceinline__ void pin(uint32_t (&d)[N]) {
#pragma unroll
    for (int q = 0; q < N; q++) asm volatile("" : "+r"(d[q])::"memory");
}
__device__ __forceinline__ void stg128(void* p, const uint32_t (&v)[4]) {
    asm volatile("st.global.v4.u32 [%0], {%1, %2, %3, %4};" ::"l"(p), "r"(v[0]), "r"(v[1]), "r"(v[2]), "r"(v[3]) : "memory");
}
__device__ __forceinline__ void ldg128(uint32_t (&v)[4], const void* p) {
    asm volatile("ld.global.L1::no_allocate.v4.u32 {%0, %1, %2, %3}, [%4];" : "=r"(v[0]), "=r"(v[1]), "=r"(v[2]), "=r"(v[3]) : "l"(p) : "memory");
}
__device__ __forceinline__ void ldg128_if(bool on, uint32_t (&v)[4], const void* p) {
    asm volatile("{\n.reg .pred p;\nsetp.ne.b32 p, %5, 0;\n@p ld.global.L1::no_allocate.v4.u32 {%0, %1, %2, %3}, [%4];\n}\n"
                 : "+r"(v[0]), "+r"(v[1]), "+r"(v[2]), "+r"(v[3]) : "l"(p), "r"((int)on) : "memory");
}
__host__ __device__ constexpr uint64_t make_desc(uint32_t addr, uint32_t lbo, uint32_t sbo) {
    return (uint64_t)((addr & 0x3FFFF) >> 4) | ((uint64_t)(lbo >> 4) << 16) | ((uint64_t)(sbo >> 4) << 32);
}
__device__ __forceinline__ void wgmma(uint32_t (&d)[12], uint32_t a0, uint32_t a1, uint32_t a2, uint32_t a3, uint64_t db, int acc) {
    asm volatile("{\n.reg .pred p;\nsetp.ne.b32 p, %17, 0;\n"
                 "wgmma.mma_async.sync.aligned.m64n48k16.f16.f16.f16 "
                 "{%0, %1, %2, %3, %4, %5, %6, %7, %8, %9, %10, %11}, "
                 "{%12, %13, %14, %15}, %16, p, 1, 1, 0;\n}\n"
                 : "+r"(d[0]), "+r"(d[1]), "+r"(d[2]), "+r"(d[3]), "+r"(d[4]), "+r"(d[5]), "+r"(d[6]), "+r"(d[7]), "+r"(d[8]), "+r"(d[9]), "+r"(d[10]), "+r"(d[11])
                 : "r"(a0), "r"(a1), "r"(a2), "r"(a3), "l"(db), "r"(acc));
}
__device__ __forceinline__ void wgmma(uint32_t (&d)[24], uint32_t a0, uint32_t a1, uint32_t a2, uint32_t a3, uint64_t db, int acc) {
    asm volatile("{\n.reg .pred p;\nsetp.ne.b32 p, %29, 0;\n"
                 "wgmma.mma_async.sync.aligned.m64n96k16.f16.f16.f16 "
                 "{%0, %1, %2, %3, %4, %5, %6, %7, %8, %9, %10, %11, %12, %13, %14, %15, %16, %17, %18, %19, %20, %21, %22, %23}, "
                 "{%24, %25, %26, %27}, %28, p, 1, 1, 0;\n}\n"
                 : "+r"(d[0]), "+r"(d[1]), "+r"(d[2]), "+r"(d[3]), "+r"(d[4]), "+r"(d[5]), "+r"(d[6]), "+r"(d[7]), "+r"(d[8]), "+r"(d[9]), "+r"(d[10]), "+r"(d[11]), "+r"(d[12]), "+r"(d[13]), "+r"(d[14]), "+r"(d[15]), "+r"(d[16]), "+r"(d[17]), "+r"(d[18]), "+r"(d[19]), "+r"(d[20]), "+r"(d[21]), "+r"(d[22]), "+r"(d[23])
                 : "r"(a0), "r"(a1), "r"(a2), "r"(a3), "l"(db), "r"(acc));
}
template <int ACC>
__device__ __forceinline__ void wgmma_rowsum(float (&d)[4], const uint32_t (&a)[4], uint64_t ones) {
    asm volatile("{\n.reg .pred p;\nsetp.ne.b32 p, %9, 0;\n"
                 "wgmma.mma_async.sync.aligned.m64n8k16.f32.bf16.bf16 {%0, %1, %2, %3}, {%4, %5, %6, %7}, %8, p, 1, 1, 0;\n}\n"
                 : "+f"(d[0]), "+f"(d[1]), "+f"(d[2]), "+f"(d[3])
                 : "r"(a[0]), "r"(a[1]), "r"(a[2]), "r"(a[3]), "l"(ones), "n"(ACC));
}
__device__ __forceinline__ void ldsm4(uint32_t (&r)[4], uint32_t addr) {
    asm volatile("ldmatrix.sync.aligned.m8n8.x4.shared.b16 {%0, %1, %2, %3}, [%4];"
                 : "=r"(r[0]), "=r"(r[1]), "=r"(r[2]), "=r"(r[3]) : "r"(addr) : "memory");
}
__device__ __forceinline__ void ldsm4_t(uint32_t (&r)[4], uint32_t addr) {
    asm volatile("ldmatrix.sync.aligned.m8n8.x4.trans.shared.b16 {%0, %1, %2, %3}, [%4];"
                 : "=r"(r[0]), "=r"(r[1]), "=r"(r[2]), "=r"(r[3]) : "r"(addr) : "memory");
}
__device__ __forceinline__ void stsm4(uint32_t addr, uint32_t a, uint32_t b, uint32_t c, uint32_t d) {
    asm volatile("stmatrix.sync.aligned.m8n8.x4.shared.b16 [%0], {%1, %2, %3, %4};"
                 ::"r"(addr), "r"(a), "r"(b), "r"(c), "r"(d) : "memory");
}
__device__ __forceinline__ uint32_t transpose8x8(uint32_t v) {
    uint32_t d; asm volatile("movmatrix.sync.aligned.m8n8.trans.b16 %0, %1;" : "=r"(d) : "r"(v)); return d;
}
__device__ __forceinline__ void spin_until(const unsigned* counter, unsigned target) {
    unsigned n = 0, c;
    do {
        asm volatile("ld.acquire.gpu.global.u32 %0, [%1];" : "=r"(c) : "l"(counter) : "memory");
        if (++n > SPIN_LIMIT) __trap();
    } while ((int)(c - target) < 0);
}
__device__ __forceinline__ void signal(unsigned* counter) {
    __syncwarp();
    if (elect_one()) asm volatile("red.release.gpu.global.add.u32 [%0], 1;" ::"l"(counter) : "memory");
    __syncwarp();
}
__device__ __forceinline__ void lds128(uint32_t& a, uint32_t& b, uint32_t& c, uint32_t& d, uint32_t addr) {
    asm volatile("ld.shared.v4.u32 {%0, %1, %2, %3}, [%4];" : "=r"(a), "=r"(b), "=r"(c), "=r"(d) : "r"(addr) : "memory");
}
__device__ __forceinline__ void lds64(uint32_t& a, uint32_t& b, uint32_t addr) {
    asm volatile("ld.shared.v2.u32 {%0, %1}, [%2];" : "=r"(a), "=r"(b) : "r"(addr) : "memory");
}
__device__ __forceinline__ void lds32(uint32_t& a, uint32_t addr) {
    asm volatile("ld.shared.u32 %0, [%1];" : "=r"(a) : "r"(addr) : "memory");
}
__device__ __forceinline__ int ldsi(uint32_t addr) {
    uint32_t v;
    lds32(v, addr);
    return (int)v;
}
__device__ __forceinline__ float ldsf(uint32_t addr) {
    uint32_t v;
    lds32(v, addr);
    return __uint_as_float(v);
}
__device__ __forceinline__ void sts32(uint32_t addr, uint32_t a) {
    asm volatile("st.shared.u32 [%0], %1;" ::"r"(addr), "r"(a) : "memory");
}
__device__ __forceinline__ void sts128(uint32_t addr, uint32_t a, uint32_t b, uint32_t c, uint32_t d) {
    asm volatile("st.shared.v4.u32 [%0], {%1, %2, %3, %4};" ::"r"(addr), "r"(a), "r"(b), "r"(c), "r"(d) : "memory");
}
__device__ __forceinline__ void sts64(uint32_t addr, uint32_t a, uint32_t b) {
    asm volatile("st.shared.v2.u32 [%0], {%1, %2};" ::"r"(addr), "r"(a), "r"(b) : "memory");
}
__device__ __forceinline__ void anchor(uint32_t addr, uint32_t a, uint32_t b, uint32_t c, uint32_t d) {
    asm volatile("{\n.reg .pred p;\nsetp.eq.b32 p, %0, 0;\n@p st.shared.v4.u32 [%0], {%1, %2, %3, %4};\n}\n"
                 ::"r"(addr), "r"(a), "r"(b), "r"(c), "r"(d) : "memory");
}
__device__ __forceinline__ uint32_t bf_fma(uint32_t a, uint32_t b, uint32_t c) {
    uint32_t d; asm("fma.rn.bf16x2 %0, %1, %2, %3;" : "=r"(d) : "r"(a), "r"(b), "r"(c)); return d;
}
__device__ __forceinline__ uint32_t bf_mul(uint32_t a, uint32_t b) {
    uint32_t d; asm("mul.rn.bf16x2 %0, %1, %2;" : "=r"(d) : "r"(a), "r"(b)); return d;
}
__device__ __forceinline__ uint32_t bf_absmax(uint32_t a, uint32_t b) {
    uint32_t d; asm("max.xorsign.abs.bf16x2 %0, %1, %2;" : "=r"(d) : "r"(a), "r"(b)); return d;
}
__device__ __forceinline__ uint32_t h_fma(uint32_t a, uint32_t b, uint32_t c) {
    uint32_t d; asm("fma.rn.f16x2 %0, %1, %2, %3;" : "=r"(d) : "r"(a), "r"(b), "r"(c)); return d;
}
__device__ __forceinline__ uint32_t h_mul(uint32_t a, uint32_t b) {
    uint32_t d; asm("mul.rn.f16x2 %0, %1, %2;" : "=r"(d) : "r"(a), "r"(b)); return d;
}
__device__ __forceinline__ uint32_t h_tanh(uint32_t a) {
    uint32_t d; asm("tanh.approx.f16x2 %0, %1;" : "=r"(d) : "r"(a)); return d;
}
__device__ __forceinline__ uint32_t pack_h2(float lo, float hi) {
    uint32_t d; asm("cvt.rn.f16x2.f32 %0, %1, %2;" : "=r"(d) : "f"(hi), "f"(lo)); return d;
}
__device__ __forceinline__ uint32_t pack_bf2(float lo, float hi) {
    uint32_t d; asm("cvt.rn.bf16x2.f32 %0, %1, %2;" : "=r"(d) : "f"(hi), "f"(lo)); return d;
}
__device__ __forceinline__ float bf_lo(uint32_t v) { return __uint_as_float(v << 16); }
__device__ __forceinline__ float bf_hi(uint32_t v) { return __uint_as_float(v & 0xffff0000u); }
__device__ __forceinline__ float h_lo(uint32_t v) { return __low2float(*reinterpret_cast<__half2*>(&v)); }
__device__ __forceinline__ float h_hi(uint32_t v) { return __high2float(*reinterpret_cast<__half2*>(&v)); }
__device__ __forceinline__ float warp_absmax(uint32_t v) {
    return __uint_as_float(__reduce_max_sync(~0u, max((v & 0x7fffu) << 16, v & 0x7fff0000u)));
}
__device__ __forceinline__ uint32_t gelu2(uint32_t z) {
    uint32_t p = h_fma(z, z, GELU_C2);
    uint32_t t = h_tanh(h_mul(z, p));
    return h_fma(z, t, z);
}
__device__ __forceinline__ float pow2i(int e) { return __uint_as_float((uint32_t)(e + 127) << 23); }
__device__ __forceinline__ int ilog2f(float v) {
    int e = (int)((__float_as_uint(v) >> 23) & 0xff) - 127;
    return max(-100, min(100, e));
}

__device__ __forceinline__ int bound_exp(float w1max) { return w1max > 0.f ? ilog2f(2.f * KZ * 96.f * w1max) : 0; }
__device__ __forceinline__ bool plain_squares(int e) { return (unsigned)(4 - e) <= 6; }
__device__ __forceinline__ int square_exp(int e) { return plain_squares(e) ? 0 : max(-14, min(4 - e, 14)); }
__device__ __forceinline__ int sum_exp(int e) { return max(-90, min(90, 33 - 2 * e)); }
__device__ __forceinline__ int row_exp(float m) { return 2 - ilog2f(m); }

struct Split {
    int per_cta, extra, period, inv_period, lenders;
    uint32_t lent_off[MAX_LENDERS * LENT];
    __host__ __device__ __forceinline__ int longer_before(int cta) const {
        const int n = (cta + period / 2) * inv_period >> 16;
        return n < extra ? n : extra;
    }
};
struct Work {
    int tA, tB, nA, nB, dir, rows, lent, index;
    __host__ __device__ __forceinline__ int tile(int j) const { return j < nA ? tA + dir * j : tB + dir * (j - nA); }
};
__host__ __device__ __forceinline__ Work get_work(int cta, const Split& sp) {
    Work w;
    const int before = sp.longer_before(cta), longer = sp.longer_before(cta + 1) - before;
    w.lent = longer && sp.lenders ? LENT : 0;
    w.index = before;
    const int t0 = cta * sp.per_cta + before, t1 = t0 + sp.per_cta + longer;
    const int tm = t1 < (t0 | 511) + 1 ? t1 : (t0 | 511) + 1;
    const bool swap = t1 > tm && t1 - tm < tm - t0, down = cta & 1;
    w.nA = swap ? t1 - tm : tm - t0;
    w.nB = t1 - t0 - w.nA;
    w.tA = down ? (swap ? tm : t0) : (swap ? t1 : tm) - 1;
    w.tB = down ? (swap ? t0 : tm) : (swap ? tm : t1) - 1;
    w.dir = down ? 1 : -1;
    w.rows = w.nA + 2 + (w.nB ? w.nB + 2 : 0);
    return w;
}
__device__ __forceinline__ int row_code(const Work& w, int i) {
    const bool in_a = i < w.nA + 2;
    const int t = in_a ? w.tA : w.tB;
    return ((t & 511) + w.dir * ((in_a ? i : i - (w.nA + 2)) - 1)) << 16 | (t >> 9) * TILE_W;
}
__host__ __device__ __forceinline__ uint32_t tile_offset(int tile) { return ((tile & 511) * IMG_W + (tile >> 9) * TILE_W) * (CH * 2); }
__device__ __forceinline__ int tile_order(int j, int n) {
    return j % ORDER_P == ORDER_P - 1 ? j / ORDER_P : n - 1 - (j - j / ORDER_P);
}
__device__ __forceinline__ void issue_region(const CUtensorMap* tm, uint32_t dst, uint32_t bar, int warp, int code) {
    mbar_expect_tx(bar, REGION_BYTES);
    tma_row(dst, tm, bar, (code & 0xffff) + (16 * warp - 1), code >> 16);
}

template <class Event>
__device__ __forceinline__ void conv_producer(const Work& wk, const CUtensorMap* tm, uint32_t sb, int warp, Event event) {
    const int lane = threadIdx.x & 31;
    const int j = lane & 15, grp = lane >> 4;
    const uint32_t reg0 = sb + SM_RING + warp * REGION_BYTES;
    const uint32_t bars = sb + SM_BAR + warp * 8;
    if (warp * 32 + lane < MAX_ROWS) {
        const int i = warp * 32 + lane, before = min(i / 5, wk.lent);
        const bool back = i % 5 == 0 && i > 0 && i / 5 <= wk.lent;
        sts32(sb + SM_TILES + i * 4, back ? tile_offset(wk.tile(before - 1)) | before
                                          : tile_offset(wk.tile(wk.lent + tile_order(i - before, wk.nA + wk.nB - 4 - wk.lent))));
    }
    const uint32_t ld64 = opaque(reg0 + grp * 8 * 192 + j * 8), ld32 = opaque(reg0 + grp * 8 * 192 + 128 + j * 4);
    const uint32_t st64 = opaque(reg0 + grp * A_SBO + (j >> 1) * A_LBO + (j & 1) * 8);
    const uint32_t st32 = opaque(reg0 + grp * A_SBO + (8 + (j >> 2)) * A_LBO + (j & 3) * 4);
    named_bar(0, NTHREADS);
    uint32_t w[3][3][3];
    mbar_wait_once(sb + BAR_F, 0);
#pragma unroll
    for (int tap = 0; tap < 9; tap++) {
        const uint32_t p = sb + SM_FILTER + (3 + wk.dir * 3 * (tap / 3 - 1) + tap % 3) * (CH * 2);
        lds64(w[tap / 3][tap % 3][0], w[tap / 3][tap % 3][1], p + 8 * j);
        lds32(w[tap / 3][tap % 3][2], p + 128 + 4 * j);
#pragma unroll
        for (int q = 0; q < 3; q++) w[tap / 3][tap % 3][q] = bf_mul(w[tap / 3][tap % 3][q], CONV_SCALE2);
    }
#pragma unroll
    for (int tap = 0; tap < 9; tap++) sts64(reg0 + (NSLOT - 1) * SLOT_BYTES + tap * 128 + j * 8, w[tap / 3][tap % 3][1], w[tap / 3][tap % 3][0]);
    named_bar(1, 128);
#pragma unroll
    for (int tap = 0; tap < 9; tap++) lds64(w[tap / 3][tap % 3][1], w[tap / 3][tap % 3][0], reg0 + (NSLOT - 1) * SLOT_BYTES + tap * 128 + j * 8);
    static_assert(2 * PREFETCH_ROWS == NSLOT && SLOT_BYTES % 32 == 0, "slot arithmetic");
    uint32_t bo = 0, so = 0, par = 0, pbo = PREFETCH_ROWS * 32, ppar = 1;
    int px, py;
    auto request = [&]() {
        mbar_wait_once(bars + (BAR_E - SM_BAR) + pbo, ppar);
        if (elect_one()) {
            mbar_expect_tx(bars + pbo, REGION_BYTES);
            tma_row(reg0 + pbo * (SLOT_BYTES / 32), tm, bars + pbo, px, py);
        }
    };
    auto advance = [&]() {
        bo += 32;
        so += SLOT_BYTES;
        if (bo == NSLOT * 32) { bo = 0; so = 0; par ^= 1; }
        pbo += 32;
        if (pbo == NSLOT * 32) { pbo = 0; ppar ^= 1; }
    };
    auto aim = [&](int row) {
        const int code = row_code(wk, row);
        px = (code & 0xffff) + (16 * warp - 1);
        py = code >> 16;
    };
    uint32_t accB[8][3], accC[8][3];
    int r = 0;
#pragma unroll 1
    while (r < wk.rows) {
        if (r == 0 || r == wk.nA + 2) {
            const uint32_t bo0 = bo;
            uint32_t bo1;
#pragma unroll 1
            for (int k = 0; k < 2; k++, r++) {
                mbar_wait_once(bars + bo, par);
                bo1 = bo;
                if (r >= 2) {
                    aim(r + PREFETCH_ROWS);
                    request();
                }
                advance();
            }
            const uint32_t so0 = bo0 * (SLOT_BYTES / 32), so1 = bo1 * (SLOT_BYTES / 32);
#pragma unroll
            for (int p = 0; p < 10; p++) {
                uint32_t u[3], v[3];
                lds64(u[0], u[1], so0 + ld64 + p * 192);
                lds32(u[2], so0 + ld32 + p * 192);
                lds64(v[0], v[1], so1 + ld64 + p * 192);
                lds32(v[2], so1 + ld32 + p * 192);
#pragma unroll
                for (int dx = 0; dx < 3; dx++) {
                    const int o = p - dx;
                    if (o < 0 || o > 7) continue;
#pragma unroll
                    for (int q = 0; q < 3; q++) {
                        accB[o][q] = bf_fma(v[q], w[1][dx][q], dx == 0 ? bf_mul(u[q], w[0][dx][q]) : bf_fma(u[q], w[0][dx][q], accB[o][q]));
                        accC[o][q] = dx == 0 ? bf_mul(v[q], w[0][dx][q]) : bf_fma(v[q], w[0][dx][q], accC[o][q]);
                    }
                }
            }
            anchor(ld64, accB[7][0], accB[7][1], accB[7][2], 0);
            __syncwarp();
            if (elect_one()) {
                mbar_arrive(bars + (BAR_A - SM_BAR) + bo0);
                mbar_arrive(bars + (BAR_E - SM_BAR) + bo0);
                mbar_arrive(bars + (BAR_A - SM_BAR) + bo1);
                mbar_arrive(bars + (BAR_E - SM_BAR) + bo1);
            }
        }
        int end = wk.rows;
        const int marks[4] = {wk.rows - PREFETCH_ROWS, wk.rows - 11, wk.nA + 2, wk.nA + 2 - PREFETCH_ROWS};
#pragma unroll
        for (int k = 0; k < 4; k++) end = marks[k] > r ? min(end, marks[k]) : end;
        const int fetch = opaque_uniform(end - wk.rows);
        aim(r + PREFETCH_ROWS);
        px = opaque_uniform(px);
        const int py_end = opaque_uniform(py + wk.dir * (end - r));
        r = end;
#pragma unroll 1
        do {
            mbar_wait(bars + bo, par);
            uint32_t out[8][3];
#pragma unroll
            for (int p = 0; p < 10; p++) {
                uint32_t xv[3];
                lds64(xv[0], xv[1], so + ld64 + p * 192);
                lds32(xv[2], so + ld32 + p * 192);
#pragma unroll
                for (int dx = 0; dx < 3; dx++) {
                    const int o = p - dx;
                    if (o < 0 || o > 7) continue;
#pragma unroll
                    for (int q = 2; q >= 0; q--) {
                        out[o][q] = bf_fma(xv[q], w[2][dx][q], dx == 0 ? accB[o][q] : out[o][q]);
                        accB[o][q] = bf_fma(xv[q], w[1][dx][q], dx == 0 ? accC[o][q] : accB[o][q]);
                        accC[o][q] = dx == 0 ? bf_mul(xv[q], w[0][dx][q]) : bf_fma(xv[q], w[0][dx][q], accC[o][q]);
                    }
                }
            }
            __syncwarp();
#pragma unroll
            for (int o = 7; o >= 0; o--) {
                sts64(so + st64 + o * 16, out[o][0], out[o][1]);
                sts32(so + st32 + o * 16, out[o][2]);
            }
            __syncwarp();
            if (elect_one()) mbar_arrive(bars + (BAR_A - SM_BAR) + bo);
            if (fetch) request();
            advance();
            py += wk.dir;
        } while (py != py_end);
        if (((wk.rows - r) & ~8) == PREFETCH_ROWS) event(wk.rows - r == PREFETCH_ROWS);
    }
}

template <bool SCALED, int K0 = 0, int K1 = 3>
__device__ __forceinline__ void gelu_sq(uint32_t (&d)[24], uint32_t (&keep)[24], uint32_t sq_addr, uint32_t scale2) {
    pin(d);
#pragma unroll
    for (int k = K0; k < K1; k++) {
        uint32_t hs[4];
        lds128(hs[0], hs[1], hs[2], hs[3], sq_addr + k * SQ_ROW);
#pragma unroll
        for (int q = 0; q < 4; q++) {
            uint32_t g0 = gelu2(d[8 * k + 2 * q]), g1 = gelu2(d[8 * k + 2 * q + 1]);
            keep[8 * k + 2 * q] = g0;
            keep[8 * k + 2 * q + 1] = g1;
            if (SCALED) { g0 = h_mul(g0, scale2); g1 = h_mul(g1, scale2); }
            hs[q] = h_fma(g1, g1, h_fma(g0, g0, hs[q]));
        }
        sts128(sq_addr + k * SQ_ROW, hs[0], hs[1], hs[2], hs[3]);
    }
}
__device__ __forceinline__ void gelu_sq_reg(uint32_t (&d)[24], uint32_t (&hs)[12]) {
    pin(d);
#pragma unroll
    for (int q = 0; q < 12; q++) {
        const uint32_t g0 = gelu2(d[2 * q]), g1 = gelu2(d[2 * q + 1]);
        hs[q] = h_fma(g1, g1, h_fma(g0, g0, hs[q]));
    }
}
__device__ __forceinline__ void gelu_to(uint32_t (&g)[12], uint32_t (&d)[12]) {
    pin(d);
#pragma unroll
    for (int q = 0; q < 12; q++) g[q] = gelu2(d[q]);
    pin(g);
}
__device__ __forceinline__ void load_tile(uint32_t (&raw)[6][4], uint32_t addr) {
#pragma unroll
    for (int s = 0; s < 6; s++) ldsm4(raw[s], addr + s * 2 * A_LBO);
}
template <class F>
__device__ __forceinline__ void layer_norm(uint32_t (&raw)[6][4], uint64_t ones, F meanwhile) {
    uint32_t sq[2][4];
#pragma unroll
    for (int s = 0; s < 6; s++)
#pragma unroll
        for (int q = 0; q < 4; q++) sq[s / 3][q] = s % 3 == 0 ? bf_mul(raw[s][q], raw[s][q]) : bf_fma(raw[s][q], raw[s][q], sq[s / 3][q]);
    float sum[4], ssq[4];
    wg_fence();
    wgmma_rowsum<0>(sum, raw[0], ones);
#pragma unroll
    for (int s = 1; s < 6; s++) wgmma_rowsum<1>(sum, raw[s], ones);
    wgmma_rowsum<0>(ssq, sq[0], ones);
    wgmma_rowsum<1>(ssq, sq[1], ones);
    wg_commit();
    meanwhile();
    wg_wait<0>();
    uint32_t sc[2], sh[2];
#pragma unroll
    for (int h = 0; h < 2; h++) {
        asm volatile("" : "+f"(sum[2 * h]), "+f"(ssq[2 * h])::"memory");
        constexpr float EPS = 1e-5f / (KZ * KZ) * 0x1p-64f;
        const float m = sum[2 * h] * (1.f / (CH * KZ));
        float rstd;
        asm("rsqrt.approx.ftz.f32 %0, %1;" : "=f"(rstd) : "f"(fmaxf(fmaf(-m, m, fmaf(ssq[2 * h], 1.f / (CH * KZ * KZ), EPS)), EPS)));
        rstd *= 0x1p-112f;
        sc[h] = pack_bf2(rstd, rstd);
        const float shift = sum[2 * h] * (-1.f / CH) * bf_hi(sc[h]);
        sh[h] = pack_bf2(shift, shift);
    }
#pragma unroll
    for (int s = 0; s < 6; s++)
#pragma unroll
        for (int q = 0; q < 4; q++) {
            const uint32_t v = bf_fma(raw[s][q], sc[q & 1], sh[q & 1]);
            asm("lop3.b32 %0, %1, %2, 0x80008000, 0xd8;" : "=r"(raw[s][q]) : "r"(v << 3), "r"(v));
        }
}
struct Cursor {
    int slot;
    uint32_t par;
    __device__ __forceinline__ void advance(int n) {
        slot += n;
        if (slot >= NSLOT) { slot -= NSLOT; par ^= 1; }
    }
};
struct Descs {
    uint64_t w1[8][6];
    uint64_t w2[24];
    uint64_t ones;
};
template <int E0, int N>
__device__ __forceinline__ void gemm1_chunk(uint32_t (&d)[N], const uint32_t (&a)[6][4], const Descs& ds, int zero) {
#pragma unroll
    for (int s = 0; s < 6; s++) wgmma(d, a[s][0], a[s][1], a[s][2], a[s][3], ds.w1[E0 / 48][s], s ? 1 : zero);
}
template <int E0, int N>
__device__ __forceinline__ void gemm2_chunk(uint32_t (&acc)[24], const uint32_t (&g)[N], const Descs& ds) {
#pragma unroll
    for (int s = 0; s < N / 4; s++) wgmma(acc, g[4 * s], g[4 * s + 1], g[4 * s + 2], g[4 * s + 3], ds.w2[E0 / 16 + s], 1);
}

struct __align__(64) Params {
    Split sp;
    int zero;
    const __nv_bfloat16 *x, *dw, *w2, *gamma, *beta;
    __nv_bfloat16* out;
    Scratch* sc;
    Descs ds;
};

__global__ void __launch_bounds__(NTHREADS, 1)
block_kernel(const __grid_constant__ CUtensorMap tmap, const __grid_constant__ CUtensorMap tmap_w1, const __grid_constant__ Params pm) {
    const Split& sp = pm.sp;
    const Descs& ds = pm.ds;
    const int& zero = pm.zero;
    const __nv_bfloat16 *const &x = pm.x, *const &dw = pm.dw, *const &w2 = pm.w2, *const &gamma = pm.gamma, *const &beta = pm.beta;
    __nv_bfloat16* const& out = pm.out;
    Scratch* const& sc = pm.sc;
    extern __shared__ __align__(1024) uint8_t smem[];
    constexpr uint32_t sb = SB;
    const int tid = threadIdx.x;
    const Work wk = get_work(blockIdx.x, sp);
    constexpr uint32_t s_red = sb + SM_RED;
    if (smem_u32(smem) != SB) __trap();

    const int warp_id = __shfl_sync(~0u, tid >> 5, 0);
    PROF(0);
    const int cw = warp_id - 4, wgi = cw >> 2, w4 = warp_id & 3;
    if (elect_one()) {
        static_assert(3 * NSLOT * 4 == 8 + 8 * 8 && BAR_F == BAR_W + 48, "barrier shares");
        const int b = warp_id - 8;
        const uint32_t bar = b < 0 ? sb + BAR_X + warp_id * 8 : b < 7 ? sb + BAR_W + b * 8 : sb + BAR_PIN;
        mbar_init(bar, 1);
        if (b < 0 || b >= 6) {
#pragma unroll
            for (int k = 0; k < 8; k++) mbar_init(sb + (b < 0 ? BAR_X + (8 + 8 * warp_id + k) * 8 : BAR_R + ((b - 6) * 8 + k) * 8), 1);
        }
        fence_async();
        if (b < 0) {
            issue_region(&tmap, sb + SM_RING + warp_id * REGION_BYTES, bar, w4, ((wk.tA & 511) + wk.dir * wgi) << 16 | (wk.tA >> 9) * TILE_W);
        } else if (b < 6) {
            mbar_expect_tx(bar, 64 * CH * 2);
            tma_2d(sb + SM_W2 + b * (64 * CH * 2), &tmap_w1, bar, 64 * b, 0);
        } else if (b == 6) {
            mbar_expect_tx(bar, 9 * CH * 2);
            bulk_load(sb + SM_FILTER, dw, 9 * CH * 2, bar);
        }
    }
    __syncwarp();
    const int ntiles = wk.nA + wk.nB;
    const int rank = (wgi + wk.lent + 2 * (ntiles - 1)) % NCONS | (wgi >> 2 & 3);
    const int spare = wk.rows % NSLOT, spare2 = spare == NSLOT - 1 ? 0 : spare + 1;
    const uint32_t sq_base = sb + (wgi < 0 ? SM_RING + spare * SLOT_BYTES : SM_SQ + rank * 2 * SQ_HALF);
    const uint32_t sq_upper = wgi < 0 ? (spare2 - spare) * SLOT_BYTES : SQ_HALF;
    const uint32_t bar_a = sb + BAR_A + w4 * 8, bar_e = sb + BAR_E + w4 * 8;
    auto max_w1 = [&](uint32_t lane) { return __uint_as_float(__reduce_max_sync(~0u, lane < 4 * NCONS ? ldsi(s_red + RED_MAX + lane * 4) : 0)); };
    auto square_scale = [&](uint32_t lane) {
        const float f = pow2i(square_exp(bound_exp(max_w1(lane))));
        return pack_h2(f, f);
    };
    uint32_t a_addr, sq;
    const uint32_t sq_warp = sq_base + w4 * 512;
    auto set_addresses = [&]() {
        a_addr = opaque(sb + SM_RING + w4 * REGION_BYTES + ((tid >> 3) & 1) * A_SBO + ((tid >> 4) & 1) * A_LBO + (tid & 7) * 16);
        sq = opaque(sq_base + (tid & 127) * 16);
    };
    uint32_t turn, turn_end, so, so_sum, bo, bo_sum, off;
    auto set_run = [&](int j, int stop, int row) {
        const int slot = row % NSLOT, both = 2 * (row % 3) + 3;
        turn = opaque_uniform(row / 3);
        turn_end = opaque_uniform(row / 3 + (stop - j + NCONS - 1) / NCONS);
        so = opaque_uniform(slot * SLOT_BYTES);
        so_sum = opaque_uniform(both * SLOT_BYTES);
        bo = opaque_uniform(bar_a + slot * 32);
        bo_sum = opaque_uniform(2 * bar_a + both * 32);
        off = opaque_uniform(tile_offset(wk.tile(j)) + w4 * WARP_BYTES - sq_warp);
    };
    const int nrest = ntiles - 4;
    int jt;
    Cursor cur;
    int fast_from;
    if (warp_id < 4) {
        conv_producer(wk, &tmap, sb, warp_id, [&](bool second) {
            if (!second) {
                if (tid == 0) sts32(s_red + RED_JOB, wk.lent ? NTILES : atomicAdd(&sc->job, 1));
                if (blockIdx.x == 0) {
#pragma unroll 1
                    for (int e = tid; e < EX; e += 128) *sc->sum(e) = 0;
                    sc->bias[tid] = 0.f;
                }
                if (blockIdx.x == 0 || wk.lent) signal(&sc->early);
                __syncwarp();
            } else {
                const int piece = opaque_uniform(ldsi(s_red + RED_JOB)) - W2_GROUPS / 2, q = 2 * piece + W2_GROUPS + (w4 >> 1);
                if (piece < 8 * LENT * sp.lenders) {
                    spin_until(&sc->early, (ldsi(s_red + RED_LAUNCH) + 1) * 4 * (sp.lenders + 1));
                    if (elect_one()) {
                        if (piece >= 0) prefetch_l2(reinterpret_cast<const char*>(out) + sp.lent_off[piece / 8] + w4 * WARP_BYTES, WARP_BYTES);
                        else { prefetch_l2(w2 + 8 * q * CH, 8 * CH * 2); prefetch_l2(beta + 8 * q, 16); }
                    }
                }
            }
        });
        const int piece = opaque_uniform(ldsi(s_red + RED_JOB)) - W2_GROUPS / 2, q = 2 * piece + W2_GROUPS + (w4 >> 1);
        const bool prepares = piece < 0, helps = piece < 8 * LENT * sp.lenders;
        set_addresses();
        const int lane = lane_id(), g = lane >> 2, t = lane & 3;
        uint32_t a[6][4];
        unsigned short bt_raw;
        if (prepares) {
#pragma unroll
            for (int m = 0; m < 3; m++) ldg128(a[m], w2 + (8 * q + g) * CH + 32 * m + 8 * t);
            asm volatile("ld.global.nc.u16 %0, [%1];" : "=h"(bt_raw) : "l"(beta + 8 * q + g) : "memory");
        } else if (helps) {
#pragma unroll
            for (int s = 0; s < 6; s++) ldg128(a[s], reinterpret_cast<const char*>(out) + sp.lent_off[piece / 8] + w4 * WARP_BYTES + lane * 16 + s * 512);
        }
        mbar_wait_once(bar_e + spare2 * 32, (wk.rows - 5) / NSLOT & 1);
        mbar_wait_once(bar_e + spare * 32, (wk.rows - 6) / NSLOT & 1);
        named_bar(1, 128);
#pragma unroll
        for (int k = 0; k < 6; k++) { sts128(sq + k * SQ_ROW, 0, 0, 0, 0); sts128(sq + sq_upper + k * SQ_ROW, 0, 0, 0, 0); }
        if (prepares) {
            const int half = w4 & 1;
            uint32_t rmax = 0;
#pragma unroll
            for (int m = 0; m < 3; m++) rmax = bf_absmax(bf_absmax(rmax, bf_absmax(a[m][0], a[m][1])), bf_absmax(a[m][2], a[m][3]));
            uint2 u = half ? make_uint2(a[0][2], a[0][3]) : make_uint2(a[0][0], a[0][1]), u1 = half ? make_uint2(a[1][2], a[1][3]) : make_uint2(a[1][0], a[1][1]);
            const uint2 u2 = half ? make_uint2(a[2][2], a[2][3]) : make_uint2(a[2][0], a[2][1]);
            const float bt = bf_lo(bt_raw);
            rmax = bf_absmax(rmax, __shfl_xor_sync(~0u, rmax, 1));
            rmax = bf_absmax(rmax, __shfl_xor_sync(~0u, rmax, 2));
            const float mx = fmaxf(fabsf(bf_lo(rmax)), fabsf(bf_hi(rmax))), rs = pow2i(row_exp(mx));
            if (t == 0 && !half) sc->w2max[8 * q + g] = mx;
#pragma unroll 1
            for (int m = 0; m < 3; m++, u = u1, u1 = u2) {
                float f[4];
#pragma unroll
                for (int k = 0; k < 2; k++) {
                    const float lo = bf_lo(k ? u.y : u.x), hi = bf_hi(k ? u.y : u.x);
                    sc->w2h[(4 * m + 2 * half + k) * 1536 + q * 32 + lane] = transpose8x8(pack_h2(lo * rs, hi * rs));
                    f[2 * k] = lo * bt;
                    f[2 * k + 1] = hi * bt;
                }
                const float r0 = (g & 2 ? f[2] : f[0]) + __shfl_xor_sync(~0u, g & 2 ? f[0] : f[2], 8);
                const float r1 = (g & 2 ? f[3] : f[1]) + __shfl_xor_sync(~0u, g & 2 ? f[1] : f[3], 8);
                float r = (g & 1 ? r1 : r0) + __shfl_xor_sync(~0u, g & 1 ? r0 : r1, 4);
                r += __shfl_xor_sync(~0u, r, 16);
                if (g < 4) atomicAdd(&sc->bias[32 * m + 8 * t + 4 * half + g], r);
            }
            asm volatile("fence.proxy.async.global;" ::: "memory");
            signal(&sc->prep);
        } else
        if (helps) {
            uint32_t d[12], gl[12];
            const uint32_t scale2 = square_scale(lane);
            wg_fence();
#pragma unroll
            for (int s = 0; s < 6; s++) wgmma(d, a[s][0], a[s][1], a[s][2], a[s][3], ds.w1[0][s] + piece % 8 * (6 * 1536 / 16), s ? 1 : 0);
            wg_commit();
            wg_wait<0>();
            gelu_to(gl, d);
#pragma unroll
            for (int s = 0; s < 3; s++) {
                sc->lent[((piece / 8 * 4 + w4) * 24 + piece % 8 * 3 + s) * 32 + lane] = make_uint4(gl[4 * s], gl[4 * s + 1], gl[4 * s + 2], gl[4 * s + 3]);
                uint32_t hs[2];
#pragma unroll
                for (int k = 0; k < 2; k++) {
                    const uint32_t g0 = h_mul(gl[4 * s + 2 * k], scale2), g1 = h_mul(gl[4 * s + 2 * k + 1], scale2);
                    hs[k] = h_fma(g1, g1, h_mul(g0, g0));
                }
                const int pair = piece % 4 * 3 + s;
                sts64(sq + (piece & 4 ? sq_upper : 0) + (pair >> 1) * SQ_ROW + (pair & 1) * 8, hs[0], hs[1]);
            }
        }
        jt = ntiles - 1;
        cur.slot = spare ? spare - 1 : NSLOT - 1;
        cur.par = (wk.rows - 1) / NSLOT & 1;
        fast_from = ntiles;
        turn = turn_end = so = so_sum = bo = bo_sum = off = rank;
    } else {
        set_addresses();
        if (wgi == NCONS - 1) named_arrive(4, 256);
        set_run(wk.lent + wgi, min(wk.nA, nrest), wk.lent + wgi + 2);
        jt = wgi < wk.lent ? wgi : wk.lent + wgi;
        cur = {2, 0};
        cur.advance(jt + (jt >= wk.nA ? 2 : 0));
        {
            const int ct = tid - 128, lane = tid & 31;
            const unsigned epoch = *reinterpret_cast<volatile unsigned*>(&sc->launch);
            const int r = lane & 7, mi = lane >> 3;
            const uint32_t src = sb + SM_W2 + (cw >> 1) * (64 * CH * 2) + r * 128 + ((((cw & 1) * 4 + mi) ^ r) * 16);
            const uint32_t dst = sb + SM_W1 + (4 * cw + mi) * 1536 + r * 16;
            const int code = row_code(wk, PREFETCH_ROWS - 1 + wgi);
            named_bar(0, NTHREADS);
            auto request = [&]() {
                if (elect_one())
                    issue_region(&tmap, sb + SM_RING + (PREFETCH_ROWS - 1 + wgi) * SLOT_BYTES + w4 * REGION_BYTES, sb + BAR_X + (cw + 8) * 8, w4, code);
                __syncwarp();
            };
#pragma unroll 1
            for (int k = 0; k < 2; k++) {
                if (wgi == k) request();
                mbar_wait_once(sb + BAR_W + (cw >> 1) * 8, 0);
            }
            uint32_t wmax[2] = {}, wsum[4] = {};
#pragma unroll 4
            for (int c = 0; c < 12; c++) {
                uint32_t u[4];
                ldsm4_t(u, src + c * 1024);
#pragma unroll
                for (int q = 0; q < 4; q++) {
                    wmax[q & 1] = bf_absmax(wmax[q & 1], u[q]);
                    wsum[q] = bf_fma(u[q], 0x3f803f80u, wsum[q]);
                    u[q] = pack_h2(__uint_as_float(u[q] * (65536 + zero)), bf_hi(u[q]));
                }
                stsm4(dst + c * 128, u[0], u[1], u[2], u[3]);
            }
            const float w1max = warp_absmax(bf_absmax(wmax[0], wmax[1]));
            if (lane == 0) sts32(s_red + RED_MAX + cw * 4, __float_as_uint(w1max));
            bool center = false;
#pragma unroll
            for (int q = 0; q < 4; q++) {
#pragma unroll
                for (int o = 1; o <= 2; o <<= 1) wsum[q] = bf_fma(__shfl_xor_sync(~0u, wsum[q], o), 0x3f803f80u, wsum[q]);
                center |= fabsf(bf_lo(wsum[q]) + bf_hi(wsum[q])) > (0.15f * CH) * w1max;
            }
            if (__builtin_expect(__any_sync(~0u, center), 0)) {
                float mean[4] = {};
#pragma unroll 1
                for (int pass = 0; pass < 2; pass++) {
                    float sum[4] = {};
#pragma unroll 1
                    for (int c = 0; c < 12; c++) {
                        uint32_t u[4];
                        ldsm4_t(u, src + c * 1024);
#pragma unroll
                        for (int q = 0; q < 4; q++) {
                            sum[q] += bf_lo(u[q]) + bf_hi(u[q]);
                            u[q] = pack_h2(bf_lo(u[q]) - mean[q], bf_hi(u[q]) - mean[q]);
                        }
                        stsm4(dst + c * 128, u[0], u[1], u[2], u[3]);
                    }
#pragma unroll
                    for (int q = 0; q < 4; q++) {
                        sum[q] += __shfl_xor_sync(~0u, sum[q], 1);
                        sum[q] += __shfl_xor_sync(~0u, sum[q], 2);
                        mean[q] = sum[q] * (1.f / CH);
                    }
                }
            }
            if (!(cw & 2)) {
#pragma unroll
                for (int c = 0; c < 12; c++) sts128(src + c * 1024, 0, 0, 0, 0);
            }
            if (ct < 32) sts32(sb + SM_ONES + ct * 4, 0x3f803f80u);
            if (ct == 0) sts32(s_red + RED_LAUNCH, epoch);
            fence_async();
            named_bar(2, CONS_THREADS);
            if (wgi == 2) request();
        }
        PROF(1);
        if (cur.par) mbar_wait_once(bar_a, 0);
        fast_from = wk.lent;
        if (!__all_sync(~0u, plain_squares(bound_exp(max_w1(lane_id()))))) {
            fast_from = ntiles;
#pragma unroll 1
            for (int q = 0; q < 6; q++) sts128(sq + SQ_HALF + q * SQ_ROW, 0, 0, 0, 0);
        }
    }
    uint32_t k1[24], k2[24], k3[24];
    uint32_t here;
    constexpr int SQC = 3 * SQ_ROW;
    auto store_at = [&](const uint32_t (&a)[6][4], uint32_t off) {
        char* ap = reinterpret_cast<char*>(out) + (off + sq);
#pragma unroll
        for (int s = 0; s < 6; s++) stg128(ap + s * 512, a[s]);
    };
    const uint32_t own_bar = 4 + wgi, next_bar = 4 + (wgi == NCONS - 1 ? 0 : wgi + 1);
    for (;;) {
        if (jt >= fast_from) {
            uint32_t hs2[12] = {}, hs3[12] = {};
            const uint32_t step = wk.dir * (NCONS * IMG_W * CH * 2);
            int second = wk.nB;
#pragma unroll 1
            for (;;) {
#pragma unroll 1
                while (turn != turn_end) {
                    uint32_t a[6][4], d0[24], d1[24], unused[24];
                    mbar_wait(bo, turn >> 1 & 1);
                    load_tile(a, a_addr + so);
                    layer_norm(a, ds.ones, [&]() { named_bar(own_bar, 256); });
                    wg_fence();
                    gemm1_chunk<0>(d0, a, ds, 0);
                    wg_commit();
                    gemm1_chunk<96>(d1, a, ds, 0);
                    wg_commit();
                    wg_wait<1>();
                    gelu_sq<false, 0, 1>(d0, unused, sq, 0);
                    gelu_sq<false, 1, 2>(d0, unused, sq, 0);
                    store_at(a, off);
                    gelu_sq<false, 2, 3>(d0, unused, sq, 0);
                    if (elect_one()) mbar_arrive(bo + (BAR_E - BAR_A));
                    wg_fence();
                    gemm1_chunk<192>(d0, a, ds, zero);
                    wg_commit();
                    named_arrive(next_bar, 256);
                    wg_wait<1>();
                    gelu_sq<false, 0, 1>(d1, unused, sq + SQC, 0);
                    gelu_sq<false, 1, 3>(d1, unused, sq + SQC, 0);
                    wg_fence();
                    gemm1_chunk<288>(d1, a, ds, zero);
                    wg_commit();
                    wg_wait<1>();
                    gelu_sq_reg(d0, hs2);
                    anchor(sq, hs2[8], hs2[9], hs2[10], hs2[11]);
                    wg_wait<0>();
                    gelu_sq_reg(d1, hs3);
                    so = so_sum - so;
                    bo = bo_sum - bo;
                    off += step;
                    turn++;
                }
                if (!second) break;
                const int j = ntiles - second + (rank + second + 2) % NCONS;
                second = 0;
                set_run(j, nrest, j + 4);
            }
            jt = nrest + rank;
            cur.slot = (bo - bar_a) >> 5;
            cur.par = turn >> 1 & 1;
#pragma unroll
            for (int k = 0; k < 3; k++) {
                sts128(sq + SQ_HALF + k * SQ_ROW, hs2[4 * k], hs2[4 * k + 1], hs2[4 * k + 2], hs2[4 * k + 3]);
                sts128(sq + SQ_HALF + SQC + k * SQ_ROW, hs3[4 * k], hs3[4 * k + 1], hs3[4 * k + 2], hs3[4 * k + 3]);
            }
        }
        const bool last = jt >= nrest;
        here = tile_offset(wk.tile(jt));
        if (last) {
            const uint32_t next = ldsi(sb + SM_TILES + rank * 4);
            if (elect_one()) {
                prefetch_l2(reinterpret_cast<const char*>(x) + here + w4 * WARP_BYTES, WARP_BYTES);
                if (rank == ORDER_P - 1) prefetch_l2(reinterpret_cast<const char*>(out) + next + w4 * WARP_BYTES, WARP_BYTES);
            }
        }
        uint32_t a[6][4], d0[24], d1[24], d3[24], k0[24];
        mbar_wait_once(bar_a + cur.slot * 32, cur.par);
        load_tile(a, a_addr + cur.slot * SLOT_BYTES);
        layer_norm(a, ds.ones, [&]() { if (jt >= wk.lent && wgi >= 0) named_bar(own_bar, 256); });
        if (!last) {
            store_at(a, here + w4 * WARP_BYTES - sq_warp);
            __syncwarp();
            if (elect_one()) mbar_arrive(bar_e + cur.slot * 32);
            if (jt < wk.lent) {
                jt += LENT;
                cur.advance(LENT);
                continue;
            }
        }
        wg_fence();
        gemm1_chunk<0>(d0, a, ds, 0);
        wg_commit();
        gemm1_chunk<96>(d1, a, ds, 0);
        wg_commit();
        const uint32_t scale2 = square_scale(lane_id());
        wg_wait<1>();
        gelu_sq<true>(d0, k0, sq, scale2);
        if (last) {
#pragma unroll
            for (int q = 0; q < 6; q++)
                sts128(sb + SM_RING + cur.slot * SLOT_BYTES + w4 * REGION_BYTES - sq_warp + sq + q * 512, k0[4 * q], k0[4 * q + 1], k0[4 * q + 2], k0[4 * q + 3]);
        }
        wg_fence();
        gemm1_chunk<192>(d0, a, ds, zero);
        wg_commit();
        if (jt + 2 < ntiles) named_arrive(next_bar, 256);
        wg_wait<1>();
        gelu_sq<true>(d1, k1, sq + SQC, scale2);
        wg_fence();
        gemm1_chunk<288>(d3, a, ds, 0);
        wg_commit();
        wg_wait<1>();
        gelu_sq<true>(d0, k2, sq + sq_upper, scale2);
        wg_wait<0>();
        gelu_sq<true>(d3, k3, sq + sq_upper + SQC, scale2);
        if (last) break;
        cur.advance(NCONS + ((jt < wk.nA && jt + NCONS >= wk.nA) ? 2 : 0));
        jt += NCONS;
    }
    const uint32_t lane = lane_id();
    uint32_t next_off = opaque_uniform(ldsi(sb + SM_TILES + rank * 4));
    const uint32_t s_fac = sb + SM_RING + spare * SLOT_BYTES + SQ_HALF;
    uint32_t inv_rho2;
    {
        if (rank == 0) {
            const int g = lane >> 2, t = lane & 3, i0 = w4 * 32 + lane;
            const bool leader = i0 == 0;
            const uint32_t pick = (g & 1) == (t & 1) ? (g & 2 ? 0x3c000000u : 0x00003c00u) : 0;
            const int be = bound_exp(max_w1(lane));
            const float to_fixed = pow2i(sum_exp(be) - 2 * square_exp(be));
            const uint32_t two_rows = sb + (w4 * 3 + (lane >> 3 & 1)) * SQ_ROW + ((lane >> 4) * 8 + (lane & 7)) * 16;
            const uint32_t third_row = sb + (w4 * 3 + 2) * SQ_ROW + lane * 16;
            unsigned short gam_raw[3];
            float rmax[3], f[3][4] = {};
            float2 bpair = make_float2(0.f, 0.f);
#pragma unroll 1
            for (int i = 0; i < 4; i++) {
                if (i == 1 && leader) {
                    spin_until(&sc->prep, (ldsi(s_red + RED_LAUNCH) + 1) * (W2_GROUPS * 2));
                    asm volatile("fence.proxy.async.global;" ::: "memory");
                    mbar_expect_tx(sb + BAR_W, 6 * SQ_HALF);
                }
                __syncwarp();
                named_bar(2, 128);
                if (i && leader) {
                    fence_async();
                    bulk_load(sb + SM_W2 + (i - 1) * 2 * SQ_HALF, reinterpret_cast<const char*>(sc->w2h) + (i - 1) * 2 * SQ_HALF, 2 * SQ_HALF, sb + BAR_W);
                }
                if (i == 1) {
#pragma unroll
                    for (int m = 0; m < 3; m++) {
                        asm volatile("ld.global.nc.u16 %0, [%1];" : "=h"(gam_raw[m]) : "l"(gamma + i0 + 128 * m) : "memory");
                        asm volatile("ld.global.cg.f32 %0, [%1];" : "=f"(rmax[m]) : "l"(&sc->w2max[i0 + 128 * m]) : "memory");
                    }
                    if (i0 < 96)
                        asm volatile("ld.global.cg.v2.f32 {%0, %1}, [%2];" : "=f"(bpair.x), "=f"(bpair.y)
                                     : "l"(&sc->bias[32 * (i0 % 24 >> 3) + 8 * (i0 / 24) + (i0 % 24 & 6)]) : "memory");
                }
                __syncwarp();
                const uint32_t from = i < NCONS ? SM_SQ + i * 2 * SQ_HALF : w4 < 2 ? SM_RING + spare * SLOT_BYTES : SM_RING + spare2 * SLOT_BYTES - SQ_HALF;
                if (i) named_bar(12 + i, 256);
#pragma unroll
                for (int r = 0; r < 12; r++) {
                    uint32_t u[4];
                    ldsm4_t(u, from + (r % 3 == 2 ? third_row + r / 3 * 512 : two_rows + (r / 3 * 2 + r % 3) * 256));
                    asm volatile("mma.sync.aligned.m16n8k16.row.col.f32.f16.f16.f32 {%0, %1, %2, %3}, {%4, %5, %6, %7}, {%8, %8}, {%0, %1, %2, %3};"
                                 : "+f"(f[r % 3][0]), "+f"(f[r % 3][1]), "+f"(f[r % 3][2]), "+f"(f[r % 3][3])
                                 : "r"(u[0]), "r"(u[1]), "r"(u[2]), "r"(u[3]), "r"(pick));
                }
            }
            unsigned long long* dst = sc->sum(96 * w4 + 8 * (g >> 1) + 2 * (t & 1) + (g & 1));
#pragma unroll
            for (int r = 0; r < 3; r++) {
                const float tot = r < 2 ? (t < 2 ? f[0][r & 1] + f[1][r & 1] : f[0][r + 2 & 3] + f[1][r + 2 & 3]) : (t < 2 ? f[2][0] + f[2][2] : f[2][1] + f[2][3]);
                atomicAdd(dst + (r < 2 ? (t >> 1) * 8 + r : 16 + (t >> 1)) * 32, __float2ull_rn(fminf(tot * to_fixed, 0x1p47f)) << 8 | 1);
            }
            PROF(2);
            float base[3], slope[3], reach[3];
            const float w1max = max_w1(lane);
            const float gbound = fmaxf(2.f * KZ * 9.7979590f * 192.f * w1max, 1.f) * 19.5959180f * INV_2KZ;
            const unsigned fixed = __reduce_max_sync(~0u, __float_as_uint(fmaf(gbound, fmaxf(fmaxf(rmax[0], rmax[1]), rmax[2]), fmaxf(fabsf(bpair.x), fabsf(bpair.y)))));
            if (lane == 0) sts32(s_red + 96 + w4 * 4, fixed);
#pragma unroll
            for (int m = 0; m < 3; m++) {
                base[m] = rmax[m] > 0.f ? pow2i(-row_exp(rmax[m])) * INV_2KZ : 0.f;
                slope[m] = base[m] * bf_lo(gam_raw[m]);
                reach[m] = fabsf(bf_lo(gam_raw[m])) * rmax[m] * gbound;
            }
            const float to_square = pow2i(-sum_exp(bound_exp(w1max))) * (INV_2KZ * INV_2KZ / 256);
#pragma unroll
            for (int m = 0; m < 3; m++) anchor(sq, __float_as_uint(base[m]), __float_as_uint(slope[m]), __float_as_uint(reach[m]), __float_as_uint(to_square));
            const unsigned epoch = ldsi(s_red + RED_LAUNCH);
            const uint32_t own_sum = (i0 >> 2) * 256 + (i0 & 3) * 8, own_fac = s_fac + i0 * 2;
            auto peek = [&](const void* p) {
                unsigned long long v;
                asm volatile("ld.relaxed.gpu.global.u64 %0, [%1];" : "=l"(v) : "l"(p) : "memory");
                return v;
            };
            const char* mine = reinterpret_cast<const char*>(sc->sums) + own_sum;
            unsigned n = 0;
            while (((unsigned)peek(sc->sum((blockIdx.x * 4 + w4) % (EX / 4) * 4)) & 255u) != gridDim.x)
                if (++n > SPIN_LIMIT) __trap();
            unsigned long long sum[3];
            for (;;) {
                bool all = true;
#pragma unroll
                for (int m = 0; m < 3; m++) {
                    sum[m] = peek(mine + m * (32 * 256));
                    all &= ((unsigned)sum[m] & 255u) == gridDim.x;
                }
                if (__all_sync(~0u, all)) break;
                if (++n > SPIN_LIMIT) __trap();
            }
            PROF(3);
            float gx[3];
#pragma unroll
            for (int m = 0; m < 3; m++) asm("sqrt.approx.ftz.f32 %0, %1;" : "=f"(gx[m]) : "f"(fmaf(__ull2float_rn(sum[m]), to_square, 1e-6f)));
            float tot = gx[0] + gx[1] + gx[2];
#pragma unroll
            for (int o = 16; o >= 1; o >>= 1) tot += __shfl_xor_sync(~0u, tot, o);
            const unsigned vwarp = __reduce_max_sync(~0u, __float_as_uint(fmaxf(fmaxf(reach[0] * gx[0], reach[1] * gx[1]), reach[2] * gx[2])));
            if (lane == 0) { sts32(s_red + 64 + w4 * 4, __float_as_uint(tot)); sts32(s_red + 80 + w4 * 4, vwarp); }
            named_bar(2, 128);
            uint32_t u[4], v[4], w[4];
            lds128(u[0], u[1], u[2], u[3], s_red + 64);
            lds128(v[0], v[1], v[2], v[3], s_red + 80);
            lds128(w[0], w[1], w[2], w[3], s_red + 96);
            tot = (__uint_as_float(u[0]) + __uint_as_float(u[1])) + (__uint_as_float(u[2]) + __uint_as_float(u[3]));
            const float vmax = __uint_as_float(max(max(v[0], v[1]), max(v[2], v[3]))), fmax2 = __uint_as_float(max(max(w[0], w[1]), max(w[2], w[3])));
            float inv_mean;
            asm("rcp.approx.ftz.f32 %0, %1;" : "=f"(inv_mean) : "f"(fmaf(tot, 1.f / EX, 1e-6f)));
            const int rho_e = 14 - ilog2f(fmaf(vmax, inv_mean, 2.f * fmax2));
            const float rho = pow2i(rho_e), inv_rho = pow2i(-rho_e);
            inv_rho2 = pack_bf2(inv_rho, inv_rho);
#pragma unroll
            for (int m = 0; m < 3; m++) {
                const float f = fmaf(slope[m] * gx[m], inv_mean, base[m]) * rho;
                asm volatile("st.shared.u16 [%0], %1;" ::"r"(own_fac + 256 * m), "h"((unsigned short)pack_h2(f, 0.f)) : "memory");
            }
            if (i0 < 96) sts32(sb + SM_BIASH + i0 * 4, pack_h2(bpair.x * rho, bpair.y * rho));
            if (i0 == 96) sts32(s_red + RED_INV_RHO, inv_rho2);
            named_arrive(12, NTHREADS);
            if (blockIdx.x == 0 && leader) { sc->launch = epoch + 1; sc->job = 0; }
            if (wk.lent) spin_until(&sc->lent_out, (epoch + 1) * 32 * LENT * sp.lenders);
        } else {
            named_arrive(12 + rank, 256);
            if (rank == NCONS && (unsigned)(ldsi(s_red + RED_JOB) - W2_GROUPS / 2) < 8 * LENT * sp.lenders) signal(&sc->lent_out);
            const int rw = rank * 4 - 4 + w4;
            const uint32_t row = sb + SM_W2 + rw * 512 + lane * 16;
            uint32_t u[W2_EARLY][4], f2[4];
            mbar_wait_once(sb + BAR_W, 1);
#pragma unroll
            for (int nb = 0; nb < W2_EARLY; nb++) {
                lds128(u[nb][0], u[nb][1], u[nb][2], u[nb][3], row + nb * 6144);
            }
            named_bar(12, NTHREADS);
            PROF(3);
            lds128(f2[0], f2[1], f2[2], f2[3], s_fac + rw * 64 + (lane >> 3) * 16);
            lds32(inv_rho2, s_red + RED_INV_RHO);
#pragma unroll
            for (int nb = 0; nb < 12; nb++) {
                uint32_t v[4];
                if (nb < W2_EARLY) { v[0] = u[nb % W2_EARLY][0]; v[1] = u[nb % W2_EARLY][1]; v[2] = u[nb % W2_EARLY][2]; v[3] = u[nb % W2_EARLY][3]; }
                else lds128(v[0], v[1], v[2], v[3], row + nb * 6144);
                sts128(row + nb * 6144, h_mul(v[0], f2[0]), h_mul(v[1], f2[1]), h_mul(v[2], f2[2]), h_mul(v[3], f2[3]));
            }
            fence_async();
            named_arrive(8, NTHREADS);
        }
    }
    uint32_t a[6][4], acc[24], rpar = 0, tile_off = here;
    const uint32_t bias_addr = sb + SM_BIASH + (lane & 3) * 96, lane16 = lane * 16, lane_off = ((lane >> 2) * CH + 8 * (lane & 3)) * 2;
    const uint32_t stage = sb + SM_RING + (spare + rank) % NSLOT * SLOT_BYTES + w4 * WARP_BYTES, bar_r = sb + BAR_R + warp_id * 8;
    auto load_bias = [&]() {
#pragma unroll
        for (int q = 0; q < 6; q++) lds128(acc[4 * q], acc[4 * q + 1], acc[4 * q + 2], acc[4 * q + 3], bias_addr + q * 16);
    };
    auto load_frags = [&]() {
#pragma unroll
        for (int s = 0; s < 6; s++) ldg128(a[s], reinterpret_cast<const char*>(out) + next_off + w4 * WARP_BYTES + lane16 + s * 512);
    };
    auto stage_x = [&]() {
        if (elect_one()) {
            mbar_expect_tx(bar_r, WARP_BYTES);
            bulk_load_stream(stage, reinterpret_cast<const char*>(x) + tile_off + w4 * WARP_BYTES, WARP_BYTES, bar_r);
        }
    };
    {
        named_bar(8 + rank, rank ? 256 : NTHREADS);
        if (rank == 0) PROF(4);
        load_bias();
        pin(k1); pin(k2); pin(k3);
        wg_fence();
        gemm2_chunk<288>(acc, k3, ds);
        wg_commit();
        gemm2_chunk<96>(acc, k1, ds);
        wg_commit();
        gemm2_chunk<192>(acc, k2, ds);
        wg_commit();
        stage_x();
        wg_wait<2>();
        uint32_t k0[24];
#pragma unroll
        for (int q = 0; q < 6; q++)
            lds128(k0[4 * q], k0[4 * q + 1], k0[4 * q + 2], k0[4 * q + 3], sb + SM_RING + cur.slot * SLOT_BYTES + w4 * REGION_BYTES + lane16 + q * 512);
        pin(k0);
        wg_fence();
        gemm2_chunk<0>(acc, k0, ds);
        wg_commit();
        if (rank < NCONS) named_arrive(9 + rank, 256);
        wg_wait<2>();
        load_frags();
        if (lane16 == 0) mbar_arrive(sb + BAR_PIN);
        mbar_wait(bar_r, rpar);
        wg_wait<0>();
    }
    auto lent = [&](uint32_t entry) { return &sc->lent[((wk.index * LENT + (entry & 3) - 1) * 4 + w4) * (24 * 32)]; };
    for (jt = rank - 4; jt < nrest; jt += 4) {
        if (jt >= zero) {
        tile_off = next_off;
        lds32(next_off, sb + SM_TILES + (jt + 4) * 4);
        if (tile_off & 3) {
            const uint4* src = lent(tile_off) + lane;
            tile_off &= ~3u;
            next_off = __shfl_sync(~0u, next_off, 0);
            stage_x();
            if (elect_one()) prefetch_l2(reinterpret_cast<const char*>(out) + next_off + w4 * WARP_BYTES, WARP_BYTES);
            load_bias();
#pragma unroll 1
            for (int half = 0; half < 2; half++, src += 12 * 32) {
                uint32_t gl[48];
#pragma unroll
                for (int s = 0; s < 12; s++) ldg128(reinterpret_cast<uint32_t (&)[4]>(gl[4 * s]), src + s * 32);
                if (!half) {
                    named_bar(4 + rank, 256);
                    named_arrive(4 + ((rank + 1) & 3), 256);
                }
                pin(gl);
                wg_fence();
#pragma unroll
                for (int s = 0; s < 12; s++) wgmma(acc, gl[4 * s], gl[4 * s + 1], gl[4 * s + 2], gl[4 * s + 3], ds.w2[12 * half + s], 1);
                wg_commit();
                wg_wait<0>();
            }
            load_frags();
            mbar_wait(bar_r, rpar);
        } else {
            uint32_t d0[12], d1[12], g0[12], g1[12];
            next_off = __shfl_sync(~0u, next_off, 0);
            const bool more = jt + 4 < nrest && !(next_off & 3);
            load_bias();
            wg_fence();
            gemm1_chunk<0>(d0, a, ds, 0);
            wg_commit();
            if (jt && jt + 1 < nrest) named_bar(4 + rank, 256);
            gemm1_chunk<48>(d1, a, ds, 0);
            wg_commit();
            wg_wait<1>();
#define CNX_STEP(C, D, G)                                                   \
    gelu_to(G, D);                                                          \
    wg_fence();                                                             \
    if (C < 6) gemm1_chunk<48 * (C < 6 ? C + 2 : 0)>(D, a, ds, zero);      \
    gemm2_chunk<48 * C>(acc, G, ds);                                       \
    wg_commit();                                                            \
    if (C == 1 && jt + 2 < nrest) named_arrive(4 + ((rank + 1) & 3), 256); \
    wg_wait<(C < 7 ? 1 : 0)>();
            CNX_STEP(0, d0, g0)
            stage_x();
            if (elect_one()) {
                if (more) prefetch_l2(reinterpret_cast<const char*>(out) + next_off + w4 * WARP_BYTES, WARP_BYTES);
                else if (next_off & 3) prefetch_l2(lent(next_off), 24 * 32 * 16);
            }
            CNX_STEP(1, d1, g1)
            CNX_STEP(2, d0, g0)
            CNX_STEP(3, d1, g1)
            CNX_STEP(4, d0, g0)
            CNX_STEP(5, d1, g1)
            CNX_STEP(6, d0, g0)
#pragma unroll
            for (int s = 0; s < 6; s++) ldg128_if(more, a[s], reinterpret_cast<const char*>(out) + next_off + w4 * WARP_BYTES + lane16 + s * 512);
            if (lane16 == 0) mbar_arrive(sb + BAR_PIN);
            mbar_wait(bar_r, rpar);
            CNX_STEP(7, d1, g1)
#undef CNX_STEP
        }
        }
        {
            pin(acc);
            rpar ^= 1;
            uint4* op = reinterpret_cast<uint4*>(reinterpret_cast<char*>(out) + tile_off + w4 * WARP_BYTES + lane_off);
#pragma unroll
            for (int h = 0; h < 2; h++)
#pragma unroll
                for (int m = 0; m < 3; m++) {
                    uint32_t xin[4], o[4];
                    lds128(xin[0], xin[1], xin[2], xin[3], stage + lane_off + h * 1536 + m * 64);
#pragma unroll
                    for (int q = 0; q < 4; q++) {
                        const uint32_t v = acc[2 * (4 * m + q) + h];
                        o[q] = bf_fma(pack_bf2(h_lo(v), h_hi(v)), inv_rho2, xin[q]);
                    }
                    __stcs(op + h * 96 + m * 4, make_uint4(o[0], o[1], o[2], o[3]));
                }
            __syncwarp();
        }
    }
    PROF(5);
}

}

typedef CUresult (*EncodeTiledFn)(CUtensorMap*, CUtensorMapDataType, cuuint32_t, void*, const cuuint64_t*, const cuuint64_t*,
                                  const cuuint32_t*, const cuuint32_t*, CUtensorMapInterleave, CUtensorMapSwizzle,
                                  CUtensorMapL2promotion, CUtensorMapFloatOOBfill);

extern "C" void kernel_launch(void* const* d_in, const int* in_sizes, int n_in, void* d_out, int out_size) {
    using namespace cnx;
    static EncodeTiledFn encode = nullptr;
    static int num_sms = 0;
    static Scratch* scratch = nullptr;
    if (!encode) {
        void* fn = nullptr;
        cudaDriverEntryPointQueryResult qr;
        cudaGetDriverEntryPoint("cuTensorMapEncodeTiled", &fn, cudaEnableDefault, &qr);
        encode = (EncodeTiledFn)fn;
        cudaGetSymbolAddress((void**)&scratch, g_scratch);
        int dev = 0;
        cudaGetDevice(&dev);
        cudaDeviceGetAttribute(&num_sms, cudaDevAttrMultiProcessorCount, dev);
        if (num_sms > MAX_CTAS) num_sms = MAX_CTAS;
        cudaFuncSetAttribute(block_kernel, cudaFuncAttributeMaxDynamicSharedMemorySize, SM_TOTAL);
    }
    CUtensorMap tm;
    cuuint64_t dims[3] = {(cuuint64_t)CH, (cuuint64_t)IMG_W, (cuuint64_t)IMG_H};
    cuuint64_t strides[2] = {(cuuint64_t)CH * 2, (cuuint64_t)CH * 2 * IMG_W};
    cuuint32_t box[3] = {(cuuint32_t)CH, (cuuint32_t)REGION_PX, 1};
    cuuint32_t estr[3] = {1, 1, 1};
    encode(&tm, CU_TENSOR_MAP_DATA_TYPE_BFLOAT16, 3, d_in[0], dims, strides, box, estr, CU_TENSOR_MAP_INTERLEAVE_NONE,
           CU_TENSOR_MAP_SWIZZLE_NONE, CU_TENSOR_MAP_L2_PROMOTION_L2_128B, CU_TENSOR_MAP_FLOAT_OOB_FILL_NONE);
    Params pm = {};
    Descs& ds = pm.ds;
    for (int c = 0; c < 8; c++)
        for (int k = 0; k < 6; k++) ds.w1[c][k] = make_desc(SB + SM_W1 + c * 6 * 1536 + k * 256, 128, 1536);
    for (int k = 0; k < 24; k++) ds.w2[k] = make_desc(SB + SM_W2 + k * 256, 128, 6144);
    ds.ones = make_desc(SB + SM_ONES, 0, 0);
    CUtensorMap tw;
    cuuint64_t wdims[2] = {(cuuint64_t)EX, (cuuint64_t)CH};
    cuuint64_t wstrides[1] = {(cuuint64_t)EX * 2};
    cuuint32_t wbox[2] = {64, (cuuint32_t)CH};
    encode(&tw, CU_TENSOR_MAP_DATA_TYPE_BFLOAT16, 2, d_in[2], wdims, wstrides, wbox, estr, CU_TENSOR_MAP_INTERLEAVE_NONE,
           CU_TENSOR_MAP_SWIZZLE_128B, CU_TENSOR_MAP_L2_PROMOTION_L2_128B, CU_TENSOR_MAP_FLOAT_OOB_FILL_NONE);
    Split& sp = pm.sp;
    sp = {NTILES / num_sms, NTILES % num_sms, 1, 1 << 16, 0, {}};
    if (sp.per_cta + 9 > MAX_ROWS) return;
    if (sp.extra && sp.extra * (8 * LENT + 1) + W2_GROUPS / 2 <= num_sms && sp.per_cta >= 5 * LENT + 8) {
        sp.period = num_sms / sp.extra;
        sp.inv_period = 65535 / sp.period + 1;
        sp.lenders = sp.extra;
        for (int l = 0; l < sp.extra; l++) {
            const Work w = get_work((l + 1) * sp.period - sp.period / 2 - 1, sp);
            for (int e = 0; e < LENT; e++) sp.lent_off[l * LENT + e] = tile_offset(w.tile(e));
            if (w.nA < 2 * LENT) sp.lenders = 0;
        }
    }
    pm.x = (const __nv_bfloat16*)d_in[0];
    pm.dw = (const __nv_bfloat16*)d_in[1];
    pm.w2 = (const __nv_bfloat16*)d_in[3];
    pm.gamma = (const __nv_bfloat16*)d_in[4];
    pm.beta = (const __nv_bfloat16*)d_in[5];
    pm.out = (__nv_bfloat16*)d_out;
    pm.sc = scratch;
    block_kernel<<<num_sms, NTHREADS, SM_TOTAL>>>(tm, tw, pm);
}
```

```cpp
#include <cuda_runtime.h>
#include <cuda_bf16.h>
#include <cuda_fp16.h>
#include <cuda.h>
#include <stdint.h>

namespace cnx {

constexpr int IMG_H = 512, IMG_W = 512, CH = 96, EX = 384;
constexpr int TILE_W = 64;
constexpr int NTILES = (IMG_W / TILE_W) * IMG_H;
constexpr int NSLOT = 6;
constexpr int REGION_PX = 18;
constexpr int REGION_BYTES = REGION_PX * CH * 2;
constexpr int SLOT_BYTES = 4 * REGION_BYTES;
constexpr int A_LBO = 144, A_SBO = 12 * A_LBO;
constexpr int PREFETCH_ROWS = 3;
constexpr int NCONS = 3;
constexpr int CONS_THREADS = 128 * NCONS;
constexpr int NTHREADS = 128 + CONS_THREADS;
constexpr int MAX_ROWS = 52;
constexpr int TILE_BYTES = TILE_W * CH * 2, WARP_BYTES = TILE_BYTES / 4;
constexpr int ORDER_P = 3;
constexpr int W2_EARLY = 10;
static_assert(MAX_ROWS <= 128, "one table entry per producer thread");
static_assert(2 * A_SBO == REGION_BYTES && REGION_BYTES % 128 == 0, "region layout");

constexpr uint32_t SB = 1024;
constexpr int SM_W1 = 0;
constexpr int SM_W2 = SM_W1 + CH * EX * 2;
constexpr int SM_RING = SM_W2 + CH * EX * 2;
constexpr int SM_BIASH = SM_RING + NSLOT * SLOT_BYTES;
constexpr int SM_RED = SM_BIASH + 384;
constexpr int RED_MAX = 0, RED_LAUNCH = 48, RED_INV_RHO = 52, RED_JOB = 56;
constexpr int SM_TILES = SM_RED + 256;
constexpr int SM_ONES = SM_TILES + MAX_ROWS * 4;
constexpr int SM_BAR = SM_ONES + 128;
constexpr int BAR_X = SM_BAR;
constexpr int BAR_A = BAR_X + NSLOT * 4 * 8;
constexpr int BAR_E = BAR_A + NSLOT * 4 * 8;
constexpr int BAR_PIN = BAR_E + NSLOT * 4 * 8;
constexpr int BAR_W = BAR_PIN + 8;
constexpr int BAR_F = BAR_W + 6 * 8;
constexpr int BAR_R = BAR_F + 8;
constexpr int SM_TOTAL = BAR_R + 16 * 8;
constexpr int SM_FILTER = SM_RING + (NSLOT - 1) * SLOT_BYTES + 9 * 128;
constexpr int SM_SQ = SM_W2;
constexpr int SQ_ROW = 128 * 16, SQ_HALF = 6 * SQ_ROW;
static_assert(SM_ONES % 16 == 0 && SM_TOTAL <= 232448, "shared memory budget");

constexpr float KZ = 0.3292034911525734f;
constexpr uint32_t GELU_C2 = 0x40d940d9u;
constexpr float INV_2KZ = 0.5f / KZ;
constexpr uint32_t CONV_SCALE2 = 0x2f802f80u;
constexpr unsigned SPIN_LIMIT = 1u << 19;

constexpr int MAX_CTAS = 170;
constexpr int W2_GROUPS = EX / 8;
constexpr int LENT = 3, MAX_LENDERS = MAX_CTAS / (8 * LENT + 1);
struct Scratch {
    uint32_t w2h[EX * CH / 2];
    float w2max[EX];
    float bias[CH + 32];
    unsigned long long sums[EX / 4][32];
    __device__ __forceinline__ unsigned long long* sum(int e) { return &sums[e >> 2][e & 3]; }
    uint4 lent[MAX_LENDERS * LENT * 8 * 4 * 3 * 32];
    unsigned launch, pad0[31], early, pad1[31], prep, pad2[31], lent_out, pad3[31];
    unsigned job;
};
__device__ __align__(128) Scratch g_scratch;

#define PROF(k)

__device__ __forceinline__ uint32_t smem_u32(const void* p) { return (uint32_t)__cvta_generic_to_shared(p); }
__device__ __forceinline__ void mbar_init(uint32_t bar, uint32_t cnt) {
    asm volatile("mbarrier.init.shared::cta.b64 [%0], %1;" ::"r"(bar), "r"(cnt) : "memory");
}
__device__ __forceinline__ void mbar_arrive(uint32_t bar) {
    asm volatile("mbarrier.arrive.shared::cta.b64 _, [%0];" ::"r"(bar) : "memory");
}
__device__ __forceinline__ void mbar_expect_tx(uint32_t bar, uint32_t bytes) {
    asm volatile("mbarrier.arrive.expect_tx.shared::cta.b64 _, [%0], %1;" ::"r"(bar), "r"(bytes) : "memory");
}
__device__ __forceinline__ bool mbar_try(uint32_t bar, uint32_t par) {
    uint32_t ok;
    asm volatile("{\n.reg .pred p;\nmbarrier.try_wait.parity.shared::cta.b64 p, [%1], %2;\nselp.u32 %0, 1, 0, p;\n}\n"
                 : "=r"(ok) : "r"(bar), "r"(par) : "memory");
    return ok != 0;
}
__device__ __forceinline__ void mbar_wait(uint32_t bar, uint32_t par) {
    unsigned n = 0;
    while (!mbar_try(bar, par)) {
        if (++n > SPIN_LIMIT) __trap();
    }
}
__device__ __forceinline__ void mbar_wait_once(uint32_t bar, uint32_t par) {
    unsigned n = 0;
    bool ok;
#pragma unroll 1
    do {
        ok = mbar_try(bar, par);
        if (++n > SPIN_LIMIT) __trap();
    } while (!ok);
}
__device__ __forceinline__ bool elect_one() {
    uint32_t ok;
    asm volatile("{\n.reg .pred p;\nelect.sync _|p, 0xffffffff;\nselp.u32 %0, 1, 0, p;\n}\n" : "=r"(ok));
    return ok != 0;
}
__device__ __forceinline__ uint32_t opaque(uint32_t v) { return __shfl_sync(~0u, v, threadIdx.x & 31); }
__device__ __forceinline__ uint32_t lane_id() { uint32_t v; asm volatile("mov.u32 %0, %%laneid;" : "=r"(v)); return v; }
__device__ __forceinline__ uint32_t opaque_uniform(uint32_t v) { return __shfl_sync(~0u, v, 0); }
__device__ __forceinline__ void named_bar(int id, int n) { asm volatile("bar.sync %0, %1;" ::"r"(id), "r"(n) : "memory"); }
__device__ __forceinline__ void named_arrive(int id, int n) { asm volatile("bar.arrive %0, %1;" ::"r"(id), "r"(n) : "memory"); }
__device__ __forceinline__ void fence_async() { asm volatile("fence.proxy.async.shared::cta;" ::: "memory"); }
constexpr uint64_t EVICT_FIRST = 0x12F0000000000000ull;
__device__ __forceinline__ void tma_row(uint32_t dst, const CUtensorMap* tm, uint32_t bar, int x, int y) {
    asm volatile("cp.async.bulk.tensor.3d.shared::cluster.global.mbarrier::complete_tx::bytes.L2::cache_hint [%0], [%1, {%3, %4, %5}], [%2], %6;"
                 ::"r"(dst), "l"(tm), "r"(bar), "r"(0), "r"(x), "r"(y), "l"(EVICT_FIRST) : "memory");
}
__device__ __forceinline__ void bulk_load_stream(uint32_t dst, const void* src, uint32_t bytes, uint32_t bar) {
    asm volatile("cp.async.bulk.shared::cluster.global.mbarrier::complete_tx::bytes.L2::cache_hint [%0], [%1], %2, [%3], %4;"
                 ::"r"(dst), "l"(src), "r"(bytes), "r"(bar), "l"(EVICT_FIRST) : "memory");
}
__device__ __forceinline__ void prefetch_l2(const void* src, uint32_t bytes) {
    asm volatile("cp.async.bulk.prefetch.L2.global [%0], %1;" ::"l"(src), "r"(bytes) : "memory");
}
__device__ __forceinline__ void tma_2d(uint32_t dst, const CUtensorMap* tm, uint32_t bar, int x, int y) {
    asm volatile("cp.async.bulk.tensor.2d.shared::cluster.global.mbarrier::complete_tx::bytes [%0], [%1, {%3, %4}], [%2];"
                 ::"r"(dst), "l"(tm), "r"(bar), "r"(x), "r"(y) : "memory");
}
__device__ __forceinline__ void bulk_load(uint32_t dst, const void* src, uint32_t bytes, uint32_t bar) {
    asm volatile("cp.async.bulk.shared::cluster.global.mbarrier::complete_tx::bytes [%0], [%1], %2, [%3];"
                 ::"r"(dst), "l"(src), "r"(bytes), "r"(bar) : "memory");
}
__device__ __forceinline__ void wg_fence() { asm volatile("wgmma.fence.sync.aligned;" ::: "memory"); }
__device__ __forceinline__ void wg_commit() { asm volatile("wgmma.commit_group.sync.aligned;" ::: "memory"); }
template <int N> __device__ __forceinline__ void wg_wait() { asm volatile("wgmma.wait_group.sync.aligned %0;" ::"n"(N) : "memory"); }
template <int N> __device__ __forceinline__ void pin(uint32_t (&d)[N]) {
#pragma unroll
    for (int q = 0; q < N; q++) asm volatile("" : "+r"(d[q])::"memory");
}
__device__ __forceinline__ void stg128(void* p, const uint32_t (&v)[4]) {
    asm volatile("st.global.v4.u32 [%0], {%1, %2, %3, %4};" ::"l"(p), "r"(v[0]), "r"(v[1]), "r"(v[2]), "r"(v[3]) : "memory");
}
__device__ __forceinline__ void ldg128(uint32_t (&v)[4], const void* p) {
    asm volatile("ld.global.L1::no_allocate.v4.u32 {%0, %1, %2, %3}, [%4];" : "=r"(v[0]), "=r"(v[1]), "=r"(v[2]), "=r"(v[3]) : "l"(p) : "memory");
}
__device__ __forceinline__ void ldg128_if(bool on, uint32_t (&v)[4], const void* p) {
    asm volatile("{\n.reg .pred p;\nsetp.ne.b32 p, %5, 0;\n@p ld.global.L1::no_allocate.v4.u32 {%0, %1, %2, %3}, [%4];\n}\n"
                 : "+r"(v[0]), "+r"(v[1]), "+r"(v[2]), "+r"(v[3]) : "l"(p), "r"((int)on) : "memory");
}
__host__ __device__ constexpr uint64_t make_desc(uint32_t addr, uint32_t lbo, uint32_t sbo) {
    return (uint64_t)((addr & 0x3FFFF) >> 4) | ((uint64_t)(lbo >> 4) << 16) | ((uint64_t)(sbo >> 4) << 32);
}
__device__ __forceinline__ void wgmma(uint32_t (&d)[12], uint32_t a0, uint32_t a1, uint32_t a2, uint32_t a3, uint64_t db, int acc) {
    asm volatile("{\n.reg .pred p;\nsetp.ne.b32 p, %17, 0;\n"
                 "wgmma.mma_async.sync.aligned.m64n48k16.f16.f16.f16 "
                 "{%0, %1, %2, %3, %4, %5, %6, %7, %8, %9, %10, %11}, "
                 "{%12, %13, %14, %15}, %16, p, 1, 1, 0;\n}\n"
                 : "+r"(d[0]), "+r"(d[1]), "+r"(d[2]), "+r"(d[3]), "+r"(d[4]), "+r"(d[5]), "+r"(d[6]), "+r"(d[7]), "+r"(d[8]), "+r"(d[9]), "+r"(d[10]), "+r"(d[11])
                 : "r"(a0), "r"(a1), "r"(a2), "r"(a3), "l"(db), "r"(acc));
}
__device__ __forceinline__ void wgmma(uint32_t (&d)[24], uint32_t a0, uint32_t a1, uint32_t a2, uint32_t a3, uint64_t db, int acc) {
    asm volatile("{\n.reg .pred p;\nsetp.ne.b32 p, %29, 0;\n"
                 "wgmma.mma_async.sync.aligned.m64n96k16.f16.f16.f16 "
                 "{%0, %1, %2, %3, %4, %5, %6, %7, %8, %9, %10, %11, %12, %13, %14, %15, %16, %17, %18, %19, %20, %21, %22, %23}, "
                 "{%24, %25, %26, %27}, %28, p, 1, 1, 0;\n}\n"
                 : "+r"(d[0]), "+r"(d[1]), "+r"(d[2]), "+r"(d[3]), "+r"(d[4]), "+r"(d[5]), "+r"(d[6]), "+r"(d[7]), "+r"(d[8]), "+r"(d[9]), "+r"(d[10]), "+r"(d[11]), "+r"(d[12]), "+r"(d[13]), "+r"(d[14]), "+r"(d[15]), "+r"(d[16]), "+r"(d[17]), "+r"(d[18]), "+r"(d[19]), "+r"(d[20]), "+r"(d[21]), "+r"(d[22]), "+r"(d[23])
                 : "r"(a0), "r"(a1), "r"(a2), "r"(a3), "l"(db), "r"(acc));
}
template <int ACC>
__device__ __forceinline__ void wgmma_rowsum(float (&d)[4], const uint32_t (&a)[4], uint64_t ones) {
    asm volatile("{\n.reg .pred p;\nsetp.ne.b32 p, %9, 0;\n"
                 "wgmma.mma_async.sync.aligned.m64n8k16.f32.bf16.bf16 {%0, %1, %2, %3}, {%4, %5, %6, %7}, %8, p, 1, 1, 0;\n}\n"
                 : "+f"(d[0]), "+f"(d[1]), "+f"(d[2]), "+f"(d[3])
                 : "r"(a[0]), "r"(a[1]), "r"(a[2]), "r"(a[3]), "l"(ones), "n"(ACC));
}
__device__ __forceinline__ void ldsm4(uint32_t (&r)[4], uint32_t addr) {
    asm volatile("ldmatrix.sync.aligned.m8n8.x4.shared.b16 {%0, %1, %2, %3}, [%4];"
                 : "=r"(r[0]), "=r"(r[1]), "=r"(r[2]), "=r"(r[3]) : "r"(addr) : "memory");
}
__device__ __forceinline__ void ldsm4_t(uint32_t (&r)[4], uint32_t addr) {
    asm volatile("ldmatrix.sync.aligned.m8n8.x4.trans.shared.b16 {%0, %1, %2, %3}, [%4];"
                 : "=r"(r[0]), "=r"(r[1]), "=r"(r[2]), "=r"(r[3]) : "r"(addr) : "memory");
}
__device__ __forceinline__ void stsm4(uint32_t addr, uint32_t a, uint32_t b, uint32_t c, uint32_t d) {
    asm volatile("stmatrix.sync.aligned.m8n8.x4.shared.b16 [%0], {%1, %2, %3, %4};"
                 ::"r"(addr), "r"(a), "r"(b), "r"(c), "r"(d) : "memory");
}
__device__ __forceinline__ uint32_t transpose8x8(uint32_t v) {
    uint32_t d; asm volatile("movmatrix.sync.aligned.m8n8.trans.b16 %0, %1;" : "=r"(d) : "r"(v)); return d;
}
__device__ __forceinline__ void spin_until(const unsigned* counter, unsigned target) {
    unsigned n = 0, c;
    do {
        asm volatile("ld.acquire.gpu.global.u32 %0, [%1];" : "=r"(c) : "l"(counter) : "memory");
        if (++n > SPIN_LIMIT) __trap();
    } while ((int)(c - target) < 0);
}
__device__ __forceinline__ void signal(unsigned* counter) {
    __syncwarp();
    if (elect_one()) asm volatile("red.release.gpu.global.add.u32 [%0], 1;" ::"l"(counter) : "memory");
    __syncwarp();
}
__device__ __forceinline__ void lds128(uint32_t& a, uint32_t& b, uint32_t& c, uint32_t& d, uint32_t addr) {
    asm volatile("ld.shared.v4.u32 {%0, %1, %2, %3}, [%4];" : "=r"(a), "=r"(b), "=r"(c), "=r"(d) : "r"(addr) : "memory");
}
__device__ __forceinline__ void lds64(uint32_t& a, uint32_t& b, uint32_t addr) {
    asm volatile("ld.shared.v2.u32 {%0, %1}, [%2];" : "=r"(a), "=r"(b) : "r"(addr) : "memory");
}
__device__ __forceinline__ void lds32(uint32_t& a, uint32_t addr) {
    asm volatile("ld.shared.u32 %0, [%1];" : "=r"(a) : "r"(addr) : "memory");
}
__device__ __forceinline__ int ldsi(uint32_t addr) {
    uint32_t v;
    lds32(v, addr);
    return (int)v;
}
__device__ __forceinline__ float ldsf(uint32_t addr) {
    uint32_t v;
    lds32(v, addr);
    return __uint_as_float(v);
}
__device__ __forceinline__ void sts32(uint32_t addr, uint32_t a) {
    asm volatile("st.shared.u32 [%0], %1;" ::"r"(addr), "r"(a) : "memory");
}
__device__ __forceinline__ void sts128(uint32_t addr, uint32_t a, uint32_t b, uint32_t c, uint32_t d) {
    asm volatile("st.shared.v4.u32 [%0], {%1, %2, %3, %4};" ::"r"(addr), "r"(a), "r"(b), "r"(c), "r"(d) : "memory");
}
__device__ __forceinline__ void sts64(uint32_t addr, uint32_t a, uint32_t b) {
    asm volatile("st.shared.v2.u32 [%0], {%1, %2};" ::"r"(addr), "r"(a), "r"(b) : "memory");
}
__device__ __forceinline__ void anchor(uint32_t addr, uint32_t a, uint32_t b, uint32_t c, uint32_t d) {
    asm volatile("{\n.reg .pred p;\nsetp.eq.b32 p, %0, 0;\n@p st.shared.v4.u32 [%0], {%1, %2, %3, %4};\n}\n"
                 ::"r"(addr), "r"(a), "r"(b), "r"(c), "r"(d) : "memory");
}
__device__ __forceinline__ uint32_t bf_fma(uint32_t a, uint32_t b, uint32_t c) {
    uint32_t d; asm("fma.rn.bf16x2 %0, %1, %2, %3;" : "=r"(d) : "r"(a), "r"(b), "r"(c)); return d;
}
__device__ __forceinline__ uint32_t bf_mul(uint32_t a, uint32_t b) {
    uint32_t d; asm("mul.rn.bf16x2 %0, %1, %2;" : "=r"(d) : "r"(a), "r"(b)); return d;
}
__device__ __forceinline__ uint32_t bf_absmax(uint32_t a, uint32_t b) {
    uint32_t d; asm("max.xorsign.abs.bf16x2 %0, %1, %2;" : "=r"(d) : "r"(a), "r"(b)); return d;
}
__device__ __forceinline__ uint32_t h_fma(uint32_t a, uint32_t b, uint32_t c) {
    uint32_t d; asm("fma.rn.f16x2 %0, %1, %2, %3;" : "=r"(d) : "r"(a), "r"(b), "r"(c)); return d;
}
__device__ __forceinline__ uint32_t h_mul(uint32_t a, uint32_t b) {
    uint32_t d; asm("mul.rn.f16x2 %0, %1, %2;" : "=r"(d) : "r"(a), "r"(b)); return d;
}
__device__ __forceinline__ uint32_t h_tanh(uint32_t a) {
    uint32_t d; asm("tanh.approx.f16x2 %0, %1;" : "=r"(d) : "r"(a)); return d;
}
__device__ __forceinline__ uint32_t pack_h2(float lo, float hi) {
    uint32_t d; asm("cvt.rn.f16x2.f32 %0, %1, %2;" : "=r"(d) : "f"(hi), "f"(lo)); return d;
}
__device__ __forceinline__ uint32_t pack_bf2(float lo, float hi) {
    uint32_t d; asm("cvt.rn.bf16x2.f32 %0, %1, %2;" : "=r"(d) : "f"(hi), "f"(lo)); return d;
}
__device__ __forceinline__ float bf_lo(uint32_t v) { return __uint_as_float(v << 16); }
__device__ __forceinline__ float bf_hi(uint32_t v) { return __uint_as_float(v & 0xffff0000u); }
__device__ __forceinline__ float h_lo(uint32_t v) { return __low2float(*reinterpret_cast<__half2*>(&v)); }
__device__ __forceinline__ float h_hi(uint32_t v) { return __high2float(*reinterpret_cast<__half2*>(&v)); }
__device__ __forceinline__ float warp_absmax(uint32_t v) {
    return __uint_as_float(__reduce_max_sync(~0u, max((v & 0x7fffu) << 16, v & 0x7fff0000u)));
}
__device__ __forceinline__ uint32_t gelu2(uint32_t z) {
    uint32_t p = h_fma(z, z, GELU_C2);
    uint32_t t = h_tanh(h_mul(z, p));
    return h_fma(z, t, z);
}
__device__ __forceinline__ float pow2i(int e) { return __uint_as_float((uint32_t)(e + 127) << 23); }
__device__ __forceinline__ int ilog2f(float v) {
    int e = (int)((__float_as_uint(v) >> 23) & 0xff) - 127;
    return max(-100, min(100, e));
}

__device__ __forceinline__ int bound_exp(float w1max) { return w1max > 0.f ? ilog2f(2.f * KZ * 96.f * w1max) : 0; }
__device__ __forceinline__ bool plain_squares(int e) { return (unsigned)(4 - e) <= 6; }
__device__ __forceinline__ int square_exp(int e) { return plain_squares(e) ? 0 : max(-14, min(4 - e, 14)); }
__device__ __forceinline__ int sum_exp(int e) { return max(-90, min(90, 33 - 2 * e)); }
__device__ __forceinline__ int row_exp(float m) { return 2 - ilog2f(m); }

struct Split {
    int per_cta, extra, period, inv_period, lenders;
    uint32_t lent_off[MAX_LENDERS * LENT];
    __host__ __device__ __forceinline__ int longer_before(int cta) const {
        const int n = (cta + period / 2) * inv_period >> 16;
        return n < extra ? n : extra;
    }
};
struct Work {
    int tA, tB, nA, nB, dir, rows, lent, index;
    __host__ __device__ __forceinline__ int tile(int j) const { return j < nA ? tA + dir * j : tB + dir * (j - nA); }
};
__host__ __device__ __forceinline__ Work get_work(int cta, const Split& sp) {
    Work w;
    const int before = sp.longer_before(cta), longer = sp.longer_before(cta + 1) - before;
    w.lent = longer && sp.lenders ? LENT : 0;
    w.index = before;
    const int t0 = cta * sp.per_cta + before, t1 = t0 + sp.per_cta + longer;
    const int tm = t1 < (t0 | 511) + 1 ? t1 : (t0 | 511) + 1;
    const bool swap = t1 > tm && t1 - tm < tm - t0, down = cta & 1;
    w.nA = swap ? t1 - tm : tm - t0;
    w.nB = t1 - t0 - w.nA;
    w.tA = down ? (swap ? tm : t0) : (swap ? t1 : tm) - 1;
    w.tB = down ? (swap ? t0 : tm) : (swap ? tm : t1) - 1;
    w.dir = down ? 1 : -1;
    w.rows = w.nA + 2 + (w.nB ? w.nB + 2 : 0);
    return w;
}
__device__ __forceinline__ int row_code(const Work& w, int i) {
    const bool in_a = i < w.nA + 2;
    const int t = in_a ? w.tA : w.tB;
    return ((t & 511) + w.dir * ((in_a ? i : i - (w.nA + 2)) - 1)) << 16 | (t >> 9) * TILE_W;
}
__host__ __device__ __forceinline__ uint32_t tile_offset(int tile) { return ((tile & 511) * IMG_W + (tile >> 9) * TILE_W) * (CH * 2); }
__device__ __forceinline__ int tile_order(int j, int n) {
    return j % ORDER_P == ORDER_P - 1 ? j / ORDER_P : n - 1 - (j - j / ORDER_P);
}
__device__ __forceinline__ void issue_region(const CUtensorMap* tm, uint32_t dst, uint32_t bar, int warp, int code) {
    mbar_expect_tx(bar, REGION_BYTES);
    tma_row(dst, tm, bar, (code & 0xffff) + (16 * warp - 1), code >> 16);
}

template <class Event>
__device__ __forceinline__ void conv_producer(const Work& wk, const CUtensorMap* tm, uint32_t sb, int warp, Event event) {
    const int lane = threadIdx.x & 31;
    const int j = lane & 15, grp = lane >> 4;
    const uint32_t reg0 = sb + SM_RING + warp * REGION_BYTES;
    const uint32_t bars = sb + SM_BAR + warp * 8;
    if (warp * 32 + lane < MAX_ROWS) {
        const int i = warp * 32 + lane, before = min(i / 5, wk.lent);
        const bool back = i % 5 == 0 && i > 0 && i / 5 <= wk.lent;
        sts32(sb + SM_TILES + i * 4, back ? tile_offset(wk.tile(before - 1)) | before
                                          : tile_offset(wk.tile(wk.lent + tile_order(i - before, wk.nA + wk.nB - 4 - wk.lent))));
    }
    const uint32_t ld64 = opaque(reg0 + grp * 8 * 192 + j * 8), ld32 = opaque(reg0 + grp * 8 * 192 + 128 + j * 4);
    const uint32_t st64 = opaque(reg0 + grp * A_SBO + (j >> 1) * A_LBO + (j & 1) * 8);
    const uint32_t st32 = opaque(reg0 + grp * A_SBO + (8 + (j >> 2)) * A_LBO + (j & 3) * 4);
    named_bar(0, NTHREADS);
    uint32_t w[3][3][3];
    mbar_wait_once(sb + BAR_F, 0);
#pragma unroll
    for (int tap = 0; tap < 9; tap++) {
        const uint32_t p = sb + SM_FILTER + (3 + wk.dir * 3 * (tap / 3 - 1) + tap % 3) * (CH * 2);
        lds64(w[tap / 3][tap % 3][0], w[tap / 3][tap % 3][1], p + 8 * j);
        lds32(w[tap / 3][tap % 3][2], p + 128 + 4 * j);
#pragma unroll
        for (int q = 0; q < 3; q++) w[tap / 3][tap % 3][q] = bf_mul(w[tap / 3][tap % 3][q], CONV_SCALE2);
    }
#pragma unroll
    for (int tap = 0; tap < 9; tap++) sts64(reg0 + (NSLOT - 1) * SLOT_BYTES + tap * 128 + j * 8, w[tap / 3][tap % 3][1], w[tap / 3][tap % 3][0]);
    named_bar(1, 128);
#pragma unroll
    for (int tap = 0; tap < 9; tap++) lds64(w[tap / 3][tap % 3][1], w[tap / 3][tap % 3][0], reg0 + (NSLOT - 1) * SLOT_BYTES + tap * 128 + j * 8);
    static_assert(2 * PREFETCH_ROWS == NSLOT && SLOT_BYTES % 32 == 0, "slot arithmetic");
    uint32_t bo = 0, so = 0, par = 0, pbo = PREFETCH_ROWS * 32, ppar = 1;
    int px, py;
    auto request = [&]() {
        mbar_wait_once(bars + (BAR_E - SM_BAR) + pbo, ppar);
        if (elect_one()) {
            mbar_expect_tx(bars + pbo, REGION_BYTES);
            tma_row(reg0 + pbo * (SLOT_BYTES / 32), tm, bars + pbo, px, py);
        }
    };
    auto advance = [&]() {
        bo += 32;
        so += SLOT_BYTES;
        if (bo == NSLOT * 32) { bo = 0; so = 0; par ^= 1; }
        pbo += 32;
        if (pbo == NSLOT * 32) { pbo = 0; ppar ^= 1; }
    };
    auto aim = [&](int row) {
        const int code = row_code(wk, row);
        px = (code & 0xffff) + (16 * warp - 1);
        py = code >> 16;
    };
    uint32_t accB[8][3], accC[8][3];
    int r = 0;
#pragma unroll 1
    while (r < wk.rows) {
        if (r == 0 || r == wk.nA + 2) {
            const uint32_t bo0 = bo;
            uint32_t bo1;
#pragma unroll 1
            for (int k = 0; k < 2; k++, r++) {
                if (r != 1) {
                    aim(r + PREFETCH_ROWS);
                    request();
                }
                mbar_wait_once(bars + bo, par);
                bo1 = bo;
                advance();
            }
            const uint32_t so0 = bo0 * (SLOT_BYTES / 32), so1 = bo1 * (SLOT_BYTES / 32);
#pragma unroll
            for (int p = 0; p < 10; p++) {
                uint32_t u[3], v[3];
                lds64(u[0], u[1], so0 + ld64 + p * 192);
                lds32(u[2], so0 + ld32 + p * 192);
                lds64(v[0], v[1], so1 + ld64 + p * 192);
                lds32(v[2], so1 + ld32 + p * 192);
#pragma unroll
                for (int dx = 0; dx < 3; dx++) {
                    const int o = p - dx;
                    if (o < 0 || o > 7) continue;
#pragma unroll
                    for (int q = 0; q < 3; q++) {
                        accB[o][q] = bf_fma(v[q], w[1][dx][q], dx == 0 ? bf_mul(u[q], w[0][dx][q]) : bf_fma(u[q], w[0][dx][q], accB[o][q]));
                        accC[o][q] = dx == 0 ? bf_mul(v[q], w[0][dx][q]) : bf_fma(v[q], w[0][dx][q], accC[o][q]);
                    }
                }
            }
            anchor(ld64, accB[7][0], accB[7][1], accB[7][2], 0);
            __syncwarp();
            if (elect_one()) {
                mbar_arrive(bars + (BAR_A - SM_BAR) + bo0);
                mbar_arrive(bars + (BAR_E - SM_BAR) + bo0);
                mbar_arrive(bars + (BAR_A - SM_BAR) + bo1);
                mbar_arrive(bars + (BAR_E - SM_BAR) + bo1);
            }
        }
        int end = wk.rows;
        const int marks[4] = {wk.rows - PREFETCH_ROWS, wk.rows - 11, wk.nA + 2, wk.nA + 2 - PREFETCH_ROWS};
#pragma unroll
        for (int k = 0; k < 4; k++) end = marks[k] > r ? min(end, marks[k]) : end;
        const int fetch = opaque_uniform(end - wk.rows);
        aim(r + PREFETCH_ROWS);
        px = opaque_uniform(px);
        const int py_end = opaque_uniform(py + wk.dir * (end - r));
        r = end;
#pragma unroll 1
        do {
            mbar_wait(bars + bo, par);
            uint32_t out[8][3];
#pragma unroll
            for (int p = 0; p < 10; p++) {
                uint32_t xv[3];
                lds64(xv[0], xv[1], so + ld64 + p * 192);
                lds32(xv[2], so + ld32 + p * 192);
#pragma unroll
                for (int dx = 0; dx < 3; dx++) {
                    const int o = p - dx;
                    if (o < 0 || o > 7) continue;
#pragma unroll
                    for (int q = 2; q >= 0; q--) {
                        out[o][q] = bf_fma(xv[q], w[2][dx][q], dx == 0 ? accB[o][q] : out[o][q]);
                        accB[o][q] = bf_fma(xv[q], w[1][dx][q], dx == 0 ? accC[o][q] : accB[o][q]);
                        accC[o][q] = dx == 0 ? bf_mul(xv[q], w[0][dx][q]) : bf_fma(xv[q], w[0][dx][q], accC[o][q]);
                    }
                }
            }
            __syncwarp();
#pragma unroll
            for (int o = 7; o >= 0; o--) {
                sts64(so + st64 + o * 16, out[o][0], out[o][1]);
                sts32(so + st32 + o * 16, out[o][2]);
            }
            __syncwarp();
            if (elect_one()) mbar_arrive(bars + (BAR_A - SM_BAR) + bo);
            if (fetch) request();
            advance();
            py += wk.dir;
        } while (py != py_end);
        if (((wk.rows - r) & ~8) == PREFETCH_ROWS) event(wk.rows - r == PREFETCH_ROWS);
    }
}

template <bool SCALED, int K0 = 0, int K1 = 3>
__device__ __forceinline__ void gelu_sq(uint32_t (&d)[24], uint32_t (&keep)[24], uint32_t sq_addr, uint32_t scale2) {
    pin(d);
#pragma unroll
    for (int k = K0; k < K1; k++) {
        uint32_t hs[4];
        lds128(hs[0], hs[1], hs[2], hs[3], sq_addr + k * SQ_ROW);
#pragma unroll
        for (int q = 0; q < 4; q++) {
            uint32_t g0 = gelu2(d[8 * k + 2 * q]), g1 = gelu2(d[8 * k + 2 * q + 1]);
            keep[8 * k + 2 * q] = g0;
            keep[8 * k + 2 * q + 1] = g1;
            if (SCALED) { g0 = h_mul(g0, scale2); g1 = h_mul(g1, scale2); }
            hs[q] = h_fma(g1, g1, h_fma(g0, g0, hs[q]));
        }
        sts128(sq_addr + k * SQ_ROW, hs[0], hs[1], hs[2], hs[3]);
    }
}
__device__ __forceinline__ void gelu_sq_reg(uint32_t (&d)[24], uint32_t (&hs)[12]) {
    pin(d);
#pragma unroll
    for (int q = 0; q < 12; q++) {
        const uint32_t g0 = gelu2(d[2 * q]), g1 = gelu2(d[2 * q + 1]);
        hs[q] = h_fma(g1, g1, h_fma(g0, g0, hs[q]));
    }
}
__device__ __forceinline__ void gelu_to(uint32_t (&g)[12], uint32_t (&d)[12]) {
    pin(d);
#pragma unroll
    for (int q = 0; q < 12; q++) g[q] = gelu2(d[q]);
    pin(g);
}
__device__ __forceinline__ void load_tile(uint32_t (&raw)[6][4], uint32_t addr) {
#pragma unroll
    for (int s = 0; s < 6; s++) ldsm4(raw[s], addr + s * 2 * A_LBO);
}
template <class F>
__device__ __forceinline__ void layer_norm(uint32_t (&raw)[6][4], uint64_t ones, F meanwhile) {
    uint32_t sq[2][4];
#pragma unroll
    for (int s = 0; s < 6; s++)
#pragma unroll
        for (int q = 0; q < 4; q++) sq[s / 3][q] = s % 3 == 0 ? bf_mul(raw[s][q], raw[s][q]) : bf_fma(raw[s][q], raw[s][q], sq[s / 3][q]);
    float sum[4], ssq[4];
    wg_fence();
    wgmma_rowsum<0>(sum, raw[0], ones);
#pragma unroll
    for (int s = 1; s < 6; s++) wgmma_rowsum<1>(sum, raw[s], ones);
    wgmma_rowsum<0>(ssq, sq[0], ones);
    wgmma_rowsum<1>(ssq, sq[1], ones);
    wg_commit();
    meanwhile();
    wg_wait<0>();
    uint32_t sc[2], sh[2];
#pragma unroll
    for (int h = 0; h < 2; h++) {
        asm volatile("" : "+f"(sum[2 * h]), "+f"(ssq[2 * h])::"memory");
        constexpr float EPS = 1e-5f / (KZ * KZ) * 0x1p-64f;
        const float m = sum[2 * h] * (1.f / (CH * KZ));
        float rstd;
        asm("rsqrt.approx.ftz.f32 %0, %1;" : "=f"(rstd) : "f"(fmaxf(fmaf(-m, m, fmaf(ssq[2 * h], 1.f / (CH * KZ * KZ), EPS)), EPS)));
        rstd *= 0x1p-112f;
        sc[h] = pack_bf2(rstd, rstd);
        const float shift = sum[2 * h] * (-1.f / CH) * bf_hi(sc[h]);
        sh[h] = pack_bf2(shift, shift);
    }
#pragma unroll
    for (int s = 0; s < 6; s++)
#pragma unroll
        for (int q = 0; q < 4; q++) {
            const uint32_t v = bf_fma(raw[s][q], sc[q & 1], sh[q & 1]);
            asm("lop3.b32 %0, %1, %2, 0x80008000, 0xd8;" : "=r"(raw[s][q]) : "r"(v << 3), "r"(v));
        }
}
struct Cursor {
    int slot;
    uint32_t par;
    __device__ __forceinline__ void advance(int n) {
        slot += n;
        if (slot >= NSLOT) { slot -= NSLOT; par ^= 1; }
    }
};
struct Descs {
    uint64_t w1[8][6];
    uint64_t w2[24];
    uint64_t ones;
};
template <int E0, int N>
__device__ __forceinline__ void gemm1_chunk(uint32_t (&d)[N], const uint32_t (&a)[6][4], const Descs& ds, int zero) {
#pragma unroll
    for (int s = 0; s < 6; s++) wgmma(d, a[s][0], a[s][1], a[s][2], a[s][3], ds.w1[E0 / 48][s], s ? 1 : zero);
}
template <int E0, int N>
__device__ __forceinline__ void gemm2_chunk(uint32_t (&acc)[24], const uint32_t (&g)[N], const Descs& ds) {
#pragma unroll
    for (int s = 0; s < N / 4; s++) wgmma(acc, g[4 * s], g[4 * s + 1], g[4 * s + 2], g[4 * s + 3], ds.w2[E0 / 16 + s], 1);
}

struct __align__(64) Params {
    Split sp;
    int zero;
    const __nv_bfloat16 *x, *dw, *w2, *gamma, *beta;
    __nv_bfloat16* out;
    Scratch* sc;
    Descs ds;
};

__global__ void __launch_bounds__(NTHREADS, 1)
block_kernel(const __grid_constant__ CUtensorMap tmap, const __grid_constant__ CUtensorMap tmap_w1, const __grid_constant__ Params pm) {
    const Split& sp = pm.sp;
    const Descs& ds = pm.ds;
    const int& zero = pm.zero;
    const __nv_bfloat16 *const &x = pm.x, *const &dw = pm.dw, *const &w2 = pm.w2, *const &gamma = pm.gamma, *const &beta = pm.beta;
    __nv_bfloat16* const& out = pm.out;
    Scratch* const& sc = pm.sc;
    extern __shared__ __align__(1024) uint8_t smem[];
    constexpr uint32_t sb = SB;
    const int tid = threadIdx.x;
    const Work wk = get_work(blockIdx.x, sp);
    constexpr uint32_t s_red = sb + SM_RED;
    if (smem_u32(smem) != SB) __trap();

    const int warp_id = __shfl_sync(~0u, tid >> 5, 0);
    PROF(0);
    const int cw = warp_id - 4, wgi = cw >> 2, w4 = warp_id & 3;
    if (elect_one()) {
        static_assert(3 * NSLOT * 4 == 8 + 8 * 8 && BAR_F == BAR_W + 48, "barrier shares");
        const int b = warp_id - 8;
        const uint32_t bar = b < 0 ? sb + BAR_X + warp_id * 8 : b < 7 ? sb + BAR_W + b * 8 : sb + BAR_PIN;
        mbar_init(bar, 1);
        if (b < 0 || b >= 6) {
#pragma unroll
            for (int k = 0; k < 8; k++) mbar_init(sb + (b < 0 ? BAR_X + (8 + 8 * warp_id + k) * 8 : BAR_R + ((b - 6) * 8 + k) * 8), 1);
        }
        fence_async();
        if (b < 0) {
            issue_region(&tmap, sb + SM_RING + warp_id * REGION_BYTES, bar, w4, ((wk.tA & 511) + wk.dir * wgi) << 16 | (wk.tA >> 9) * TILE_W);
        } else if (b < 6) {
            mbar_expect_tx(bar, 64 * CH * 2);
            tma_2d(sb + SM_W2 + b * (64 * CH * 2), &tmap_w1, bar, 64 * b, 0);
        } else if (b == 6) {
            mbar_expect_tx(bar, 9 * CH * 2);
            bulk_load(sb + SM_FILTER, dw, 9 * CH * 2, bar);
        }
    }
    __syncwarp();
    const int ntiles = wk.nA + wk.nB;
    const int rank = (wgi + wk.lent + 2 * (ntiles - 1)) % NCONS | (wgi >> 2 & 3);
    const int spare = wk.rows % NSLOT, spare2 = spare == NSLOT - 1 ? 0 : spare + 1;
    const uint32_t sq_base = sb + (wgi < 0 ? SM_RING + spare * SLOT_BYTES : SM_SQ + rank * 2 * SQ_HALF);
    const uint32_t sq_upper = wgi < 0 ? (spare2 - spare) * SLOT_BYTES : SQ_HALF;
    const uint32_t bar_a = sb + BAR_A + w4 * 8, bar_e = sb + BAR_E + w4 * 8;
    auto max_w1 = [&](uint32_t lane) { return __uint_as_float(__reduce_max_sync(~0u, lane < 4 * NCONS ? ldsi(s_red + RED_MAX + lane * 4) : 0)); };
    auto square_scale = [&](uint32_t lane) {
        const float f = pow2i(square_exp(bound_exp(max_w1(lane))));
        return pack_h2(f, f);
    };
    uint32_t a_addr, sq;
    const uint32_t sq_warp = sq_base + w4 * 512;
    auto set_addresses = [&]() {
        a_addr = opaque(sb + SM_RING + w4 * REGION_BYTES + ((tid >> 3) & 1) * A_SBO + ((tid >> 4) & 1) * A_LBO + (tid & 7) * 16);
        sq = opaque(sq_base + (tid & 127) * 16);
    };
    uint32_t turn, turn_end, so, so_sum, bo, bo_sum, off;
    auto set_run = [&](int j, int stop, int row) {
        const int slot = row % NSLOT, both = 2 * (row % 3) + 3;
        turn = opaque_uniform(row / 3);
        turn_end = opaque_uniform(row / 3 + (stop - j + NCONS - 1) / NCONS);
        so = opaque_uniform(slot * SLOT_BYTES);
        so_sum = opaque_uniform(both * SLOT_BYTES);
        bo = opaque_uniform(bar_a + slot * 32);
        bo_sum = opaque_uniform(2 * bar_a + both * 32);
        off = opaque_uniform(tile_offset(wk.tile(j)) + w4 * WARP_BYTES - sq_warp);
    };
    const int nrest = ntiles - 4;
    int jt;
    Cursor cur;
    int fast_from;
    if (warp_id < 4) {
        conv_producer(wk, &tmap, sb, warp_id, [&](bool second) {
            if (!second) {
                if (tid == 0) sts32(s_red + RED_JOB, wk.lent ? NTILES : atomicAdd(&sc->job, 1));
                if (blockIdx.x == 0) {
#pragma unroll 1
                    for (int e = tid; e < EX; e += 128) *sc->sum(e) = 0;
                    sc->bias[tid] = 0.f;
                }
                if (blockIdx.x == 0 || wk.lent) signal(&sc->early);
                __syncwarp();
            } else {
                const int piece = opaque_uniform(ldsi(s_red + RED_JOB)) - W2_GROUPS / 2, q = 2 * piece + W2_GROUPS + (w4 >> 1);
                if (piece < 8 * LENT * sp.lenders) {
                    spin_until(&sc->early, (ldsi(s_red + RED_LAUNCH) + 1) * 4 * (sp.lenders + 1));
                    if (elect_one()) {
                        if (piece >= 0) prefetch_l2(reinterpret_cast<const char*>(out) + sp.lent_off[piece / 8] + w4 * WARP_BYTES, WARP_BYTES);
                        else { prefetch_l2(w2 + 8 * q * CH, 8 * CH * 2); prefetch_l2(beta + 8 * q, 16); }
                    }
                }
            }
        });
        const int piece = opaque_uniform(ldsi(s_red + RED_JOB)) - W2_GROUPS / 2, q = 2 * piece + W2_GROUPS + (w4 >> 1);
        const bool prepares = piece < 0, helps = piece < 8 * LENT * sp.lenders;
        set_addresses();
        const int lane = lane_id(), g = lane >> 2, t = lane & 3;
        uint32_t a[6][4];
        unsigned short bt_raw;
        if (prepares) {
#pragma unroll
            for (int m = 0; m < 3; m++) ldg128(a[m], w2 + (8 * q + g) * CH + 32 * m + 8 * t);
            asm volatile("ld.global.nc.u16 %0, [%1];" : "=h"(bt_raw) : "l"(beta + 8 * q + g) : "memory");
        } else if (helps) {
#pragma unroll
            for (int s = 0; s < 6; s++) ldg128(a[s], reinterpret_cast<const char*>(out) + sp.lent_off[piece / 8] + w4 * WARP_BYTES + lane * 16 + s * 512);
        }
        mbar_wait_once(bar_e + spare2 * 32, (wk.rows - 5) / NSLOT & 1);
        mbar_wait_once(bar_e + spare * 32, (wk.rows - 6) / NSLOT & 1);
        named_bar(1, 128);
#pragma unroll
        for (int k = 0; k < 6; k++) { sts128(sq + k * SQ_ROW, 0, 0, 0, 0); sts128(sq + sq_upper + k * SQ_ROW, 0, 0, 0, 0); }
        if (prepares) {
            const int half = w4 & 1;
            uint32_t rmax = 0;
#pragma unroll
            for (int m = 0; m < 3; m++) rmax = bf_absmax(bf_absmax(rmax, bf_absmax(a[m][0], a[m][1])), bf_absmax(a[m][2], a[m][3]));
            uint2 u = half ? make_uint2(a[0][2], a[0][3]) : make_uint2(a[0][0], a[0][1]), u1 = half ? make_uint2(a[1][2], a[1][3]) : make_uint2(a[1][0], a[1][1]);
            const uint2 u2 = half ? make_uint2(a[2][2], a[2][3]) : make_uint2(a[2][0], a[2][1]);
            const float bt = bf_lo(bt_raw);
            rmax = bf_absmax(rmax, __shfl_xor_sync(~0u, rmax, 1));
            rmax = bf_absmax(rmax, __shfl_xor_sync(~0u, rmax, 2));
            const float mx = fmaxf(fabsf(bf_lo(rmax)), fabsf(bf_hi(rmax))), rs = pow2i(row_exp(mx));
            if (t == 0 && !half) sc->w2max[8 * q + g] = mx;
#pragma unroll 1
            for (int m = 0; m < 3; m++, u = u1, u1 = u2) {
                float f[4];
#pragma unroll
                for (int k = 0; k < 2; k++) {
                    const float lo = bf_lo(k ? u.y : u.x), hi = bf_hi(k ? u.y : u.x);
                    sc->w2h[(4 * m + 2 * half + k) * 1536 + q * 32 + lane] = transpose8x8(pack_h2(lo * rs, hi * rs));
                    f[2 * k] = lo * bt;
                    f[2 * k + 1] = hi * bt;
                }
                const float r0 = (g & 2 ? f[2] : f[0]) + __shfl_xor_sync(~0u, g & 2 ? f[0] : f[2], 8);
                const float r1 = (g & 2 ? f[3] : f[1]) + __shfl_xor_sync(~0u, g & 2 ? f[1] : f[3], 8);
                float r = (g & 1 ? r1 : r0) + __shfl_xor_sync(~0u, g & 1 ? r0 : r1, 4);
                r += __shfl_xor_sync(~0u, r, 16);
                if (g < 4) atomicAdd(&sc->bias[32 * m + 8 * t + 4 * half + g], r);
            }
            asm volatile("fence.proxy.async.global;" ::: "memory");
            signal(&sc->prep);
        } else
        if (helps) {
            uint32_t d[12], gl[12];
            const uint32_t scale2 = square_scale(lane);
            wg_fence();
#pragma unroll
            for (int s = 0; s < 6; s++) wgmma(d, a[s][0], a[s][1], a[s][2], a[s][3], ds.w1[0][s] + piece % 8 * (6 * 1536 / 16), s ? 1 : 0);
            wg_commit();
            wg_wait<0>();
            gelu_to(gl, d);
#pragma unroll
            for (int s = 0; s < 3; s++) {
                sc->lent[((piece / 8 * 4 + w4) * 24 + piece % 8 * 3 + s) * 32 + lane] = make_uint4(gl[4 * s], gl[4 * s + 1], gl[4 * s + 2], gl[4 * s + 3]);
                uint32_t hs[2];
#pragma unroll
                for (int k = 0; k < 2; k++) {
                    const uint32_t g0 = h_mul(gl[4 * s + 2 * k], scale2), g1 = h_mul(gl[4 * s + 2 * k + 1], scale2);
                    hs[k] = h_fma(g1, g1, h_mul(g0, g0));
                }
                const int pair = piece % 4 * 3 + s;
                sts64(sq + (piece & 4 ? sq_upper : 0) + (pair >> 1) * SQ_ROW + (pair & 1) * 8, hs[0], hs[1]);
            }
        }
        jt = ntiles - 1;
        cur.slot = spare ? spare - 1 : NSLOT - 1;
        cur.par = (wk.rows - 1) / NSLOT & 1;
        fast_from = ntiles;
        turn = turn_end = so = so_sum = bo = bo_sum = off = rank;
    } else {
        set_addresses();
        if (wgi == NCONS - 1) named_arrive(4, 256);
        set_run(wk.lent + wgi, min(wk.nA, nrest), wk.lent + wgi + 2);
        jt = wgi < wk.lent ? wgi : wk.lent + wgi;
        cur = {2, 0};
        cur.advance(jt + (jt >= wk.nA ? 2 : 0));
        {
            const int ct = tid - 128, lane = tid & 31;
            const unsigned epoch = *reinterpret_cast<volatile unsigned*>(&sc->launch);
            const int r = lane & 7, mi = lane >> 3;
            const uint32_t src = sb + SM_W2 + (cw >> 1) * (64 * CH * 2) + r * 128 + ((((cw & 1) * 4 + mi) ^ r) * 16);
            const uint32_t dst = sb + SM_W1 + (4 * cw + mi) * 1536 + r * 16;
            const int code = row_code(wk, PREFETCH_ROWS - 1 + wgi);
            named_bar(0, NTHREADS);
            auto request = [&]() {
                if (elect_one())
                    issue_region(&tmap, sb + SM_RING + (PREFETCH_ROWS - 1 + wgi) * SLOT_BYTES + w4 * REGION_BYTES, sb + BAR_X + (cw + 8) * 8, w4, code);
                __syncwarp();
            };
            if (wgi == 0) request();
            mbar_wait_once(sb + BAR_W + (cw >> 1) * 8, 0);
            uint32_t wmax[2] = {}, wsum[4] = {};
#pragma unroll 4
            for (int c = 0; c < 12; c++) {
                uint32_t u[4];
                ldsm4_t(u, src + c * 1024);
#pragma unroll
                for (int q = 0; q < 4; q++) {
                    wmax[q & 1] = bf_absmax(wmax[q & 1], u[q]);
                    wsum[q] = bf_fma(u[q], 0x3f803f80u, wsum[q]);
                    u[q] = pack_h2(__uint_as_float(u[q] * (65536 + zero)), bf_hi(u[q]));
                }
                stsm4(dst + c * 128, u[0], u[1], u[2], u[3]);
            }
            const float w1max = warp_absmax(bf_absmax(wmax[0], wmax[1]));
            if (lane == 0) sts32(s_red + RED_MAX + cw * 4, __float_as_uint(w1max));
            bool center = false;
#pragma unroll
            for (int q = 0; q < 4; q++) {
#pragma unroll
                for (int o = 1; o <= 2; o <<= 1) wsum[q] = bf_fma(__shfl_xor_sync(~0u, wsum[q], o), 0x3f803f80u, wsum[q]);
                center |= fabsf(bf_lo(wsum[q]) + bf_hi(wsum[q])) > (0.15f * CH) * w1max;
            }
            if (__builtin_expect(__any_sync(~0u, center), 0)) {
                float mean[4] = {};
#pragma unroll 1
                for (int pass = 0; pass < 2; pass++) {
                    float sum[4] = {};
#pragma unroll 1
                    for (int c = 0; c < 12; c++) {
                        uint32_t u[4];
                        ldsm4_t(u, src + c * 1024);
#pragma unroll
                        for (int q = 0; q < 4; q++) {
                            sum[q] += bf_lo(u[q]) + bf_hi(u[q]);
                            u[q] = pack_h2(bf_lo(u[q]) - mean[q], bf_hi(u[q]) - mean[q]);
                        }
                        stsm4(dst + c * 128, u[0], u[1], u[2], u[3]);
                    }
#pragma unroll
                    for (int q = 0; q < 4; q++) {
                        sum[q] += __shfl_xor_sync(~0u, sum[q], 1);
                        sum[q] += __shfl_xor_sync(~0u, sum[q], 2);
                        mean[q] = sum[q] * (1.f / CH);
                    }
                }
            }
            if (ct < 32) sts32(sb + SM_ONES + ct * 4, 0x3f803f80u);
            if (ct == 0) sts32(s_red + RED_LAUNCH, epoch);
            fence_async();
            named_bar(2, CONS_THREADS);
            if (wgi == 2) request();
        }
        PROF(1);
        if (wgi) mbar_wait_once(bar_a + 64, 0);
#pragma unroll
        for (int q = 0; q < 6; q++) sts128(sq_base + (tid & 127) * 16 + q * SQ_ROW, 0, 0, 0, 0);
        fast_from = wk.lent;
        if (!__all_sync(~0u, plain_squares(bound_exp(max_w1(lane_id()))))) {
            fast_from = ntiles;
#pragma unroll 1
            for (int q = 0; q < 6; q++) sts128(sq + SQ_HALF + q * SQ_ROW, 0, 0, 0, 0);
        }
    }
    uint32_t k1[24], k2[24], k3[24];
    uint32_t here;
    constexpr int SQC = 3 * SQ_ROW;
    auto store_at = [&](const uint32_t (&a)[6][4], uint32_t off) {
        char* ap = reinterpret_cast<char*>(out) + (off + sq);
#pragma unroll
        for (int s = 0; s < 6; s++) stg128(ap + s * 512, a[s]);
    };
    const uint32_t own_bar = 4 + wgi, next_bar = 4 + (wgi == NCONS - 1 ? 0 : wgi + 1);
    for (;;) {
        if (jt >= fast_from) {
            uint32_t hs2[12] = {}, hs3[12] = {};
            const uint32_t step = wk.dir * (NCONS * IMG_W * CH * 2);
            int second = wk.nB;
#pragma unroll 1
            for (;;) {
#pragma unroll 1
                while (turn != turn_end) {
                    uint32_t a[6][4], d0[24], d1[24], unused[24];
                    mbar_wait(bo, turn >> 1 & 1);
                    load_tile(a, a_addr + so);
                    layer_norm(a, ds.ones, [&]() { named_bar(own_bar, 256); });
                    wg_fence();
                    gemm1_chunk<0>(d0, a, ds, 0);
                    wg_commit();
                    gemm1_chunk<96>(d1, a, ds, 0);
                    wg_commit();
                    wg_wait<1>();
                    gelu_sq<false, 0, 1>(d0, unused, sq, 0);
                    gelu_sq<false, 1, 2>(d0, unused, sq, 0);
                    store_at(a, off);
                    gelu_sq<false, 2, 3>(d0, unused, sq, 0);
                    if (elect_one()) mbar_arrive(bo + (BAR_E - BAR_A));
                    wg_fence();
                    gemm1_chunk<192>(d0, a, ds, zero);
                    wg_commit();
                    named_arrive(next_bar, 256);
                    wg_wait<1>();
                    gelu_sq<false, 0, 1>(d1, unused, sq + SQC, 0);
                    gelu_sq<false, 1, 3>(d1, unused, sq + SQC, 0);
                    wg_fence();
                    gemm1_chunk<288>(d1, a, ds, zero);
                    wg_commit();
                    wg_wait<1>();
                    gelu_sq_reg(d0, hs2);
                    anchor(sq, hs2[8], hs2[9], hs2[10], hs2[11]);
                    wg_wait<0>();
                    gelu_sq_reg(d1, hs3);
                    so = so_sum - so;
                    bo = bo_sum - bo;
                    off += step;
                    turn++;
                }
                if (!second) break;
                const int j = ntiles - second + (rank + second + 2) % NCONS;
                second = 0;
                set_run(j, nrest, j + 4);
            }
            jt = nrest + rank;
            cur.slot = (bo - bar_a) >> 5;
            cur.par = turn >> 1 & 1;
#pragma unroll
            for (int k = 0; k < 3; k++) {
                sts128(sq + SQ_HALF + k * SQ_ROW, hs2[4 * k], hs2[4 * k + 1], hs2[4 * k + 2], hs2[4 * k + 3]);
                sts128(sq + SQ_HALF + SQC + k * SQ_ROW, hs3[4 * k], hs3[4 * k + 1], hs3[4 * k + 2], hs3[4 * k + 3]);
            }
        }
        const bool last = jt >= nrest;
        here = tile_offset(wk.tile(jt));
        if (last) {
            const uint32_t next = ldsi(sb + SM_TILES + rank * 4);
            if (elect_one()) {
                prefetch_l2(reinterpret_cast<const char*>(x) + here + w4 * WARP_BYTES, WARP_BYTES);
                if (rank == ORDER_P - 1) prefetch_l2(reinterpret_cast<const char*>(out) + next + w4 * WARP_BYTES, WARP_BYTES);
            }
        }
        uint32_t a[6][4], d0[24], d1[24], d3[24], k0[24];
        mbar_wait_once(bar_a + cur.slot * 32, cur.par);
        load_tile(a, a_addr + cur.slot * SLOT_BYTES);
        layer_norm(a, ds.ones, [&]() { if (jt >= wk.lent && wgi >= 0) named_bar(own_bar, 256); });
        if (!last) {
            store_at(a, here + w4 * WARP_BYTES - sq_warp);
            __syncwarp();
            if (elect_one()) mbar_arrive(bar_e + cur.slot * 32);
            if (jt < wk.lent) {
                jt += LENT;
                cur.advance(LENT);
                continue;
            }
        }
        wg_fence();
        gemm1_chunk<0>(d0, a, ds, 0);
        wg_commit();
        gemm1_chunk<96>(d1, a, ds, 0);
        wg_commit();
        const uint32_t scale2 = square_scale(lane_id());
        wg_wait<1>();
        gelu_sq<true>(d0, k0, sq, scale2);
        if (last) {
#pragma unroll
            for (int q = 0; q < 6; q++)
                sts128(sb + SM_RING + cur.slot * SLOT_BYTES + w4 * REGION_BYTES - sq_warp + sq + q * 512, k0[4 * q], k0[4 * q + 1], k0[4 * q + 2], k0[4 * q + 3]);
        }
        wg_fence();
        gemm1_chunk<192>(d0, a, ds, zero);
        wg_commit();
        if (jt + 2 < ntiles) named_arrive(next_bar, 256);
        wg_wait<1>();
        gelu_sq<true>(d1, k1, sq + SQC, scale2);
        wg_fence();
        gemm1_chunk<288>(d3, a, ds, 0);
        wg_commit();
        wg_wait<1>();
        gelu_sq<true>(d0, k2, sq + sq_upper, scale2);
        wg_wait<0>();
        gelu_sq<true>(d3, k3, sq + sq_upper + SQC, scale2);
        if (last) break;
        cur.advance(NCONS + ((jt < wk.nA && jt + NCONS >= wk.nA) ? 2 : 0));
        jt += NCONS;
    }
    const uint32_t lane = lane_id();
    uint32_t next_off = opaque_uniform(ldsi(sb + SM_TILES + rank * 4));
    const uint32_t s_fac = sb + SM_RING + spare * SLOT_BYTES + SQ_HALF;
    uint32_t inv_rho2;
    {
        if (rank == 0) {
            const int g = lane >> 2, t = lane & 3, i0 = w4 * 32 + lane;
            const bool leader = i0 == 0;
            const uint32_t pick = (g & 1) == (t & 1) ? (g & 2 ? 0x3c000000u : 0x00003c00u) : 0;
            const int be = bound_exp(max_w1(lane));
            const float to_fixed = pow2i(sum_exp(be) - 2 * square_exp(be));
            const uint32_t two_rows = sb + (w4 * 3 + (lane >> 3 & 1)) * SQ_ROW + ((lane >> 4) * 8 + (lane & 7)) * 16;
            const uint32_t third_row = sb + (w4 * 3 + 2) * SQ_ROW + lane * 16;
            unsigned short gam_raw[3];
            float rmax[3], f[3][4] = {};
            float2 bpair = make_float2(0.f, 0.f);
#pragma unroll 1
            for (int i = 0; i < 4; i++) {
                if (i == 1 && leader) {
                    spin_until(&sc->prep, (ldsi(s_red + RED_LAUNCH) + 1) * (W2_GROUPS * 2));
                    asm volatile("fence.proxy.async.global;" ::: "memory");
                    mbar_expect_tx(sb + BAR_W, 6 * SQ_HALF);
                }
                __syncwarp();
                named_bar(2, 128);
                if (i && leader) {
                    fence_async();
                    bulk_load(sb + SM_W2 + (i - 1) * 2 * SQ_HALF, reinterpret_cast<const char*>(sc->w2h) + (i - 1) * 2 * SQ_HALF, 2 * SQ_HALF, sb + BAR_W);
                }
                if (i == 1) {
#pragma unroll
                    for (int m = 0; m < 3; m++) {
                        asm volatile("ld.global.nc.u16 %0, [%1];" : "=h"(gam_raw[m]) : "l"(gamma + i0 + 128 * m) : "memory");
                        asm volatile("ld.global.cg.f32 %0, [%1];" : "=f"(rmax[m]) : "l"(&sc->w2max[i0 + 128 * m]) : "memory");
                    }
                    if (i0 < 96)
                        asm volatile("ld.global.cg.v2.f32 {%0, %1}, [%2];" : "=f"(bpair.x), "=f"(bpair.y)
                                     : "l"(&sc->bias[32 * (i0 % 24 >> 3) + 8 * (i0 / 24) + (i0 % 24 & 6)]) : "memory");
                }
                __syncwarp();
                const uint32_t from = i < NCONS ? SM_SQ + i * 2 * SQ_HALF : w4 < 2 ? SM_RING + spare * SLOT_BYTES : SM_RING + spare2 * SLOT_BYTES - SQ_HALF;
                if (i) named_bar(12 + i, 256);
#pragma unroll
                for (int r = 0; r < 12; r++) {
                    uint32_t u[4];
                    ldsm4_t(u, from + (r % 3 == 2 ? third_row + r / 3 * 512 : two_rows + (r / 3 * 2 + r % 3) * 256));
                    asm volatile("mma.sync.aligned.m16n8k16.row.col.f32.f16.f16.f32 {%0, %1, %2, %3}, {%4, %5, %6, %7}, {%8, %8}, {%0, %1, %2, %3};"
                                 : "+f"(f[r % 3][0]), "+f"(f[r % 3][1]), "+f"(f[r % 3][2]), "+f"(f[r % 3][3])
                                 : "r"(u[0]), "r"(u[1]), "r"(u[2]), "r"(u[3]), "r"(pick));
                }
            }
            unsigned long long* dst = sc->sum(96 * w4 + 8 * (g >> 1) + 2 * (t & 1) + (g & 1));
#pragma unroll
            for (int r = 0; r < 3; r++) {
                const float tot = r < 2 ? (t < 2 ? f[0][r & 1] + f[1][r & 1] : f[0][r + 2 & 3] + f[1][r + 2 & 3]) : (t < 2 ? f[2][0] + f[2][2] : f[2][1] + f[2][3]);
                atomicAdd(dst + (r < 2 ? (t >> 1) * 8 + r : 16 + (t >> 1)) * 32, __float2ull_rn(fminf(tot * to_fixed, 0x1p47f)) << 8 | 1);
            }
            PROF(2);
            float base[3], slope[3], reach[3];
            const float w1max = max_w1(lane);
            const float gbound = fmaxf(2.f * KZ * 9.7979590f * 192.f * w1max, 1.f) * 19.5959180f * INV_2KZ;
            const unsigned fixed = __reduce_max_sync(~0u, __float_as_uint(fmaf(gbound, fmaxf(fmaxf(rmax[0], rmax[1]), rmax[2]), fmaxf(fabsf(bpair.x), fabsf(bpair.y)))));
            if (lane == 0) sts32(s_red + 96 + w4 * 4, fixed);
#pragma unroll
            for (int m = 0; m < 3; m++) {
                base[m] = rmax[m] > 0.f ? pow2i(-row_exp(rmax[m])) * INV_2KZ : 0.f;
                slope[m] = base[m] * bf_lo(gam_raw[m]);
                reach[m] = fabsf(bf_lo(gam_raw[m])) * rmax[m] * gbound;
            }
            const float to_square = pow2i(-sum_exp(bound_exp(w1max))) * (INV_2KZ * INV_2KZ / 256);
#pragma unroll
            for (int m = 0; m < 3; m++) anchor(sq, __float_as_uint(base[m]), __float_as_uint(slope[m]), __float_as_uint(reach[m]), __float_as_uint(to_square));
            const unsigned epoch = ldsi(s_red + RED_LAUNCH);
            const uint32_t own_sum = (i0 >> 2) * 256 + (i0 & 3) * 8, own_fac = s_fac + i0 * 2;
            auto peek = [&](const void* p) {
                unsigned long long v;
                asm volatile("ld.relaxed.gpu.global.u64 %0, [%1];" : "=l"(v) : "l"(p) : "memory");
                return v;
            };
            const char* mine = reinterpret_cast<const char*>(sc->sums) + own_sum;
            unsigned n = 0;
            while (((unsigned)peek(sc->sum((blockIdx.x * 4 + w4) % (EX / 4) * 4)) & 255u) != gridDim.x)
                if (++n > SPIN_LIMIT) __trap();
            unsigned long long sum[3];
            for (;;) {
                bool all = true;
#pragma unroll
                for (int m = 0; m < 3; m++) {
                    sum[m] = peek(mine + m * (32 * 256));
                    all &= ((unsigned)sum[m] & 255u) == gridDim.x;
                }
                if (__all_sync(~0u, all)) break;
                if (++n > SPIN_LIMIT) __trap();
            }
            PROF(3);
            float gx[3];
#pragma unroll
            for (int m = 0; m < 3; m++) asm("sqrt.approx.ftz.f32 %0, %1;" : "=f"(gx[m]) : "f"(fmaf(__ull2float_rn(sum[m]), to_square, 1e-6f)));
            float tot = gx[0] + gx[1] + gx[2];
#pragma unroll
            for (int o = 16; o >= 1; o >>= 1) tot += __shfl_xor_sync(~0u, tot, o);
            const unsigned vwarp = __reduce_max_sync(~0u, __float_as_uint(fmaxf(fmaxf(reach[0] * gx[0], reach[1] * gx[1]), reach[2] * gx[2])));
            if (lane == 0) { sts32(s_red + 64 + w4 * 4, __float_as_uint(tot)); sts32(s_red + 80 + w4 * 4, vwarp); }
            named_bar(2, 128);
            uint32_t u[4], v[4], w[4];
            lds128(u[0], u[1], u[2], u[3], s_red + 64);
            lds128(v[0], v[1], v[2], v[3], s_red + 80);
            lds128(w[0], w[1], w[2], w[3], s_red + 96);
            tot = (__uint_as_float(u[0]) + __uint_as_float(u[1])) + (__uint_as_float(u[2]) + __uint_as_float(u[3]));
            const float vmax = __uint_as_float(max(max(v[0], v[1]), max(v[2], v[3]))), fmax2 = __uint_as_float(max(max(w[0], w[1]), max(w[2], w[3])));
            float inv_mean;
            asm("rcp.approx.ftz.f32 %0, %1;" : "=f"(inv_mean) : "f"(fmaf(tot, 1.f / EX, 1e-6f)));
            const int rho_e = 14 - ilog2f(fmaf(vmax, inv_mean, 2.f * fmax2));
            const float rho = pow2i(rho_e), inv_rho = pow2i(-rho_e);
            inv_rho2 = pack_bf2(inv_rho, inv_rho);
#pragma unroll
            for (int m = 0; m < 3; m++) {
                const float f = fmaf(slope[m] * gx[m], inv_mean, base[m]) * rho;
                asm volatile("st.shared.u16 [%0], %1;" ::"r"(own_fac + 256 * m), "h"((unsigned short)pack_h2(f, 0.f)) : "memory");
            }
            if (i0 < 96) sts32(sb + SM_BIASH + i0 * 4, pack_h2(bpair.x * rho, bpair.y * rho));
            if (i0 == 96) sts32(s_red + RED_INV_RHO, inv_rho2);
            named_arrive(12, NTHREADS);
            if (blockIdx.x == 0 && leader) { sc->launch = epoch + 1; sc->job = 0; }
            if (wk.lent) spin_until(&sc->lent_out, (epoch + 1) * 32 * LENT * sp.lenders);
        } else {
            named_arrive(12 + rank, 256);
            if (rank == NCONS && (unsigned)(ldsi(s_red + RED_JOB) - W2_GROUPS / 2) < 8 * LENT * sp.lenders) signal(&sc->lent_out);
            const int rw = rank * 4 - 4 + w4;
            const uint32_t row = sb + SM_W2 + rw * 512 + lane * 16;
            uint32_t u[W2_EARLY][4], f2[4];
            mbar_wait_once(sb + BAR_W, 1);
#pragma unroll
            for (int nb = 0; nb < W2_EARLY; nb++) {
                lds128(u[nb][0], u[nb][1], u[nb][2], u[nb][3], row + nb * 6144);
            }
            named_bar(12, NTHREADS);
            PROF(3);
            lds128(f2[0], f2[1], f2[2], f2[3], s_fac + rw * 64 + (lane >> 3) * 16);
            lds32(inv_rho2, s_red + RED_INV_RHO);
#pragma unroll
            for (int nb = 0; nb < 12; nb++) {
                uint32_t v[4];
                if (nb < W2_EARLY) { v[0] = u[nb % W2_EARLY][0]; v[1] = u[nb % W2_EARLY][1]; v[2] = u[nb % W2_EARLY][2]; v[3] = u[nb % W2_EARLY][3]; }
                else lds128(v[0], v[1], v[2], v[3], row + nb * 6144);
                sts128(row + nb * 6144, h_mul(v[0], f2[0]), h_mul(v[1], f2[1]), h_mul(v[2], f2[2]), h_mul(v[3], f2[3]));
            }
            fence_async();
            named_arrive(8, NTHREADS);
        }
    }
    uint32_t a[6][4], acc[24], rpar = 0, tile_off = here;
    const uint32_t bias_addr = sb + SM_BIASH + (lane & 3) * 96, lane16 = lane * 16, lane_off = ((lane >> 2) * CH + 8 * (lane & 3)) * 2;
    const uint32_t stage = sb + SM_RING + (spare + rank) % NSLOT * SLOT_BYTES + w4 * WARP_BYTES, bar_r = sb + BAR_R + warp_id * 8;
    auto load_bias = [&]() {
#pragma unroll
        for (int q = 0; q < 6; q++) lds128(acc[4 * q], acc[4 * q + 1], acc[4 * q + 2], acc[4 * q + 3], bias_addr + q * 16);
    };
    auto load_frags = [&]() {
#pragma unroll
        for (int s = 0; s < 6; s++) ldg128(a[s], reinterpret_cast<const char*>(out) + next_off + w4 * WARP_BYTES + lane16 + s * 512);
    };
    auto stage_x = [&]() {
        if (elect_one()) {
            mbar_expect_tx(bar_r, WARP_BYTES);
            bulk_load_stream(stage, reinterpret_cast<const char*>(x) + tile_off + w4 * WARP_BYTES, WARP_BYTES, bar_r);
        }
    };
    {
        named_bar(8 + rank, rank ? 256 : NTHREADS);
        if (rank == 0) PROF(4);
        load_bias();
        pin(k1); pin(k2); pin(k3);
        wg_fence();
        gemm2_chunk<288>(acc, k3, ds);
        wg_commit();
        gemm2_chunk<96>(acc, k1, ds);
        wg_commit();
        gemm2_chunk<192>(acc, k2, ds);
        wg_commit();
        stage_x();
        wg_wait<2>();
        uint32_t k0[24];
#pragma unroll
        for (int q = 0; q < 6; q++)
            lds128(k0[4 * q], k0[4 * q + 1], k0[4 * q + 2], k0[4 * q + 3], sb + SM_RING + cur.slot * SLOT_BYTES + w4 * REGION_BYTES + lane16 + q * 512);
        pin(k0);
        wg_fence();
        gemm2_chunk<0>(acc, k0, ds);
        wg_commit();
        if (rank < NCONS) named_arrive(9 + rank, 256);
        wg_wait<2>();
        load_frags();
        if (lane16 == 0) mbar_arrive(sb + BAR_PIN);
        mbar_wait(bar_r, rpar);
        wg_wait<0>();
    }
    auto lent = [&](uint32_t entry) { return &sc->lent[((wk.index * LENT + (entry & 3) - 1) * 4 + w4) * (24 * 32)]; };
    for (jt = rank - 4; jt < nrest; jt += 4) {
        if (jt >= zero) {
        tile_off = next_off;
        lds32(next_off, sb + SM_TILES + (jt + 4) * 4);
        if (tile_off & 3) {
            const uint4* src = lent(tile_off) + lane;
            tile_off &= ~3u;
            next_off = __shfl_sync(~0u, next_off, 0);
            stage_x();
            if (elect_one()) prefetch_l2(reinterpret_cast<const char*>(out) + next_off + w4 * WARP_BYTES, WARP_BYTES);
            load_bias();
#pragma unroll 1
            for (int half = 0; half < 2; half++, src += 12 * 32) {
                uint32_t gl[48];
#pragma unroll
                for (int s = 0; s < 12; s++) ldg128(reinterpret_cast<uint32_t (&)[4]>(gl[4 * s]), src + s * 32);
                if (!half) {
                    named_bar(4 + rank, 256);
                    named_arrive(4 + ((rank + 1) & 3), 256);
                }
                pin(gl);
                wg_fence();
#pragma unroll
                for (int s = 0; s < 12; s++) wgmma(acc, gl[4 * s], gl[4 * s + 1], gl[4 * s + 2], gl[4 * s + 3], ds.w2[12 * half + s], 1);
                wg_commit();
                wg_wait<0>();
            }
            load_frags();
            mbar_wait(bar_r, rpar);
        } else {
            uint32_t d0[12], d1[12], g0[12], g1[12];
            next_off = __shfl_sync(~0u, next_off, 0);
            const bool more = jt + 4 < nrest && !(next_off & 3);
            load_bias();
            wg_fence();
            gemm1_chunk<0>(d0, a, ds, 0);
            wg_commit();
            if (jt && jt + 1 < nrest) named_bar(4 + rank, 256);
            gemm1_chunk<48>(d1, a, ds, 0);
            wg_commit();
            wg_wait<1>();
#define CNX_STEP(C, D, G)                                                   \
    gelu_to(G, D);                                                          \
    wg_fence();                                                             \
    if (C < 6) gemm1_chunk<48 * (C < 6 ? C + 2 : 0)>(D, a, ds, zero);      \
    gemm2_chunk<48 * C>(acc, G, ds);                                       \
    wg_commit();                                                            \
    if (C == 1 && jt + 2 < nrest) named_arrive(4 + ((rank + 1) & 3), 256); \
    wg_wait<(C < 7 ? 1 : 0)>();
            CNX_STEP(0, d0, g0)
            stage_x();
            if (elect_one()) {
                if (more) prefetch_l2(reinterpret_cast<const char*>(out) + next_off + w4 * WARP_BYTES, WARP_BYTES);
                else if (next_off & 3) prefetch_l2(lent(next_off), 24 * 32 * 16);
            }
            CNX_STEP(1, d1, g1)
            CNX_STEP(2, d0, g0)
            CNX_STEP(3, d1, g1)
            CNX_STEP(4, d0, g0)
            CNX_STEP(5, d1, g1)
            CNX_STEP(6, d0, g0)
#pragma unroll
            for (int s = 0; s < 6; s++) ldg128_if(more, a[s], reinterpret_cast<const char*>(out) + next_off + w4 * WARP_BYTES + lane16 + s * 512);
            if (lane16 == 0) mbar_arrive(sb + BAR_PIN);
            mbar_wait(bar_r, rpar);
            CNX_STEP(7, d1, g1)
#undef CNX_STEP
        }
        }
        {
            pin(acc);
            rpar ^= 1;
            uint4* op = reinterpret_cast<uint4*>(reinterpret_cast<char*>(out) + tile_off + w4 * WARP_BYTES + lane_off);
#pragma unroll
            for (int h = 0; h < 2; h++)
#pragma unroll
                for (int m = 0; m < 3; m++) {
                    uint32_t xin[4], o[4];
                    lds128(xin[0], xin[1], xin[2], xin[3], stage + lane_off + h * 1536 + m * 64);
#pragma unroll
                    for (int q = 0; q < 4; q++) {
                        const uint32_t v = acc[2 * (4 * m + q) + h];
                        o[q] = bf_fma(pack_bf2(h_lo(v), h_hi(v)), inv_rho2, xin[q]);
                    }
                    __stcs(op + h * 96 + m * 4, make_uint4(o[0], o[1], o[2], o[3]));
                }
            __syncwarp();
        }
    }
    PROF(5);
}

}

typedef CUresult (*EncodeTiledFn)(CUtensorMap*, CUtensorMapDataType, cuuint32_t, void*, const cuuint64_t*, const cuuint64_t*,
                                  const cuuint32_t*, const cuuint32_t*, CUtensorMapInterleave, CUtensorMapSwizzle,
                                  CUtensorMapL2promotion, CUtensorMapFloatOOBfill);

extern "C" void kernel_launch(void* const* d_in, const int* in_sizes, int n_in, void* d_out, int out_size) {
    using namespace cnx;
    static EncodeTiledFn encode = nullptr;
    static int num_sms = 0;
    static Scratch* scratch = nullptr;
    if (!encode) {
        void* fn = nullptr;
        cudaDriverEntryPointQueryResult qr;
        cudaGetDriverEntryPoint("cuTensorMapEncodeTiled", &fn, cudaEnableDefault, &qr);
        encode = (EncodeTiledFn)fn;
        cudaGetSymbolAddress((void**)&scratch, g_scratch);
        int dev = 0;
        cudaGetDevice(&dev);
        cudaDeviceGetAttribute(&num_sms, cudaDevAttrMultiProcessorCount, dev);
        if (num_sms > MAX_CTAS) num_sms = MAX_CTAS;
        cudaFuncSetAttribute(block_kernel, cudaFuncAttributeMaxDynamicSharedMemorySize, SM_TOTAL);
    }
    CUtensorMap tm;
    cuuint64_t dims[3] = {(cuuint64_t)CH, (cuuint64_t)IMG_W, (cuuint64_t)IMG_H};
    cuuint64_t strides[2] = {(cuuint64_t)CH * 2, (cuuint64_t)CH * 2 * IMG_W};
    cuuint32_t box[3] = {(cuuint32_t)CH, (cuuint32_t)REGION_PX, 1};
    cuuint32_t estr[3] = {1, 1, 1};
    encode(&tm, CU_TENSOR_MAP_DATA_TYPE_BFLOAT16, 3, d_in[0], dims, strides, box, estr, CU_TENSOR_MAP_INTERLEAVE_NONE,
           CU_TENSOR_MAP_SWIZZLE_NONE, CU_TENSOR_MAP_L2_PROMOTION_L2_128B, CU_TENSOR_MAP_FLOAT_OOB_FILL_NONE);
    Params pm = {};
    Descs& ds = pm.ds;
    for (int c = 0; c < 8; c++)
        for (int k = 0; k < 6; k++) ds.w1[c][k] = make_desc(SB + SM_W1 + c * 6 * 1536 + k * 256, 128, 1536);
    for (int k = 0; k < 24; k++) ds.w2[k] = make_desc(SB + SM_W2 + k * 256, 128, 6144);
    ds.ones = make_desc(SB + SM_ONES, 0, 0);
    CUtensorMap tw;
    cuuint64_t wdims[2] = {(cuuint64_t)EX, (cuuint64_t)CH};
    cuuint64_t wstrides[1] = {(cuuint64_t)EX * 2};
    cuuint32_t wbox[2] = {64, (cuuint32_t)CH};
    encode(&tw, CU_TENSOR_MAP_DATA_TYPE_BFLOAT16, 2, d_in[2], wdims, wstrides, wbox, estr, CU_TENSOR_MAP_INTERLEAVE_NONE,
           CU_TENSOR_MAP_SWIZZLE_128B, CU_TENSOR_MAP_L2_PROMOTION_L2_128B, CU_TENSOR_MAP_FLOAT_OOB_FILL_NONE);
    Split& sp = pm.sp;
    sp = {NTILES / num_sms, NTILES % num_sms, 1, 1 << 16, 0, {}};
    if (sp.per_cta + 9 > MAX_ROWS) return;
    if (sp.extra && sp.extra * (8 * LENT + 1) + W2_GROUPS / 2 <= num_sms && sp.per_cta >= 5 * LENT + 8) {
        sp.period = num_sms / sp.extra;
        sp.inv_period = 65535 / sp.period + 1;
        sp.lenders = sp.extra;
        for (int l = 0; l < sp.extra; l++) {
            const Work w = get_work((l + 1) * sp.period - sp.period / 2 - 1, sp);
            for (int e = 0; e < LENT; e++) sp.lent_off[l * LENT + e] = tile_offset(w.tile(e));
            if (w.nA < 2 * LENT) sp.lenders = 0;
        }
    }
    pm.x = (const __nv_bfloat16*)d_in[0];
    pm.dw = (const __nv_bfloat16*)d_in[1];
    pm.w2 = (const __nv_bfloat16*)d_in[3];
    pm.gamma = (const __nv_bfloat16*)d_in[4];
    pm.beta = (const __nv_bfloat16*)d_in[5];
    pm.out = (__nv_bfloat16*)d_out;
    pm.sc = scratch;
    block_kernel<<<num_sms, NTHREADS, SM_TOTAL>>>(tm, tw, pm);
}
```

```cpp
#include <cuda_runtime.h>
#include <cuda_bf16.h>
#include <cuda_fp16.h>
#include <cuda.h>
#include <stdint.h>

namespace cnx {

constexpr int IMG_H = 512, IMG_W = 512, CH = 96, EX = 384;
constexpr int TILE_W = 64;
constexpr int NTILES = (IMG_W / TILE_W) * IMG_H;
constexpr int NSLOT = 6;
constexpr int REGION_PX = 18;
constexpr int REGION_BYTES = REGION_PX * CH * 2;
constexpr int SLOT_BYTES = 4 * REGION_BYTES;
constexpr int A_LBO = 144, A_SBO = 12 * A_LBO;
constexpr int PREFETCH_ROWS = 3;
constexpr int NCONS = 3;
constexpr int CONS_THREADS = 128 * NCONS;
constexpr int NTHREADS = 128 + CONS_THREADS;
constexpr int MAX_ROWS = 52;
constexpr int TILE_BYTES = TILE_W * CH * 2, WARP_BYTES = TILE_BYTES / 4;
constexpr int ORDER_P = 3;
constexpr int W2_EARLY = 10;
static_assert(MAX_ROWS <= 128, "one table entry per producer thread");
static_assert(2 * A_SBO == REGION_BYTES && REGION_BYTES % 128 == 0, "region layout");

constexpr uint32_t SB = 1024;
constexpr int SM_W1 = 0;
constexpr int SM_W2 = SM_W1 + CH * EX * 2;
constexpr int SM_RING = SM_W2 + CH * EX * 2;
constexpr int SM_BIASH = SM_RING + NSLOT * SLOT_BYTES;
constexpr int SM_RED = SM_BIASH + 384;
constexpr int RED_MAX = 0, RED_LAUNCH = 48, RED_INV_RHO = 52, RED_JOB = 56;
constexpr int SM_TILES = SM_RED + 256;
constexpr int SM_ONES = SM_TILES + MAX_ROWS * 4;
constexpr int SM_BAR = SM_ONES + 128;
constexpr int BAR_X = SM_BAR;
constexpr int BAR_A = BAR_X + NSLOT * 4 * 8;
constexpr int BAR_E = BAR_A + NSLOT * 4 * 8;
constexpr int BAR_PIN = BAR_E + NSLOT * 4 * 8;
constexpr int BAR_W = BAR_PIN + 8;
constexpr int BAR_F = BAR_W + 6 * 8;
constexpr int BAR_R = BAR_F + 8;
constexpr int SM_TOTAL = BAR_R + 16 * 8;
constexpr int SM_FILTER = SM_RING + (NSLOT - 1) * SLOT_BYTES + 9 * 128;
constexpr int SM_SQ = SM_W2;
constexpr int SQ_ROW = 128 * 16, SQ_HALF = 6 * SQ_ROW;
static_assert(SM_ONES % 16 == 0 && SM_TOTAL <= 232448, "shared memory budget");

constexpr float KZ = 0.3292034911525734f;
constexpr uint32_t GELU_C2 = 0x40d940d9u;
constexpr float INV_2KZ = 0.5f / KZ;
constexpr uint32_t CONV_SCALE2 = 0x2f802f80u;
constexpr unsigned SPIN_LIMIT = 1u << 19;

constexpr int MAX_CTAS = 170;
constexpr int W2_GROUPS = EX / 8;
constexpr int LENT = 3, MAX_LENDERS = MAX_CTAS / (8 * LENT + 1);
struct Scratch {
    uint32_t w2h[EX * CH / 2];
    float w2max[EX];
    float bias[CH + 32];
    unsigned long long sums[EX / 4][32];
    __device__ __forceinline__ unsigned long long* sum(int e) { return &sums[e >> 2][e & 3]; }
    uint4 lent[MAX_LENDERS * LENT * 8 * 4 * 3 * 32];
    unsigned launch, pad0[31], early, pad1[31], prep, pad2[31], lent_out, pad3[31];
    unsigned job;
};
__device__ __align__(128) Scratch g_scratch;

#define PROF(k)

__device__ __forceinline__ uint32_t smem_u32(const void* p) { return (uint32_t)__cvta_generic_to_shared(p); }
__device__ __forceinline__ void mbar_init(uint32_t bar, uint32_t cnt) {
    asm volatile("mbarrier.init.shared::cta.b64 [%0], %1;" ::"r"(bar), "r"(cnt) : "memory");
}
__device__ __forceinline__ void mbar_arrive(uint32_t bar) {
    asm volatile("mbarrier.arrive.shared::cta.b64 _, [%0];" ::"r"(bar) : "memory");
}
__device__ __forceinline__ void mbar_expect_tx(uint32_t bar, uint32_t bytes) {
    asm volatile("mbarrier.arrive.expect_tx.shared::cta.b64 _, [%0], %1;" ::"r"(bar), "r"(bytes) : "memory");
}
__device__ __forceinline__ bool mbar_try(uint32_t bar, uint32_t par) {
    uint32_t ok;
    asm volatile("{\n.reg .pred p;\nmbarrier.try_wait.parity.shared::cta.b64 p, [%1], %2;\nselp.u32 %0, 1, 0, p;\n}\n"
                 : "=r"(ok) : "r"(bar), "r"(par) : "memory");
    return ok != 0;
}
__device__ __forceinline__ void mbar_wait(uint32_t bar, uint32_t par) {
    unsigned n = 0;
    while (!mbar_try(bar, par)) {
        if (++n > SPIN_LIMIT) __trap();
    }
}
__device__ __forceinline__ void mbar_wait_once(uint32_t bar, uint32_t par) {
    unsigned n = 0;
    bool ok;
#pragma unroll 1
    do {
        ok = mbar_try(bar, par);
        if (++n > SPIN_LIMIT) __trap();
    } while (!ok);
}
__device__ __forceinline__ bool elect_one() {
    uint32_t ok;
    asm volatile("{\n.reg .pred p;\nelect.sync _|p, 0xffffffff;\nselp.u32 %0, 1, 0, p;\n}\n" : "=r"(ok));
    return ok != 0;
}
__device__ __forceinline__ uint32_t opaque(uint32_t v) { return __shfl_sync(~0u, v, threadIdx.x & 31); }
__device__ __forceinline__ uint32_t opaque_uniform(uint32_t v) { return __shfl_sync(~0u, v, 0); }
__device__ __forceinline__ uint32_t lane_id() { uint32_t v; asm volatile("mov.u32 %0, %%laneid;" : "=r"(v)); return v; }
__device__ __forceinline__ void named_bar(int id, int n) { asm volatile("bar.sync %0, %1;" ::"r"(id), "r"(n) : "memory"); }
__device__ __forceinline__ void named_arrive(int id, int n) { asm volatile("bar.arrive %0, %1;" ::"r"(id), "r"(n) : "memory"); }
__device__ __forceinline__ void fence_async() { asm volatile("fence.proxy.async.shared::cta;" ::: "memory"); }
constexpr uint64_t EVICT_FIRST = 0x12F0000000000000ull;
__device__ __forceinline__ void tma_row(uint32_t dst, const CUtensorMap* tm, uint32_t bar, int x, int y) {
    asm volatile("cp.async.bulk.tensor.3d.shared::cluster.global.mbarrier::complete_tx::bytes.L2::cache_hint [%0], [%1, {%3, %4, %5}], [%2], %6;"
                 ::"r"(dst), "l"(tm), "r"(bar), "r"(0), "r"(x), "r"(y), "l"(EVICT_FIRST) : "memory");
}
__device__ __forceinline__ void bulk_load_stream(uint32_t dst, const void* src, uint32_t bytes, uint32_t bar) {
    asm volatile("cp.async.bulk.shared::cluster.global.mbarrier::complete_tx::bytes.L2::cache_hint [%0], [%1], %2, [%3], %4;"
                 ::"r"(dst), "l"(src), "r"(bytes), "r"(bar), "l"(EVICT_FIRST) : "memory");
}
__device__ __forceinline__ void prefetch_l2(const void* src, uint32_t bytes) {
    asm volatile("cp.async.bulk.prefetch.L2.global [%0], %1;" ::"l"(src), "r"(bytes) : "memory");
}
__device__ __forceinline__ void tma_2d(uint32_t dst, const CUtensorMap* tm, uint32_t bar, int x, int y) {
    asm volatile("cp.async.bulk.tensor.2d.shared::cluster.global.mbarrier::complete_tx::bytes [%0], [%1, {%3, %4}], [%2];"
                 ::"r"(dst), "l"(tm), "r"(bar), "r"(x), "r"(y) : "memory");
}
__device__ __forceinline__ void bulk_load(uint32_t dst, const void* src, uint32_t bytes, uint32_t bar) {
    asm volatile("cp.async.bulk.shared::cluster.global.mbarrier::complete_tx::bytes [%0], [%1], %2, [%3];"
                 ::"r"(dst), "l"(src), "r"(bytes), "r"(bar) : "memory");
}
__device__ __forceinline__ void wg_fence() { asm volatile("wgmma.fence.sync.aligned;" ::: "memory"); }
__device__ __forceinline__ void wg_commit() { asm volatile("wgmma.commit_group.sync.aligned;" ::: "memory"); }
template <int N> __device__ __forceinline__ void wg_wait() { asm volatile("wgmma.wait_group.sync.aligned %0;" ::"n"(N) : "memory"); }
template <int N> __device__ __forceinline__ void pin(uint32_t (&d)[N]) {
#pragma unroll
    for (int q = 0; q < N; q++) asm volatile("" : "+r"(d[q])::"memory");
}
__device__ __forceinline__ void stg128(void* p, const uint32_t (&v)[4]) {
    asm volatile("st.global.v4.u32 [%0], {%1, %2, %3, %4};" ::"l"(p), "r"(v[0]), "r"(v[1]), "r"(v[2]), "r"(v[3]) : "memory");
}
__device__ __forceinline__ void ldg128(uint32_t (&v)[4], const void* p) {
    asm volatile("ld.global.L1::no_allocate.v4.u32 {%0, %1, %2, %3}, [%4];" : "=r"(v[0]), "=r"(v[1]), "=r"(v[2]), "=r"(v[3]) : "l"(p) : "memory");
}
__device__ __forceinline__ void ldg128_if(bool on, uint32_t (&v)[4], const void* p) {
    asm volatile("{\n.reg .pred p;\nsetp.ne.b32 p, %5, 0;\n@p ld.global.L1::no_allocate.v4.u32 {%0, %1, %2, %3}, [%4];\n}\n"
                 : "+r"(v[0]), "+r"(v[1]), "+r"(v[2]), "+r"(v[3]) : "l"(p), "r"((int)on) : "memory");
}
__host__ __device__ constexpr uint64_t make_desc(uint32_t addr, uint32_t lbo, uint32_t sbo) {
    return (uint64_t)((addr & 0x3FFFF) >> 4) | ((uint64_t)(lbo >> 4) << 16) | ((uint64_t)(sbo >> 4) << 32);
}
__device__ __forceinline__ void wgmma(uint32_t (&d)[12], uint32_t a0, uint32_t a1, uint32_t a2, uint32_t a3, uint64_t db, int acc) {
    asm volatile("{\n.reg .pred p;\nsetp.ne.b32 p, %17, 0;\n"
                 "wgmma.mma_async.sync.aligned.m64n48k16.f16.f16.f16 "
                 "{%0, %1, %2, %3, %4, %5, %6, %7, %8, %9, %10, %11}, "
                 "{%12, %13, %14, %15}, %16, p, 1, 1, 0;\n}\n"
                 : "+r"(d[0]), "+r"(d[1]), "+r"(d[2]), "+r"(d[3]), "+r"(d[4]), "+r"(d[5]), "+r"(d[6]), "+r"(d[7]), "+r"(d[8]), "+r"(d[9]), "+r"(d[10]), "+r"(d[11])
                 : "r"(a0), "r"(a1), "r"(a2), "r"(a3), "l"(db), "r"(acc));
}
__device__ __forceinline__ void wgmma(uint32_t (&d)[24], uint32_t a0, uint32_t a1, uint32_t a2, uint32_t a3, uint64_t db, int acc) {
    asm volatile("{\n.reg .pred p;\nsetp.ne.b32 p, %29, 0;\n"
                 "wgmma.mma_async.sync.aligned.m64n96k16.f16.f16.f16 "
                 "{%0, %1, %2, %3, %4, %5, %6, %7, %8, %9, %10, %11, %12, %13, %14, %15, %16, %17, %18, %19, %20, %21, %22, %23}, "
                 "{%24, %25, %26, %27}, %28, p, 1, 1, 0;\n}\n"
                 : "+r"(d[0]), "+r"(d[1]), "+r"(d[2]), "+r"(d[3]), "+r"(d[4]), "+r"(d[5]), "+r"(d[6]), "+r"(d[7]), "+r"(d[8]), "+r"(d[9]), "+r"(d[10]), "+r"(d[11]), "+r"(d[12]), "+r"(d[13]), "+r"(d[14]), "+r"(d[15]), "+r"(d[16]), "+r"(d[17]), "+r"(d[18]), "+r"(d[19]), "+r"(d[20]), "+r"(d[21]), "+r"(d[22]), "+r"(d[23])
                 : "r"(a0), "r"(a1), "r"(a2), "r"(a3), "l"(db), "r"(acc));
}
template <int ACC>
__device__ __forceinline__ void wgmma_rowsum(float (&d)[4], const uint32_t (&a)[4], uint64_t ones) {
    asm volatile("{\n.reg .pred p;\nsetp.ne.b32 p, %9, 0;\n"
                 "wgmma.mma_async.sync.aligned.m64n8k16.f32.bf16.bf16 {%0, %1, %2, %3}, {%4, %5, %6, %7}, %8, p, 1, 1, 0;\n}\n"
                 : "+f"(d[0]), "+f"(d[1]), "+f"(d[2]), "+f"(d[3])
                 : "r"(a[0]), "r"(a[1]), "r"(a[2]), "r"(a[3]), "l"(ones), "n"(ACC));
}
__device__ __forceinline__ void ldsm4(uint32_t (&r)[4], uint32_t addr) {
    asm volatile("ldmatrix.sync.aligned.m8n8.x4.shared.b16 {%0, %1, %2, %3}, [%4];"
                 : "=r"(r[0]), "=r"(r[1]), "=r"(r[2]), "=r"(r[3]) : "r"(addr) : "memory");
}
__device__ __forceinline__ void ldsm4_t(uint32_t (&r)[4], uint32_t addr) {
    asm volatile("ldmatrix.sync.aligned.m8n8.x4.trans.shared.b16 {%0, %1, %2, %3}, [%4];"
                 : "=r"(r[0]), "=r"(r[1]), "=r"(r[2]), "=r"(r[3]) : "r"(addr) : "memory");
}
__device__ __forceinline__ void stsm4(uint32_t addr, uint32_t a, uint32_t b, uint32_t c, uint32_t d) {
    asm volatile("stmatrix.sync.aligned.m8n8.x4.shared.b16 [%0], {%1, %2, %3, %4};"
                 ::"r"(addr), "r"(a), "r"(b), "r"(c), "r"(d) : "memory");
}
__device__ __forceinline__ uint32_t transpose8x8(uint32_t v) {
    uint32_t d; asm volatile("movmatrix.sync.aligned.m8n8.trans.b16 %0, %1;" : "=r"(d) : "r"(v)); return d;
}
__device__ __forceinline__ void spin_until(const unsigned* counter, unsigned target) {
    unsigned n = 0, c;
    do {
        asm volatile("ld.acquire.gpu.global.u32 %0, [%1];" : "=r"(c) : "l"(counter) : "memory");
        if (++n > SPIN_LIMIT) __trap();
    } while ((int)(c - target) < 0);
}
__device__ __forceinline__ void signal(unsigned* counter) {
    __syncwarp();
    if (elect_one()) asm volatile("red.release.gpu.global.add.u32 [%0], 1;" ::"l"(counter) : "memory");
    __syncwarp();
}
__device__ __forceinline__ void lds128(uint32_t& a, uint32_t& b, uint32_t& c, uint32_t& d, uint32_t addr) {
    asm volatile("ld.shared.v4.u32 {%0, %1, %2, %3}, [%4];" : "=r"(a), "=r"(b), "=r"(c), "=r"(d) : "r"(addr) : "memory");
}
__device__ __forceinline__ void lds64(uint32_t& a, uint32_t& b, uint32_t addr) {
    asm volatile("ld.shared.v2.u32 {%0, %1}, [%2];" : "=r"(a), "=r"(b) : "r"(addr) : "memory");
}
__device__ __forceinline__ void lds32(uint32_t& a, uint32_t addr) {
    asm volatile("ld.shared.u32 %0, [%1];" : "=r"(a) : "r"(addr) : "memory");
}
__device__ __forceinline__ int ldsi(uint32_t addr) {
    uint32_t v;
    lds32(v, addr);
    return (int)v;
}
__device__ __forceinline__ void sts32(uint32_t addr, uint32_t a) {
    asm volatile("st.shared.u32 [%0], %1;" ::"r"(addr), "r"(a) : "memory");
}
__device__ __forceinline__ void sts128(uint32_t addr, uint32_t a, uint32_t b, uint32_t c, uint32_t d) {
    asm volatile("st.shared.v4.u32 [%0], {%1, %2, %3, %4};" ::"r"(addr), "r"(a), "r"(b), "r"(c), "r"(d) : "memory");
}
__device__ __forceinline__ void sts64(uint32_t addr, uint32_t a, uint32_t b) {
    asm volatile("st.shared.v2.u32 [%0], {%1, %2};" ::"r"(addr), "r"(a), "r"(b) : "memory");
}
__device__ __forceinline__ void anchor(uint32_t addr, uint32_t a, uint32_t b, uint32_t c, uint32_t d) {
    asm volatile("{\n.reg .pred p;\nsetp.eq.b32 p, %0, 0;\n@p st.shared.v4.u32 [%0], {%1, %2, %3, %4};\n}\n"
                 ::"r"(addr), "r"(a), "r"(b), "r"(c), "r"(d) : "memory");
}
__device__ __forceinline__ uint32_t bf_fma(uint32_t a, uint32_t b, uint32_t c) {
    uint32_t d; asm("fma.rn.bf16x2 %0, %1, %2, %3;" : "=r"(d) : "r"(a), "r"(b), "r"(c)); return d;
}
__device__ __forceinline__ uint32_t bf_mul(uint32_t a, uint32_t b) {
    uint32_t d; asm("mul.rn.bf16x2 %0, %1, %2;" : "=r"(d) : "r"(a), "r"(b)); return d;
}
__device__ __forceinline__ uint32_t bf_absmax(uint32_t a, uint32_t b) {
    uint32_t d; asm("max.xorsign.abs.bf16x2 %0, %1, %2;" : "=r"(d) : "r"(a), "r"(b)); return d;
}
__device__ __forceinline__ uint32_t h_fma(uint32_t a, uint32_t b, uint32_t c) {
    uint32_t d; asm("fma.rn.f16x2 %0, %1, %2, %3;" : "=r"(d) : "r"(a), "r"(b), "r"(c)); return d;
}
__device__ __forceinline__ uint32_t h_mul(uint32_t a, uint32_t b) {
    uint32_t d; asm("mul.rn.f16x2 %0, %1, %2;" : "=r"(d) : "r"(a), "r"(b)); return d;
}
__device__ __forceinline__ uint32_t h_tanh(uint32_t a) {
    uint32_t d; asm("tanh.approx.f16x2 %0, %1;" : "=r"(d) : "r"(a)); return d;
}
__device__ __forceinline__ uint32_t pack_h2(float lo, float hi) {
    uint32_t d; asm("cvt.rn.f16x2.f32 %0, %1, %2;" : "=r"(d) : "f"(hi), "f"(lo)); return d;
}
__device__ __forceinline__ uint32_t pack_bf2(float lo, float hi) {
    uint32_t d; asm("cvt.rn.bf16x2.f32 %0, %1, %2;" : "=r"(d) : "f"(hi), "f"(lo)); return d;
}
__device__ __forceinline__ float bf_lo(uint32_t v) { return __uint_as_float(v << 16); }
__device__ __forceinline__ float bf_hi(uint32_t v) { return __uint_as_float(v & 0xffff0000u); }
__device__ __forceinline__ float h_lo(uint32_t v) { return __low2float(*reinterpret_cast<__half2*>(&v)); }
__device__ __forceinline__ float h_hi(uint32_t v) { return __high2float(*reinterpret_cast<__half2*>(&v)); }
__device__ __forceinline__ float warp_absmax(uint32_t v) {
    return __uint_as_float(__reduce_max_sync(~0u, max((v & 0x7fffu) << 16, v & 0x7fff0000u)));
}
__device__ __forceinline__ uint32_t gelu2(uint32_t z) {
    uint32_t p = h_fma(z, z, GELU_C2);
    uint32_t t = h_tanh(h_mul(z, p));
    return h_fma(z, t, z);
}
__device__ __forceinline__ float pow2i(int e) { return __uint_as_float((uint32_t)(e + 127) << 23); }
__device__ __forceinline__ int ilog2f(float v) {
    int e = (int)((__float_as_uint(v) >> 23) & 0xff) - 127;
    return max(-100, min(100, e));
}

__device__ __forceinline__ int bound_exp(float w1max) { return w1max > 0.f ? ilog2f(2.f * KZ * 96.f * w1max) : 0; }
__device__ __forceinline__ bool plain_squares(int e) { return (unsigned)(4 - e) <= 6; }
__device__ __forceinline__ int square_exp(int e) { return plain_squares(e) ? 0 : max(-14, min(4 - e, 14)); }
__device__ __forceinline__ int sum_exp(int e) { return max(-90, min(90, 33 - 2 * e)); }
__device__ __forceinline__ int row_exp(float m) { return 2 - ilog2f(m); }

struct Split {
    int per_cta, extra, period, inv_period, lenders;
    uint32_t lent_off[MAX_LENDERS * LENT];
    __host__ __device__ __forceinline__ int longer_before(int cta) const {
        const int n = (cta + period / 2) * inv_period >> 16;
        return n < extra ? n : extra;
    }
};
struct Work {
    int tA, tB, nA, nB, dir, rows, lent, index;
    __host__ __device__ __forceinline__ int tile(int j) const { return j < nA ? tA + dir * j : tB + dir * (j - nA); }
};
__host__ __device__ __forceinline__ Work get_work(int cta, const Split& sp) {
    Work w;
    const int before = sp.longer_before(cta), longer = sp.longer_before(cta + 1) - before;
    w.lent = longer && sp.lenders ? LENT : 0;
    w.index = before;
    const int t0 = cta * sp.per_cta + before, t1 = t0 + sp.per_cta + longer;
    const int tm = t1 < (t0 | 511) + 1 ? t1 : (t0 | 511) + 1;
    const bool swap = t1 > tm && t1 - tm < tm - t0, down = cta & 1;
    w.nA = swap ? t1 - tm : tm - t0;
    w.nB = t1 - t0 - w.nA;
    w.tA = down ? (swap ? tm : t0) : (swap ? t1 : tm) - 1;
    w.tB = down ? (swap ? t0 : tm) : (swap ? tm : t1) - 1;
    w.dir = down ? 1 : -1;
    w.rows = w.nA + 2 + (w.nB ? w.nB + 2 : 0);
    return w;
}
__device__ __forceinline__ int row_code(const Work& w, int i) {
    const bool in_a = i < w.nA + 2;
    const int t = in_a ? w.tA : w.tB;
    return ((t & 511) + w.dir * ((in_a ? i : i - (w.nA + 2)) - 1)) << 16 | (t >> 9) * TILE_W;
}
__host__ __device__ __forceinline__ uint32_t tile_offset(int tile) { return ((tile & 511) * IMG_W + (tile >> 9) * TILE_W) * (CH * 2); }
__device__ __forceinline__ int tile_order(int j, int n) {
    return j % ORDER_P == ORDER_P - 1 ? j / ORDER_P : n - 1 - (j - j / ORDER_P);
}
__device__ __forceinline__ void issue_region(const CUtensorMap* tm, uint32_t dst, uint32_t bar, int warp, int code) {
    mbar_expect_tx(bar, REGION_BYTES);
    tma_row(dst, tm, bar, (code & 0xffff) + (16 * warp - 1), code >> 16);
}

template <class Event>
__device__ __forceinline__ void conv_producer(const Work& wk, const CUtensorMap* tm, uint32_t sb, int warp, Event event) {
    const int lane = threadIdx.x & 31;
    const int j = lane & 15, grp = lane >> 4;
    const uint32_t reg0 = sb + SM_RING + warp * REGION_BYTES;
    const uint32_t bars = sb + SM_BAR + warp * 8;
    if (warp * 32 + lane < MAX_ROWS) {
        const int i = warp * 32 + lane, before = min(i / 5, wk.lent);
        const bool back = i % 5 == 0 && i > 0 && i / 5 <= wk.lent;
        sts32(sb + SM_TILES + i * 4, back ? tile_offset(wk.tile(before - 1)) | before
                                          : tile_offset(wk.tile(wk.lent + tile_order(i - before, wk.nA + wk.nB - 4 - wk.lent))));
    }
    const uint32_t ld64 = opaque(reg0 + grp * 8 * 192 + j * 8), ld32 = opaque(reg0 + grp * 8 * 192 + 128 + j * 4);
    const uint32_t st64 = opaque(reg0 + grp * A_SBO + (j >> 1) * A_LBO + (j & 1) * 8);
    const uint32_t st32 = opaque(reg0 + grp * A_SBO + (8 + (j >> 2)) * A_LBO + (j & 3) * 4);
    named_bar(0, NTHREADS);
    uint32_t w[3][3][3];
    mbar_wait_once(sb + BAR_F, 0);
#pragma unroll
    for (int tap = 0; tap < 9; tap++) {
        const uint32_t p = sb + SM_FILTER + (3 + wk.dir * 3 * (tap / 3 - 1) + tap % 3) * (CH * 2);
        lds64(w[tap / 3][tap % 3][0], w[tap / 3][tap % 3][1], p + 8 * j);
        lds32(w[tap / 3][tap % 3][2], p + 128 + 4 * j);
#pragma unroll
        for (int q = 0; q < 3; q++) w[tap / 3][tap % 3][q] = bf_mul(w[tap / 3][tap % 3][q], CONV_SCALE2);
    }
#pragma unroll
    for (int tap = 0; tap < 9; tap++) sts64(reg0 + (NSLOT - 1) * SLOT_BYTES + tap * 128 + j * 8, w[tap / 3][tap % 3][1], w[tap / 3][tap % 3][0]);
    named_bar(1, 128);
#pragma unroll
    for (int tap = 0; tap < 9; tap++) lds64(w[tap / 3][tap % 3][1], w[tap / 3][tap % 3][0], reg0 + (NSLOT - 1) * SLOT_BYTES + tap * 128 + j * 8);
    static_assert(2 * PREFETCH_ROWS == NSLOT && SLOT_BYTES % 32 == 0, "slot arithmetic");
    uint32_t bo = 0, so = 0, par = 0, pbo = PREFETCH_ROWS * 32, ppar = 1;
    int px, py;
    auto request = [&]() {
        mbar_wait_once(bars + (BAR_E - SM_BAR) + pbo, ppar);
        if (elect_one()) {
            mbar_expect_tx(bars + pbo, REGION_BYTES);
            tma_row(reg0 + pbo * (SLOT_BYTES / 32), tm, bars + pbo, px, py);
        }
    };
    auto advance = [&]() {
        bo += 32;
        so += SLOT_BYTES;
        if (bo == NSLOT * 32) { bo = 0; so = 0; par ^= 1; }
        pbo += 32;
        if (pbo == NSLOT * 32) { pbo = 0; ppar ^= 1; }
    };
    auto aim = [&](int row) {
        const int code = row_code(wk, row);
        px = (code & 0xffff) + (16 * warp - 1);
        py = code >> 16;
    };
    uint32_t accB[8][3], accC[8][3];
    int r = 0;
#pragma unroll 1
    while (r < wk.rows) {
        if (r == 0 || r == wk.nA + 2) {
            const uint32_t bo0 = bo;
            uint32_t bo1;
#pragma unroll 1
            for (int k = 0; k < 2; k++, r++) {
                if (r != 1) {
                    aim(r + PREFETCH_ROWS);
                    request();
                }
                mbar_wait_once(bars + bo, par);
                bo1 = bo;
                advance();
            }
            const uint32_t so0 = bo0 * (SLOT_BYTES / 32), so1 = bo1 * (SLOT_BYTES / 32);
#pragma unroll
            for (int p = 0; p < 10; p++) {
                uint32_t u[3], v[3];
                lds64(u[0], u[1], so0 + ld64 + p * 192);
                lds32(u[2], so0 + ld32 + p * 192);
                lds64(v[0], v[1], so1 + ld64 + p * 192);
                lds32(v[2], so1 + ld32 + p * 192);
#pragma unroll
                for (int dx = 0; dx < 3; dx++) {
                    const int o = p - dx;
                    if (o < 0 || o > 7) continue;
#pragma unroll
                    for (int q = 0; q < 3; q++) {
                        accB[o][q] = bf_fma(v[q], w[1][dx][q], dx == 0 ? bf_mul(u[q], w[0][dx][q]) : bf_fma(u[q], w[0][dx][q], accB[o][q]));
                        accC[o][q] = dx == 0 ? bf_mul(v[q], w[0][dx][q]) : bf_fma(v[q], w[0][dx][q], accC[o][q]);
                    }
                }
            }
            anchor(ld64, accB[7][0], accB[7][1], accB[7][2], 0);
            __syncwarp();
            if (elect_one()) {
                mbar_arrive(bars + (BAR_A - SM_BAR) + bo0);
                mbar_arrive(bars + (BAR_E - SM_BAR) + bo0);
                mbar_arrive(bars + (BAR_A - SM_BAR) + bo1);
                mbar_arrive(bars + (BAR_E - SM_BAR) + bo1);
            }
        }
        int end = wk.rows;
        const int marks[4] = {wk.rows - PREFETCH_ROWS, wk.rows - 11, wk.nA + 2, wk.nA + 2 - PREFETCH_ROWS};
#pragma unroll
        for (int k = 0; k < 4; k++) end = marks[k] > r ? min(end, marks[k]) : end;
        const int fetch = opaque_uniform(end - wk.rows);
        aim(r + PREFETCH_ROWS);
        px = opaque_uniform(px);
        const int py_end = opaque_uniform(py + wk.dir * (end - r));
        r = end;
#pragma unroll 1
        do {
            mbar_wait(bars + bo, par);
            uint32_t out[8][3];
#pragma unroll
            for (int p = 0; p < 10; p++) {
                uint32_t xv[3];
                lds64(xv[0], xv[1], so + ld64 + p * 192);
                lds32(xv[2], so + ld32 + p * 192);
#pragma unroll
                for (int dx = 0; dx < 3; dx++) {
                    const int o = p - dx;
                    if (o < 0 || o > 7) continue;
#pragma unroll
                    for (int q = 2; q >= 0; q--) {
                        out[o][q] = bf_fma(xv[q], w[2][dx][q], dx == 0 ? accB[o][q] : out[o][q]);
                        accB[o][q] = bf_fma(xv[q], w[1][dx][q], dx == 0 ? accC[o][q] : accB[o][q]);
                        accC[o][q] = dx == 0 ? bf_mul(xv[q], w[0][dx][q]) : bf_fma(xv[q], w[0][dx][q], accC[o][q]);
                    }
                }
            }
            __syncwarp();
#pragma unroll
            for (int o = 7; o >= 0; o--) {
                sts64(so + st64 + o * 16, out[o][0], out[o][1]);
                sts32(so + st32 + o * 16, out[o][2]);
            }
            __syncwarp();
            if (elect_one()) mbar_arrive(bars + (BAR_A - SM_BAR) + bo);
            if (fetch) request();
            advance();
            py += wk.dir;
        } while (py != py_end);
        if (((wk.rows - r) & ~8) == PREFETCH_ROWS) event(wk.rows - r == PREFETCH_ROWS);
    }
}

template <bool SCALED, int K0 = 0, int K1 = 3>
__device__ __forceinline__ void gelu_sq(uint32_t (&d)[24], uint32_t (&keep)[24], uint32_t sq_addr, uint32_t scale2) {
    pin(d);
#pragma unroll
    for (int k = K0; k < K1; k++) {
        uint32_t hs[4];
        lds128(hs[0], hs[1], hs[2], hs[3], sq_addr + k * SQ_ROW);
#pragma unroll
        for (int q = 0; q < 4; q++) {
            uint32_t g0 = gelu2(d[8 * k + 2 * q]), g1 = gelu2(d[8 * k + 2 * q + 1]);
            keep[8 * k + 2 * q] = g0;
            keep[8 * k + 2 * q + 1] = g1;
            if (SCALED) { g0 = h_mul(g0, scale2); g1 = h_mul(g1, scale2); }
            hs[q] = h_fma(g1, g1, h_fma(g0, g0, hs[q]));
        }
        sts128(sq_addr + k * SQ_ROW, hs[0], hs[1], hs[2], hs[3]);
    }
}
__device__ __forceinline__ void gelu_sq_reg(uint32_t (&d)[24], uint32_t (&hs)[12]) {
    pin(d);
#pragma unroll
    for (int q = 0; q < 12; q++) {
        const uint32_t g0 = gelu2(d[2 * q]), g1 = gelu2(d[2 * q + 1]);
        hs[q] = h_fma(g1, g1, h_fma(g0, g0, hs[q]));
    }
}
__device__ __forceinline__ void gelu_to(uint32_t (&g)[12], uint32_t (&d)[12]) {
    pin(d);
#pragma unroll
    for (int q = 0; q < 12; q++) g[q] = gelu2(d[q]);
    pin(g);
}
__device__ __forceinline__ void load_tile(uint32_t (&raw)[6][4], uint32_t addr) {
#pragma unroll
    for (int s = 0; s < 6; s++) ldsm4(raw[s], addr + s * 2 * A_LBO);
}
template <class F>
__device__ __forceinline__ void layer_norm(uint32_t (&raw)[6][4], uint64_t ones, F meanwhile) {
    uint32_t sq[2][4];
#pragma unroll
    for (int s = 0; s < 6; s++)
#pragma unroll
        for (int q = 0; q < 4; q++) sq[s / 3][q] = s % 3 == 0 ? bf_mul(raw[s][q], raw[s][q]) : bf_fma(raw[s][q], raw[s][q], sq[s / 3][q]);
    float sum[4], ssq[4];
    wg_fence();
    wgmma_rowsum<0>(sum, raw[0], ones);
#pragma unroll
    for (int s = 1; s < 6; s++) wgmma_rowsum<1>(sum, raw[s], ones);
    wgmma_rowsum<0>(ssq, sq[0], ones);
    wgmma_rowsum<1>(ssq, sq[1], ones);
    wg_commit();
    meanwhile();
    wg_wait<0>();
    uint32_t sc[2], sh[2];
#pragma unroll
    for (int h = 0; h < 2; h++) {
        asm volatile("" : "+f"(sum[2 * h]), "+f"(ssq[2 * h])::"memory");
        constexpr float EPS = 1e-5f / (KZ * KZ) * 0x1p-64f;
        const float m = sum[2 * h] * (1.f / (CH * KZ));
        float rstd;
        asm("rsqrt.approx.ftz.f32 %0, %1;" : "=f"(rstd) : "f"(fmaxf(fmaf(-m, m, fmaf(ssq[2 * h], 1.f / (CH * KZ * KZ), EPS)), EPS)));
        rstd *= 0x1p-112f;
        sc[h] = pack_bf2(rstd, rstd);
        const float shift = sum[2 * h] * (-1.f / CH) * bf_hi(sc[h]);
        sh[h] = pack_bf2(shift, shift);
    }
#pragma unroll
    for (int s = 0; s < 6; s++)
#pragma unroll
        for (int q = 0; q < 4; q++) {
            const uint32_t v = bf_fma(raw[s][q], sc[q & 1], sh[q & 1]);
            asm("lop3.b32 %0, %1, %2, 0x80008000, 0xd8;" : "=r"(raw[s][q]) : "r"(v << 3), "r"(v));
        }
}
struct Cursor {
    int slot;
    uint32_t par;
    __device__ __forceinline__ void advance(int n) {
        slot += n;
        if (slot >= NSLOT) { slot -= NSLOT; par ^= 1; }
    }
};
struct Descs {
    uint64_t w1[8][6];
    uint64_t w2[24];
    uint64_t ones;
};
template <int E0, int N>
__device__ __forceinline__ void gemm1_chunk(uint32_t (&d)[N], const uint32_t (&a)[6][4], const Descs& ds, int zero) {
#pragma unroll
    for (int s = 0; s < 6; s++) wgmma(d, a[s][0], a[s][1], a[s][2], a[s][3], ds.w1[E0 / 48][s], s ? 1 : zero);
}
template <int E0, int N>
__device__ __forceinline__ void gemm2_chunk(uint32_t (&acc)[24], const uint32_t (&g)[N], const Descs& ds) {
#pragma unroll
    for (int s = 0; s < N / 4; s++) wgmma(acc, g[4 * s], g[4 * s + 1], g[4 * s + 2], g[4 * s + 3], ds.w2[E0 / 16 + s], 1);
}

struct __align__(64) Params {
    Split sp;
    int zero;
    const __nv_bfloat16 *x, *dw, *w2, *gamma, *beta;
    __nv_bfloat16* out;
    Scratch* sc;
    Descs ds;
};

__global__ void __launch_bounds__(NTHREADS, 1)
block_kernel(const __grid_constant__ CUtensorMap tmap, const __grid_constant__ CUtensorMap tmap_w1, const __grid_constant__ Params pm) {
    const Split& sp = pm.sp;
    const Descs& ds = pm.ds;
    const int& zero = pm.zero;
    const __nv_bfloat16 *const &x = pm.x, *const &dw = pm.dw, *const &w2 = pm.w2, *const &gamma = pm.gamma, *const &beta = pm.beta;
    __nv_bfloat16* const& out = pm.out;
    Scratch* const& sc = pm.sc;
    extern __shared__ __align__(1024) uint8_t smem[];
    constexpr uint32_t sb = SB;
    const int tid = threadIdx.x;
    const Work wk = get_work(blockIdx.x, sp);
    constexpr uint32_t s_red = sb + SM_RED;
    if (smem_u32(smem) != SB) __trap();

    const int warp_id = __shfl_sync(~0u, tid >> 5, 0);
    PROF(0);
    const int cw = warp_id - 4, wgi = cw >> 2, w4 = warp_id & 3;
    if (elect_one()) {
        static_assert(3 * NSLOT * 4 == 8 + 8 * 8 && BAR_F == BAR_W + 48, "barrier shares");
        const int b = warp_id - 8;
        const uint32_t bar = b < 0 ? sb + BAR_X + warp_id * 8 : b < 7 ? sb + BAR_W + b * 8 : sb + BAR_PIN;
        mbar_init(bar, 1);
        if (b < 0 || b >= 6) {
#pragma unroll
            for (int k = 0; k < 8; k++) mbar_init(sb + (b < 0 ? BAR_X + (8 + 8 * warp_id + k) * 8 : BAR_R + ((b - 6) * 8 + k) * 8), 1);
        }
        fence_async();
        if (b < 0) {
            issue_region(&tmap, sb + SM_RING + warp_id * REGION_BYTES, bar, w4, ((wk.tA & 511) + wk.dir * wgi) << 16 | (wk.tA >> 9) * TILE_W);
        } else if (b < 6) {
            mbar_expect_tx(bar, 64 * CH * 2);
            tma_2d(sb + SM_W2 + b * (64 * CH * 2), &tmap_w1, bar, 64 * b, 0);
        } else if (b == 6) {
            mbar_expect_tx(bar, 9 * CH * 2);
            bulk_load(sb + SM_FILTER, dw, 9 * CH * 2, bar);
        }
    }
    __syncwarp();
    const int ntiles = wk.nA + wk.nB;
    const int rank = (wgi + wk.lent + 2 * (ntiles - 1)) % NCONS | (wgi >> 2 & 3);
    const int spare = wk.rows % NSLOT, spare2 = spare == NSLOT - 1 ? 0 : spare + 1;
    const uint32_t sq_base = sb + (wgi < 0 ? SM_RING + spare * SLOT_BYTES : SM_SQ + rank * 2 * SQ_HALF);
    const uint32_t sq_upper = wgi < 0 ? (spare2 - spare) * SLOT_BYTES : SQ_HALF;
    const uint32_t bar_a = sb + BAR_A + w4 * 8, bar_e = sb + BAR_E + w4 * 8;
    auto max_w1 = [&](uint32_t lane) { return __uint_as_float(__reduce_max_sync(~0u, lane < 4 * NCONS ? ldsi(s_red + RED_MAX + lane * 4) : 0)); };
    auto square_scale = [&](uint32_t lane) {
        const float f = pow2i(square_exp(bound_exp(max_w1(lane))));
        return pack_h2(f, f);
    };
    uint32_t a_addr, sq;
    const uint32_t sq_warp = sq_base + w4 * 512;
    auto set_addresses = [&]() {
        a_addr = opaque(sb + SM_RING + w4 * REGION_BYTES + ((tid >> 3) & 1) * A_SBO + ((tid >> 4) & 1) * A_LBO + (tid & 7) * 16);
        sq = opaque(sq_base + (tid & 127) * 16);
    };
    uint32_t turn, turn_end, so, so_sum, bo, bo_sum, off;
    auto set_run = [&](int j, int stop, int row) {
        const int slot = row % NSLOT, both = 2 * (row % 3) + 3;
        turn = opaque_uniform(row / 3);
        turn_end = opaque_uniform(row / 3 + (stop - j + NCONS - 1) / NCONS);
        so = opaque_uniform(slot * SLOT_BYTES);
        so_sum = opaque_uniform(both * SLOT_BYTES);
        bo = opaque_uniform(bar_a + slot * 32);
        bo_sum = opaque_uniform(2 * bar_a + both * 32);
        off = opaque_uniform(tile_offset(wk.tile(j)) + w4 * WARP_BYTES - sq_warp);
    };
    const int nrest = ntiles - 4;
    int jt;
    Cursor cur;
    int fast_from;
    if (warp_id < 4) {
        conv_producer(wk, &tmap, sb, warp_id, [&](bool second) {
            if (!second) {
                if (tid == 0) sts32(s_red + RED_JOB, wk.lent ? NTILES : atomicAdd(&sc->job, 1));
                if (blockIdx.x == 0) {
#pragma unroll 1
                    for (int e = tid; e < EX; e += 128) *sc->sum(e) = 0;
                    sc->bias[tid] = 0.f;
                }
                if (blockIdx.x == 0 || wk.lent) signal(&sc->early);
                __syncwarp();
            } else {
                const int piece = opaque_uniform(ldsi(s_red + RED_JOB)) - W2_GROUPS / 2, q = 2 * piece + W2_GROUPS + (w4 >> 1);
                if (piece < 8 * LENT * sp.lenders) {
                    spin_until(&sc->early, (ldsi(s_red + RED_LAUNCH) + 1) * 4 * (sp.lenders + 1));
                    if (elect_one()) {
                        if (piece >= 0) prefetch_l2(reinterpret_cast<const char*>(out) + sp.lent_off[piece / 8] + w4 * WARP_BYTES, WARP_BYTES);
                        else { prefetch_l2(w2 + 8 * q * CH, 8 * CH * 2); prefetch_l2(beta + 8 * q, 16); }
                    }
                }
            }
        });
        const int piece = opaque_uniform(ldsi(s_red + RED_JOB)) - W2_GROUPS / 2, q = 2 * piece + W2_GROUPS + (w4 >> 1);
        const bool prepares = piece < 0, helps = piece < 8 * LENT * sp.lenders;
        set_addresses();
        const int lane = lane_id(), g = lane >> 2, t = lane & 3;
        uint32_t a[6][4];
        unsigned short bt_raw;
        if (prepares) {
#pragma unroll
            for (int m = 0; m < 3; m++) ldg128(a[m], w2 + (8 * q + g) * CH + 32 * m + 8 * t);
            asm volatile("ld.global.nc.u16 %0, [%1];" : "=h"(bt_raw) : "l"(beta + 8 * q + g) : "memory");
        } else if (helps) {
#pragma unroll
            for (int s = 0; s < 6; s++) ldg128(a[s], reinterpret_cast<const char*>(out) + sp.lent_off[piece / 8] + w4 * WARP_BYTES + lane * 16 + s * 512);
        }
        mbar_wait_once(bar_e + spare2 * 32, (wk.rows - 5) / NSLOT & 1);
        mbar_wait_once(bar_e + spare * 32, (wk.rows - 6) / NSLOT & 1);
        named_bar(1, 128);
#pragma unroll
        for (int k = 0; k < 6; k++) { sts128(sq + k * SQ_ROW, 0, 0, 0, 0); sts128(sq + sq_upper + k * SQ_ROW, 0, 0, 0, 0); }
        if (prepares) {
            const int half = w4 & 1;
            uint32_t rmax = 0;
#pragma unroll
            for (int m = 0; m < 3; m++) rmax = bf_absmax(bf_absmax(rmax, bf_absmax(a[m][0], a[m][1])), bf_absmax(a[m][2], a[m][3]));
            uint2 u = half ? make_uint2(a[0][2], a[0][3]) : make_uint2(a[0][0], a[0][1]), u1 = half ? make_uint2(a[1][2], a[1][3]) : make_uint2(a[1][0], a[1][1]);
            const uint2 u2 = half ? make_uint2(a[2][2], a[2][3]) : make_uint2(a[2][0], a[2][1]);
            const float bt = bf_lo(bt_raw);
            rmax = bf_absmax(rmax, __shfl_xor_sync(~0u, rmax, 1));
            rmax = bf_absmax(rmax, __shfl_xor_sync(~0u, rmax, 2));
            const float mx = fmaxf(fabsf(bf_lo(rmax)), fabsf(bf_hi(rmax))), rs = pow2i(row_exp(mx));
            if (t == 0 && !half) sc->w2max[8 * q + g] = mx;
#pragma unroll 1
            for (int m = 0; m < 3; m++, u = u1, u1 = u2) {
                float f[4];
#pragma unroll
                for (int k = 0; k < 2; k++) {
                    const float lo = bf_lo(k ? u.y : u.x), hi = bf_hi(k ? u.y : u.x);
                    sc->w2h[(4 * m + 2 * half + k) * 1536 + q * 32 + lane] = transpose8x8(pack_h2(lo * rs, hi * rs));
                    f[2 * k] = lo * bt;
                    f[2 * k + 1] = hi * bt;
                }
                const float r0 = (g & 2 ? f[2] : f[0]) + __shfl_xor_sync(~0u, g & 2 ? f[0] : f[2], 8);
                const float r1 = (g & 2 ? f[3] : f[1]) + __shfl_xor_sync(~0u, g & 2 ? f[1] : f[3], 8);
                float r = (g & 1 ? r1 : r0) + __shfl_xor_sync(~0u, g & 1 ? r0 : r1, 4);
                r += __shfl_xor_sync(~0u, r, 16);
                if (g < 4) atomicAdd(&sc->bias[32 * m + 8 * t + 4 * half + g], r);
            }
            asm volatile("fence.proxy.async.global;" ::: "memory");
            signal(&sc->prep);
        } else if (helps) {
            uint32_t d[12], gl[12];
            const uint32_t scale2 = square_scale(lane);
            wg_fence();
#pragma unroll
            for (int s = 0; s < 6; s++) wgmma(d, a[s][0], a[s][1], a[s][2], a[s][3], ds.w1[0][s] + piece % 8 * (6 * 1536 / 16), s ? 1 : 0);
            wg_commit();
            wg_wait<0>();
            gelu_to(gl, d);
#pragma unroll
            for (int s = 0; s < 3; s++) {
                sc->lent[((piece / 8 * 4 + w4) * 24 + piece % 8 * 3 + s) * 32 + lane] = make_uint4(gl[4 * s], gl[4 * s + 1], gl[4 * s + 2], gl[4 * s + 3]);
                uint32_t hs[2];
#pragma unroll
                for (int k = 0; k < 2; k++) {
                    const uint32_t g0 = h_mul(gl[4 * s + 2 * k], scale2), g1 = h_mul(gl[4 * s + 2 * k + 1], scale2);
                    hs[k] = h_fma(g1, g1, h_mul(g0, g0));
                }
                const int pair = piece % 4 * 3 + s;
                sts64(sq + (piece & 4 ? sq_upper : 0) + (pair >> 1) * SQ_ROW + (pair & 1) * 8, hs[0], hs[1]);
            }
        }
        jt = ntiles - 1;
        cur.slot = spare ? spare - 1 : NSLOT - 1;
        cur.par = (wk.rows - 1) / NSLOT & 1;
        fast_from = ntiles;
        turn = turn_end = so = so_sum = bo = bo_sum = off = rank;
    } else {
        set_addresses();
        if (wgi == NCONS - 1) named_arrive(4, 256);
        set_run(wk.lent + wgi, min(wk.nA, nrest), wk.lent + wgi + 2);
        jt = wgi < wk.lent ? wgi : wk.lent + wgi;
        cur = {2, 0};
        cur.advance(jt + (jt >= wk.nA ? 2 : 0));
        {
            const int ct = tid - 128, lane = tid & 31;
            const unsigned epoch = *reinterpret_cast<volatile unsigned*>(&sc->launch);
            const int r = lane & 7, mi = lane >> 3;
            const uint32_t src = sb + SM_W2 + (cw >> 1) * (64 * CH * 2) + r * 128 + ((((cw & 1) * 4 + mi) ^ r) * 16);
            const uint32_t dst = sb + SM_W1 + (4 * cw + mi) * 1536 + r * 16;
            const int code = row_code(wk, PREFETCH_ROWS - 1 + wgi);
            named_bar(0, NTHREADS);
            auto request = [&]() {
                if (elect_one())
                    issue_region(&tmap, sb + SM_RING + (PREFETCH_ROWS - 1 + wgi) * SLOT_BYTES + w4 * REGION_BYTES, sb + BAR_X + (cw + 8) * 8, w4, code);
                __syncwarp();
            };
            if (wgi == 0) request();
            mbar_wait_once(sb + BAR_W + (cw >> 1) * 8, 0);
            uint32_t wmax[2] = {}, wsum[4] = {};
#pragma unroll 4
            for (int c = 0; c < 12; c++) {
                uint32_t u[4];
                ldsm4_t(u, src + c * 1024);
#pragma unroll
                for (int q = 0; q < 4; q++) {
                    wmax[q & 1] = bf_absmax(wmax[q & 1], u[q]);
                    wsum[q] = bf_fma(u[q], 0x3f803f80u, wsum[q]);
                    u[q] = pack_h2(__uint_as_float(u[q] * (65536 + zero)), bf_hi(u[q]));
                }
                stsm4(dst + c * 128, u[0], u[1], u[2], u[3]);
            }
            const float w1max = warp_absmax(bf_absmax(wmax[0], wmax[1]));
            if (lane == 0) sts32(s_red + RED_MAX + cw * 4, __float_as_uint(w1max));
            bool center = false;
#pragma unroll
            for (int q = 0; q < 4; q++) {
#pragma unroll
                for (int o = 1; o <= 2; o <<= 1) wsum[q] = bf_fma(__shfl_xor_sync(~0u, wsum[q], o), 0x3f803f80u, wsum[q]);
                center |= fabsf(bf_lo(wsum[q]) + bf_hi(wsum[q])) > (0.15f * CH) * w1max;
            }
            if (__builtin_expect(__any_sync(~0u, center), 0)) {
                float mean[4] = {};
#pragma unroll 1
                for (int pass = 0; pass < 2; pass++) {
                    float sum[4] = {};
#pragma unroll 1
                    for (int c = 0; c < 12; c++) {
                        uint32_t u[4];
                        ldsm4_t(u, src + c * 1024);
#pragma unroll
                        for (int q = 0; q < 4; q++) {
                            sum[q] += bf_lo(u[q]) + bf_hi(u[q]);
                            u[q] = pack_h2(bf_lo(u[q]) - mean[q], bf_hi(u[q]) - mean[q]);
                        }
                        stsm4(dst + c * 128, u[0], u[1], u[2], u[3]);
                    }
#pragma unroll
                    for (int q = 0; q < 4; q++) {
                        sum[q] += __shfl_xor_sync(~0u, sum[q], 1);
                        sum[q] += __shfl_xor_sync(~0u, sum[q], 2);
                        mean[q] = sum[q] * (1.f / CH);
                    }
                }
            }
            if (ct < 32) sts32(sb + SM_ONES + ct * 4, 0x3f803f80u);
            if (ct == 0) sts32(s_red + RED_LAUNCH, epoch);
            fence_async();
            named_bar(2, CONS_THREADS);
            if (wgi == 2) request();
        }
        PROF(1);
        if (wgi) mbar_wait_once(bar_a + 64, 0);
#pragma unroll
        for (int q = 0; q < 6; q++) sts128(sq_base + (tid & 127) * 16 + q * SQ_ROW, 0, 0, 0, 0);
        fast_from = wk.lent;
        if (!__all_sync(~0u, plain_squares(bound_exp(max_w1(lane_id()))))) {
            fast_from = ntiles;
#pragma unroll 1
            for (int q = 0; q < 6; q++) sts128(sq + SQ_HALF + q * SQ_ROW, 0, 0, 0, 0);
        }
    }
    uint32_t k1[24], k2[24], k3[24];
    uint32_t here;
    constexpr int SQC = 3 * SQ_ROW;
    auto store_at = [&](const uint32_t (&a)[6][4], uint32_t off) {
        char* ap = reinterpret_cast<char*>(out) + (off + sq);
#pragma unroll
        for (int s = 0; s < 6; s++) stg128(ap + s * 512, a[s]);
    };
    const uint32_t own_bar = 4 + wgi, next_bar = 4 + (wgi == NCONS - 1 ? 0 : wgi + 1);
    for (;;) {
        if (jt >= fast_from) {
            uint32_t hs2[12] = {}, hs3[12] = {};
            const uint32_t step = wk.dir * (NCONS * IMG_W * CH * 2);
            int second = wk.nB;
#pragma unroll 1
            for (;;) {
#pragma unroll 1
                while (turn != turn_end) {
                    uint32_t a[6][4], d0[24], d1[24], unused[24];
                    mbar_wait(bo, turn >> 1 & 1);
                    load_tile(a, a_addr + so);
                    layer_norm(a, ds.ones, [&]() { named_bar(own_bar, 256); });
                    wg_fence();
                    gemm1_chunk<0>(d0, a, ds, 0);
                    wg_commit();
                    gemm1_chunk<96>(d1, a, ds, 0);
                    wg_commit();
                    wg_wait<1>();
                    gelu_sq<false, 0, 1>(d0, unused, sq, 0);
                    gelu_sq<false, 1, 2>(d0, unused, sq, 0);
                    store_at(a, off);
                    gelu_sq<false, 2, 3>(d0, unused, sq, 0);
                    if (elect_one()) mbar_arrive(bo + (BAR_E - BAR_A));
                    wg_fence();
                    gemm1_chunk<192>(d0, a, ds, zero);
                    wg_commit();
                    named_arrive(next_bar, 256);
                    wg_wait<1>();
                    gelu_sq<false, 0, 1>(d1, unused, sq + SQC, 0);
                    gelu_sq<false, 1, 3>(d1, unused, sq + SQC, 0);
                    wg_fence();
                    gemm1_chunk<288>(d1, a, ds, zero);
                    wg_commit();
                    wg_wait<1>();
                    gelu_sq_reg(d0, hs2);
                    anchor(sq, hs2[8], hs2[9], hs2[10], hs2[11]);
                    wg_wait<0>();
                    gelu_sq_reg(d1, hs3);
                    so = so_sum - so;
                    bo = bo_sum - bo;
                    off += step;
                    turn++;
                }
                if (!second) break;
                const int j = ntiles - second + (rank + second + 2) % NCONS;
                second = 0;
                set_run(j, nrest, j + 4);
            }
            jt = nrest + rank;
            cur.slot = (bo - bar_a) >> 5;
            cur.par = turn >> 1 & 1;
#pragma unroll
            for (int k = 0; k < 3; k++) {
                sts128(sq + SQ_HALF + k * SQ_ROW, hs2[4 * k], hs2[4 * k + 1], hs2[4 * k + 2], hs2[4 * k + 3]);
                sts128(sq + SQ_HALF + SQC + k * SQ_ROW, hs3[4 * k], hs3[4 * k + 1], hs3[4 * k + 2], hs3[4 * k + 3]);
            }
        }
        const bool last = jt >= nrest;
        here = tile_offset(wk.tile(jt));
        if (last) {
            const uint32_t next = ldsi(sb + SM_TILES + rank * 4);
            if (elect_one()) {
                prefetch_l2(reinterpret_cast<const char*>(x) + here + w4 * WARP_BYTES, WARP_BYTES);
                if (rank == ORDER_P - 1) prefetch_l2(reinterpret_cast<const char*>(out) + next + w4 * WARP_BYTES, WARP_BYTES);
            }
        }
        uint32_t a[6][4], d0[24], d1[24], d3[24], k0[24];
        mbar_wait_once(bar_a + cur.slot * 32, cur.par);
        load_tile(a, a_addr + cur.slot * SLOT_BYTES);
        layer_norm(a, ds.ones, [&]() { if (jt >= wk.lent && wgi >= 0) named_bar(own_bar, 256); });
        if (!last) {
            store_at(a, here + w4 * WARP_BYTES - sq_warp);
            __syncwarp();
            if (elect_one()) mbar_arrive(bar_e + cur.slot * 32);
            if (jt < wk.lent) {
                jt += LENT;
                cur.advance(LENT);
                continue;
            }
        }
        wg_fence();
        gemm1_chunk<0>(d0, a, ds, 0);
        wg_commit();
        gemm1_chunk<96>(d1, a, ds, 0);
        wg_commit();
        const uint32_t scale2 = square_scale(lane_id());
        wg_wait<1>();
        gelu_sq<true>(d0, k0, sq, scale2);
        if (last) {
#pragma unroll
            for (int q = 0; q < 6; q++)
                sts128(sb + SM_RING + cur.slot * SLOT_BYTES + w4 * REGION_BYTES - sq_warp + sq + q * 512, k0[4 * q], k0[4 * q + 1], k0[4 * q + 2], k0[4 * q + 3]);
        }
        wg_fence();
        gemm1_chunk<192>(d0, a, ds, zero);
        wg_commit();
        if (jt + 2 < ntiles) named_arrive(next_bar, 256);
        wg_wait<1>();
        gelu_sq<true>(d1, k1, sq + SQC, scale2);
        wg_fence();
        gemm1_chunk<288>(d3, a, ds, 0);
        wg_commit();
        wg_wait<1>();
        gelu_sq<true>(d0, k2, sq + sq_upper, scale2);
        wg_wait<0>();
        gelu_sq<true>(d3, k3, sq + sq_upper + SQC, scale2);
        if (last) break;
        cur.advance(NCONS + ((jt < wk.nA && jt + NCONS >= wk.nA) ? 2 : 0));
        jt += NCONS;
    }
    const uint32_t lane = lane_id();
    uint32_t next_off = opaque_uniform(ldsi(sb + SM_TILES + rank * 4));
    const uint32_t s_fac = sb + SM_RING + spare * SLOT_BYTES + SQ_HALF;
    uint32_t inv_rho2;
    {
        if (rank == 0) {
            const int g = lane >> 2, t = lane & 3, i0 = w4 * 32 + lane;
            const bool leader = i0 == 0;
            const uint32_t pick = (g & 1) == (t & 1) ? (g & 2 ? 0x3c000000u : 0x00003c00u) : 0;
            const int be = bound_exp(max_w1(lane));
            const float to_fixed = pow2i(sum_exp(be) - 2 * square_exp(be));
            const uint32_t two_rows = sb + (w4 * 3 + (lane >> 3 & 1)) * SQ_ROW + ((lane >> 4) * 8 + (lane & 7)) * 16;
            const uint32_t third_row = sb + (w4 * 3 + 2) * SQ_ROW + lane * 16;
            unsigned short gam_raw[3];
            float rmax[3], f[3][4] = {};
            float2 bpair = make_float2(0.f, 0.f);
#pragma unroll 1
            for (int i = 0; i < 4; i++) {
                if (i == 1 && leader) {
                    spin_until(&sc->prep, (ldsi(s_red + RED_LAUNCH) + 1) * (W2_GROUPS * 2));
                    asm volatile("fence.proxy.async.global;" ::: "memory");
                    mbar_expect_tx(sb + BAR_W, 6 * SQ_HALF);
                }
                __syncwarp();
                named_bar(2, 128);
                if (i && leader) {
                    fence_async();
                    bulk_load(sb + SM_W2 + (i - 1) * 2 * SQ_HALF, reinterpret_cast<const char*>(sc->w2h) + (i - 1) * 2 * SQ_HALF, 2 * SQ_HALF, sb + BAR_W);
                }
                if (i == 1) {
#pragma unroll
                    for (int m = 0; m < 3; m++) {
                        asm volatile("ld.global.nc.u16 %0, [%1];" : "=h"(gam_raw[m]) : "l"(gamma + i0 + 128 * m) : "memory");
                        asm volatile("ld.global.cg.f32 %0, [%1];" : "=f"(rmax[m]) : "l"(&sc->w2max[i0 + 128 * m]) : "memory");
                    }
                    if (i0 < 96)
                        asm volatile("ld.global.cg.v2.f32 {%0, %1}, [%2];" : "=f"(bpair.x), "=f"(bpair.y)
                                     : "l"(&sc->bias[32 * (i0 % 24 >> 3) + 8 * (i0 / 24) + (i0 % 24 & 6)]) : "memory");
                }
                __syncwarp();
                const uint32_t from = i < NCONS ? SM_SQ + i * 2 * SQ_HALF : w4 < 2 ? SM_RING + spare * SLOT_BYTES : SM_RING + spare2 * SLOT_BYTES - SQ_HALF;
                if (i) named_bar(12 + i, 256);
#pragma unroll
                for (int r = 0; r < 12; r++) {
                    uint32_t u[4];
                    ldsm4_t(u, from + (r % 3 == 2 ? third_row + r / 3 * 512 : two_rows + (r / 3 * 2 + r % 3) * 256));
                    asm volatile("mma.sync.aligned.m16n8k16.row.col.f32.f16.f16.f32 {%0, %1, %2, %3}, {%4, %5, %6, %7}, {%8, %8}, {%0, %1, %2, %3};"
                                 : "+f"(f[r % 3][0]), "+f"(f[r % 3][1]), "+f"(f[r % 3][2]), "+f"(f[r % 3][3])
                                 : "r"(u[0]), "r"(u[1]), "r"(u[2]), "r"(u[3]), "r"(pick));
                }
            }
            unsigned long long* dst = sc->sum(96 * w4 + 8 * (g >> 1) + 2 * (t & 1) + (g & 1));
#pragma unroll
            for (int r = 0; r < 3; r++) {
                const float tot = r < 2 ? (t < 2 ? f[0][r & 1] + f[1][r & 1] : f[0][r + 2 & 3] + f[1][r + 2 & 3]) : (t < 2 ? f[2][0] + f[2][2] : f[2][1] + f[2][3]);
                atomicAdd(dst + (r < 2 ? (t >> 1) * 8 + r : 16 + (t >> 1)) * 32, __float2ull_rn(fminf(tot * to_fixed, 0x1p47f)) << 8 | 1);
            }
            PROF(2);
            float base[3], slope[3], reach[3];
            const float w1max = max_w1(lane);
            const float gbound = fmaxf(2.f * KZ * 9.7979590f * 192.f * w1max, 1.f) * 19.5959180f * INV_2KZ;
            const unsigned fixed = __reduce_max_sync(~0u, __float_as_uint(fmaf(gbound, fmaxf(fmaxf(rmax[0], rmax[1]), rmax[2]), fmaxf(fabsf(bpair.x), fabsf(bpair.y)))));
            if (lane == 0) sts32(s_red + 96 + w4 * 4, fixed);
#pragma unroll
            for (int m = 0; m < 3; m++) {
                base[m] = rmax[m] > 0.f ? pow2i(-row_exp(rmax[m])) * INV_2KZ : 0.f;
                slope[m] = base[m] * bf_lo(gam_raw[m]);
                reach[m] = fabsf(bf_lo(gam_raw[m])) * rmax[m] * gbound;
            }
            const float to_square = pow2i(-sum_exp(bound_exp(w1max))) * (INV_2KZ * INV_2KZ / 256);
#pragma unroll
            for (int m = 0; m < 3; m++) anchor(sq, __float_as_uint(base[m]), __float_as_uint(slope[m]), __float_as_uint(reach[m]), __float_as_uint(to_square));
            const unsigned epoch = ldsi(s_red + RED_LAUNCH);
            const uint32_t own_sum = (i0 >> 2) * 256 + (i0 & 3) * 8, own_fac = s_fac + i0 * 2;
            auto peek = [&](const void* p) {
                unsigned long long v;
                asm volatile("ld.relaxed.gpu.global.u64 %0, [%1];" : "=l"(v) : "l"(p) : "memory");
                return v;
            };
            const char* mine = reinterpret_cast<const char*>(sc->sums) + own_sum;
            unsigned n = 0;
            while (((unsigned)peek(sc->sum((blockIdx.x * 4 + w4) % (EX / 4) * 4)) & 255u) != gridDim.x)
                if (++n > SPIN_LIMIT) __trap();
            unsigned long long sum[3];
            for (;;) {
                bool all = true;
#pragma unroll
                for (int m = 0; m < 3; m++) {
                    sum[m] = peek(mine + m * (32 * 256));
                    all &= ((unsigned)sum[m] & 255u) == gridDim.x;
                }
                if (__all_sync(~0u, all)) break;
                if (++n > SPIN_LIMIT) __trap();
            }
            PROF(3);
            float gx[3];
#pragma unroll
            for (int m = 0; m < 3; m++) asm("sqrt.approx.ftz.f32 %0, %1;" : "=f"(gx[m]) : "f"(fmaf(__ull2float_rn(sum[m]), to_square, 1e-6f)));
            float tot = gx[0] + gx[1] + gx[2];
#pragma unroll
            for (int o = 16; o >= 1; o >>= 1) tot += __shfl_xor_sync(~0u, tot, o);
            const unsigned vwarp = __reduce_max_sync(~0u, __float_as_uint(fmaxf(fmaxf(reach[0] * gx[0], reach[1] * gx[1]), reach[2] * gx[2])));
            if (lane == 0) { sts32(s_red + 64 + w4 * 4, __float_as_uint(tot)); sts32(s_red + 80 + w4 * 4, vwarp); }
            named_bar(2, 128);
            uint32_t u[4], v[4], w[4];
            lds128(u[0], u[1], u[2], u[3], s_red + 64);
            lds128(v[0], v[1], v[2], v[3], s_red + 80);
            lds128(w[0], w[1], w[2], w[3], s_red + 96);
            tot = (__uint_as_float(u[0]) + __uint_as_float(u[1])) + (__uint_as_float(u[2]) + __uint_as_float(u[3]));
            const float vmax = __uint_as_float(max(max(v[0], v[1]), max(v[2], v[3]))), fmax2 = __uint_as_float(max(max(w[0], w[1]), max(w[2], w[3])));
            float inv_mean;
            asm("rcp.approx.ftz.f32 %0, %1;" : "=f"(inv_mean) : "f"(fmaf(tot, 1.f / EX, 1e-6f)));
            const int rho_e = 14 - ilog2f(fmaf(vmax, inv_mean, 2.f * fmax2));
            const float rho = pow2i(rho_e), inv_rho = pow2i(-rho_e);
            inv_rho2 = pack_bf2(inv_rho, inv_rho);
#pragma unroll
            for (int m = 0; m < 3; m++) {
                const float f = fmaf(slope[m] * gx[m], inv_mean, base[m]) * rho;
                asm volatile("st.shared.u16 [%0], %1;" ::"r"(own_fac + 256 * m), "h"((unsigned short)pack_h2(f, 0.f)) : "memory");
            }
            if (i0 < 96) sts32(sb + SM_BIASH + i0 * 4, pack_h2(bpair.x * rho, bpair.y * rho));
            if (i0 == 96) sts32(s_red + RED_INV_RHO, inv_rho2);
            named_arrive(12, NTHREADS);
            if (blockIdx.x == 0 && leader) { sc->launch = epoch + 1; sc->job = 0; }
            if (wk.lent) spin_until(&sc->lent_out, (epoch + 1) * 32 * LENT * sp.lenders);
        } else {
            named_arrive(12 + rank, 256);
            if (rank == NCONS && (unsigned)(ldsi(s_red + RED_JOB) - W2_GROUPS / 2) < 8 * LENT * sp.lenders) signal(&sc->lent_out);
            const int rw = rank * 4 - 4 + w4;
            const uint32_t row = sb + SM_W2 + rw * 512 + lane * 16;
            uint32_t u[W2_EARLY][4], f2[4];
            mbar_wait_once(sb + BAR_W, 1);
#pragma unroll
            for (int nb = 0; nb < W2_EARLY; nb++) lds128(u[nb][0], u[nb][1], u[nb][2], u[nb][3], row + nb * 6144);
            named_bar(12, NTHREADS);
            PROF(3);
            lds128(f2[0], f2[1], f2[2], f2[3], s_fac + rw * 64 + (lane >> 3) * 16);
            lds32(inv_rho2, s_red + RED_INV_RHO);
#pragma unroll
            for (int nb = 0; nb < 12; nb++) {
                uint32_t v[4];
                if (nb < W2_EARLY) { v[0] = u[nb % W2_EARLY][0]; v[1] = u[nb % W2_EARLY][1]; v[2] = u[nb % W2_EARLY][2]; v[3] = u[nb % W2_EARLY][3]; }
                else lds128(v[0], v[1], v[2], v[3], row + nb * 6144);
                sts128(row + nb * 6144, h_mul(v[0], f2[0]), h_mul(v[1], f2[1]), h_mul(v[2], f2[2]), h_mul(v[3], f2[3]));
            }
            fence_async();
            named_arrive(8, NTHREADS);
        }
    }
    uint32_t a[6][4], acc[24], rpar = 0, tile_off = here;
    const uint32_t bias_addr = sb + SM_BIASH + (lane & 3) * 96, lane16 = lane * 16, lane_off = ((lane >> 2) * CH + 8 * (lane & 3)) * 2;
    const uint32_t stage = sb + SM_RING + (spare + rank) % NSLOT * SLOT_BYTES + w4 * WARP_BYTES, bar_r = sb + BAR_R + warp_id * 8;
    auto load_bias = [&]() {
#pragma unroll
        for (int q = 0; q < 6; q++) lds128(acc[4 * q], acc[4 * q + 1], acc[4 * q + 2], acc[4 * q + 3], bias_addr + q * 16);
    };
    auto load_frags = [&]() {
#pragma unroll
        for (int s = 0; s < 6; s++) ldg128(a[s], reinterpret_cast<const char*>(out) + next_off + w4 * WARP_BYTES + lane16 + s * 512);
    };
    auto stage_x = [&]() {
        if (elect_one()) {
            mbar_expect_tx(bar_r, WARP_BYTES);
            bulk_load_stream(stage, reinterpret_cast<const char*>(x) + tile_off + w4 * WARP_BYTES, WARP_BYTES, bar_r);
        }
    };
    {
        named_bar(8 + rank, rank ? 256 : NTHREADS);
        if (rank == 0) PROF(4);
        load_bias();
        pin(k1); pin(k2); pin(k3);
        wg_fence();
        gemm2_chunk<288>(acc, k3, ds);
        wg_commit();
        gemm2_chunk<96>(acc, k1, ds);
        wg_commit();
        gemm2_chunk<192>(acc, k2, ds);
        wg_commit();
        stage_x();
        wg_wait<2>();
        uint32_t k0[24];
#pragma unroll
        for (int q = 0; q < 6; q++)
            lds128(k0[4 * q], k0[4 * q + 1], k0[4 * q + 2], k0[4 * q + 3], sb + SM_RING + cur.slot * SLOT_BYTES + w4 * REGION_BYTES + lane16 + q * 512);
        pin(k0);
        wg_fence();
        gemm2_chunk<0>(acc, k0, ds);
        wg_commit();
        if (rank < NCONS) named_arrive(9 + rank, 256);
        wg_wait<2>();
        load_frags();
        if (lane16 == 0) mbar_arrive(sb + BAR_PIN);
        mbar_wait(bar_r, rpar);
        wg_wait<0>();
    }
    auto lent = [&](uint32_t entry) { return &sc->lent[((wk.index * LENT + (entry & 3) - 1) * 4 + w4) * (24 * 32)]; };
    for (jt = rank - 4; jt < nrest; jt += 4) {
        if (jt >= zero) {
            tile_off = next_off;
            lds32(next_off, sb + SM_TILES + (jt + 4) * 4);
            if (tile_off & 3) {
                const uint4* src = lent(tile_off) + lane;
                tile_off &= ~3u;
                next_off = __shfl_sync(~0u, next_off, 0);
                stage_x();
                if (elect_one()) prefetch_l2(reinterpret_cast<const char*>(out) + next_off + w4 * WARP_BYTES, WARP_BYTES);
                load_bias();
#pragma unroll 1
                for (int half = 0; half < 2; half++, src += 12 * 32) {
                    uint32_t gl[48];
#pragma unroll
                    for (int s = 0; s < 12; s++) ldg128(reinterpret_cast<uint32_t (&)[4]>(gl[4 * s]), src + s * 32);
                    if (!half) {
                        named_bar(4 + rank, 256);
                        named_arrive(4 + ((rank + 1) & 3), 256);
                    }
                    pin(gl);
                    wg_fence();
#pragma unroll
                    for (int s = 0; s < 12; s++) wgmma(acc, gl[4 * s], gl[4 * s + 1], gl[4 * s + 2], gl[4 * s + 3], ds.w2[12 * half + s], 1);
                    wg_commit();
                    wg_wait<0>();
                }
                load_frags();
                mbar_wait(bar_r, rpar);
            } else {
                uint32_t d0[12], d1[12], g0[12], g1[12];
                next_off = __shfl_sync(~0u, next_off, 0);
                const bool more = jt + 4 < nrest && !(next_off & 3);
                load_bias();
                wg_fence();
                gemm1_chunk<0>(d0, a, ds, 0);
                wg_commit();
                if (jt && jt + 1 < nrest) named_bar(4 + rank, 256);
                gemm1_chunk<48>(d1, a, ds, 0);
                wg_commit();
                wg_wait<1>();
#define CNX_STEP(C, D, G)                                                   \
    gelu_to(G, D);                                                          \
    wg_fence();                                                             \
    if (C < 6) gemm1_chunk<48 * (C < 6 ? C + 2 : 0)>(D, a, ds, zero);      \
    gemm2_chunk<48 * C>(acc, G, ds);                                       \
    wg_commit();                                                            \
    if (C == 1 && jt + 2 < nrest) named_arrive(4 + ((rank + 1) & 3), 256); \
    wg_wait<(C < 7 ? 1 : 0)>();
                CNX_STEP(0, d0, g0)
                stage_x();
                if (elect_one()) {
                    if (more) prefetch_l2(reinterpret_cast<const char*>(out) + next_off + w4 * WARP_BYTES, WARP_BYTES);
                    else if (next_off & 3) prefetch_l2(lent(next_off), 24 * 32 * 16);
                }
                CNX_STEP(1, d1, g1)
                CNX_STEP(2, d0, g0)
                CNX_STEP(3, d1, g1)
                CNX_STEP(4, d0, g0)
                CNX_STEP(5, d1, g1)
                CNX_STEP(6, d0, g0)
#pragma unroll
                for (int s = 0; s < 6; s++) ldg128_if(more, a[s], reinterpret_cast<const char*>(out) + next_off + w4 * WARP_BYTES + lane16 + s * 512);
                if (lane16 == 0) mbar_arrive(sb + BAR_PIN);
                mbar_wait(bar_r, rpar);
                CNX_STEP(7, d1, g1)
#undef CNX_STEP
            }
        }
        {
            pin(acc);
            rpar ^= 1;
            uint4* op = reinterpret_cast<uint4*>(reinterpret_cast<char*>(out) + tile_off + w4 * WARP_BYTES + lane_off);
#pragma unroll
            for (int h = 0; h < 2; h++)
#pragma unroll
                for (int m = 0; m < 3; m++) {
                    uint32_t xin[4], o[4];
                    lds128(xin[0], xin[1], xin[2], xin[3], stage + lane_off + h * 1536 + m * 64);
#pragma unroll
                    for (int q = 0; q < 4; q++) {
                        const uint32_t v = acc[2 * (4 * m + q) + h];
                        o[q] = bf_fma(pack_bf2(h_lo(v), h_hi(v)), inv_rho2, xin[q]);
                    }
                    __stcs(op + h * 96 + m * 4, make_uint4(o[0], o[1], o[2], o[3]));
                }
            __syncwarp();
        }
    }
    PROF(5);
}

}

typedef CUresult (*EncodeTiledFn)(CUtensorMap*, CUtensorMapDataType, cuuint32_t, void*, const cuuint64_t*, const cuuint64_t*,
                                  const cuuint32_t*, const cuuint32_t*, CUtensorMapInterleave, CUtensorMapSwizzle,
                                  CUtensorMapL2promotion, CUtensorMapFloatOOBfill);

extern "C" void kernel_launch(void* const* d_in, const int* in_sizes, int n_in, void* d_out, int out_size) {
    using namespace cnx;
    static EncodeTiledFn encode = nullptr;
    static int num_sms = 0;
    static Scratch* scratch = nullptr;
    if (!encode) {
        void* fn = nullptr;
        cudaDriverEntryPointQueryResult qr;
        cudaGetDriverEntryPoint("cuTensorMapEncodeTiled", &fn, cudaEnableDefault, &qr);
        encode = (EncodeTiledFn)fn;
        cudaGetSymbolAddress((void**)&scratch, g_scratch);
        int dev = 0;
        cudaGetDevice(&dev);
        cudaDeviceGetAttribute(&num_sms, cudaDevAttrMultiProcessorCount, dev);
        if (num_sms > MAX_CTAS) num_sms = MAX_CTAS;
        cudaFuncSetAttribute(block_kernel, cudaFuncAttributeMaxDynamicSharedMemorySize, SM_TOTAL);
    }
    CUtensorMap tm;
    cuuint64_t dims[3] = {(cuuint64_t)CH, (cuuint64_t)IMG_W, (cuuint64_t)IMG_H};
    cuuint64_t strides[2] = {(cuuint64_t)CH * 2, (cuuint64_t)CH * 2 * IMG_W};
    cuuint32_t box[3] = {(cuuint32_t)CH, (cuuint32_t)REGION_PX, 1};
    cuuint32_t estr[3] = {1, 1, 1};
    encode(&tm, CU_TENSOR_MAP_DATA_TYPE_BFLOAT16, 3, d_in[0], dims, strides, box, estr, CU_TENSOR_MAP_INTERLEAVE_NONE,
           CU_TENSOR_MAP_SWIZZLE_NONE, CU_TENSOR_MAP_L2_PROMOTION_L2_128B, CU_TENSOR_MAP_FLOAT_OOB_FILL_NONE);
    Params pm = {};
    Descs& ds = pm.ds;
    for (int c = 0; c < 8; c++)
        for (int k = 0; k < 6; k++) ds.w1[c][k] = make_desc(SB + SM_W1 + c * 6 * 1536 + k * 256, 128, 1536);
    for (int k = 0; k < 24; k++) ds.w2[k] = make_desc(SB + SM_W2 + k * 256, 128, 6144);
    ds.ones = make_desc(SB + SM_ONES, 0, 0);
    CUtensorMap tw;
    cuuint64_t wdims[2] = {(cuuint64_t)EX, (cuuint64_t)CH};
    cuuint64_t wstrides[1] = {(cuuint64_t)EX * 2};
    cuuint32_t wbox[2] = {64, (cuuint32_t)CH};
    encode(&tw, CU_TENSOR_MAP_DATA_TYPE_BFLOAT16, 2, d_in[2], wdims, wstrides, wbox, estr, CU_TENSOR_MAP_INTERLEAVE_NONE,
           CU_TENSOR_MAP_SWIZZLE_128B, CU_TENSOR_MAP_L2_PROMOTION_L2_128B, CU_TENSOR_MAP_FLOAT_OOB_FILL_NONE);
    Split& sp = pm.sp;
    sp = {NTILES / num_sms, NTILES % num_sms, 1, 1 << 16, 0, {}};
    if (sp.per_cta + 9 > MAX_ROWS) return;
    if (sp.extra && sp.extra * (8 * LENT + 1) + W2_GROUPS / 2 <= num_sms && sp.per_cta >= 5 * LENT + 8) {
        sp.period = num_sms / sp.extra;
        sp.inv_period = 65535 / sp.period + 1;
        sp.lenders = sp.extra;
        for (int l = 0; l < sp.extra; l++) {
            const Work w = get_work((l + 1) * sp.period - sp.period / 2 - 1, sp);
            for (int e = 0; e < LENT; e++) sp.lent_off[l * LENT + e] = tile_offset(w.tile(e));
            if (w.nA < 2 * LENT) sp.lenders = 0;
        }
    }
    pm.x = (const __nv_bfloat16*)d_in[0];
    pm.dw = (const __nv_bfloat16*)d_in[1];
    pm.w2 = (const __nv_bfloat16*)d_in[3];
    pm.gamma = (const __nv_bfloat16*)d_in[4];
    pm.beta = (const __nv_bfloat16*)d_in[5];
    pm.out = (__nv_bfloat16*)d_out;
    pm.sc = scratch;
    block_kernel<<<num_sms, NTHREADS, SM_TOTAL>>>(tm, tw, pm);
}
```
